```python
import torch

def _softmax(x, axis=-1):
    return torch.softmax(x, dim=axis)

def _gelu(x):
    return torch.nn.functional.gelu(x, approximate='tanh')

def _silu(x):
    return torch.nn.functional.silu(x)

def _sigmoid(x):
    return torch.sigmoid(x)

def _layernorm(x, axis=-1, eps=1e-05):
    m = x.mean(dim=axis, keepdim=True)
    v = x.var(dim=axis, keepdim=True, unbiased=False)
    return (x - m) / torch.sqrt(v + eps)

def _scatter_add(tgt, idx, src, axis=0):
    return tgt.clone().index_add_(axis, idx, src)

def _segment_sum(src, seg, n):
    out = torch.zeros((n,) + src.shape[1:], dtype=src.dtype)
    return out.index_add_(0, seg, src)

def _pad(x, pw):
    flat = tuple((v for pair in reversed(pw) for v in pair))
    return torch.nn.functional.pad(x, flat)
kernel_name = 'adaLN_cond__compressed_kv_cla__glu_gated_geglu__decode'

def setup_inputs():

    _w = lambda a: (lambda t: t.to(torch.bfloat16) if t.is_floating_point() else t)(torch.as_tensor(a))

    def _A_setup():
        B, H, Sq, Sk, D, M = (1, 32, 1, 32768, 128, 512)
        Dc = 4 * D
        return {'x': _w((lambda *s: torch.randn(*s, dtype=torch.bfloat16) * 0.1)(B, Sq, M)), 'c_kv': _w((lambda *s: torch.randn(*s, dtype=torch.bfloat16) * 3.2)(B, Sk, Dc)), 'w_q': _w((lambda *s: torch.randn(*s, dtype=torch.bfloat16) * 0.8)(M, H, D) * M ** (-0.5)), 'w_uk': _w((lambda *s: torch.randn(*s, dtype=torch.bfloat16) * 0.8)(Dc, H, D) * Dc ** (-0.5)), 'w_uv': _w((lambda *s: torch.randn(*s, dtype=torch.bfloat16) * 3.2)(Dc, H, D) * Dc ** (-0.5)), 'w_o': _w((lambda *s: torch.randn(*s, dtype=torch.bfloat16) * 3.2)(H, D, M) * (H * D) ** (-0.5))}
    _A_in = _A_setup()

    def _B_setup():
        B, S, Dm, Df = (1, 1, 512, 1792)
        return {'x': _w((lambda *s: torch.randn(*s, dtype=torch.bfloat16) * 0.1)(B, S, Dm)), 'w_gate': _w((lambda *s: torch.randn(*s, dtype=torch.bfloat16) * 1.6)(Dm, Df) * Dm ** (-0.5)), 'w_up': _w((lambda *s: torch.randn(*s, dtype=torch.bfloat16) * 1.6)(Dm, Df) * Dm ** (-0.5)), 'w_down': _w((lambda *s: torch.randn(*s, dtype=torch.bfloat16) * 1.6)(Df, Dm) * Df ** (-0.5))}
    _B_in = _B_setup()
    return {'A_x': _A_in['x'], 'A_c_kv': _A_in['c_kv'], 'A_w_q': _A_in['w_q'], 'A_w_uk': _A_in['w_uk'], 'A_w_uv': _A_in['w_uv'], 'A_w_o': _A_in['w_o'], 'B_x': _B_in['x'], 'B_w_gate': _B_in['w_gate'], 'B_w_up': _B_in['w_up'], 'B_w_down': _B_in['w_down'], 'c': _w((lambda *s: torch.randn(*s, dtype=torch.bfloat16) * 0.1)(1, 512) * 8.0), 'w_mod': _w((lambda *s: torch.randn(*s, dtype=torch.bfloat16) * 0.1)(512, 6 * 512) * 512 ** (-0.5) * 8.0)}

def reference(A_x, A_c_kv, A_w_q, A_w_uk, A_w_uv, A_w_o, B_x, B_w_gate, B_w_up, B_w_down, c, w_mod):

    def _A_ref(x, c_kv, w_q, w_uk, w_uv, w_o):
        B, Sq, M = (x.shape[0], x.shape[1], x.shape[2])
        Sk = c_kv.shape[1]
        H, D = (w_q.shape[1], w_q.shape[2])
        q = torch.einsum('bqm,mhd->bhqd', x, w_q)
        k = torch.einsum('bkc,chd->bhkd', c_kv, w_uk)
        v = torch.einsum('bkc,chd->bhkd', c_kv, w_uv)
        scores = torch.einsum('bhqd,bhkd->bhqk', q, k) * D ** (-0.5)
        off = Sk - Sq
        qi = torch.arange(Sq)[:, None]
        kj = torch.arange(Sk)[None, :]
        cmask = kj <= qi + off
        scores = torch.where(cmask[None, None], scores, -1000000000.0)
        p = _softmax(scores, axis=-1)
        ctx = torch.einsum('bhqk,bhkd->bhqd', p, v)
        return torch.einsum('bhqd,hdm->bqm', ctx, w_o)

    def _B_ref(x, w_gate, w_up, w_down):
        g = torch.einsum('bsd,df->bsf', x, w_gate)
        u = torch.einsum('bsd,df->bsf', x, w_up)
        h = _gelu(g) * u
        return torch.einsum('bsf,fd->bsd', h, w_down)
    x = A_x
    mod = (_silu(c) @ w_mod).reshape(c.shape[0], 6, 1, -1)
    sa, ca, ga, sb, cb, gb = (mod[:, 0].clone(), mod[:, 1].clone(), mod[:, 2].clone(), mod[:, 3].clone(), mod[:, 4].clone(), mod[:, 5].clone())
    h = _layernorm(x, axis=-1) * (1 + ca) + sa
    x = x + ga * _A_ref(h, A_c_kv, A_w_q, A_w_uk, A_w_uv, A_w_o)
    h = _layernorm(x, axis=-1) * (1 + cb) + sb
    x = x + gb * _B_ref(h, B_w_gate, B_w_up, B_w_down)
    return x
```

```cpp
#include <cuda_runtime.h>
#include <cuda_bf16.h>
#include <cuda.h>
#include <stdint.h>

namespace {

constexpr int NCTA = 128;
constexpr int NTHREADS = 512;
constexpr int NUNITS = 8;
constexpr int NFF = 112;
constexpr uint32_t SPIN_LIMIT = 1u << 22;

#define STAG 300
#define TU 2
#define W_FIRST 5
#define I_FIRST 9
#define W_HEAD 4
#define I_MID 18
#define W_MID 5
#define I_TAIL 46
#define W_TAIL 4
#define I_POST 54
#define W_POST 5
#define NUMA 1
#define NPROBE 3
#define ADAPT 4
#define TAU 325
#define T_OFF 0
#define A_FROM 20
#define A_TO 41
#define NCP 2
#define W0 4
#define RD_ITEM 15
#define JAN_SLEEP 100
#define RD_SLEEP 400
#define HA_DELAY 200
#define H_SLEEP 100
#define QA_DELAY 600
#define QA_SLEEP 200
#define ML_DELAY 300
#define ML_SLEEP 50
#define E1_SLEEP 50
#define E2_SLEEP 0
#define E3_SLEEP 0
#define E5_SLEEP 0
#define MB_SLEEP 100
#define ORDER "01234567VMOGD"
#define UBUF 0x10543210
#define B_WUV 2
#define B_WO 4
#define B_GU 5
#define B_DN 3

constexpr int SM_U = 0;
constexpr int SM_XA = 6 * 32768;
constexpr int SM_XB = SM_XA + 12288;
constexpr int SM_MX = SM_XB + 16384;
constexpr int SM_MB = B_DN * 32768 + 16384;
constexpr int SM_FZ = SM_XB + 8192;
constexpr int SM_PB = SM_XB;
constexpr int SM_R3 = SM_XB + 2560;
constexpr int SM_RED = SM_XB + 4096;
constexpr int SM_FS = SM_XB + 20480;
constexpr int SM_FV = SM_FS + 1024;
constexpr int SM_QX = SM_XA + 8192;
constexpr int SM_FQ = SM_FV + 512;
constexpr int SM_CLS = SM_FQ + 128;
constexpr int SM_W = SM_FQ + 256;
constexpr int SM_SCR = SM_XA + 9216;
constexpr int SM_TR = SM_XB + 19456;
constexpr int SM_BAR = SM_W + 256;
constexpr int SM_TOTAL = SM_BAR + 1024;
static_assert(SM_TOTAL <= 232448, "smem");

enum { IT_MODA = 0, IT_WQ = 1, IT_WUK = 5, IT_CKV = 9, IT_WUV = 41, IT_MODB = 45, IT_WO = 47, IT_GU = 51, IT_DOWN = 55, NITEMS = 57,
       EB_WQ = NITEMS, EB_WUK, MBB, QT, QB, JD,
       SF0 = 64,
       PF0 = 80,
       EB_UNIT0 = 96 };

enum { MP_WQ = 0, MP_WUK, MP_CKV, MP_MODB, MP_WUV, MP_WO, MP_GATE, MP_UP, MP_DOWN, NMAPS };
struct First { const uint8_t* w[2]; const __nv_bfloat16* v[2]; };
struct Maps { CUtensorMap m[NMAPS]; uint32_t sched[64]; };

enum { B_HA = 0,
       B_E3 = 4,
       B_MB = 6,
       B_RD = 7,
       B_E2 = 8,
       B_QA = 16,
       B_ML = 32,
       B_E5 = 64,
       B_PR = 96,
       B_TR = 100 };
constexpr int G_E1 = 1 << 19;
constexpr int G_TR = B_TR * 4096;
__device__ __align__(1024) uint32_t g_scratch[(8 << 20) / 4];

#define TRACE(slot) do {} while (0)
#define TRACE_Q(slot) do {} while (0)
#define TRACE_GT(slot) do {} while (0)

#define CLK(var, cond) do {} while (0)
#define CLKD(var, cond, dep) do {} while (0)
__device__ __forceinline__ uint32_t s2u(const void* p) { return (uint32_t)__cvta_generic_to_shared(p); }
__device__ __forceinline__ void mbar_init(uint32_t b, int c) { asm volatile("mbarrier.init.shared::cta.b64 [%0], %1;" :: "r"(b), "r"(c) : "memory"); }
__device__ __forceinline__ void mbar_expect(uint32_t b, uint32_t bytes) { asm volatile("mbarrier.arrive.expect_tx.shared::cta.b64 _, [%0], %1;" :: "r"(b), "r"(bytes) : "memory"); }
__device__ __forceinline__ void mbar_arrive(uint32_t b) { asm volatile("mbarrier.arrive.shared::cta.b64 _, [%0];" :: "r"(b) : "memory"); }
__device__ __forceinline__ void mbar_wait(uint32_t b, uint32_t ph) {
    asm volatile("{\n.reg .pred p;\nW: mbarrier.try_wait.parity.shared::cta.b64 p, [%0], %1;\n@!p bra W;\n}" :: "r"(b), "r"(ph) : "memory");
}
__device__ __forceinline__ void mbar_waitb(uint32_t b, uint32_t ph) {
    asm volatile("{\n.reg .pred p;\n.reg .u32 n;\nmov.u32 n, 0;\n"
                 "W: mbarrier.try_wait.parity.shared::cta.b64 p, [%0], %1;\n@p bra D;\n"
                 "add.u32 n, n, 1;\nsetp.lt.u32 p, n, 0x100000;\n@p bra W;\ntrap;\nD:\n}" :: "r"(b), "r"(ph) : "memory");
}
__device__ __forceinline__ uint32_t mbar_test(uint32_t b, uint32_t ph) {
    uint32_t ok;
    asm volatile("{\n.reg .pred p;\nmbarrier.test_wait.parity.shared::cta.b64 p, [%1], %2;\nselp.u32 %0, 1, 0, p;\n}" : "=r"(ok) : "r"(b), "r"(ph) : "memory");
    return ok;
}
__device__ __forceinline__ void bar_sync(int id, int n) { asm volatile("bar.sync %0, %1;" :: "r"(id), "r"(n) : "memory"); }
__device__ __forceinline__ void bar_arrive(int id, int n) { asm volatile("bar.arrive %0, %1;" :: "r"(id), "r"(n) : "memory"); }
__device__ __forceinline__ uint32_t peer_addr(uint32_t a, uint32_t rank) { uint32_t r; asm("mapa.shared::cluster.u32 %0, %1, %2;" : "=r"(r) : "r"(a), "r"(rank)); return r; }
__device__ __forceinline__ void st_async1(uint32_t a, float x, uint32_t bar) {
    asm volatile("st.async.weak.shared::cluster.mbarrier::complete_tx::bytes.f32 [%0], %1, [%2];" :: "r"(a), "f"(x), "r"(bar) : "memory");
}
__device__ __forceinline__ void st_async2(uint32_t a, float x, float y, uint32_t bar) {
    asm volatile("st.async.weak.shared::cluster.mbarrier::complete_tx::bytes.v2.f32 [%0], {%1, %2}, [%3];" :: "r"(a), "f"(x), "f"(y), "r"(bar) : "memory");
}
__device__ __forceinline__ uint32_t gtime() { uint32_t t; asm volatile("mov.u32 %0, %%globaltimer_lo;" : "=r"(t)); return t; }
__device__ __forceinline__ void fence_gpu() { asm volatile("fence.acq_rel.gpu;" ::: "memory"); }

__device__ __forceinline__ uint32_t enc(uint32_t b) { uint32_t r; asm("max.u32 %0, %1, 1;" : "=r"(r) : "r"(b)); return r; }
__device__ __forceinline__ uint32_t encf(float f) { return enc(__float_as_uint(f)); }
__device__ __forceinline__ void st_x1(uint32_t* p, uint32_t v) { asm volatile("st.relaxed.gpu.global.u32 [%0], %1;" :: "l"(p), "r"(v) : "memory"); }
__device__ __forceinline__ void st_x4(void* p, uint32_t a, uint32_t b, uint32_t c, uint32_t d) {
    asm volatile("st.relaxed.gpu.global.v4.u32 [%0], {%1, %2, %3, %4};" :: "l"(p), "r"(a), "r"(b), "r"(c), "r"(d) : "memory");
}
__device__ __forceinline__ void st2_x1(uint32_t* p, uint32_t v) { st_x1(p, v); st_x1(p + 1024, v); }
__device__ __forceinline__ void st2_x4(uint32_t* p, uint32_t a, uint32_t b, uint32_t c, uint32_t d) { st_x4(p, a, b, c, d); st_x4(p + 1024, a, b, c, d); }
__device__ __forceinline__ int near_off(int b, uint32_t cls) { return b * 4096 + (((__popc(b & 0x2C) ^ cls) & 1) << 10); }
__device__ __forceinline__ void ld_x(uint32_t& v, const void* p) { asm volatile("ld.relaxed.gpu.global.u32 %0, [%1];" : "=r"(v) : "l"(p) : "memory"); }
__device__ __forceinline__ void ld_x(uint4& v, const void* p) {
    asm volatile("ld.relaxed.gpu.global.v4.u32 {%0, %1, %2, %3}, [%4];" : "=r"(v.x), "=r"(v.y), "=r"(v.z), "=r"(v.w) : "l"(p) : "memory");
}
__device__ __forceinline__ void ld_x(uint2& v, const void* p) { asm volatile("ld.relaxed.gpu.global.v2.u32 {%0, %1}, [%2];" : "=r"(v.x), "=r"(v.y) : "l"(p) : "memory"); }
__device__ __forceinline__ bool okv(const uint32_t& v) { return v != 0; }
__device__ __forceinline__ bool okv(const uint2& v) { return v.x != 0 && v.y != 0; }
__device__ __forceinline__ void zero(uint2& v) { v.x = 0; v.y = 0; }
__device__ __forceinline__ bool okv(const uint4& v) { return v.x != 0 && v.y != 0 && v.z != 0 && v.w != 0; }
__device__ __forceinline__ void zero(uint32_t& v) { v = 0; }
__device__ __forceinline__ void zero(uint4& v) { v.x = 0; v.y = 0; v.z = 0; v.w = 0; }

template <int STRIDE, typename T, int N>
__device__ __forceinline__ void poll_start(T (&v)[N], const void* base) {
#pragma unroll
    for (int i = 0; i < N; i++) ld_x(v[i], (const uint8_t*)base + i * STRIDE);
}
template <int STRIDE, int SLEEP, bool STARTED = false, int S4 = 4 * STRIDE, typename T, int N>
__device__ __forceinline__ void poll(T (&v)[N], const void* base) {
    if (!STARTED) {
#pragma unroll
        for (int i = 0; i < N; i++) zero(v[i]);
    }
#pragma unroll 1
    for (uint32_t it = 0;; it++) {
        bool all = true;
#pragma unroll
        for (int i = 0; i < N; i++) if (!okv(v[i])) { ld_x(v[i], (const uint8_t*)base + (i & 3) * STRIDE + (i >> 2) * S4); all = false; }
        if (__all_sync(0xffffffffu, all)) break;
        if (SLEEP && it > 0) __nanosleep(SLEEP);
        if (it > SPIN_LIMIT) __trap();
    }
}

__device__ __forceinline__ float bflo(uint32_t w) { return __uint_as_float(w << 16); }
__device__ __forceinline__ float bfhi(uint32_t w) { return __uint_as_float(w & 0xffff0000u); }
__device__ __forceinline__ uint32_t pack2(float lo, float hi) {
    uint32_t r; asm("cvt.rn.bf16x2.f32 %0, %1, %2;" : "=r"(r) : "f"(hi), "f"(lo)); return r;
}
__device__ __forceinline__ float rbf(float x) { return __uint_as_float(pack2(0.f, x)); }
__device__ __forceinline__ float sumlo(const uint32_t (&v)[4]) { return (bflo(v[0]) + bflo(v[1])) + (bflo(v[2]) + bflo(v[3])); }
__device__ __forceinline__ float sumhi(const uint32_t (&v)[4]) { return (bfhi(v[0]) + bfhi(v[1])) + (bfhi(v[2]) + bfhi(v[3])); }
__device__ __forceinline__ float ex2(float x) { float r; asm("ex2.approx.ftz.f32 %0, %1;" : "=f"(r) : "f"(x)); return r; }
__device__ __forceinline__ float shx(float v, int m) { return __shfl_xor_sync(0xffffffffu, v, m); }
__device__ __forceinline__ uint4 lds128(uint32_t a) { uint4 v; asm volatile("ld.shared.v4.u32 {%0, %1, %2, %3}, [%4];" : "=r"(v.x), "=r"(v.y), "=r"(v.z), "=r"(v.w) : "r"(a) : "memory"); return v; }
__device__ __forceinline__ uint32_t lds32(uint32_t a) { uint32_t v; asm volatile("ld.shared.u32 %0, [%1];" : "=r"(v) : "r"(a) : "memory"); return v; }
__device__ __forceinline__ void sts32(uint32_t a, uint32_t v) { asm volatile("st.shared.u32 [%0], %1;" :: "r"(a), "r"(v) : "memory"); }
__device__ __forceinline__ void sts16(uint32_t a, uint32_t v) { asm volatile("st.shared.u16 [%0], %1;" :: "r"(a), "h"((uint16_t)v) : "memory"); }
__device__ __forceinline__ int frag_off(int k) { return (k >> 5) * 64 + ((k >> 1) & 3) * 16 + ((k >> 4) & 1) * 8 + ((k >> 3) & 1) * 4 + (k & 1) * 2; }

template <bool TRANS>
__device__ __forceinline__ uint4 ldsm(uint32_t a) {
    uint4 r;
    if (TRANS) asm volatile("ldmatrix.sync.aligned.m8n8.x4.trans.shared.b16 {%0, %1, %2, %3}, [%4];" : "=r"(r.x), "=r"(r.y), "=r"(r.z), "=r"(r.w) : "r"(a) : "memory");
    else asm volatile("ldmatrix.sync.aligned.m8n8.x4.shared.b16 {%0, %1, %2, %3}, [%4];" : "=r"(r.x), "=r"(r.y), "=r"(r.z), "=r"(r.w) : "r"(a) : "memory");
    return r;
}
__device__ __forceinline__ void mma(float (&c)[4], uint32_t a0, uint32_t a1, uint32_t a2, uint32_t a3, uint32_t b0, uint32_t b1) {
    asm volatile("mma.sync.aligned.m16n8k16.row.col.f32.bf16.bf16.f32 {%0,%1,%2,%3}, {%4,%5,%6,%7}, {%8,%9}, {%0,%1,%2,%3};"
                 : "+f"(c[0]), "+f"(c[1]), "+f"(c[2]), "+f"(c[3]) : "r"(a0), "r"(a1), "r"(a2), "r"(a3), "r"(b0), "r"(b1));
}
template <bool TRANS, typename F>
__device__ __forceinline__ void load8(uint4 (&a)[8], F addr) {
    __syncwarp();
#pragma unroll
    for (int s = 0; s < 8; s++) a[s] = ldsm<TRANS>(addr(s));
}
__device__ __forceinline__ void mma8(float (&c)[4], const uint4 (&a)[8], const uint4 (&b)[4]) {
    float e[4][4];
#pragma unroll
    for (int s = 0; s < 8; s++) {
        if (s < 4) e[s][0] = e[s][1] = e[s][2] = e[s][3] = 0.f;
        mma(e[s & 3], a[s].x, a[s].y, a[s].z, a[s].w, (s & 1) ? b[s >> 1].z : b[s >> 1].x, (s & 1) ? b[s >> 1].w : b[s >> 1].y);
    }
#pragma unroll
    for (int i = 0; i < 4; i++) c[i] = (e[0][i] + e[1][i]) + (e[2][i] + e[3][i]);
}
__device__ __forceinline__ void ldfrag(uint4 (&b)[4], uint32_t a) {
    asm volatile("ld.shared.v4.u32 {%0,%1,%2,%3}, [%16];\nld.shared.v4.u32 {%4,%5,%6,%7}, [%16+64];\n"
                 "ld.shared.v4.u32 {%8,%9,%10,%11}, [%16+128];\nld.shared.v4.u32 {%12,%13,%14,%15}, [%16+192];\n"
                 : "=r"(b[0].x), "=r"(b[0].y), "=r"(b[0].z), "=r"(b[0].w), "=r"(b[1].x), "=r"(b[1].y), "=r"(b[1].z), "=r"(b[1].w),
                   "=r"(b[2].x), "=r"(b[2].y), "=r"(b[2].z), "=r"(b[2].w), "=r"(b[3].x), "=r"(b[3].y), "=r"(b[3].z), "=r"(b[3].w) : "r"(a) : "memory");
}
__device__ __forceinline__ void pin(uint32_t& x) { asm volatile("" : "+r"(x)); }
template <typename T> __device__ __forceinline__ void pin(T*& x) { asm volatile("" : "+l"(x)); }
__device__ __forceinline__ float4 ldsf4(uint32_t a) { const uint4 v = lds128(a); return make_float4(__uint_as_float(v.x), __uint_as_float(v.y), __uint_as_float(v.z), __uint_as_float(v.w)); }
__device__ __forceinline__ float sum4(const float4& f) { return (f.x + f.y) + (f.z + f.w); }
__device__ __forceinline__ void stsf(uint32_t a, float v) { sts32(a, __float_as_uint(v)); }

__device__ __forceinline__ void wg_fence() { asm volatile("wgmma.fence.sync.aligned;" ::: "memory"); }
__device__ __forceinline__ void wg_commit() { asm volatile("wgmma.commit_group.sync.aligned;" ::: "memory"); }
__device__ __forceinline__ void wg_wait1() { asm volatile("wgmma.wait_group.sync.aligned 1;" ::: "memory"); }
__device__ __forceinline__ void wg_wait0() { asm volatile("wgmma.wait_group.sync.aligned 0;" ::: "memory"); }
#define R8(o) "+f"(d[o]), "+f"(d[o + 1]), "+f"(d[o + 2]), "+f"(d[o + 3]), "+f"(d[o + 4]), "+f"(d[o + 5]), "+f"(d[o + 6]), "+f"(d[o + 7])
__device__ __forceinline__ void wgmma_rs_n32(float (&d)[16], const uint4& a, uint64_t db, int acc) {
    asm volatile("{\n.reg .pred p;\nsetp.ne.b32 p, %21, 0;\n"
        "wgmma.mma_async.sync.aligned.m64n32k16.f32.bf16.bf16 "
        "{%0,%1,%2,%3,%4,%5,%6,%7,%8,%9,%10,%11,%12,%13,%14,%15}, {%16,%17,%18,%19}, %20, p, 1, 1, 0;\n}"
        : R8(0), R8(8) : "r"(a.x), "r"(a.y), "r"(a.z), "r"(a.w), "l"(db), "r"(acc));
}
#define PV_LO "{%0,%1,%2,%3,%4,%5,%6,%7,%8,%9,%10,%11,%12,%13,%14,%15,%16,%17,%18,%19,%20,%21,%22,%23,%24,%25,%26,%27,%28,%29,%30,%31,%32,%33,%34,%35,%36,%37,%38,%39,%40,%41,%42,%43,%44,%45,%46,%47,%48,%49,%50,%51,%52,%53,%54,%55,%56,%57,%58,%59,%60,%61,%62,%63}, "
#define PV_HI "{%64,%65,%66,%67,%68,%69,%70,%71,%72,%73,%74,%75,%76,%77,%78,%79,%80,%81,%82,%83,%84,%85,%86,%87,%88,%89,%90,%91,%92,%93,%94,%95,%96,%97,%98,%99,%100,%101,%102,%103,%104,%105,%106,%107,%108,%109,%110,%111,%112,%113,%114,%115,%116,%117,%118,%119,%120,%121,%122,%123,%124,%125,%126,%127}, "
__device__ __forceinline__ void wgmma_pv(float (&d)[128], const uint4& a, uint32_t blo, int acc) {
    asm volatile("{\n.reg .pred p;\n.reg .b32 u0, u1, u2, u3, t;\n.reg .b64 d0, d1, d2, d3;\nsetp.ne.b32 p, %133, 0;\n"
        "mov.b64 d0, {%132, 0x40000100};\nadd.u32 t, %132, 512;\nmov.b64 d1, {t, 0x40000100};\n"
        "add.u32 t, %132, 128;\nmov.b64 d2, {t, 0x40000100};\nadd.u32 t, %132, 640;\nmov.b64 d3, {t, 0x40000100};\n"
        "wgmma.fence.sync.aligned;\n"
        "wgmma.mma_async.sync.aligned.m64n128k16.f32.bf16.bf16 " PV_LO "{%128, u0, %129, u1}, d0, p, 1, 1, 1;\n"
        "wgmma.mma_async.sync.aligned.m64n128k16.f32.bf16.bf16 " PV_LO "{%130, u2, %131, u3}, d1, 1, 1, 1, 1;\n"
        "wgmma.commit_group.sync.aligned;\n"
        "wgmma.mma_async.sync.aligned.m64n128k16.f32.bf16.bf16 " PV_HI "{%128, u0, %129, u1}, d2, p, 1, 1, 1;\n"
        "wgmma.mma_async.sync.aligned.m64n128k16.f32.bf16.bf16 " PV_HI "{%130, u2, %131, u3}, d3, 1, 1, 1, 1;\n"
        "wgmma.commit_group.sync.aligned;\n}"
        : R8(0), R8(8), R8(16), R8(24), R8(32), R8(40), R8(48), R8(56), R8(64), R8(72), R8(80), R8(88), R8(96), R8(104), R8(112), R8(120)
        : "r"(a.x), "r"(a.y), "r"(a.z), "r"(a.w), "r"(blo), "r"(acc) : "memory");
}

__host__ __device__ __forceinline__ int unit_buf(int u) { return (UBUF >> (4 * u)) & 7; }

template <int NW>
__device__ __forceinline__ void ln_stats(float s, float q, float sh, float* scr, int w, int lane, int bar, float& mean_b, float& sd_b) {
#pragma unroll
    for (int o = 16; o; o >>= 1) { s += shx(s, o); q += shx(q, o); }
    constexpr float n = 512.f / NW;
    if (lane == 0) { scr[w] = sh + s * (1.f / n); scr[NW + w] = q - s * s * (1.f / n); }
    bar_sync(bar, NW * 32);
    float mu = 0.f, m2 = 0.f;
#pragma unroll
    for (int i = 0; i < NW; i++) { mu += scr[i]; m2 += scr[NW + i]; }
    mu *= 1.f / NW;
#pragma unroll
    for (int i = 0; i < NW; i++) { const float d = scr[i] - mu; m2 = fmaf(n * d, d, m2); }
    mean_b = rbf(mu);
    sd_b = rbf(sqrtf(rbf(rbf(fmaxf(m2, 0.f) * (1.f / 512.f)) + 1e-5f)));
}
__device__ __forceinline__ float ln_mod(float x, float mean_b, float sd_b, float c, float s) {
    return rbf(rbf(__fdividef(rbf(x - mean_b), sd_b)) * rbf(1.f + c)) + s;
}

__global__ void __cluster_dims__(2, 1, 1) __launch_bounds__(NTHREADS, 1)
fused_kernel(const __grid_constant__ First F, __nv_bfloat16* __restrict__ out, uint32_t* __restrict__ gs, const __grid_constant__ Maps M) {
    extern __shared__ __align__(1024) uint8_t sm[];
    const uint32_t sb = s2u(sm);
    const int tid = threadIdx.x, lane = tid & 31;
    const int j = blockIdx.x, rk = j & 1;
    const int g = lane >> 2, t = lane & 3;
    const int r8 = lane & 7, lb3 = (lane >> 3) & 1, lb4 = lane >> 4;
    const uint64_t pol = 0x12F0000000000000ull;
    uint32_t in1 = 0, in2 = 0;
    {
        auto cpa = [&](uint32_t d, const uint8_t* s) {
            asm volatile("cp.async.cg.shared.global.L2::cache_hint.L2::128B [%0], [%1], 16, %2;" :: "r"(d), "l"(s), "l"(pol) : "memory");
        };
        const uint32_t ut = threadIdx.x, uj = blockIdx.x;
        const uint8_t* w = F.w[ut >= 128];
        if (ut < 128) {
            const uint32_t dq = (sb + ut * 16) ^ ((ut * 2) & 0x70);
            const uint8_t* sq = w + (uint32_t)(((uj & 1) * 256 + (ut >> 3)) * 8192 + (uj >> 1) * 128 + (ut & 7) * 16);
#pragma unroll
            for (int i = 0; i < 4 * NCP; i++) cpa(dq + 4 * 32768 + i * 2048, sq + i * 131072);
        } else if (ut < 384) {
            const uint32_t dm = (sb + ut * 16) ^ ((ut * 2) & 0x10);
            const uint8_t* sa = w + (uint32_t)(((uj >> 5) * 128 + (ut >> 1) - 64) * 6144 + (uj & 31) * 32 + (ut & 1) * 16);
            cpa(dm + SM_XA - 2048, sa); cpa(dm + SM_XA + 2048, sa + 1024);
        }
    }
    const int warp = __shfl_sync(0xffffffffu, tid >> 5, 0);
    const __nv_bfloat16* const xin = F.v[0];
    uint32_t* const pl = gs + (warp < 2 ? (B_PR + (j >> 5)) * 4096 + (j & 31) * 32 : G_E1 + j * 8192) + (warp & 1) * 1024 + lane;
    if (warp < 4) {
        in1 = *(const uint32_t*)(xin + 2 * tid); in2 = *(const uint32_t*)(xin + 256 + 2 * tid);
        st_x1(pl, 1u);
    } else if (warp < 12) in1 = *(const uint32_t*)(F.v[1] + 2 * (tid - 128));
    auto BAR = [&](int i) -> uint32_t { return sb + SM_BAR + i * 8; };
    const uint32_t a16 = (r8 + 8 * lb4) * 32 + ((lb3 ^ (r8 >> 2)) * 16);
    const uint32_t a64 = (r8 + 8 * lb4) * 64 + ((lb3 ^ (r8 >> 1)) * 16);
    const int pi = j < NFF ? rk * 128 + (warp - 4) * 16 + (lane & 15) : (j - NFF) * 16 + (lane & 15);
    auto ldcls = [&]() -> uint32_t { return *(const volatile uint32_t*)(sm + SM_CLS); };
    auto tma = [&](uint32_t dst, int mp, uint32_t bar, int c0, int c1, int c2, int c3) {
        asm volatile("{\n.reg .pred p;\nelect.sync _|p, 0xffffffff;\n"
                     "@p cp.async.bulk.tensor.4d.shared::cluster.global.mbarrier::complete_tx::bytes.L2::cache_hint [%0], [%1, {%3, %4, %5, %6}], [%2], %7;\n}"
                     :: "r"(dst), "l"(&M.m[mp]), "r"(bar), "r"(c0), "r"(c1), "r"(c2), "r"(c3), "l"(pol) : "memory");
    };
    if (warp <= 12) {
        const int grp = warp == 12 ? 0 : warp + 1;
        const uint32_t cnt = grp < 10 ? 1 : 4, cnt2 = grp == 7 ? 8 : cnt;
        if (lane == 0) {
#pragma unroll
            for (int i = 0; i < 8; i++) mbar_init(BAR(grp * 8 + i), (i < 2 && grp == 0) ? (i ? 128 : 256) : i ? cnt2 : cnt);
        }
        __syncwarp();
        if (grp < 10 && lane < (grp == 7 ? NITEMS - 56 : 8) && (grp || lane > NCP)) mbar_expect(BAR(grp * 8 + lane), grp < 8 ? 8192 : 4096);
        asm volatile("fence.mbarrier_init.release.cluster;" ::: "memory");
        __syncwarp();
        if (warp == 12) {
#pragma unroll
            for (int i = NCP + 1; i < W0; i++) tma(sb + (15 + i) * 8192, MP_WQ, BAR(i), 0, rk * 256 + (i - 1) * 64, j >> 1, 0);
        }
    } else if (warp == 13 && lane < NMAPS) asm volatile("prefetch.tensormap [%0];" :: "l"(&M.m[lane]) : "memory");
    __syncthreads();
    if (warp < 12) asm volatile("cp.async.mbarrier.arrive.noinc.shared::cta.b64 [%0];" :: "r"(BAR(warp < 4)) : "memory");
    asm volatile("barrier.cluster.arrive.relaxed.aligned;" ::: "memory");

    if (warp >= 12) {
    asm volatile("setmaxnreg.dec.sync.aligned.u32 80;");
    if (warp == 12) {
        static_assert(W0 > NCP && W0 <= 5 && NCP >= 1 && NCP <= 4, "W0");
        uint32_t e = M.sched[W0];
        uint32_t tn = gtime() + T_OFF;
#pragma unroll 1
        for (int i = W0; i < NITEMS; i++) {
            const uint32_t en = M.sched[i + 1];
            const int id = e & 63, w0 = (e >> 11) & 127, w1 = (e >> 18) & 127;
            int mp, c0 = 0, c1 = 0, c2 = 0, c3 = 0;
            if (id < IT_CKV) { const int k = id - IT_WQ; mp = MP_WQ + (k >> 2); c1 = rk * 256 + (k & 3) * 64; c2 = j >> 1; }
            else if (id < IT_WUV) { const int k = id - IT_CKV; mp = MP_CKV; c2 = rk * 4; c3 = (k * 64 + (j >> 1)) * 2; }
            else if (id < IT_MODB) { mp = MP_WUV; c1 = (j & 3) * 32 + (id - IT_WUV) * 128; c2 = (j >> 2) * 2; }
            else if (id < IT_WO) { mp = MP_MODB; c0 = 1024 + (j >> 1) * 32; c1 = rk * 256 + (id - IT_MODB) * 128; }
            else if (id < IT_GU) { mp = MP_WO; c0 = (j & 15) * 32; c1 = (j >> 4) * 512 + (id - IT_WO) * 128; }
            else {
                if (j >= NFF) { e = en; continue; }
                const int k = id - IT_GU;
                if (k < 4) { mp = MP_GATE + (k >> 1); c0 = (j >> 1) * 32; c1 = rk * 256 + (k & 1) * 128; }
                else { mp = MP_DOWN; c1 = j * 16; c2 = (k - 4) * 4; }
            }
            if (w0) mbar_wait(BAR(w0 - 1), 0);
            const int w2 = e >> 25;
            tn += TAU;
            if (w2) {
                mbar_wait(BAR(w2 - 1), 0);
                while (!__any_sync(0xffffffffu, mbar_test(BAR(w1 - 1), 0) | ((int)(gtime() - tn) > 0))) {}
            } else if (w1 && (j < NFF || w1 <= IT_GU)) mbar_wait(BAR(w1 - 1), 0);
            tma(sb + ((e >> 6) & 31) * 8192, mp, BAR(id), c0, c1, c2, c3);
            e = en;
        }
    } else if (warp == 13) {
#pragma unroll
        for (int i = 0; i < 2; i++) st2_x4(gs + (B_ML + rk * 16 + i * 8 + g) * 4096 + (j >> 1) * 16 + t * 4, 0u, 0u, 0u, 0u);
        if (lane < 16) st2_x4(gs + (B_E2 + (j >> 4)) * 4096 + (j & 15) * 64 + lane * 4, 0u, 0u, 0u, 0u);
        if (lane < 16) st2_x1(gs + (B_E3 + ((j >> 3) & 1)) * 4096 + (j >> 4) * 128 + (j & 7) * 16 + lane, 0u);
        if (lane < 8) st2_x1(gs + B_MB * 4096 + j * 8 + lane, 0u);
        if (j < NFF) {
#pragma unroll
            for (int i = 0; i < 2; i++) st2_x4(gs + (B_E5 + (i * 8 + g) * 2 + (j >> 6)) * 4096 + (j & 63) * 16 + t * 4, 0u, 0u, 0u, 0u);
        }
        bar_sync(9, 64);
        const uint32_t cs = ldcls();
#pragma unroll 1
        for (int i = 0; i < 32; i++) {
            st_x4(gs + G_E1 + j * 8192 + (i >> 3) * 2048 + ((((cs >> 1) ^ (i >> 3)) & 1) << 10) + (i & 7) * 128 + lane * 4, 0u, 0u, 0u, 0u);
            __nanosleep(JAN_SLEEP);
        }
        fence_gpu();
        if (lane < 8) st2_x1(gs + B_RD * 4096 + j * 8 + lane, 1u + (cs >> 1));
        if (lane == 0) TRACE(41);
        uint32_t rd[4];
        mbar_wait(BAR(IT_CKV + RD_ITEM), 0);
        poll<1024, RD_SLEEP>(rd, gs + near_off(B_RD, cs) + lane * 8);
#pragma unroll
        for (int i = 0; i < 4; i++) {
            const uint32_t m = __ballot_sync(0xffffffffu, rd[i] == 2u);
            if (lane == 0) sts32(sb + SM_CLS + 16 + i * 4, m);
        }
        __syncwarp();
        if (lane < 8) mbar_arrive(BAR(JD));
        if (lane == 0) TRACE(42);
        bar_sync(7, 288);
        float c[4] = {0.f, 0.f, 0.f, 0.f}, e[4] = {0.f, 0.f, 0.f, 0.f};
        mbar_wait(BAR(IT_MODB), 0); mbar_wait(BAR(IT_MODB + 1), 0);
        __syncwarp();
        const uint32_t am = sb + SM_MB + (a64 ^ (rk * 32));
#pragma unroll 1
        for (int s = 0; s < 8; s++) {
            const uint4 bb = lds128(sb + SM_FS + rk * 512 + s * 64 + t * 16);
            const uint4 x = ldsm<true>(am + s * 2048), y = ldsm<true>(am + s * 2048 + 1024);
            const uint4 z = ldsm<true>((am ^ 32) + s * 2048), w = ldsm<true>((am ^ 32) + s * 2048 + 1024);
            mma(c, x.x, x.y, x.z, x.w, bb.x, bb.y); mma(e, z.x, z.y, z.z, z.w, bb.x, bb.y);
            mma(c, y.x, y.y, y.z, y.w, bb.z, bb.w); mma(e, w.x, w.y, w.z, w.w, bb.z, bb.w);
        }
        if (t == 0) {
            st_async2(peer_addr(sb + SM_FQ + 64 + g * 8, rk ^ 1), e[0], e[2], peer_addr(BAR(MBB), rk ^ 1));
            mbar_expect(BAR(MBB), 8);
        }
        mbar_wait(BAR(MBB), 0);
        const float2 pp = *(const float2*)(sm + SM_FQ + 64 + g * 8);
        const float mine = t ? c[2] + pp.y : c[0] + pp.x, other = shx(mine, 4);
        if (t < 2 && !(g & 1)) st2_x1(gs + B_MB * 4096 + j * 8 + t * 4 + (g >> 1), enc(pack2(mine, other)));
        if (lane == 0) TRACE(11);
    } else if (warp == 14) {
        uint2 ml[2];
        mbar_waitb(BAR(JD), 0);
        const uint32_t cls = ldcls();
        mbar_waitb(BAR(PF0 + 2 * NUNITS - 1), 0);
        __nanosleep(ML_DELAY);
        poll<64, ML_SLEEP>(ml, gs + near_off(B_ML + (j >> 2), cls) + lane * 32);
        bar_arrive(3, 288);
        if (lane == 0) TRACE_Q(37);
        const float m0 = __uint_as_float(ml[0].x), m1 = __uint_as_float(ml[1].x);
        const int mi = __float_as_int(fmaxf(m0, m1));
        const int mr = __reduce_max_sync(0xffffffffu, mi ^ ((mi >> 31) & 0x7fffffff));
        const float mm = __int_as_float(mr ^ ((mr >> 31) & 0x7fffffff));
        const uint32_t w0 = pack2(ex2(m0 - mm), 0.f), w1 = pack2(ex2(m1 - mm), 0.f);
        const uint32_t wa = sb + SM_W + (lane >> 3) * 64 + (lane & 1) * 32 + ((lane >> 1) & 3) * 4;
        sts32(wa, w0 * 0x10001u); sts32(wa + 16, w1 * 0x10001u);
        bar_arrive(8, 288);
        float L = bflo(w0) * __uint_as_float(ml[0].y) + bflo(w1) * __uint_as_float(ml[1].y);
#pragma unroll
        for (int o = 16; o; o >>= 1) L += shx(L, o);
        if (lane == 0) *(float*)(sm + SM_FQ) = __frcp_rn(L);
        if (lane == 0) TRACE(10);
        bar_sync(4, 288);
        st2_x1(gs + (B_HA + ((j >> 4) & 1) * 2 + lb4) * 4096 + (j >> 5) * 256 + (j & 15) * 16 + (lane & 15), 0u);
        st2_x4(gs + (B_QA + rk * 8 + ((j >> 1) & 1) * 4 + (j >> 5)) * 4096 + g * 128 + ((j >> 2) & 7) * 16 + t * 4, 0u, 0u, 0u, 0u);
        if (lane < 8) st2_x1(gs + B_RD * 4096 + j * 8 + lane, 0u);
    } else if (warp == 15) {
        mbar_waitb(BAR(j < NFF ? NITEMS - 1 : IT_GU - 1), 0);
    }
    } else if (warp < 4) {
        float* scr = (float*)(sm + SM_SCR);
        uint32_t cls;
        {
            uint2 ha[8];
            {
                uint32_t best = 0xffffffffu;
#pragma unroll
                for (int i = 0; i < NPROBE; i++) {
                    uint32_t t0, t1, o;
                    asm volatile("mov.u32 %0, %%clock;" : "=r"(t0));
                    asm volatile("atom.relaxed.gpu.global.exch.b32 %0, [%1], %2;" : "=r"(o) : "l"(pl), "r"(2u + i) : "memory");
                    asm volatile("{\n.reg .pred p;\nsetp.ne.u32 p, %1, 0x1234567;\nmov.u32 %0, 0;\n@p mov.u32 %0, %%clock;\n}" : "=r"(t1) : "r"(o));
                    best = min(best, t1 - t0);
                }
                if (lane == 0) scr[16 + warp] = __uint_as_float(best);
            }
            const float sh = __shfl_sync(0xffffffffu, bflo(in1), 0);
            const float v0 = bflo(in1) - sh, v1 = bfhi(in1) - sh, v2 = bflo(in2) - sh, v3 = bfhi(in2) - sh;
            float mb, sd;
            ln_stats<4>((v0 + v1) + (v2 + v3), (v0 * v0 + v1 * v1) + (v2 * v2 + v3 * v3), sh, scr, warp, lane, 2, mb, sd);
            if (!rk) in2 = in1;
            const uint4 lt = *(const uint4*)(scr + 16);
            cls = NUMA ? ((lt.y < lt.x) ^ (__popc((B_PR + (j >> 5)) & 0x2C) & 1)) | (lt.w < lt.z) << 1 : 0;
            if (warp == 0) { if (lane == 0) sts32(sb + SM_CLS, cls); bar_arrive(9, 64); }
            if (tid == 0) TRACE(38);
            asm volatile("barrier.cluster.wait.aligned;" ::: "memory");
            mbar_wait(BAR(IT_MODA), 0);
            __nanosleep(HA_DELAY);
            poll<1024, H_SLEEP, false, 16384>(ha, gs + near_off(B_HA + rk * 2, cls) + 2 * tid);
            auto rsum = [](uint32_t a, uint32_t b, uint32_t c, uint32_t d) { return rbf((__uint_as_float(a) + __uint_as_float(b)) + (__uint_as_float(c) + __uint_as_float(d))); };
            sts32(sb + SM_FV + frag_off(2 * tid),
                  pack2(ln_mod(bflo(in2), mb, sd, rsum(ha[4].x, ha[5].x, ha[6].x, ha[7].x), rsum(ha[0].x, ha[1].x, ha[2].x, ha[3].x)),
                        ln_mod(bfhi(in2), mb, sd, rsum(ha[4].y, ha[5].y, ha[6].y, ha[7].y), rsum(ha[0].y, ha[1].y, ha[2].y, ha[3].y))));
            bar_arrive(5, 384);
            mbar_wait(BAR(QB), 0);
            if (tid < 64) {
                const float* qx = (const float*)(sm + SM_QX) + tid;
                sts16(sb + SM_FQ + frag_off(tid), pack2((qx[0] + qx[64]) + (qx[128] + qx[192]), 0.f));
            }
            bar_arrive(6, 384);
        }
        asm volatile("setmaxnreg.inc.sync.aligned.u32 176;");
        float acc[128];
        float M = 0.f;
        uint32_t pa = sb + SM_XA + warp * 512 + lane * 16, ma = sb + SM_MX + (warp * 8 + g) * 4, pf = BAR(PF0);
        uint32_t blo = __reduce_or_sync(0xffffffffu, (((sb + SM_U) & 0x3FFFFu) >> 4) | 0x400000u);
        uint32_t* e1[4];
#pragma unroll
        for (int i = 0; i < 4; i++) e1[i] = gs + G_E1 + (warp * 8 + g) * 4 * 8192 + (rk * 2 + (j >> 6)) * 2048 + ((j >> 1) & 31) * 32 + t * 4;
        uint32_t ck[10] = {0, 0, 0, 0, 0, 0, 0, 0, 0, 0};
#pragma unroll 1
        for (int h = 0; h < 2 * NUNITS; h++) {
            CLK(ck[0], h == 2 * TU); CLK(ck[5], h == 2 * TU + 1);
            mbar_wait(pf, 0);
            CLK(ck[1], h == 2 * TU); CLK(ck[6], h == 2 * TU + 1);
            const float m = __uint_as_float(lds32(ma));
            const uint4 pn = lds128(pa);
            wg_wait0();
#pragma unroll
            for (int i = 0; i < 128; i++) asm volatile("" : "+f"(acc[i]) :: "memory");
            CLK(ck[2], h == 2 * TU); CLK(ck[7], h == 2 * TU + 1);
            if (h == 0) M = m;
            uint32_t b2 = 0x3f803f80u;
            if (__builtin_expect(__any_sync(0xffffffffu, m != M), 0)) {
                const float Mn = fmaxf(M, m), alpha = ex2(M - Mn), beta = ex2(m - Mn);
                M = Mn;
                b2 = pack2(beta, beta);
#pragma unroll
                for (int jj = 0; jj < 32; jj++) { acc[4 * jj] *= alpha; acc[4 * jj + 1] *= alpha; }
            }
            auto mul2 = [](uint32_t x, uint32_t y) { uint32_t r; asm("mul.rn.bf16x2 %0, %1, %2;" : "=r"(r) : "r"(x), "r"(y)); return r; };
            const uint4 p = make_uint4(mul2(pn.x, b2), mul2(pn.y, b2), mul2(pn.z, b2), mul2(pn.w, b2));
            if (tid == 0 && (h & 1)) TRACE_Q(48 + (h >> 1));
            CLK(ck[3], h == 2 * TU); CLK(ck[8], h == 2 * TU + 1);
            wgmma_pv(acc, p, blo, h);
            CLK(ck[4], h == 2 * TU); CLK(ck[9], h == 2 * TU + 1);
            if (lane == 0 && h > 0 && !(h & 1)) mbar_arrive(BAR(EB_UNIT0 + (h >> 1) - 1));
            blo += h == 11 ? -11 * 1024 : 1024;
            pa += (h == 5 || h == 11) ? -5 * 2048 : 2048;
            ma += 128; pf += 8;
            if (h == 2 * NUNITS - 3) {
                mbar_wait(BAR(JD), 0);
                const uint32_t hm = (*(const uint32_t*)(sm + SM_CLS + 16 + warp * 4) >> (g * 4)) ^ ((j >> 6) ? 15u : 0u);
#pragma unroll
                for (int i = 0; i < 4; i++) e1[i] += ((hm >> i) & 1) << 10;
            }
        }
#pragma unroll
        for (int vv = 0; vv < 2; vv++) {
            if (vv && M == 1.f) __trap();
            if (vv) wg_wait0(); else wg_wait1();
#pragma unroll
            for (int i = 0; i < 64; i++) asm volatile("" : "+f"(acc[vv * 64 + i]) :: "memory");
            if (tid == 0 && !vv) TRACE_Q(63);
#pragma unroll
            for (int i = 0; i < 4; i++) {
                const float* a = &acc[vv * 64 + i * 16];
                st_x4(e1[i] + i * 8192 + vv * 16, enc(pack2(a[0], a[1])), enc(pack2(a[4], a[5])), enc(pack2(a[8], a[9])), enc(pack2(a[12], a[13])));
            }
        }
        if (tid == 0) TRACE_Q(17);
    } else {
        const int u8 = tid - 128, w8 = warp - 4;
        const int v = w8 >> 2, wq4 = w8 & 3;
        const uint32_t xw = *(const uint32_t*)(xin + 2 * pi);
        {
            const float c0 = bflo(in1), c1 = bfhi(in1);
            sts32(sb + SM_FS + frag_off(2 * u8), pack2(__fdividef(c0, 1.f + __expf(-c0)), __fdividef(c1, 1.f + __expf(-c1))));
        }
        bar_arrive(7, 288);
        bar_sync(1, 256);
        asm volatile("barrier.cluster.wait.aligned;" ::: "memory");
        uint4 a[8], b[4]; float c[4];
        if (w8 < 2) {
            ldfrag(b, sb + SM_FS + (j >> 5) * 256 + t * 16);
            mbar_wait(BAR(IT_MODA), 0);
            if (u8 == 0) TRACE(12);
            const uint32_t ab = sb + SM_XA + w8 * 4096 + a16;
            load8<true>(a, [&](int s) { return ab + s * 512; });
            mma8(c, a, b);
            if (t < 2) st2_x1(gs + (B_HA + ((j >> 4) & 1) * 2 + w8) * 4096 + (j >> 5) * 256 + (j & 15) * 16 + t * 8 + g, encf(t ? c[2] : c[0]));
        }
        const uint32_t a128 = v * 4096 + (r8 + 8 * lb4) * 128 + (((wq4 * 2 + lb3) ^ r8) * 16);
        {
            mbar_wait(BAR(IT_WQ + 2 * v <= NCP ? 1 : IT_WQ + 2 * v), 0); mbar_wait(BAR(IT_WQ + 2 * v + 1 <= NCP ? 1 : IT_WQ + 2 * v + 1), 0);
            const uint32_t ab = sb + SM_U + 4 * 32768 + v * 12288 + a128;
            load8<true>(a, [&](int s) { return ab + s * 2048; });
            if (lane == 0) mbar_arrive(BAR(EB_WQ));
            bar_sync(5, 384);
            if (u8 == 0) TRACE(13);
            ldfrag(b, sb + SM_FV + v * 256 + t * 16);
            mma8(c, a, b);
            if (t < 2) {
                const float qv = t ? c[2] : c[0];
                const uint32_t qa_ = sb + SM_QX + ((rk * 2 + v) * 64 + wq4 * 16 + t * 8 + g) * 4;
                asm volatile("st.async.weak.shared::cluster.mbarrier::complete_tx::bytes.f32 [%0], %1, [%2];"
                             :: "r"(peer_addr(qa_, rk ^ 1)), "f"(qv), "r"(peer_addr(BAR(QB), rk ^ 1)) : "memory");
                sts32(qa_, __float_as_uint(qv));
            }
            __syncwarp();
            if (lane == 0) mbar_expect(BAR(QB), 64);
        }
        {
            mbar_wait(BAR(IT_WUK + v), 0); mbar_wait(BAR(IT_WUK + v + 2), 0);
            const uint32_t ab = sb + SM_U + 5 * 32768 + (w8 * 16 + r8 + 8 * lb3) * 128;
            const uint32_t x16 = (lb4 ^ r8) * 16;
            load8<false>(a, [&](int s) { return ab + (s & 1) * 16384 + (x16 ^ ((s >> 1) * 32)); });
            bar_sync(6, 384);
            if (u8 == 0) TRACE(14);
            b[0] = lds128(sb + SM_FQ + t * 16); b[1] = lds128(sb + SM_FQ + 64 + t * 16);
            float e[4] = {0.f, 0.f, 0.f, 0.f};
            c[0] = c[1] = c[2] = c[3] = 0.f;
#pragma unroll
            for (int k = 0; k < 4; k++) {
                const uint32_t b0 = (k & 1) ? b[k >> 1].z : b[k >> 1].x, b1 = (k & 1) ? b[k >> 1].w : b[k >> 1].y;
                mma(c, a[2 * k].x, a[2 * k].y, a[2 * k].z, a[2 * k].w, b0, b1);
                mma(e, a[2 * k + 1].x, a[2 * k + 1].y, a[2 * k + 1].z, a[2 * k + 1].w, b0, b1);
            }
            const float mine = ((t & 1) ? ((t & 2) ? e[2] : e[0]) : ((t & 2) ? c[2] : c[0])) * 0.12751743f;
            const float other = shx(mine, 4);
            if (!(g & 1)) st2_x1(gs + (B_QA + rk * 8 + ((j >> 1) & 1) * 4 + (j >> 5)) * 4096 + w8 * 128 + ((j >> 2) & 7) * 16 + (g >> 1) * 4 + t, enc(pack2(mine, other)));
            if (u8 == 0) TRACE(15);
        }
        const uint32_t cls = ldcls();
        __nanosleep(QA_DELAY);
        {
            uint4 qb[8];
            const uint32_t* pq = gs + near_off(B_QA + rk * 8 + wq4, cls) + lane * 4;
            const uint32_t* pq2 = gs + near_off(B_QA + rk * 8 + 4 + wq4, cls) + lane * 4;
            if (lane == 0) {
                mbar_expect(BAR(QT), 4096);
                asm volatile("cp.async.bulk.shared::cluster.global.mbarrier::complete_tx::bytes [%0], [%1], 4096, [%2];"
                             :: "r"(sb + SM_U + 5 * 32768 + w8 * 4096), "l"(gs + near_off(B_QA + rk * 8 + w8, cls)), "r"(BAR(QT)) : "memory");
            }
            const uint32_t qs = sb + SM_U + 5 * 32768 + wq4 * 4096 + lane * 16;
            mbar_wait(BAR(QT), 0);
#pragma unroll
            for (int i = 0; i < 8; i++) { a[i] = lds128(qs + i * 512); qb[i] = lds128(qs + 16384 + i * 512); }
            poll<512, QA_SLEEP, true>(a, pq);
            poll<512, QA_SLEEP, true>(qb, pq2);
            if (lane == 0) mbar_arrive(BAR(EB_WUK));
            auto add2 = [](uint32_t x, uint32_t y) { uint32_t r; asm("add.rn.bf16x2 %0, %1, %2;" : "=r"(r) : "r"(x), "r"(y)); return r; };
#pragma unroll
            for (int i = 0; i < 8; i++) a[i] = make_uint4(add2(a[i].x, qb[i].x), add2(a[i].y, qb[i].y), add2(a[i].z, qb[i].z), add2(a[i].w, qb[i].w));
        }
        if (u8 == 0) TRACE(8);
        {
            float m = -INFINITY, l = 0.f;
            uint32_t xl = sb + SM_XB + w8 * 2048 + lane * 16, xr = peer_addr(xl, rk ^ 1), bsr = peer_addr(BAR(SF0 + v), rk ^ 1);
            uint32_t pa = sb + SM_XA + v * 2048 + wq4 * 512 + lane * 16, ma = sb + SM_MX + v * 128 + (wq4 * 8 + g) * 4;
            uint32_t fb = BAR(IT_CKV + v * 2), sf = BAR(SF0 + v);
            uint32_t dlo = __reduce_or_sync(0xffffffffu, (((sb + SM_U + v * 16384) & 0x3FFFFu) >> 4) | 0x10000u);
            static_assert(UBUF == 0x10543210, "unit buffers");
            uint32_t ck[9] = {0, 0, 0, 0, 0, 0, 0, 0, 0};
            if (STAG && v) __nanosleep(STAG);
#pragma unroll 1
            for (int n = 0; n < NUNITS; n++) {
                CLK(ck[0], n == TU); CLK(ck[8], n == TU + 1);
                float d[2][16], sc[8];
#pragma unroll
                for (int i = 0; i < 2; i++) {
                    mbar_wait(fb + i * 8, 0);
                    if (i == 0) CLK(ck[1], n == TU);
                    wg_fence();
#pragma unroll
                    for (int s = 0; s < 8; s++) wgmma_rs_n32(d[i], a[s], (0x40000080ull << 32) | (dlo + i * 512 + (s >> 2) * 64 + (s & 3) * 2), s);
                    wg_commit();
                }
                CLK(ck[2], n == TU);
#pragma unroll
                for (int i = 0; i < 2; i++) {
                    if (i) wg_wait0(); else wg_wait1();
#pragma unroll
                    for (int k = 0; k < 16; k++) asm volatile("" : "+f"(d[i][k]) :: "memory");
                    sc[4 * i] = d[i][0] + d[i][6]; sc[4 * i + 1] = d[i][1] + d[i][7]; sc[4 * i + 2] = d[i][8] + d[i][14]; sc[4 * i + 3] = d[i][9] + d[i][15];
                    asm volatile("st.async.weak.shared::cluster.mbarrier::complete_tx::bytes.v4.f32 [%0], {%1, %2, %3, %4}, [%5];"
                                 :: "r"(xr + i * 1024), "f"(sc[4 * i]), "f"(sc[4 * i + 1]), "f"(sc[4 * i + 2]), "f"(sc[4 * i + 3]), "r"(bsr) : "memory");
                }
                CLK(ck[3], n == TU);
                if (u8 == 128) TRACE_Q(56 + (n < 6 ? n : -40));
                if (n >= 3) mbar_wait(BAR(EB_UNIT0 + n - 3), 0);
                dlo += n == 5 ? -5 * 2048 : 2048;
                fb += 32; xr ^= 512; bsr += 16;
                pin(fb); pin(xr); pin(bsr);
                CLK(ck[4], n == TU);
                mbar_wait(sf, 0);
                CLK(ck[5], n == TU);
                const float4 x = ldsf4(xl), y = ldsf4(xl + 1024);
                sc[0] += x.x; sc[1] += x.y; sc[2] += x.z; sc[3] += x.w; sc[4] += y.x; sc[5] += y.y; sc[6] += y.z; sc[7] += y.w;
                float pr[8];
#pragma unroll
                for (int i = 0; i < 8; i++) pr[i] = ex2(sc[i] - m);
                float mx = fmaxf(fmaxf(fmaxf(sc[0], sc[1]), fmaxf(sc[2], sc[3])), fmaxf(fmaxf(sc[4], sc[5]), fmaxf(sc[6], sc[7])));
                if (__builtin_expect(__any_sync(0xffffffffu, mx > m), 0)) {
                    mx = fmaxf(mx, shx(mx, 1));
                    mx = fmaxf(mx, shx(mx, 2));
                    const float mn = fmaxf(m, ceilf(mx * 0.0625f) * 16.f);
                    l *= ex2(m - mn);
                    m = mn;
#pragma unroll
                    for (int i = 0; i < 8; i++) pr[i] = ex2(sc[i] - m);
                }
                CLK(ck[6], n == TU);
                stsf(ma, m);
                asm volatile("st.shared.v4.u32 [%0], {%1, %2, %3, %4};" :: "r"(pa), "r"(pack2(pr[0], pr[1])), "r"(pack2(pr[2], pr[3])),
                             "r"(pack2(pr[4], pr[5])), "r"(pack2(pr[6], pr[7])) : "memory");
                __syncwarp();
                if (lane == 0) mbar_arrive(sf + (PF0 - SF0) * 8);
                CLK(ck[7], n == TU);
                l += ((pr[0] + pr[1]) + (pr[2] + pr[3])) + ((pr[4] + pr[5]) + (pr[6] + pr[7]));
                xl ^= 512; sf += 16; ma += 256; pa += (n == 2 || n == 5) ? -8192 : 4096;
            }
            l += shx(l, 1);
            l += shx(l, 2);
            float2* mlx = (float2*)(sm + SM_MX + 2048) + wq4 * 8 + g;
            if (v == 0) { *mlx = make_float2(m, l); bar_arrive(11, 256); }
            else {
                mbar_wait(BAR(JD), 0);
                bar_sync(11, 256);
                const float2 o = *mlx;
                const float mn = fmaxf(m, o.x);
                l = l * ex2(m - mn) + o.y * ex2(o.x - mn);
                if ((wq4 >> 1) == rk) st_x4(gs + (B_ML + wq4 * 8 + g) * 4096 + (t >> 1) * 1024 + (j >> 1) * 16 + (t & 1) * 4, encf(mn), encf(l), 1u, 1u);
            }
        }
        uint32_t rl = sb + SM_RED + lane * 16;
        {
#pragma unroll 1
            for (int i = 0; i < 4; i++) mbar_wait(BAR(IT_WUV + i), 0);
            const uint32_t ab = sb + SM_U + B_WUV * 32768 + a128;
            load8<true>(a, [&](int s) { return ab + (s >> 1) * 8192 + (s & 1) * 2048; });
            uint32_t pa = sb + SM_PB + wq4 * 320 + frag_off(64 * v + 32 * (g >> 2) + 16 * (t & 1) + 8 * (t >> 1) + 2 * (g & 3));
            uint32_t fa = sb + SM_PB + g * 320 + t * 16, ra = sb + SM_RED + w8 * 288 + g * 16 + t * 4;
            uint32_t rb = sb + SM_RED + (u8 & 15) * 144 + ((u8 >> 4) & 3) * 32;
            const uint32_t* pe = gs + G_E1 + j * 8192 + (w8 >> 1) * 2048 + ((((cls >> 1) ^ (w8 >> 1)) & 1) << 10) + (((w8 & 1) * 16 + t) * 8 + g) * 4;
            uint32_t* p2 = gs + (B_E2 + (j >> 4)) * 4096 + (u8 >> 6) * 1024 + (j & 15) * 64 + (u8 & 63);
            pin(pa); pin(fa); pin(ra); pin(rb); pin(rl); pin(pe); pin(p2);
            uint4 pv[4];
            bar_sync(3, 288);
            poll_start<512>(pv, pe);
            bar_sync(8, 288);
            const uint4 wa = lds128(sb + SM_W + (wq4 * 4 + t) * 16);
            const uint32_t mk = (g & 1) ? 0xffff0000u : 0x0000ffffu, m0 = (g & 2) ? 0u : mk, m1 = (g & 2) ? mk : 0u;
            uint32_t wb[8] = {wa.x & m0, wa.x & m1, wa.y & m0, wa.y & m1, wa.z & m0, wa.z & m1, wa.w & m0, wa.w & m1};
#pragma unroll
            for (int i = 0; i < 8; i++) pin(wb[i]);
            poll<512, E1_SLEEP, true>(pv, pe);
            if (u8 == 0) TRACE_Q(18);
            float e[4][4];
#pragma unroll
            for (int i = 0; i < 4; i++) {
                e[i][0] = e[i][1] = e[i][2] = e[i][3] = 0.f;
                mma(e[i], pv[i].x, pv[i].y, pv[i].z, pv[i].w, wb[2 * i], wb[2 * i + 1]);
            }
            const float r0 = (t & 2) ? (e[0][2] + e[1][2]) + (e[2][2] + e[3][2]) : (e[0][0] + e[1][0]) + (e[2][0] + e[3][0]);
            const float r1 = (t & 2) ? (e[0][3] + e[1][3]) + (e[2][3] + e[3][3]) : (e[0][1] + e[1][1]) + (e[2][1] + e[3][1]);
            const uint32_t hi = pack2(r0, r1);
            sts32(pa, hi); sts32(pa + 1280, pack2(r0 - bflo(hi), r1 - bfhi(hi)));
            bar_sync(1, 256);
            if (u8 == 0) TRACE(19);
            ldfrag(b, fa);
            mma8(c, a, b);
            stsf(ra, c[0] + c[1]); stsf(ra + 144, c[2] + c[3]);
            bar_sync(4, 288);
            if (w8 < 4) {
                const float inv = *(const float*)(sm + SM_FQ);
                st_x1(p2, enc(pack2(sum4(ldsf4(rb)) * inv, sum4(ldsf4(rb + 16)) * inv)));
            }
            if (u8 == 0) TRACE(20);
        }
        uint32_t mb[4];
        poll_start<1024>(mb, gs + near_off(B_MB, cls) + pi);
        {
            const uint32_t nz = lb4 ? 0x80008000u : 0u;
#pragma unroll
            for (int i = 0; i < 4; i++) b[i] = make_uint4(nz, nz, nz, nz);
            const bool early = __all_sync(0xffffffffu, mbar_test(BAR(IT_WO + (w8 >> 1)), 0));
            const uint32_t ab = sb + SM_U + B_WO * 32768 + (w8 >> 1) * 8192 + (a64 ^ ((w8 & 1) * 32));
            if (early) load8<true>(a, [&](int s) { return ab + s * 1024; });
            uint32_t ra = sb + SM_R3 + ((w8 & 1) * 16 + g) * 48 + (w8 >> 1) * 8 + t * 4, rb = sb + SM_R3 + (lane & 15) * 96;
            uint32_t* p3 = gs + (B_E3 + ((j >> 3) & 1)) * 4096 + lb4 * 1024 + (j >> 4) * 128 + (j & 7) * 16 + (lane & 15);
            pin(ra); pin(rb); pin(p3);
            poll<16, E2_SLEEP, true>(b, gs + near_off(B_E2 + (j >> 4), cls) + (w8 >> 1) * 256 + lane * 16);
            if (!early) { mbar_wait(BAR(IT_WO + (w8 >> 1)), 0); load8<true>(a, [&](int s) { return ab + s * 1024; }); }
            if (u8 == 0) TRACE(21);
            mma8(c, a, b);
            if (t < 2) { stsf(ra, c[0] + c[1]); stsf(ra + 384, c[2] + c[3]); }
            bar_sync(1, 256);
            if (w8 == 0) st_x1(p3, enc(pack2(sum4(ldsf4(rb)) + sum4(ldsf4(rb + 16)), sum4(ldsf4(rb + 48)) + sum4(ldsf4(rb + 64)))));
            if (u8 == 0) TRACE(22);
        }
        poll<1024, MB_SLEEP, true>(mb, gs + near_off(B_MB, cls) + pi);
        const uint32_t* p3 = gs + near_off(B_E3 + (pi >> 7), cls) + lb4 * 512 + (pi & 127);
        const float x0 = lb4 ? 0.f : bflo(xw), x1 = lb4 ? 0.f : bfhi(xw);
        uint32_t e3[4];
        if (j < NFF) {
            const int ct = (w8 >> 1) & 1, kh = w8 & 1;
            const uint32_t kk = pack2(1.f + bflo(mb[2]), 1.f + bfhi(mb[2]));
            uint32_t za = sb + SM_FZ + frag_off(w8 * 32 + (lane & 15) * 2);
            sts32(za + (4 + lb4) * 576, lb4 ? mb[1] : kk);
            za += lb4 * 2 * 576;
            const bool early = __all_sync(0xffffffffu, mbar_test(BAR(IT_GU + v * 2 + kh), 0));
            const uint32_t ab = sb + SM_U + B_GU * 32768 + (v * 2 + kh) * 8192 + (a64 ^ (ct * 32));
            if (early) load8<true>(a, [&](int s) { return ab + s * 1024; });
            uint32_t fa = sb + SM_FZ + (g < 6 ? g : 0) * 576 + kh * 256 + t * 16;
            uint32_t ra = peer_addr(sb + SM_RED + (rk * 2 + kh) * 512 + (v * 16 + g) * 16 + t * 4, ct), tbo = peer_addr(BAR(QB), ct);
            uint32_t sa = peer_addr(sb + SM_RED + 2048 + (rk * 8 + w8) * 8, lane & 1), tbs = peer_addr(BAR(QB), lane & 1);
            uint32_t ad = sb + SM_U + B_DN * 32768 + w8 * 2048 + (r8 + 8 * lb4) * 128 + (lb3 ^ r8) * 16;
            uint32_t* p5 = gs + (B_E5 + (w8 * 2 + (t >> 1)) * 2 + (j >> 6)) * 4096 + (j & 63) * 16 + (t & 1) * 8 + g;
            pin(za); pin(fa); pin(ra); pin(tbo); pin(sa); pin(tbs); pin(ad); pin(p5);
            if (lane == 0) mbar_expect(BAR(QB), 272);
            poll<512, E3_SLEEP>(e3, p3);
            if (u8 == 0) TRACE(23);
            const float y0 = fmaf(bflo(mb[0]), sumlo(e3), x0), y1 = fmaf(bfhi(mb[0]), sumhi(e3), x1);
            const float z0 = y0 * bflo(kk), z1 = y1 * bfhi(kk);
            const uint32_t zh = pack2(z0, z1);
            sts32(za, zh); sts32(za + 576, pack2(z0 - bflo(zh), z1 - bfhi(zh)));
            const float yo = shx(lb4 ? y0 : y1, 16);
            bar_sync(1, 256);
            if (u8 == 0) TRACE(24);
            ldfrag(b, fa);
            if (!early) { mbar_wait(BAR(IT_GU + v * 2 + kh), 0); load8<true>(a, [&](int s) { return ab + s * 1024; }); }
            mma8(c, a, b);
            {
                const float y = (lb4 ? y1 : y0) + yo;
                float s = y, q = y * y;
#pragma unroll
                for (int o = 16; o; o >>= 1) { s += shx(s, o); q += shx(q, o); }
                if (lane < 2) st_async2(sa, s, q, tbs);
            }
            {
                const float s1 = shx(c[1], 1), s3 = shx(c[3], 1);
                st_async1(ra, t < 2 ? c[0] + c[1] : t == 2 ? c[0] : s1, tbo);
                st_async1(ra + 128, t < 2 ? c[2] + c[3] : t == 2 ? c[2] : s3, tbo);
            }
            const bool early5 = __all_sync(0xffffffffu, mbar_test(BAR(IT_DOWN + v), 0));
            if (early5) {
#pragma unroll
                for (int k = 0; k < 4; k++) a[k] = ldsm<true>(ad ^ (k * 32));
            }
            mbar_wait(BAR(QB), 1);
            if (u8 == 0) TRACE(25);
            const float4 f0 = ldsf4(rl), f1 = ldsf4(rl + 512), f2 = ldsf4(rl + 1024), f3 = ldsf4(rl + 1536);
            float4 st[8];
#pragma unroll
            for (int i = 0; i < 8; i++) st[i] = *(const float4*)(sm + SM_RED + 2048 + i * 16);
            const float su = (((st[0].x + st[0].z) + (st[1].x + st[1].z)) + ((st[2].x + st[2].z) + (st[3].x + st[3].z)))
                           + (((st[4].x + st[4].z) + (st[5].x + st[5].z)) + ((st[6].x + st[6].z) + (st[7].x + st[7].z)));
            const float sq = (((st[0].y + st[0].w) + (st[1].y + st[1].w)) + ((st[2].y + st[2].w) + (st[3].y + st[3].w)))
                           + (((st[4].y + st[4].w) + (st[5].y + st[5].w)) + ((st[6].y + st[6].w) + (st[7].y + st[7].w)));
            const float mu = su * (1.f / 512.f);
            float rstd;
            asm("rsqrt.approx.ftz.f32 %0, %1;" : "=f"(rstd) : "f"(fmaxf(fmaf(-mu, mu, sq * (1.f / 512.f)), 0.f) + 1e-5f));
            const float fz = ((f0.x + f0.y) + (f1.x + f1.y)) + ((f2.x + f2.y) + (f3.x + f3.y));
            const float gu = fmaf(rstd, fmaf(-mu, (f0.z + f1.z) + (f2.z + f3.z), fz), (f0.w + f1.w) + (f2.w + f3.w));
            const float uu = shx(gu, 16);
            const float hh = __fdividef(gu, 1.f + ex2(-gu * fmaf(gu * gu, 0.10294324f, 2.3022082f))) * uu;
            const uint32_t b0 = pack2(__shfl_sync(0xffffffffu, hh, 2 * t), __shfl_sync(0xffffffffu, hh, 2 * t + 1));
            const uint32_t b1 = pack2(__shfl_sync(0xffffffffu, hh, 2 * t + 8), __shfl_sync(0xffffffffu, hh, 2 * t + 9));
            if (!early5) {
                mbar_wait(BAR(IT_DOWN + v), 0);
#pragma unroll
                for (int k = 0; k < 4; k++) a[k] = ldsm<true>(ad ^ (k * 32));
            }
            uint32_t res = 0;
#pragma unroll
            for (int k = 0; k < 4; k++) {
                c[0] = c[1] = c[2] = c[3] = 0.f;
                mma(c, a[k].x, a[k].y, a[k].z, a[k].w, b0, b1);
                if (t == k) res = pack2(c[0], c[2]);
            }
            st2_x1(p5, enc(res));
            if (u8 == 0) { TRACE(27); TRACE_GT(47); }
        } else {
            float y0 = 0.f, y1 = 0.f;
            if (w8 == 0) {
                poll<512, 100>(e3, p3);
                y0 = fmaf(bflo(mb[0]), sumlo(e3), x0); y1 = fmaf(bfhi(mb[0]), sumhi(e3), x1);
                y0 += shx(y0, 16); y1 += shx(y1, 16);
            }
            uint32_t ra = sb + SM_RED + (lb3 * 16 + r8) * 80 + (w8 * 2 + lb4) * 4, rb = sb + SM_RED + lane * 160;
            uint32_t* po = (uint32_t*)out + pi;
            pin(ra); pin(rb); pin(po);
            uint32_t yv[7];
            poll<1024, E5_SLEEP, false, 16384>(yv, gs + near_off(B_E5 + (j - NFF) * 2, cls) + (2 * w8 + lb4) * 16 + (lane & 15));
            if (u8 == 0) TRACE(26);
            stsf(ra, ((bflo(yv[0]) + bflo(yv[1])) + (bflo(yv[2]) + bflo(yv[3]))) + ((bflo(yv[4]) + bflo(yv[5])) + bflo(yv[6])));
            stsf(ra + 640, ((bfhi(yv[0]) + bfhi(yv[1])) + (bfhi(yv[2]) + bfhi(yv[3]))) + ((bfhi(yv[4]) + bfhi(yv[5])) + bfhi(yv[6])));
            bar_sync(1, 256);
            if (u8 < 16) {
                const float s0 = (sum4(ldsf4(rb)) + sum4(ldsf4(rb + 16))) + (sum4(ldsf4(rb + 32)) + sum4(ldsf4(rb + 48)));
                const float s1 = (sum4(ldsf4(rb + 80)) + sum4(ldsf4(rb + 96))) + (sum4(ldsf4(rb + 112)) + sum4(ldsf4(rb + 128)));
                *po = pack2(fmaf(bflo(mb[3]), s0, y0), fmaf(bfhi(mb[3]), s1, y1));
            }
            if (u8 == 0) TRACE(27);
        }
    }
}

typedef CUresult (*EncFn)(CUtensorMap*, CUtensorMapDataType, cuuint32_t, void*, const cuuint64_t*, const cuuint64_t*,
                          const cuuint32_t*, const cuuint32_t*, CUtensorMapInterleave, CUtensorMapSwizzle,
                          CUtensorMapL2promotion, CUtensorMapFloatOOBfill);

void make_map(EncFn enc_fn, CUtensorMap* m, const void* p, cuuint64_t d0, cuuint64_t d1, cuuint64_t d2, cuuint64_t d3,
              cuuint64_t s1, cuuint64_t s2, cuuint64_t s3, cuuint32_t b0, cuuint32_t b1, cuuint32_t b2, cuuint32_t b3, CUtensorMapSwizzle sw) {
    const cuuint64_t dims[4] = {d0, d1, d2, d3}, strides[3] = {s1, s2, s3};
    const cuuint32_t box[4] = {b0, b1, b2, b3}, es[4] = {1, 1, 1, 1};
    enc_fn(m, CU_TENSOR_MAP_DATA_TYPE_BFLOAT16, 4, (void*)p, dims, strides, box, es,
           CU_TENSOR_MAP_INTERLEAVE_NONE, sw, CU_TENSOR_MAP_L2_PROMOTION_L2_64B, CU_TENSOR_MAP_FLOAT_OOB_FILL_NONE);
}

uint32_t* scratch = nullptr;

}

extern "C" void kernel_launch(void* const* d_in, const int* in_sizes, int n_in, void* d_out, int out_size) {
    (void)in_sizes; (void)n_in; (void)out_size;
    static Maps maps;
    static const void* cached[12] = {};
    static bool ready = false;
    bool same = ready;
    for (int i = 0; i < 12 && same; i++) same = cached[i] == d_in[i];
    if (!same) {
        void* fn = nullptr;
        cudaDriverEntryPointQueryResult qr;
        cudaGetDriverEntryPoint("cuTensorMapEncodeTiled", &fn, cudaEnableDefault, &qr);
        EncFn e = (EncFn)fn;
        const CUtensorMapSwizzle S64 = CU_TENSOR_MAP_SWIZZLE_64B, S128 = CU_TENSOR_MAP_SWIZZLE_128B;
        make_map(e, &maps.m[MP_WQ], d_in[2], 64, 512, 64, 1, 8192, 128, 8192, 64, 64, 1, 1, S128);
        make_map(e, &maps.m[MP_WUK], d_in[3], 64, 512, 64, 1, 8192, 128, 8192, 64, 64, 1, 1, S128);
        make_map(e, &maps.m[MP_CKV], d_in[1], 64, 8, 8, 4096, 1024, 128, 8192, 64, 8, 4, 2, S128);
        make_map(e, &maps.m[MP_MODB], d_in[11], 3072, 512, 1, 1, 6144, 6144, 6144, 32, 128, 1, 1, S64);
        make_map(e, &maps.m[MP_WUV], d_in[4], 64, 512, 64, 1, 8192, 128, 8192, 64, 32, 2, 1, S128);
        make_map(e, &maps.m[MP_WO], d_in[5], 512, 4096, 1, 1, 1024, 1024, 1024, 32, 128, 1, 1, S64);
        make_map(e, &maps.m[MP_GATE], d_in[7], 1792, 512, 1, 1, 3584, 3584, 3584, 32, 128, 1, 1, S64);
        make_map(e, &maps.m[MP_UP], d_in[8], 1792, 512, 1, 1, 3584, 3584, 3584, 32, 128, 1, 1, S64);
        make_map(e, &maps.m[MP_DOWN], d_in[9], 64, 1792, 8, 1, 1024, 128, 1024, 64, 16, 4, 1, S128);
        {
            int ids[64], slot[64], dep[64], n = 0;
            auto add = [&](int id0, int cnt, int slot0, int d) { for (int k = 0; k < cnt; k++) { ids[n] = id0 + k; slot[n] = slot0 + k; dep[n] = k ? -1 : d; n++; } };
            int occ[6] = {-1, -1, -1, -1, EB_WQ, EB_WUK};
            auto put = [&](int id0, int cnt, int buf, int rel) { add(id0, cnt, 4 * buf, occ[buf]); occ[buf] = rel; };
            add(IT_MODA, 1, SM_XA / 8192, -1); add(IT_WQ, 8, 16, -1);
            for (const char* c = ORDER; *c; c++) {
                if (*c >= '0' && *c <= '7') put(IT_CKV + 4 * (*c - '0'), 4, unit_buf(*c - '0'), EB_UNIT0 + (*c - '0'));
                if (*c == 'V') put(IT_WUV, 4, B_WUV, -1);
                if (*c == 'O') put(IT_WO, 4, B_WO, -1);
                if (*c == 'M') add(IT_MODB, 2, SM_MB / 8192, occ[B_DN]);
                if (*c == 'G') put(IT_GU, 4, B_GU, -1);
                if (*c == 'D') add(IT_DOWN, 2, 4 * B_DN, occ[B_DN]);
            }
            for (int i = 0; i < 64; i++) maps.sched[i] = 0;
            for (int i = 0; i < n; i++) {
                const int w = i >= I_POST ? W_POST : i < I_FIRST ? W_FIRST : i < I_MID ? W_HEAD : i < I_TAIL ? W_MID : W_TAIL;
                const int wi = (i >= W0 && i - w >= 0) ? (ids[i - w] && ids[i - w] <= NCP ? 1 : ids[i - w]) + 1 : 0;
                const int wb = (i >= A_FROM && i < A_TO && i - w - ADAPT >= 0) ? ids[i - w - ADAPT] + 1 : 0;
                maps.sched[i] = ids[i] | slot[i] << 6 | (dep[i] + 1) << 11 | wi << 18 | wb << 25;
            }
        }
        cudaGetSymbolAddress((void**)&scratch, g_scratch);
        scratch = (uint32_t*)(((uintptr_t)scratch + (2u << 20) - 1) & ~(uintptr_t)((2u << 20) - 1));
        cudaFuncSetAttribute(fused_kernel, cudaFuncAttributeMaxDynamicSharedMemorySize, SM_TOTAL);
        for (int i = 0; i < 12; i++) cached[i] = d_in[i];
        ready = true;
    }
    const First f = {{(const uint8_t*)d_in[2], (const uint8_t*)d_in[11]}, {(const __nv_bfloat16*)d_in[0], (const __nv_bfloat16*)d_in[10]}};
    fused_kernel<<<NCTA, NTHREADS, SM_TOTAL>>>(f, (__nv_bfloat16*)d_out, scratch, maps);
}
```

```cpp
#include <cuda_runtime.h>
#include <cuda_bf16.h>
#include <cuda.h>
#include <stdint.h>

namespace {

constexpr int NCTA = 128;
constexpr int NTHREADS = 512;
constexpr int NUNITS = 8;
constexpr int NFF = 56, J_RED = 104, J_END = 120;
constexpr uint32_t SPIN_LIMIT = 1u << 22;

#define XC_LATE 4
#define MODA_PF ".L2::128B"
#define PREZERO 1
#define E1_DIRECT 0
#define STAG 300
#define TU 2
#define NUMA 1
#define NPROBE 3
#define NCP 2
#define W0 4
#define RD_ITEM 15
#define JAN_SLEEP 100
#define RD_SLEEP 400
#define HA_DELAY 200
#define H_SLEEP 100
#define QA_DELAY 600
#define QA_SLEEP 200
#define ML_DELAY 300
#define ML_SLEEP 50
#define E1_SLEEP 50
#define E2_SLEEP 0
#define E3_SLEEP 0
#define E5_SLEEP 0
#define MB_SLEEP 100
constexpr int B_WUV = 2, B_WO = 3, B_X = 4  , B_DN = 0;

constexpr int SM_U = 0;
constexpr int SM_XA = 6 * 32768;
constexpr int SM_XB = SM_XA + 12288;
constexpr int SM_MX = SM_XB + 16384;
constexpr int SM_FZ = SM_XB + 8192;
constexpr int SM_PB = SM_XB;
constexpr int SM_R3 = SM_XB + 2560;
constexpr int SM_Y = SM_XB + 12288;
constexpr int SM_RED = SM_XB + 4096;
constexpr int SM_FS = SM_XB + 20480;
constexpr int SM_FV = SM_FS + 1024;
constexpr int SM_QX = SM_XA + 8192;
constexpr int SM_FQ = SM_FV + 512;
constexpr int SM_CLS = SM_FQ + 128;
constexpr int SM_W = SM_FQ + 256;
constexpr int SM_SCR = SM_XA + 9216;
constexpr int SM_TR = SM_XB + 19456;
constexpr int SM_BAR = SM_W + 256;
constexpr int SM_TOTAL = SM_BAR + 1024;
static_assert(SM_TOTAL <= 232448, "smem");

enum { IT_MODA = 0, IT_WQ = 1, IT_WUK = 5, IT_CKV = 9, IT_WUV = 41, IT_WO = 45, IT_X = 49  , IT_DOWN = 53, NITEMS = 55,
       NEVER = 63,
       SF0 = 64,
       PF0 = 80,
       EB_UNIT0 = 96, MBB = 103,
       EB_WQ = 104, EB_WUK, QT, QB, JD };

enum { MP_WQ = 0, MP_WUK, MP_CKV, MP_MODB, MP_WUV, MP_WO, MP_GATE, MP_UP, MP_DOWN, NMAPS };
struct First { const uint8_t* w[2]; const __nv_bfloat16* v[2]; };
struct Maps { CUtensorMap m[NMAPS]; uint32_t sched[3][72]; };

enum { B_HA = 0,
       B_MB = 6,
       B_RD = 7,
       B_E2 = 8,
       B_QA = 16,
       B_ML = 32,
       B_E5 = 64,
       B_E3 = 80,
       B_PR = 96,
       B_TR = 100 };
constexpr int G_E1 = 1 << 19;
constexpr int G_TR = B_TR * 4096;
__device__ __align__(1024) uint32_t g_scratch[(8 << 20) / 4];

#define TRACE(slot) do {} while (0)
#define TRACE_Q(slot) do {} while (0)
#define TRACE_GT(slot) do {} while (0)

#define CLK(var, cond) do {} while (0)
#define CLKD(var, cond, dep) do {} while (0)
#define TK(i) do {} while (0)
#define TKD(i, dep) do {} while (0)
__device__ __forceinline__ uint32_t s2u(const void* p) { return (uint32_t)__cvta_generic_to_shared(p); }
__device__ __forceinline__ void mbar_init(uint32_t b, int c) { asm volatile("mbarrier.init.shared::cta.b64 [%0], %1;" :: "r"(b), "r"(c) : "memory"); }
__device__ __forceinline__ void mbar_expect(uint32_t b, uint32_t bytes) { asm volatile("mbarrier.arrive.expect_tx.shared::cta.b64 _, [%0], %1;" :: "r"(b), "r"(bytes) : "memory"); }
__device__ __forceinline__ void mbar_arrive(uint32_t b) { asm volatile("mbarrier.arrive.shared::cta.b64 _, [%0];" :: "r"(b) : "memory"); }
__device__ __forceinline__ void mbar_wait(uint32_t b, uint32_t ph) {
    asm volatile("{\n.reg .pred p;\nW: mbarrier.try_wait.parity.shared::cta.b64 p, [%0], %1;\n@!p bra W;\n}" :: "r"(b), "r"(ph) : "memory");
}
__device__ __forceinline__ void mbar_waitb(uint32_t b, uint32_t ph) {
    asm volatile("{\n.reg .pred p;\n.reg .u32 n;\nmov.u32 n, 0;\n"
                 "W: mbarrier.try_wait.parity.shared::cta.b64 p, [%0], %1;\n@p bra D;\n"
                 "add.u32 n, n, 1;\nsetp.lt.u32 p, n, 0x100000;\n@p bra W;\ntrap;\nD:\n}" :: "r"(b), "r"(ph) : "memory");
}
__device__ __forceinline__ uint32_t mbar_test(uint32_t b, uint32_t ph) {
    uint32_t ok;
    asm volatile("{\n.reg .pred p;\nmbarrier.test_wait.parity.shared::cta.b64 p, [%1], %2;\nselp.u32 %0, 1, 0, p;\n}" : "=r"(ok) : "r"(b), "r"(ph) : "memory");
    return ok;
}
__device__ __forceinline__ void bar_sync(int id, int n) { asm volatile("bar.sync %0, %1;" :: "r"(id), "r"(n) : "memory"); }
__device__ __forceinline__ void bar_arrive(int id, int n) { asm volatile("bar.arrive %0, %1;" :: "r"(id), "r"(n) : "memory"); }
__device__ __forceinline__ uint32_t peer_addr(uint32_t a, uint32_t rank) { uint32_t r; asm("mapa.shared::cluster.u32 %0, %1, %2;" : "=r"(r) : "r"(a), "r"(rank)); return r; }
__device__ __forceinline__ void st_async1(uint32_t a, float x, uint32_t bar) {
    asm volatile("st.async.weak.shared::cluster.mbarrier::complete_tx::bytes.f32 [%0], %1, [%2];" :: "r"(a), "f"(x), "r"(bar) : "memory");
}
__device__ __forceinline__ void st_async2(uint32_t a, float x, float y, uint32_t bar) {
    asm volatile("st.async.weak.shared::cluster.mbarrier::complete_tx::bytes.v2.f32 [%0], {%1, %2}, [%3];" :: "r"(a), "f"(x), "f"(y), "r"(bar) : "memory");
}
__device__ __forceinline__ uint32_t gtime() { uint32_t t; asm volatile("mov.u32 %0, %%globaltimer_lo;" : "=r"(t)); return t; }
__device__ __forceinline__ void fence_gpu() { asm volatile("fence.acq_rel.gpu;" ::: "memory"); }

__device__ __forceinline__ uint32_t enc(uint32_t b) { uint32_t r; asm("max.u32 %0, %1, 1;" : "=r"(r) : "r"(b)); return r; }
__device__ __forceinline__ uint32_t encf(float f) { return enc(__float_as_uint(f)); }
__device__ __forceinline__ void st_x1(uint32_t* p, uint32_t v) { asm volatile("st.relaxed.gpu.global.u32 [%0], %1;" :: "l"(p), "r"(v) : "memory"); }
__device__ __forceinline__ void st_x4(void* p, uint32_t a, uint32_t b, uint32_t c, uint32_t d) {
    asm volatile("st.relaxed.gpu.global.v4.u32 [%0], {%1, %2, %3, %4};" :: "l"(p), "r"(a), "r"(b), "r"(c), "r"(d) : "memory");
}
__device__ __forceinline__ void st2_x1(uint32_t* p, uint32_t v) { st_x1(p, v); st_x1(p + 1024, v); }
__device__ __forceinline__ void st2_x4(uint32_t* p, uint32_t a, uint32_t b, uint32_t c, uint32_t d) { st_x4(p, a, b, c, d); st_x4(p + 1024, a, b, c, d); }
__device__ __forceinline__ int near_off(int b, uint32_t cls) { return b * 4096 + (((__popc(b & 0x2C) ^ cls) & 1) << 10); }
__device__ __forceinline__ void ld_x(uint32_t& v, const void* p) { asm volatile("ld.relaxed.gpu.global.u32 %0, [%1];" : "=r"(v) : "l"(p) : "memory"); }
__device__ __forceinline__ void ld_x(uint4& v, const void* p) {
    asm volatile("ld.relaxed.gpu.global.v4.u32 {%0, %1, %2, %3}, [%4];" : "=r"(v.x), "=r"(v.y), "=r"(v.z), "=r"(v.w) : "l"(p) : "memory");
}
__device__ __forceinline__ void ld_x(uint2& v, const void* p) { asm volatile("ld.relaxed.gpu.global.v2.u32 {%0, %1}, [%2];" : "=r"(v.x), "=r"(v.y) : "l"(p) : "memory"); }
__device__ __forceinline__ uint32_t minw(uint32_t v) { return v; }
__device__ __forceinline__ uint32_t minw(const uint2& v) { return min(v.x, v.y); }
__device__ __forceinline__ uint32_t minw(const uint4& v) { return min(__vimin3_u32(v.x, v.y, v.z), v.w); }
template <int N> __device__ __forceinline__ uint32_t mint(const uint32_t* m) {
    if constexpr (N == 1) return m[0];
    else if constexpr (N == 2) return min(m[0], m[1]);
    else return __vimin3_u32(mint<(N + 2) / 3>(m), mint<(N + 1) / 3>(m + (N + 2) / 3), mint<N / 3>(m + (N + 2) / 3 + (N + 1) / 3));
}

template <int STRIDE, int S4 = 4 * STRIDE, typename T, int N>
__device__ __forceinline__ void poll_start(T (&v)[N], const void* base) {
#pragma unroll
    for (int i = 0; i < N; i++) ld_x(v[i], (const uint8_t*)base + (i & 3) * STRIDE + (i >> 2) * S4);
}
struct Nop { __device__ void operator()() const {} };
template <int STRIDE, int SLEEP, bool STARTED = false, int S4 = 4 * STRIDE, typename T, int N, typename F = Nop>
__device__ __forceinline__ void poll(T (&v)[N], const void* base, F idle = F()) {
    if (!STARTED) { poll_start<STRIDE, S4>(v, base); idle(); }
#pragma unroll 1
    for (uint32_t it = 0;; it++) {
        uint32_t m[N];
#pragma unroll
        for (int i = 0; i < N; i++) m[i] = minw(v[i]);
        if (__all_sync(0xffffffffu, mint<N>(m) != 0)) break;
        if (SLEEP && it > 0) __nanosleep(SLEEP);
#pragma unroll
        for (int i = 0; i < N; i++) if (!m[i]) ld_x(v[i], (const uint8_t*)base + (i & 3) * STRIDE + (i >> 2) * S4);
        idle();
        if (it > SPIN_LIMIT) __trap();
    }
}

__device__ __forceinline__ float bflo(uint32_t w) { return __uint_as_float(w << 16); }
__device__ __forceinline__ float bfhi(uint32_t w) { return __uint_as_float(w & 0xffff0000u); }
__device__ __forceinline__ uint32_t pack2(float lo, float hi) {
    uint32_t r; asm("cvt.rn.bf16x2.f32 %0, %1, %2;" : "=r"(r) : "f"(hi), "f"(lo)); return r;
}
__device__ __forceinline__ float rbf(float x) { return __uint_as_float(pack2(0.f, x)); }
__device__ __forceinline__ float sumlo(const uint32_t (&v)[8]) { return ((bflo(v[0]) + bflo(v[1])) + (bflo(v[2]) + bflo(v[3]))) + ((bflo(v[4]) + bflo(v[5])) + (bflo(v[6]) + bflo(v[7]))); }
__device__ __forceinline__ float sumhi(const uint32_t (&v)[8]) { return ((bfhi(v[0]) + bfhi(v[1])) + (bfhi(v[2]) + bfhi(v[3]))) + ((bfhi(v[4]) + bfhi(v[5])) + (bfhi(v[6]) + bfhi(v[7]))); }
__device__ __forceinline__ float ex2(float x) { float r; asm("ex2.approx.ftz.f32 %0, %1;" : "=f"(r) : "f"(x)); return r; }
__device__ __forceinline__ float shx(float v, int m) { return __shfl_xor_sync(0xffffffffu, v, m); }
__device__ __forceinline__ uint4 lds128(uint32_t a) { uint4 v; asm volatile("ld.shared.v4.u32 {%0, %1, %2, %3}, [%4];" : "=r"(v.x), "=r"(v.y), "=r"(v.z), "=r"(v.w) : "r"(a) : "memory"); return v; }
__device__ __forceinline__ uint32_t lds32(uint32_t a) { uint32_t v; asm volatile("ld.shared.u32 %0, [%1];" : "=r"(v) : "r"(a) : "memory"); return v; }
__device__ __forceinline__ void sts32(uint32_t a, uint32_t v) { asm volatile("st.shared.u32 [%0], %1;" :: "r"(a), "r"(v) : "memory"); }
__device__ __forceinline__ void sts16(uint32_t a, uint32_t v) { asm volatile("st.shared.u16 [%0], %1;" :: "r"(a), "h"((uint16_t)v) : "memory"); }
__device__ __forceinline__ int frag_off(int k) { return (k >> 5) * 64 + ((k >> 1) & 3) * 16 + ((k >> 4) & 1) * 8 + ((k >> 3) & 1) * 4 + (k & 1) * 2; }

template <bool TRANS>
__device__ __forceinline__ uint4 ldsm(uint32_t a) {
    uint4 r;
    if (TRANS) asm volatile("ldmatrix.sync.aligned.m8n8.x4.trans.shared.b16 {%0, %1, %2, %3}, [%4];" : "=r"(r.x), "=r"(r.y), "=r"(r.z), "=r"(r.w) : "r"(a) : "memory");
    else asm volatile("ldmatrix.sync.aligned.m8n8.x4.shared.b16 {%0, %1, %2, %3}, [%4];" : "=r"(r.x), "=r"(r.y), "=r"(r.z), "=r"(r.w) : "r"(a) : "memory");
    return r;
}
__device__ __forceinline__ void mma(float (&c)[4], uint32_t a0, uint32_t a1, uint32_t a2, uint32_t a3, uint32_t b0, uint32_t b1) {
    asm volatile("mma.sync.aligned.m16n8k16.row.col.f32.bf16.bf16.f32 {%0,%1,%2,%3}, {%4,%5,%6,%7}, {%8,%9}, {%0,%1,%2,%3};"
                 : "+f"(c[0]), "+f"(c[1]), "+f"(c[2]), "+f"(c[3]) : "r"(a0), "r"(a1), "r"(a2), "r"(a3), "r"(b0), "r"(b1));
}
template <bool TRANS, typename F>
__device__ __forceinline__ void load8(uint4 (&a)[8], F addr) {
    __syncwarp();
#pragma unroll
    for (int s = 0; s < 8; s++) a[s] = ldsm<TRANS>(addr(s));
}
__device__ __forceinline__ void mma8(float (&c)[4], const uint4 (&a)[8], const uint4 (&b)[4]) {
    float e[4][4];
#pragma unroll
    for (int s = 0; s < 8; s++) {
        if (s < 4) e[s][0] = e[s][1] = e[s][2] = e[s][3] = 0.f;
        mma(e[s & 3], a[s].x, a[s].y, a[s].z, a[s].w, (s & 1) ? b[s >> 1].z : b[s >> 1].x, (s & 1) ? b[s >> 1].w : b[s >> 1].y);
    }
#pragma unroll
    for (int i = 0; i < 4; i++) c[i] = (e[0][i] + e[1][i]) + (e[2][i] + e[3][i]);
}
__device__ __forceinline__ void ldfrag(uint4 (&b)[4], uint32_t a) {
    asm volatile("ld.shared.v4.u32 {%0,%1,%2,%3}, [%16];\nld.shared.v4.u32 {%4,%5,%6,%7}, [%16+64];\n"
                 "ld.shared.v4.u32 {%8,%9,%10,%11}, [%16+128];\nld.shared.v4.u32 {%12,%13,%14,%15}, [%16+192];\n"
                 : "=r"(b[0].x), "=r"(b[0].y), "=r"(b[0].z), "=r"(b[0].w), "=r"(b[1].x), "=r"(b[1].y), "=r"(b[1].z), "=r"(b[1].w),
                   "=r"(b[2].x), "=r"(b[2].y), "=r"(b[2].z), "=r"(b[2].w), "=r"(b[3].x), "=r"(b[3].y), "=r"(b[3].z), "=r"(b[3].w) : "r"(a) : "memory");
}
__device__ __forceinline__ void pin(uint32_t& x) { asm volatile("" : "+r"(x)); }
template <typename T> __device__ __forceinline__ void pin(T*& x) { asm volatile("" : "+l"(x)); }
__device__ __forceinline__ float4 ldsf4(uint32_t a) { const uint4 v = lds128(a); return make_float4(__uint_as_float(v.x), __uint_as_float(v.y), __uint_as_float(v.z), __uint_as_float(v.w)); }
__device__ __forceinline__ float sum4(const float4& f) { return (f.x + f.y) + (f.z + f.w); }
__device__ __forceinline__ void stsf(uint32_t a, float v) { sts32(a, __float_as_uint(v)); }

__device__ __forceinline__ void wg_fence() { asm volatile("wgmma.fence.sync.aligned;" ::: "memory"); }
__device__ __forceinline__ void wg_commit() { asm volatile("wgmma.commit_group.sync.aligned;" ::: "memory"); }
__device__ __forceinline__ void wg_wait1() { asm volatile("wgmma.wait_group.sync.aligned 1;" ::: "memory"); }
__device__ __forceinline__ void wg_wait0() { asm volatile("wgmma.wait_group.sync.aligned 0;" ::: "memory"); }
#define R8(o) "+f"(d[o]), "+f"(d[o + 1]), "+f"(d[o + 2]), "+f"(d[o + 3]), "+f"(d[o + 4]), "+f"(d[o + 5]), "+f"(d[o + 6]), "+f"(d[o + 7])
__device__ __forceinline__ void wgmma_rs_n32(float (&d)[16], const uint4& a, uint64_t db, int acc) {
    asm volatile("{\n.reg .pred p;\nsetp.ne.b32 p, %21, 0;\n"
        "wgmma.mma_async.sync.aligned.m64n32k16.f32.bf16.bf16 "
        "{%0,%1,%2,%3,%4,%5,%6,%7,%8,%9,%10,%11,%12,%13,%14,%15}, {%16,%17,%18,%19}, %20, p, 1, 1, 0;\n}"
        : R8(0), R8(8) : "r"(a.x), "r"(a.y), "r"(a.z), "r"(a.w), "l"(db), "r"(acc));
}
#define PV_LO "{%0,%1,%2,%3,%4,%5,%6,%7,%8,%9,%10,%11,%12,%13,%14,%15,%16,%17,%18,%19,%20,%21,%22,%23,%24,%25,%26,%27,%28,%29,%30,%31,%32,%33,%34,%35,%36,%37,%38,%39,%40,%41,%42,%43,%44,%45,%46,%47,%48,%49,%50,%51,%52,%53,%54,%55,%56,%57,%58,%59,%60,%61,%62,%63}, "
#define PV_HI "{%64,%65,%66,%67,%68,%69,%70,%71,%72,%73,%74,%75,%76,%77,%78,%79,%80,%81,%82,%83,%84,%85,%86,%87,%88,%89,%90,%91,%92,%93,%94,%95,%96,%97,%98,%99,%100,%101,%102,%103,%104,%105,%106,%107,%108,%109,%110,%111,%112,%113,%114,%115,%116,%117,%118,%119,%120,%121,%122,%123,%124,%125,%126,%127}, "
__device__ __forceinline__ void wgmma_pv(float (&d)[128], const uint4& a, uint32_t blo, int acc) {
    asm volatile("{\n.reg .pred p;\n.reg .b32 u0, u1, u2, u3, t;\n.reg .b64 d0, d1, d2, d3;\nsetp.ne.b32 p, %133, 0;\n"
        "mov.b64 d0, {%132, 0x40000100};\nadd.u32 t, %132, 512;\nmov.b64 d1, {t, 0x40000100};\n"
        "add.u32 t, %132, 128;\nmov.b64 d2, {t, 0x40000100};\nadd.u32 t, %132, 640;\nmov.b64 d3, {t, 0x40000100};\n"
        "wgmma.fence.sync.aligned;\n"
        "wgmma.mma_async.sync.aligned.m64n128k16.f32.bf16.bf16 " PV_LO "{%128, u0, %129, u1}, d0, p, 1, 1, 1;\n"
        "wgmma.mma_async.sync.aligned.m64n128k16.f32.bf16.bf16 " PV_LO "{%130, u2, %131, u3}, d1, 1, 1, 1, 1;\n"
        "wgmma.commit_group.sync.aligned;\n"
        "wgmma.mma_async.sync.aligned.m64n128k16.f32.bf16.bf16 " PV_HI "{%128, u0, %129, u1}, d2, p, 1, 1, 1;\n"
        "wgmma.mma_async.sync.aligned.m64n128k16.f32.bf16.bf16 " PV_HI "{%130, u2, %131, u3}, d3, 1, 1, 1, 1;\n"
        "wgmma.commit_group.sync.aligned;\n}"
        : R8(0), R8(8), R8(16), R8(24), R8(32), R8(40), R8(48), R8(56), R8(64), R8(72), R8(80), R8(88), R8(96), R8(104), R8(112), R8(120)
        : "r"(a.x), "r"(a.y), "r"(a.z), "r"(a.w), "r"(blo), "r"(acc) : "memory");
}

template <int NW>
__device__ __forceinline__ void ln_stats(float s, float q, float sh, float* scr, int w, int lane, int bar, float& mean_b, float& sd_b) {
#pragma unroll
    for (int o = 16; o; o >>= 1) { s += shx(s, o); q += shx(q, o); }
    constexpr float n = 512.f / NW;
    if (lane == 0) { scr[w] = sh + s * (1.f / n); scr[NW + w] = q - s * s * (1.f / n); }
    bar_sync(bar, NW * 32);
    float mu = 0.f, m2 = 0.f;
#pragma unroll
    for (int i = 0; i < NW; i++) { mu += scr[i]; m2 += scr[NW + i]; }
    mu *= 1.f / NW;
#pragma unroll
    for (int i = 0; i < NW; i++) { const float d = scr[i] - mu; m2 = fmaf(n * d, d, m2); }
    mean_b = rbf(mu);
    sd_b = rbf(sqrtf(rbf(rbf(fmaxf(m2, 0.f) * (1.f / 512.f)) + 1e-5f)));
}
__device__ __forceinline__ float ln_mod(float x, float mean_b, float sd_b, float c, float s) {
    return rbf(rbf(__fdividef(rbf(x - mean_b), sd_b)) * rbf(1.f + c)) + s;
}

__global__ void __cluster_dims__(2, 1, 1) __launch_bounds__(NTHREADS, 1)
fused_kernel(const __grid_constant__ First F, __nv_bfloat16* __restrict__ out, uint32_t* __restrict__ gs, const __grid_constant__ Maps M) {
    extern __shared__ __align__(1024) uint8_t sm[];
    const uint32_t sb = s2u(sm);
    const int tid = threadIdx.x, lane = tid & 31;
    const int j = blockIdx.x, rk = j & 1;
    const int g = lane >> 2, t = lane & 3;
    const int r8 = lane & 7, lb3 = (lane >> 3) & 1, lb4 = lane >> 4;
    const uint64_t pol = 0x12F0000000000000ull;
    uint32_t in1 = 0, in2 = 0;
    {
        auto cpa = [&](uint32_t d, const uint8_t* s) {
            asm volatile("cp.async.cg.shared.global.L2::cache_hint.L2::128B [%0], [%1], 16, %2;" :: "r"(d), "l"(s), "l"(pol) : "memory");
        };
        const uint32_t ut = threadIdx.x, uj = blockIdx.x;
        const uint8_t* w = F.w[ut >= 128];
        if (ut < 128) {
            const uint32_t dq = (sb + ut * 16) ^ ((ut * 2) & 0x70);
            const uint8_t* sq = w + (uint32_t)(((uj & 1) * 256 + (ut >> 3)) * 8192 + (uj >> 1) * 128 + (ut & 7) * 16);
#pragma unroll
            for (int i = 0; i < 4 * NCP; i++) cpa(dq + 4 * 32768 + i * 2048, sq + i * 131072);
        } else if (ut < 384) {
            const uint32_t dm = (sb + ut * 16) ^ ((ut * 2) & 0x10);
            const uint8_t* sa = w + (uint32_t)(((uj >> 5) * 128 + (ut >> 1) - 64) * 6144 + (uj & 31) * 32 + (ut & 1) * 16);
            asm volatile("cp.async.cg.shared.global.L2::cache_hint" MODA_PF " [%0], [%1], 16, %2;" :: "r"(dm + SM_XA - 2048), "l"(sa), "l"(pol) : "memory");
            asm volatile("cp.async.cg.shared.global.L2::cache_hint" MODA_PF " [%0], [%1], 16, %2;" :: "r"(dm + SM_XA + 2048), "l"(sa + 1024), "l"(pol) : "memory");
        }
        else if (ut == 480 && uj < 16 * XC_LATE) asm volatile("prefetch.global.L2 [%0];" :: "l"(F.v[(uj >> 3) & 1] + (uj & 7) * 64));
    }
    const int warp = __shfl_sync(0xffffffffu, tid >> 5, 0);
    const __nv_bfloat16* const xin = F.v[0];
    uint32_t* const pl = gs + (warp < 2 ? (B_PR + (j >> 5)) * 4096 + (j & 31) * 32 : G_E1 + j * 8192) + (warp & 1) * 1024 + lane;
    auto small_loads = [&]() {
        if (warp < 4) { in1 = *(const uint32_t*)(xin + 2 * tid); in2 = *(const uint32_t*)(xin + 256 + 2 * tid); }
        else if (warp < 12) in1 = *(const uint32_t*)(F.v[1] + 2 * (tid - 128));
    };
    if (!XC_LATE) small_loads();
    if (warp < 4) st_x1(pl, 1u);
    auto BAR = [&](int i) -> uint32_t { return sb + SM_BAR + i * 8; };
    const uint32_t a16 = (r8 + 8 * lb4) * 32 + ((lb3 ^ (r8 >> 2)) * 16);
    const uint32_t a128 = (r8 + 8 * lb4) * 128 + ((((warp & 3) * 2 + lb3) ^ r8) * 16);
    auto ldcls = [&]() -> uint32_t { return *(const volatile uint32_t*)(sm + SM_CLS); };
    auto clear_head = [&]() {
        st2_x1(gs + (B_HA + ((j >> 4) & 1) * 2 + lb4) * 4096 + (j >> 5) * 256 + (j & 15) * 16 + (lane & 15), 0u);
        st2_x4(gs + (B_QA + rk * 8 + ((j >> 1) & 1) * 4 + (j >> 5)) * 4096 + g * 128 + ((j >> 2) & 7) * 16 + t * 4, 0u, 0u, 0u, 0u);
        if (lane < 8) st2_x1(gs + B_RD * 4096 + j * 8 + lane, 0u);
    };
    auto tma = [&](uint32_t dst, int mp, uint32_t bar, int c0, int c1, int c2, int c3) {
        asm volatile("{\n.reg .pred p;\nelect.sync _|p, 0xffffffff;\n"
                     "@p cp.async.bulk.tensor.4d.shared::cluster.global.mbarrier::complete_tx::bytes.L2::cache_hint [%0], [%1, {%3, %4, %5, %6}], [%2], %7;\n}"
                     :: "r"(dst), "l"(&M.m[mp]), "r"(bar), "r"(c0), "r"(c1), "r"(c2), "r"(c3), "l"(pol) : "memory");
    };
    if (warp <= 12 || warp == 15) {
        const int grp = warp == 12 ? 0 : warp == 15 ? 13 : warp + 1;
        const uint32_t cnt = grp < 10 ? 1 : grp < 13 ? 4 : 8;
        if (lane == 0) {
#pragma unroll
            for (int i = 0; i < 8; i++) mbar_init(BAR(grp * 8 + i), (i < 2 && grp == 0) ? (i ? 128 : 256) : cnt);
        }
        __syncwarp();
        if (grp < 10 && lane < 8 && (grp || lane > NCP)) mbar_expect(BAR(grp * 8 + lane), grp >= 8 ? 4096 : grp * 8 + lane < IT_X ? 8192 : 16384);
        asm volatile("fence.mbarrier_init.release.cluster;" ::: "memory");
        __syncwarp();
        if (warp == 12) {
#pragma unroll
            for (int i = NCP + 1; i < W0; i++) tma(sb + (15 + i) * 8192, MP_WQ, BAR(i), 0, rk * 256 + (i - 1) * 64, j >> 1, 0);
        }
    } else if (warp == 13) {
        if (lane < NMAPS) asm volatile("prefetch.tensormap [%0];" :: "l"(&M.m[lane]) : "memory");
    } else if (warp == 14 && PREZERO) {
        clear_head();
    }
    __syncthreads();
    if (XC_LATE) small_loads();
    if (warp < 12) asm volatile("cp.async.mbarrier.arrive.noinc.shared::cta.b64 [%0];" :: "r"(BAR(warp < 4)) : "memory");
    asm volatile("barrier.cluster.arrive.relaxed.aligned;" ::: "memory");

    if (warp >= 12) {
    asm volatile("setmaxnreg.dec.sync.aligned.u32 56;");
    if (warp == 12) {
        static_assert(W0 > NCP && W0 <= 5 && NCP >= 1 && NCP <= 4, "W0");
        const uint32_t* sched = M.sched[j < NFF ? 0 : j < J_RED ? 1 : 2];
        uint32_t e = sched[W0];
        uint32_t tn = gtime() + sched[1];
        const uint32_t tau = sched[0];
#pragma unroll 1
        for (int i = W0; e; i++) {
            const uint32_t en = sched[i + 1];
            const int id = e & 63, w0 = (e >> 11) & 127, w1 = (e >> 18) & 127;
            int mp, c0 = 0, c1 = 0, c2 = 0, c3 = 0;
            tn += tau;
            if (id < IT_CKV) { const int k = id - IT_WQ; mp = MP_WQ + (k >> 2); c1 = rk * 256 + (k & 3) * 64; c2 = j >> 1; }
            else if (id < IT_WUV) { const int k = id - IT_CKV; mp = MP_CKV; c2 = rk * 4; c3 = (k * 64 + (j >> 1)) * 2; }
            else if (id < IT_WO) { mp = MP_WUV; c1 = (j & 3) * 32 + (id - IT_WUV) * 128; c2 = (j >> 2) * 2; }
            else if (id < IT_X) { mp = MP_WO; c0 = (j & 7) * 64; c1 = (j >> 3) * 256 + (id - IT_WO) * 64; }
            else if (id < IT_DOWN) {
                if (j >= J_END) break;
                const int k = id - IT_X;
                mp = j < NFF ? MP_GATE + (k >> 1) : MP_MODB; c0 = (j >> 1) * 64 + (j < NFF ? 0 : 1024 - NFF * 32); c1 = rk * 256 + (k & 1) * 128;
            } else {
                if (id == NEVER) { e = en; continue; }
                mp = MP_DOWN; c1 = j * 32; c2 = (id - IT_DOWN) * 4;
            }
            if (w0) mbar_wait(BAR(w0 - 1), 0);
            const int w2 = e >> 25;
            if (w2) {
                mbar_wait(BAR(w2 - 1), 0);
                while (!__any_sync(0xffffffffu, mbar_test(BAR(w1 - 1), 0) | ((int)(gtime() - tn) > 0))) {}
            } else if (w1) mbar_wait(BAR(w1 - 1), 0);
            tma(sb + ((e >> 6) & 31) * 8192, mp, BAR(id), c0, c1, c2, c3);
            e = en;
        }
    } else if (warp == 13) {
#pragma unroll
        for (int i = 0; i < 2; i++) st2_x4(gs + (B_ML + rk * 16 + i * 8 + g) * 4096 + (j >> 1) * 16 + t * 4, 0u, 0u, 0u, 0u);
        if (lane < 16) st2_x4(gs + (B_E2 + (j >> 4)) * 4096 + (j & 15) * 64 + lane * 4, 0u, 0u, 0u, 0u);
        st2_x1(gs + (B_E3 + (j >> 5)) * 4096 + (j & 31) * 32 + lane, 0u);
        if (lane < 8) st2_x1(gs + B_MB * 4096 + j * 8 + lane, 0u);
        if (j < NFF) {
#pragma unroll
            for (int i = 0; i < 2; i++) st2_x4(gs + (B_E5 + i * 8 + g) * 4096 + j * 16 + t * 4, 0u, 0u, 0u, 0u);
        }
        bar_sync(9, 64);
        const uint32_t cs = ldcls();
#pragma unroll 1
        for (int i = 0; i < 32; i++) {
            st_x4(gs + G_E1 + j * 8192 + (i >> 3) * 2048 + ((((cs >> 1) ^ (i >> 3)) & 1) << 10) + (i & 7) * 128 + lane * 4, 0u, 0u, 0u, 0u);
            __nanosleep(JAN_SLEEP);
        }
        fence_gpu();
        if (lane < 8) st2_x1(gs + B_RD * 4096 + j * 8 + lane, 1u + (cs >> 1));
        if (lane == 0) TRACE(41);
        uint32_t rd[4];
        mbar_wait(BAR(IT_CKV + RD_ITEM), 0);
        poll<1024, RD_SLEEP>(rd, gs + near_off(B_RD, cs) + lane * 8);
#pragma unroll
        for (int i = 0; i < 4; i++) {
            const uint32_t m = __ballot_sync(0xffffffffu, rd[i] == 2u);
            if (lane == 0) sts32(sb + SM_CLS + 16 + i * 4, m);
        }
        __syncwarp();
        if (lane < 8) mbar_arrive(BAR(JD));
        if (lane == 0) TRACE(42);
    } else if (warp == 14) {
        uint2 ml[2];
        mbar_waitb(BAR(JD), 0);
        const uint32_t cls = ldcls();
        mbar_waitb(BAR(PF0 + 2 * NUNITS - 1), 0);
        __nanosleep(ML_DELAY);
        poll<64, ML_SLEEP>(ml, gs + near_off(B_ML + (j >> 2), cls) + lane * 32);
        if (!E1_DIRECT) bar_arrive(3, 288);
        if (lane == 0) TRACE_Q(37);
        const float m0 = __uint_as_float(ml[0].x), m1 = __uint_as_float(ml[1].x);
        const int mi = __float_as_int(fmaxf(m0, m1));
        const int mr = __reduce_max_sync(0xffffffffu, mi ^ ((mi >> 31) & 0x7fffffff));
        const float mm = __int_as_float(mr ^ ((mr >> 31) & 0x7fffffff));
        const uint32_t w0 = pack2(ex2(m0 - mm), 0.f), w1 = pack2(ex2(m1 - mm), 0.f);
        const uint32_t wa = sb + SM_W + (lane >> 3) * 64 + (lane & 1) * 32 + ((lane >> 1) & 3) * 4;
        sts32(wa, w0 * 0x10001u); sts32(wa + 16, w1 * 0x10001u);
        bar_arrive(8, 288);
        float L = bflo(w0) * __uint_as_float(ml[0].y) + bflo(w1) * __uint_as_float(ml[1].y);
#pragma unroll
        for (int o = 16; o; o >>= 1) L += shx(L, o);
        if (lane == 0) *(float*)(sm + SM_FQ) = __frcp_rn(L);
        if (lane == 0) TRACE(10);
        bar_sync(4, 288);
        clear_head();
        if (j < NFF) {
            uint32_t ya = sb + SM_Y + lane * 16, sa = peer_addr(sb + SM_RED + 2048 + rk * 8, lane & 1), tb = peer_addr(BAR(QB), lane & 1);
            pin(ya); pin(sa); pin(tb);
            bar_sync(7, 288);
            const float4 y0 = ldsf4(ya), y1 = ldsf4(ya + 512);
            float s = sum4(y0) + sum4(y1);
            float q = (fmaf(y0.x, y0.x, y0.y * y0.y) + fmaf(y0.z, y0.z, y0.w * y0.w)) + (fmaf(y1.x, y1.x, y1.y * y1.y) + fmaf(y1.z, y1.z, y1.w * y1.w));
#pragma unroll
            for (int o = 16; o; o >>= 1) { s += shx(s, o); q += shx(q, o); }
            if (lane < 2) st_async2(sa, s, q, tb);
        }
    } else if (warp == 15) {
        mbar_waitb(BAR(IT_X - 1), 0);
        if (j < J_END) mbar_waitb(BAR(j < NFF ? NITEMS - 1 : MBB), 0);
    }
    } else if (warp < 4) {
        float* scr = (float*)(sm + SM_SCR);
        uint32_t cls;
        {
            uint2 ha[8];
            {
                uint32_t best = 0xffffffffu;
#pragma unroll
                for (int i = 0; i < NPROBE; i++) {
                    uint32_t t0, t1, o;
                    asm volatile("mov.u32 %0, %%clock;" : "=r"(t0));
                    asm volatile("atom.relaxed.gpu.global.exch.b32 %0, [%1], %2;" : "=r"(o) : "l"(pl), "r"(2u + i) : "memory");
                    asm volatile("{\n.reg .pred p;\nsetp.ne.u32 p, %1, 0x1234567;\nmov.u32 %0, 0;\n@p mov.u32 %0, %%clock;\n}" : "=r"(t1) : "r"(o));
                    best = min(best, t1 - t0);
                }
                if (lane == 0) scr[16 + warp] = __uint_as_float(best);
            }
            const float sh = __shfl_sync(0xffffffffu, bflo(in1), 0);
            const float v0 = bflo(in1) - sh, v1 = bfhi(in1) - sh, v2 = bflo(in2) - sh, v3 = bfhi(in2) - sh;
            float mb, sd;
            ln_stats<4>((v0 + v1) + (v2 + v3), (v0 * v0 + v1 * v1) + (v2 * v2 + v3 * v3), sh, scr, warp, lane, 2, mb, sd);
            if (!rk) in2 = in1;
            const uint4 lt = *(const uint4*)(scr + 16);
            cls = NUMA ? ((lt.y < lt.x) ^ (__popc((B_PR + (j >> 5)) & 0x2C) & 1)) | (lt.w < lt.z) << 1 : 0;
            if (warp == 0) { if (lane == 0) sts32(sb + SM_CLS, cls); bar_arrive(9, 64); }
            if (tid == 0) TRACE(38);
            asm volatile("barrier.cluster.wait.aligned;" ::: "memory");
            mbar_wait(BAR(IT_MODA), 0);
            __nanosleep(HA_DELAY);
            poll<1024, H_SLEEP, false, 16384>(ha, gs + near_off(B_HA + rk * 2, cls) + 2 * tid);
            auto rsum = [](uint32_t a, uint32_t b, uint32_t c, uint32_t d) { return rbf((__uint_as_float(a) + __uint_as_float(b)) + (__uint_as_float(c) + __uint_as_float(d))); };
            sts32(sb + SM_FV + frag_off(2 * tid),
                  pack2(ln_mod(bflo(in2), mb, sd, rsum(ha[4].x, ha[5].x, ha[6].x, ha[7].x), rsum(ha[0].x, ha[1].x, ha[2].x, ha[3].x)),
                        ln_mod(bfhi(in2), mb, sd, rsum(ha[4].y, ha[5].y, ha[6].y, ha[7].y), rsum(ha[0].y, ha[1].y, ha[2].y, ha[3].y))));
            bar_arrive(5, 384);
            mbar_wait(BAR(QB), 0);
            if (tid < 64) {
                const float* qx = (const float*)(sm + SM_QX) + tid;
                sts16(sb + SM_FQ + frag_off(tid), pack2((qx[0] + qx[64]) + (qx[128] + qx[192]), 0.f));
            }
            bar_arrive(6, 384);
        }
        asm volatile("setmaxnreg.inc.sync.aligned.u32 168;");
        float acc[128];
        float M = 0.f;
        uint32_t pa = sb + SM_XA + warp * 512 + lane * 16, ma = sb + SM_MX + (warp * 8 + g) * 4, pf = BAR(PF0);
        uint32_t blo = __reduce_or_sync(0xffffffffu, (((sb + SM_U) & 0x3FFFFu) >> 4) | 0x400000u);
        uint32_t* e1[4];
#pragma unroll
        for (int i = 0; i < 4; i++) e1[i] = gs + G_E1 + (warp * 8 + g) * 4 * 8192 + (rk * 2 + (j >> 6)) * 2048 + ((j >> 1) & 31) * 32 + t * 4;
        uint32_t ck[10] = {0, 0, 0, 0, 0, 0, 0, 0, 0, 0};
#pragma unroll 1
        for (int h = 0; h < 2 * NUNITS; h++) {
            CLK(ck[0], h == 2 * TU); CLK(ck[5], h == 2 * TU + 1);
            mbar_wait(pf, 0);
            CLK(ck[1], h == 2 * TU); CLK(ck[6], h == 2 * TU + 1);
            const float m = __uint_as_float(lds32(ma));
            const uint4 pn = lds128(pa);
            wg_wait0();
#pragma unroll
            for (int i = 0; i < 128; i++) asm volatile("" : "+f"(acc[i]) :: "memory");
            CLK(ck[2], h == 2 * TU); CLK(ck[7], h == 2 * TU + 1);
            if (h == 0) M = m;
            uint32_t b2 = 0x3f803f80u;
            if (__builtin_expect(__any_sync(0xffffffffu, m != M), 0)) {
                const float Mn = fmaxf(M, m), alpha = ex2(M - Mn), beta = ex2(m - Mn);
                M = Mn;
                b2 = pack2(beta, beta);
#pragma unroll
                for (int jj = 0; jj < 32; jj++) { acc[4 * jj] *= alpha; acc[4 * jj + 1] *= alpha; }
            }
            auto mul2 = [](uint32_t x, uint32_t y) { uint32_t r; asm("mul.rn.bf16x2 %0, %1, %2;" : "=r"(r) : "r"(x), "r"(y)); return r; };
            const uint4 p = make_uint4(mul2(pn.x, b2), mul2(pn.y, b2), mul2(pn.z, b2), mul2(pn.w, b2));
            if (tid == 0 && (h & 1)) TRACE_Q(48 + (h >> 1));
            CLK(ck[3], h == 2 * TU); CLK(ck[8], h == 2 * TU + 1);
            wgmma_pv(acc, p, blo, h);
            CLK(ck[4], h == 2 * TU); CLK(ck[9], h == 2 * TU + 1);
            if (lane == 0 && h > 0 && !(h & 1)) mbar_arrive(BAR(EB_UNIT0 + (h >> 1) - 1));
            blo += h == 11 ? -11 * 1024 : 1024;
            pa += (h == 5 || h == 11) ? -5 * 2048 : 2048;
            ma += 128; pf += 8;
            if (h == 2 * NUNITS - 3) {
                mbar_wait(BAR(JD), 0);
                const uint32_t hm = (*(const uint32_t*)(sm + SM_CLS + 16 + warp * 4) >> (g * 4)) ^ ((j >> 6) ? 15u : 0u);
#pragma unroll
                for (int i = 0; i < 4; i++) e1[i] += ((hm >> i) & 1) << 10;
            }
        }
#pragma unroll
        for (int vv = 0; vv < 2; vv++) {
            if (vv && M == 1.f) __trap();
            if (vv) wg_wait0(); else wg_wait1();
#pragma unroll
            for (int i = 0; i < 64; i++) asm volatile("" : "+f"(acc[vv * 64 + i]) :: "memory");
            if (tid == 0 && !vv) TRACE_Q(63);
#pragma unroll
            for (int i = 0; i < 4; i++) {
                const float* a = &acc[vv * 64 + i * 16];
                st_x4(e1[i] + i * 8192 + vv * 16, enc(pack2(a[0], a[1])), enc(pack2(a[4], a[5])), enc(pack2(a[8], a[9])), enc(pack2(a[12], a[13])));
            }
        }
        if (tid == 0) TRACE_Q(17);
        if (j >= NFF && j < J_END) {
            uint4 a[8], b[4];
            float c[4], e[4];
            const bool own = (warp >> 1) == rk;
            const uint32_t xa = sb + SM_FV + (warp & 1) * 64 + g * 8;
            if (lane == 0) mbar_expect(BAR(MBB), own ? 64 : 0);
#pragma unroll
            for (int i = 0; i < 2; i++) {
                ldfrag(b, sb + SM_FS + rk * 512 + i * 256 + t * 16);
                mbar_wait(BAR(IT_X + i), 0);
                const uint32_t ab = sb + SM_U + B_X * 32768 + i * 16384 + a128;
                load8<true>(a, [&](int s) { return ab + s * 2048; });
                mma8(i ? e : c, a, b);
            }
            c[0] += e[0]; c[2] += e[2];
            if (!own) {
                if (t == 0) st_async2(peer_addr(xa, rk ^ 1), c[0], c[2], peer_addr(BAR(MBB), rk ^ 1));
            } else {
                mbar_wait(BAR(MBB), 0);
                const float2 pp = *(const float2*)(sm + (xa - sb));
                const float mine = t ? c[2] + pp.y : c[0] + pp.x, other = shx(mine, 4);
                const uint32_t w = (warp & 1) * 8 + t * 4 + (g >> 1), val = enc(pack2(mine, other));
                if (t < 2 && !(g & 1)) {
                    if (j < J_RED) st2_x1(gs + B_MB * 4096 + (j - NFF) * 16 + w, val);
                    else sts32(sb + SM_FV + 256 + w * 4, val);
                }
                if (j >= J_RED) bar_arrive(7, 320);
                if (lane == 0) TRACE(11);
            }
        }
    } else {
        const int u8 = tid - 128, w8 = warp - 4;
        const int v = w8 >> 2, wq4 = w8 & 3;
        {
            const float c0 = bflo(in1), c1 = bfhi(in1);
            sts32(sb + SM_FS + frag_off(2 * u8), pack2(__fdividef(c0, 1.f + __expf(-c0)), __fdividef(c1, 1.f + __expf(-c1))));
        }
        bar_sync(1, 256);
        asm volatile("barrier.cluster.wait.aligned;" ::: "memory");
        uint4 a[8], b[4]; float c[4];
        if (w8 < 2) {
            ldfrag(b, sb + SM_FS + (j >> 5) * 256 + t * 16);
            mbar_wait(BAR(IT_MODA), 0);
            if (u8 == 0) TRACE(12);
            const uint32_t ab = sb + SM_XA + w8 * 4096 + a16;
            load8<true>(a, [&](int s) { return ab + s * 512; });
            mma8(c, a, b);
            if (t < 2) st2_x1(gs + (B_HA + ((j >> 4) & 1) * 2 + w8) * 4096 + (j >> 5) * 256 + (j & 15) * 16 + t * 8 + g, encf(t ? c[2] : c[0]));
        }
        {
            mbar_wait(BAR(IT_WQ + 2 * v <= NCP ? 1 : IT_WQ + 2 * v), 0); mbar_wait(BAR(IT_WQ + 2 * v + 1 <= NCP ? 1 : IT_WQ + 2 * v + 1), 0);
            const uint32_t ab = sb + SM_U + 4 * 32768 + v * 16384 + a128;
            load8<true>(a, [&](int s) { return ab + s * 2048; });
            if (lane == 0) mbar_arrive(BAR(EB_WQ));
            bar_sync(5, 384);
            if (u8 == 0) TRACE(13);
            ldfrag(b, sb + SM_FV + v * 256 + t * 16);
            mma8(c, a, b);
            if (t < 2) {
                const float qv = t ? c[2] : c[0];
                const uint32_t qa_ = sb + SM_QX + ((rk * 2 + v) * 64 + wq4 * 16 + t * 8 + g) * 4;
                asm volatile("st.async.weak.shared::cluster.mbarrier::complete_tx::bytes.f32 [%0], %1, [%2];"
                             :: "r"(peer_addr(qa_, rk ^ 1)), "f"(qv), "r"(peer_addr(BAR(QB), rk ^ 1)) : "memory");
                sts32(qa_, __float_as_uint(qv));
            }
            __syncwarp();
            if (lane == 0) mbar_expect(BAR(QB), 64);
        }
        {
            mbar_wait(BAR(IT_WUK + v), 0); mbar_wait(BAR(IT_WUK + v + 2), 0);
            const uint32_t ab = sb + SM_U + 5 * 32768 + (w8 * 16 + r8 + 8 * lb3) * 128;
            const uint32_t x16 = (lb4 ^ r8) * 16;
            load8<false>(a, [&](int s) { return ab + (s & 1) * 16384 + (x16 ^ ((s >> 1) * 32)); });
            bar_sync(6, 384);
            if (u8 == 0) TRACE(14);
            b[0] = lds128(sb + SM_FQ + t * 16); b[1] = lds128(sb + SM_FQ + 64 + t * 16);
            float e[4] = {0.f, 0.f, 0.f, 0.f};
            c[0] = c[1] = c[2] = c[3] = 0.f;
#pragma unroll
            for (int k = 0; k < 4; k++) {
                const uint32_t b0 = (k & 1) ? b[k >> 1].z : b[k >> 1].x, b1 = (k & 1) ? b[k >> 1].w : b[k >> 1].y;
                mma(c, a[2 * k].x, a[2 * k].y, a[2 * k].z, a[2 * k].w, b0, b1);
                mma(e, a[2 * k + 1].x, a[2 * k + 1].y, a[2 * k + 1].z, a[2 * k + 1].w, b0, b1);
            }
            const float mine = ((t & 1) ? ((t & 2) ? e[2] : e[0]) : ((t & 2) ? c[2] : c[0])) * 0.12751743f;
            const float other = shx(mine, 4);
            if (!(g & 1)) st2_x1(gs + (B_QA + rk * 8 + ((j >> 1) & 1) * 4 + (j >> 5)) * 4096 + w8 * 128 + ((j >> 2) & 7) * 16 + (g >> 1) * 4 + t, enc(pack2(mine, other)));
            if (u8 == 0) TRACE(15);
        }
        const uint32_t cls = ldcls();
        __nanosleep(QA_DELAY);
        {
            uint4 qb[8];
            const uint32_t* pq = gs + near_off(B_QA + rk * 8 + wq4, cls) + lane * 4;
            const uint32_t* pq2 = gs + near_off(B_QA + rk * 8 + 4 + wq4, cls) + lane * 4;
            if (lane == 0) {
                mbar_expect(BAR(QT), 4096);
                asm volatile("cp.async.bulk.shared::cluster.global.mbarrier::complete_tx::bytes [%0], [%1], 4096, [%2];"
                             :: "r"(sb + SM_U + 5 * 32768 + w8 * 4096), "l"(gs + near_off(B_QA + rk * 8 + w8, cls)), "r"(BAR(QT)) : "memory");
            }
            const uint32_t qs = sb + SM_U + 5 * 32768 + wq4 * 4096 + lane * 16;
            mbar_wait(BAR(QT), 0);
#pragma unroll
            for (int i = 0; i < 8; i++) { a[i] = lds128(qs + i * 512); qb[i] = lds128(qs + 16384 + i * 512); }
            poll<512, QA_SLEEP, true>(a, pq);
            poll<512, QA_SLEEP, true>(qb, pq2);
            if (lane == 0) mbar_arrive(BAR(EB_WUK));
            auto add2 = [](uint32_t x, uint32_t y) { uint32_t r; asm("add.rn.bf16x2 %0, %1, %2;" : "=r"(r) : "r"(x), "r"(y)); return r; };
#pragma unroll
            for (int i = 0; i < 8; i++) a[i] = make_uint4(add2(a[i].x, qb[i].x), add2(a[i].y, qb[i].y), add2(a[i].z, qb[i].z), add2(a[i].w, qb[i].w));
        }
        if (u8 == 0) TRACE(8);
        {
            float m = -INFINITY, l = 0.f;
            uint32_t xl = sb + SM_XB + w8 * 2048 + lane * 16, xr = peer_addr(xl, rk ^ 1), bsr = peer_addr(BAR(SF0 + v), rk ^ 1);
            uint32_t pa = sb + SM_XA + v * 2048 + wq4 * 512 + lane * 16, ma = sb + SM_MX + v * 128 + (wq4 * 8 + g) * 4;
            uint32_t fb = BAR(IT_CKV + v * 2), sf = BAR(SF0 + v);
            uint32_t dlo = __reduce_or_sync(0xffffffffu, (((sb + SM_U + v * 16384) & 0x3FFFFu) >> 4) | 0x10000u);
            uint32_t ck[9] = {0, 0, 0, 0, 0, 0, 0, 0, 0};
            if (STAG && v) __nanosleep(STAG);
#pragma unroll 1
            for (int n = 0; n < NUNITS; n++) {
                CLK(ck[0], n == TU); CLK(ck[8], n == TU + 1);
                float d[2][16], sc[8];
#pragma unroll
                for (int i = 0; i < 2; i++) {
                    mbar_wait(fb + i * 8, 0);
                    if (i == 0) CLK(ck[1], n == TU);
                    wg_fence();
#pragma unroll
                    for (int s = 0; s < 8; s++) wgmma_rs_n32(d[i], a[s], (0x40000080ull << 32) | (dlo + i * 512 + (s >> 2) * 64 + (s & 3) * 2), s);
                    wg_commit();
                }
                CLK(ck[2], n == TU);
#pragma unroll
                for (int i = 0; i < 2; i++) {
                    if (i) wg_wait0(); else wg_wait1();
#pragma unroll
                    for (int k = 0; k < 16; k++) asm volatile("" : "+f"(d[i][k]) :: "memory");
                    sc[4 * i] = d[i][0] + d[i][6]; sc[4 * i + 1] = d[i][1] + d[i][7]; sc[4 * i + 2] = d[i][8] + d[i][14]; sc[4 * i + 3] = d[i][9] + d[i][15];
                    asm volatile("st.async.weak.shared::cluster.mbarrier::complete_tx::bytes.v4.f32 [%0], {%1, %2, %3, %4}, [%5];"
                                 :: "r"(xr + i * 1024), "f"(sc[4 * i]), "f"(sc[4 * i + 1]), "f"(sc[4 * i + 2]), "f"(sc[4 * i + 3]), "r"(bsr) : "memory");
                }
                CLK(ck[3], n == TU);
                if (u8 == 128) TRACE_Q(56 + (n < 6 ? n : -40));
                if (n >= 3) mbar_wait(BAR(EB_UNIT0 + n - 3), 0);
                dlo += n == 5 ? -5 * 2048 : 2048;
                fb += 32; xr ^= 512; bsr += 16;
                pin(fb); pin(xr); pin(bsr);
                CLK(ck[4], n == TU);
                mbar_wait(sf, 0);
                CLK(ck[5], n == TU);
                const float4 x = ldsf4(xl), y = ldsf4(xl + 1024);
                sc[0] += x.x; sc[1] += x.y; sc[2] += x.z; sc[3] += x.w; sc[4] += y.x; sc[5] += y.y; sc[6] += y.z; sc[7] += y.w;
                float pr[8];
#pragma unroll
                for (int i = 0; i < 8; i++) pr[i] = ex2(sc[i] - m);
                float mx = fmaxf(fmaxf(fmaxf(sc[0], sc[1]), fmaxf(sc[2], sc[3])), fmaxf(fmaxf(sc[4], sc[5]), fmaxf(sc[6], sc[7])));
                if (__builtin_expect(__any_sync(0xffffffffu, mx > m), 0)) {
                    mx = fmaxf(mx, shx(mx, 1));
                    mx = fmaxf(mx, shx(mx, 2));
                    const float mn = fmaxf(m, ceilf(mx * 0.0625f) * 16.f);
                    l *= ex2(m - mn);
                    m = mn;
#pragma unroll
                    for (int i = 0; i < 8; i++) pr[i] = ex2(sc[i] - m);
                }
                CLK(ck[6], n == TU);
                stsf(ma, m);
                asm volatile("st.shared.v4.u32 [%0], {%1, %2, %3, %4};" :: "r"(pa), "r"(pack2(pr[0], pr[1])), "r"(pack2(pr[2], pr[3])),
                             "r"(pack2(pr[4], pr[5])), "r"(pack2(pr[6], pr[7])) : "memory");
                __syncwarp();
                if (lane == 0) mbar_arrive(sf + (PF0 - SF0) * 8);
                CLK(ck[7], n == TU);
                l += ((pr[0] + pr[1]) + (pr[2] + pr[3])) + ((pr[4] + pr[5]) + (pr[6] + pr[7]));
                xl ^= 512; sf += 16; ma += 256; pa += (n == 2 || n == 5) ? -8192 : 4096;
            }
            l += shx(l, 1);
            l += shx(l, 2);
            float2* mlx = (float2*)(sm + SM_MX + 2048) + wq4 * 8 + g;
            if (v == 0) { *mlx = make_float2(m, l); bar_arrive(11, 256); }
            else {
                mbar_wait(BAR(JD), 0);
                bar_sync(11, 256);
                const float2 o = *mlx;
                const float mn = fmaxf(m, o.x);
                l = l * ex2(m - mn) + o.y * ex2(o.x - mn);
                if ((wq4 >> 1) == rk) st_x4(gs + (B_ML + wq4 * 8 + g) * 4096 + (t >> 1) * 1024 + (j >> 1) * 16 + (t & 1) * 4, encf(mn), encf(l), 1u, 1u);
            }
        }
        asm volatile("setmaxnreg.inc.sync.aligned.u32 144;");
        const int pi = j < NFF ? rk * 128 + w8 * 16 + (lane & 15) : ((j - J_RED) & 15) * 16 + v * 8 + lb4 * 4 + wq4;
        const uint32_t xw = *(const uint32_t*)(xin + 2 * pi);
        uint32_t rl = sb + SM_RED + lane * 16;
        {
#pragma unroll 1
            for (int i = 0; i < 4; i++) mbar_wait(BAR(IT_WUV + i), 0);
            const uint32_t ab = sb + SM_U + B_WUV * 32768 + v * 4096 + a128;
            load8<true>(a, [&](int s) { return ab + (s >> 1) * 8192 + (s & 1) * 2048; });
            uint32_t pa = sb + SM_PB + wq4 * 320 + frag_off(64 * v + 32 * (g >> 2) + 16 * (t & 1) + 8 * (t >> 1) + 2 * (g & 3));
            uint32_t fa = sb + SM_PB + g * 320 + t * 16, ra = sb + SM_RED + w8 * 288 + g * 16 + t * 4;
            uint32_t rb = sb + SM_RED + (u8 & 15) * 144 + ((u8 >> 4) & 3) * 32;
            const uint32_t* pe = gs + G_E1 + j * 8192 + (w8 >> 1) * 2048 + ((((cls >> 1) ^ (w8 >> 1)) & 1) << 10) + (((w8 & 1) * 16 + t) * 8 + g) * 4;
            uint32_t* p2 = gs + (B_E2 + (j >> 4)) * 4096 + (u8 >> 6) * 1024 + (j & 15) * 64 + (u8 & 63);
            pin(pa); pin(fa); pin(ra); pin(rb); pin(rl); pin(pe); pin(p2);
            uint4 pv[4];
            bar_sync(3, 288);
            TK(0);
            poll_start<512>(pv, pe);
            bar_sync(8, 288);
            const uint4 wa = lds128(sb + SM_W + (wq4 * 4 + t) * 16);
            const uint32_t mk = (g & 1) ? 0xffff0000u : 0x0000ffffu, m0 = (g & 2) ? 0u : mk, m1 = (g & 2) ? mk : 0u;
            uint32_t wb[8] = {wa.x & m0, wa.x & m1, wa.y & m0, wa.y & m1, wa.z & m0, wa.z & m1, wa.w & m0, wa.w & m1};
#pragma unroll
            for (int i = 0; i < 8; i++) pin(wb[i]);
            poll<512, E1_SLEEP, true>(pv, pe);
            if (u8 == 0) TRACE_Q(18);
            TK(1);
            float e[4][4];
#pragma unroll
            for (int i = 0; i < 4; i++) {
                e[i][0] = e[i][1] = e[i][2] = e[i][3] = 0.f;
                mma(e[i], pv[i].x, pv[i].y, pv[i].z, pv[i].w, wb[2 * i], wb[2 * i + 1]);
            }
            const float r0 = (t & 2) ? (e[0][2] + e[1][2]) + (e[2][2] + e[3][2]) : (e[0][0] + e[1][0]) + (e[2][0] + e[3][0]);
            const float r1 = (t & 2) ? (e[0][3] + e[1][3]) + (e[2][3] + e[3][3]) : (e[0][1] + e[1][1]) + (e[2][1] + e[3][1]);
            const uint32_t hi = pack2(r0, r1);
            sts32(pa, hi); sts32(pa + 1280, pack2(r0 - bflo(hi), r1 - bfhi(hi)));
            TK(2);
            bar_sync(1, 256);
            TK(3);
            if (u8 == 0) TRACE(19);
            ldfrag(b, fa);
            mma8(c, a, b);
            stsf(ra, c[0] + c[1]); stsf(ra + 144, c[2] + c[3]);
            TK(4);
            bar_sync(4, 288);
            TK(5);
            if (w8 < 4) {
                const float inv = *(const float*)(sm + SM_FQ);
                st_x1(p2, enc(pack2(sum4(ldsf4(rb)) * inv, sum4(ldsf4(rb + 16)) * inv)));
            }
            TK(6);
            if (u8 == 0) TRACE(20);
        }
        uint32_t mb[3] = {0u, 0u, 0u};
        const uint32_t* pm = gs + near_off(B_MB, cls) + pi;
        pin(pm);
        if (j < NFF) poll_start<1024>(mb, pm);
        {
            const uint32_t nz = lb4 ? 0x80008000u : 0u;
#pragma unroll
            for (int i = 0; i < 4; i++) b[i] = make_uint4(nz, nz, nz, nz);
            const bool early = __all_sync(0xffffffffu, mbar_test(BAR(IT_WO + 2 * v), 0) & mbar_test(BAR(IT_WO + 2 * v + 1), 0));
            const uint32_t ab = sb + SM_U + B_WO * 32768 + v * 16384 + a128;
            if (early) load8<true>(a, [&](int s) { return ab + s * 2048; });
            uint32_t ra = sb + SM_R3 + (wq4 * 16 + g) * 16 + v * 8 + t * 4, rb = sb + SM_R3 + lane * 32;
            uint32_t* p3 = gs + (B_E3 + ((j >> 2) & 1) * 2 + (j >> 6)) * 4096 + w8 * 1024 + ((j >> 3) & 7) * 128 + (j & 3) * 32 + lane;
            pin(ra); pin(rb); pin(p3);
            TK(7);
            poll<16, E2_SLEEP, true>(b, gs + near_off(B_E2 + (j >> 4), cls) + (((j >> 3) & 1) * 2 + v) * 256 + lane * 16);
            if (!early) { mbar_wait(BAR(IT_WO + 2 * v), 0); mbar_wait(BAR(IT_WO + 2 * v + 1), 0); load8<true>(a, [&](int s) { return ab + s * 2048; }); }
            TK(8);
            if (u8 == 0) TRACE(21);
            mma8(c, a, b);
            if (t < 2) { stsf(ra, c[0] + c[1]); stsf(ra + 128, c[2] + c[3]); }
            TK(9);
            bar_sync(1, 256);
            TK(10);
            if (w8 < 2) st_x1(p3, enc(pack2(sum4(ldsf4(rb)), sum4(ldsf4(rb + 16)))));
            TK(11);
            if (u8 == 0) TRACE(22);
        }
        if (j < NFF) {
            const uint32_t* p3 = gs + near_off(B_E3 + rk * 2 + lb4, cls) + (pi & 127);
            uint32_t za = sb + SM_FZ + lb4 * 576 + frag_off(w8 * 32 + (lane & 15) * 2);
            uint32_t fa = sb + SM_FZ + (g & 3) * 576 + lb4 * 256 + t * 16, ya = sb + SM_Y + u8 * 4;
            poll<1024, MB_SLEEP, true>(mb, pm);
            const uint32_t kk = pack2(1.f + bflo(mb[2]), 1.f + bfhi(mb[2]));
            sts32(za + 2 * 576, lb4 ? mb[1] : kk);
            uint32_t e3[8] = {0u, 0u, 0u, 0u, 0u, 0u, 0u, 0u};
            uint32_t ra = peer_addr(sb + SM_RED + (rk * 2 + v) * 512 + ((wq4 & 1) * 16 + (t >> 1) * 8 + g) * 16 + (t & 1) * 8, wq4 >> 1), tbo = peer_addr(BAR(QB), wq4 >> 1);
            uint32_t ad = sb + SM_U + B_DN * 32768 + w8 * 4096 + (r8 + 8 * lb4) * 128 + (lb3 ^ r8) * 16;
            uint32_t* p5 = gs + (B_E5 + w8 * 2 + (t >> 1)) * 4096 + j * 16 + (t & 1) * 8 + g;
            pin(za); pin(fa); pin(ya); pin(ra); pin(tbo); pin(ad); pin(p5);
            if (lane == 0) mbar_expect(BAR(QB), 258);
            uint4 a2[8];
            TK(12);
            const uint32_t gb = BAR(IT_X + v * 2), ab = sb + SM_U + (B_X + v) * 32768 + a128;
            bool early = false, early2 = false;
            poll<512, 0, true>(e3, p3, [&]() {
                if (!early) {
                    early = __all_sync(0xffffffffu, mbar_test(gb, 0));
                    if (early) load8<true>(a, [&](int s) { return ab + s * 2048; });
                }
                if (!early2) {
                    early2 = __all_sync(0xffffffffu, mbar_test(gb + 8, 0));
                    if (early2) load8<true>(a2, [&](int s) { return ab + 16384 + s * 2048; });
                }
            });
            TK(13);
            if (u8 == 0) TRACE(23);
            const float s0 = sumlo(e3), s1 = sumhi(e3);
            const float y0 = fmaf(bflo(mb[0]), s0 + shx(s0, 16), bflo(xw)), y1 = fmaf(bfhi(mb[0]), s1 + shx(s1, 16), bfhi(xw));
            stsf(ya, lb4 ? y1 : y0);
            const float z0 = y0 * bflo(kk), z1 = y1 * bfhi(kk);
            const uint32_t zh = pack2(z0, z1);
            sts32(za, lb4 ? pack2(z0 - bflo(zh), z1 - bfhi(zh)) : zh);
            TK(14);
            bar_sync(7, 288);
            TK(15);
            if (u8 == 0) TRACE(24);
            ldfrag(b, fa);
            if (!early) { mbar_wait(gb, 0); load8<true>(a, [&](int s) { return ab + s * 2048; }); }
            if (!early2) { mbar_wait(gb + 8, 0); load8<true>(a2, [&](int s) { return ab + 16384 + s * 2048; }); }
            {
                float e[4][4];
#pragma unroll
                for (int s = 0; s < 16; s++) {
                    const uint4& x = (s & 2) ? a2[(s >> 2) * 2 + (s & 1)] : a[(s >> 2) * 2 + (s & 1)];
                    const uint4& y = b[s >> 2];
                    if (s < 4) e[s][0] = e[s][1] = e[s][2] = e[s][3] = 0.f;
                    mma(e[s & 3], x.x, x.y, x.z, x.w, (s & 1) ? y.z : y.x, (s & 1) ? y.w : y.y);
                }
                const bool hi = t >> 1;
                const float k0 = hi ? e[2][2] + e[3][2] : e[0][0] + e[1][0], k1 = hi ? e[2][3] + e[3][3] : e[0][1] + e[1][1];
                const float o0 = hi ? e[2][0] + e[3][0] : e[0][2] + e[1][2], o1 = hi ? e[2][1] + e[3][1] : e[0][3] + e[1][3];
                TKD(16, o0);
                st_async2(ra, k0 + shx(o0, 2), k1 + shx(o1, 2), tbo);
            }
            TK(17);
            const bool early5 = __all_sync(0xffffffffu, mbar_test(BAR(IT_DOWN + v), 0));
            if (early5) load8<true>(a, [&](int s) { return (ad ^ ((s & 3) * 32)) + (s >> 2) * 2048; });
            TK(18);
            mbar_wait(BAR(QB), 1);
            TK(19);
            if (u8 == 0) TRACE(25);
            const float4 st = ldsf4(sb + SM_RED + 2048);
            const float4 f0 = ldsf4(rl), f1 = ldsf4(rl + 512), f2 = ldsf4(rl + 1024), f3 = ldsf4(rl + 1536);
            const float mu = (st.x + st.z) * (1.f / 512.f);
            float rstd;
            asm("rsqrt.approx.ftz.f32 %0, %1;" : "=f"(rstd) : "f"(fmaxf(fmaf(-mu, mu, (st.y + st.w) * (1.f / 512.f)), 0.f) + 1e-5f));
            const float gg = fmaf(rstd, fmaf(-mu, f0.z + f2.z, (f0.x + f0.y) + (f2.x + f2.y)), f0.w + f2.w);
            const float uu = fmaf(rstd, fmaf(-mu, f1.z + f3.z, (f1.x + f1.y) + (f3.x + f3.y)), f1.w + f3.w);
            TKD(20, gg);
            const float hh = __fdividef(gg * uu, 1.f + ex2(-gg * fmaf(gg * gg, 0.10294324f, 2.3022082f)));
            uint32_t hb[4];
#pragma unroll
            for (int i = 0; i < 4; i++) hb[i] = pack2(__shfl_sync(0xffffffffu, hh, 2 * t + 8 * i), __shfl_sync(0xffffffffu, hh, 2 * t + 8 * i + 1));
            TKD(21, __uint_as_float(hb[3]));
            if (!early5) { mbar_wait(BAR(IT_DOWN + v), 0); load8<true>(a, [&](int s) { return (ad ^ ((s & 3) * 32)) + (s >> 2) * 2048; }); }
            uint32_t res = 0;
#pragma unroll
            for (int k = 0; k < 4; k++) {
                c[0] = c[1] = c[2] = c[3] = 0.f;
                mma(c, a[k].x, a[k].y, a[k].z, a[k].w, hb[0], hb[1]);
                mma(c, a[k + 4].x, a[k + 4].y, a[k + 4].z, a[k + 4].w, hb[2], hb[3]);
                if (t == k) res = pack2(c[0], c[2]);
            }
            st2_x1(p5, enc(res));
            TK(22);
            if (u8 == 0) { TRACE(27); TRACE_GT(47); }
        } else if (j >= J_RED && j < J_END) {
            uint32_t ga[1], e3[1];
            poll<0, MB_SLEEP>(ga, pm);
            poll<0, 100>(e3, gs + near_off(B_E3 + (pi >> 7) * 2 + lb3, cls) + r8 * 128 + (pi & 127));
            float y0 = bflo(e3[0]), y1 = bfhi(e3[0]);
#pragma unroll
            for (int o = 8; o; o >>= 1) { y0 += shx(y0, o); y1 += shx(y1, o); }
            y0 = fmaf(bflo(ga[0]), y0, bflo(xw)); y1 = fmaf(bfhi(ga[0]), y1, bfhi(xw));
            bar_sync(7, 320);
            const uint32_t gb = lds32(sb + SM_FV + 256 + (pi & 15) * 4);
            uint32_t* po = (uint32_t*)out + pi;
            pin(po);
            const uint32_t nz = lane < NFF / 2 ? 0u : 0x80008000u;
            uint2 yv[2] = {make_uint2(nz, nz), make_uint2(nz, nz)};
            poll<NFF * 32, E5_SLEEP, true>(yv, gs + near_off(B_E5 + j - J_RED, cls) + lane * 16 + w8 * 2);
            if (u8 == 0) TRACE(26);
            const float l0 = bflo(yv[0].x) + bflo(yv[1].x), h0 = bfhi(yv[0].x) + bfhi(yv[1].x);
            const float l1 = bflo(yv[0].y) + bflo(yv[1].y), h1 = bfhi(yv[0].y) + bfhi(yv[1].y);
            float s0 = (lb4 ? h0 : l0) + shx(lb4 ? l0 : h0, 16), s1 = (lb4 ? h1 : l1) + shx(lb4 ? l1 : h1, 16);
#pragma unroll
            for (int o = 8; o; o >>= 1) { s0 += shx(s0, o); s1 += shx(s1, o); }
            if (!(lane & 15)) *po = pack2(fmaf(bflo(gb), s0, y0), fmaf(bfhi(gb), s1, y1));
            if (u8 == 0) TRACE(27);
        }
    }
}

typedef CUresult (*EncFn)(CUtensorMap*, CUtensorMapDataType, cuuint32_t, void*, const cuuint64_t*, const cuuint64_t*,
                          const cuuint32_t*, const cuuint32_t*, CUtensorMapInterleave, CUtensorMapSwizzle,
                          CUtensorMapL2promotion, CUtensorMapFloatOOBfill);

void make_map(EncFn enc_fn, CUtensorMap* m, const void* p, cuuint64_t d0, cuuint64_t d1, cuuint64_t d2, cuuint64_t d3,
              cuuint64_t s1, cuuint64_t s2, cuuint64_t s3, cuuint32_t b0, cuuint32_t b1, cuuint32_t b2, cuuint32_t b3, CUtensorMapSwizzle sw) {
    const cuuint64_t dims[4] = {d0, d1, d2, d3}, strides[3] = {s1, s2, s3};
    const cuuint32_t box[4] = {b0, b1, b2, b3}, es[4] = {1, 1, 1, 1};
    enc_fn(m, CU_TENSOR_MAP_DATA_TYPE_BFLOAT16, 4, (void*)p, dims, strides, box, es,
           CU_TENSOR_MAP_INTERLEAVE_NONE, sw, CU_TENSOR_MAP_L2_PROMOTION_L2_64B, CU_TENSOR_MAP_FLOAT_OOB_FILL_NONE);
}

uint32_t* scratch = nullptr;

struct Tune { const char* win; const char* late; int tau, t_off; const char* tail[3][3]; };
Tune tune = {"66666666655555555555555555555555555555555",
             "00000000000000000000999999999999999999999", 315, -200,
             {{"VVVVOOOOguguDD", "55554444445555", "00000000000000"},
              {"VVVVMMOOOO", "5555456666", "0000000000"},
              {"VVVVOOOO......MM", "55554444000000zz", "0000000000000088"}}};
bool ready = false;

}

extern "C" void kernel_launch(void* const* d_in, const int* in_sizes, int n_in, void* d_out, int out_size) {
    (void)in_sizes; (void)n_in; (void)out_size;
    static Maps maps;
    static const void* cached[12] = {};
    bool same = ready;
    for (int i = 0; i < 12 && same; i++) same = cached[i] == d_in[i];
    if (!same) {
        void* fn = nullptr;
        cudaDriverEntryPointQueryResult qr;
        cudaGetDriverEntryPoint("cuTensorMapEncodeTiled", &fn, cudaEnableDefault, &qr);
        EncFn e = (EncFn)fn;
        const CUtensorMapSwizzle S128 = CU_TENSOR_MAP_SWIZZLE_128B;
        make_map(e, &maps.m[MP_WQ], d_in[2], 64, 512, 64, 1, 8192, 128, 8192, 64, 64, 1, 1, S128);
        make_map(e, &maps.m[MP_WUK], d_in[3], 64, 512, 64, 1, 8192, 128, 8192, 64, 64, 1, 1, S128);
        make_map(e, &maps.m[MP_CKV], d_in[1], 64, 8, 8, 4096, 1024, 128, 8192, 64, 8, 4, 2, S128);
        make_map(e, &maps.m[MP_MODB], d_in[11], 3072, 512, 1, 1, 6144, 6144, 6144, 64, 128, 1, 1, S128);
        make_map(e, &maps.m[MP_WUV], d_in[4], 64, 512, 64, 1, 8192, 128, 8192, 64, 32, 2, 1, S128);
        make_map(e, &maps.m[MP_WO], d_in[5], 512, 4096, 1, 1, 1024, 1024, 1024, 64, 64, 1, 1, S128);
        make_map(e, &maps.m[MP_GATE], d_in[7], 1792, 512, 1, 1, 3584, 3584, 3584, 64, 128, 1, 1, S128);
        make_map(e, &maps.m[MP_UP], d_in[8], 1792, 512, 1, 1, 3584, 3584, 3584, 64, 128, 1, 1, S128);
        make_map(e, &maps.m[MP_DOWN], d_in[9], 64, 1792, 8, 1, 1024, 128, 1024, 64, 32, 4, 1, S128);
        for (int r = 0; r < 3; r++) {
            int ids[72], real[72], nreal = 0, cnt[128] = {};
            uint32_t* sc = maps.sched[r];
            auto dig = [](char ch) { return ch >= 'a' ? ch - 'a' + 10 : ch - '0'; };
            for (int i = 0; i < 72; i++) sc[i] = 0;
            for (int i = 0;; i++) {
                int id = i, buf, dep, w, wl;
                if (i < IT_WUV) {
                    const int u = (i - IT_CKV) >> 2;
                    buf = i < IT_CKV ? 4 + ((i - 1) >> 2) : u % 6;
                    dep = i < IT_CKV || u < 4 ? -1 : u < 6 ? EB_WQ + u - 4 : EB_UNIT0 + u - 6;
                    w = dig(tune.win[i]); wl = dig(tune.late[i]);
                } else {
                    const char ch = tune.tail[r][0][i - IT_WUV];
                    if (!ch) break;
                    if (ch == '.') { sc[i] = NEVER; continue; }
                    buf = ch == 'V' ? B_WUV : ch == 'O' ? B_WO : ch == 'D' ? B_DN : ch == 'u' ? B_X + 1 : B_X;
                    id = (ch == 'V' ? IT_WUV : ch == 'O' ? IT_WO : ch == 'D' ? IT_DOWN : ch == 'u' ? IT_X + 2 : IT_X) + cnt[(int)ch]++;
                    dep = EB_UNIT0 + (buf < 2 ? buf + 6 : buf);
                    w = dig(tune.tail[r][1][i - IT_WUV]); wl = dig(tune.tail[r][2][i - IT_WUV]);
                }
                if (id < IT_X ? (id - 1) & 3 : (id - IT_X) & 1) dep = -1;
                ids[i] = id;
                auto back = [&](int d) { const int k = nreal - d; return k < 0 ? 0 : (ids[real[k]] && ids[real[k]] <= NCP ? 1 : ids[real[k]]) + 1; };
                sc[i] = id | (buf * 4 + (id < IT_X ? (id - 1) & 3 : ((id - IT_X) & 1) * 2)) << 6 | (dep + 1) << 11 | (w > 32 ? NEVER + 1 : back(w)) << 18 | (wl ? back(wl) : 0) << 25;
                real[nreal++] = i;
            }
            sc[0] = tune.tau; sc[1] = tune.t_off;
        }
        cudaGetSymbolAddress((void**)&scratch, g_scratch);
        scratch = (uint32_t*)(((uintptr_t)scratch + (2u << 20) - 1) & ~(uintptr_t)((2u << 20) - 1));
        cudaFuncSetAttribute(fused_kernel, cudaFuncAttributeMaxDynamicSharedMemorySize, SM_TOTAL);
        for (int i = 0; i < 12; i++) cached[i] = d_in[i];
        ready = true;
    }
    const First f = {{(const uint8_t*)d_in[2], (const uint8_t*)d_in[11]}, {(const __nv_bfloat16*)d_in[0], (const __nv_bfloat16*)d_in[10]}};
    fused_kernel<<<NCTA, NTHREADS, SM_TOTAL>>>(f, (__nv_bfloat16*)d_out, scratch, maps);
}
```

```cpp
#include <cuda_runtime.h>
#include <cuda_bf16.h>
#include <cuda.h>
#include <stdint.h>

namespace {

constexpr int NCTA = 128;
constexpr int NTHREADS = 512;
constexpr int NUNITS = 8;
constexpr int NFF = 56, J_RED = 104, J_END = 120;
constexpr uint32_t SPIN_LIMIT = 1u << 22;

#define P2 0
#define P2_GAP 250
#define XC_LATE 4
#define MODA_PF ".L2::128B"
#define PREZERO 1
#define E1_DIRECT 0
#define STAG 300
#define TU 2
#define NUMA 1
#define NPROBE 3
#define NCP 2
#define W0 4
#define RD_ITEM 15
#define JAN_SLEEP 100
#define RD_SLEEP 400
#define HA_DELAY 200
#define H_SLEEP 100
#define QA_DELAY 600
#define QA_SLEEP 200
#define ML_DELAY 300
#define ML_SLEEP 50
#define E1_SLEEP 50
#define E2_SLEEP 0
#define E3_SLEEP 0
#define E5_SLEEP 0
#define MB_SLEEP 100
constexpr int B_WUV = 2, B_WO = 3, B_X = 4  , B_DN = 0;

constexpr int SM_U = 0;
constexpr int SM_XA = 6 * 32768;
constexpr int SM_XB = SM_XA + 12288;
constexpr int SM_MX = SM_XB + 16384;
constexpr int SM_FZ = SM_XB + 8192;
constexpr int SM_PB = SM_XB;
constexpr int SM_R3 = SM_XB + 2560;
constexpr int SM_Y = SM_XB + 12288;
constexpr int SM_RED = SM_XB + 4096;
constexpr int SM_FS = SM_XB + 20480;
constexpr int SM_FV = SM_FS + 1024;
constexpr int SM_QX = SM_XA + 8192;
constexpr int SM_FQ = SM_FV + 512;
constexpr int SM_CLS = SM_FQ + 128;
constexpr int SM_W = SM_FQ + 256;
constexpr int SM_SCR = SM_XA + 9216;
constexpr int SM_TR = SM_XB + 19456;
constexpr int SM_BAR = SM_W + 256;
constexpr int SM_TOTAL = SM_BAR + 1024;
static_assert(SM_TOTAL <= 232448, "smem");

enum { IT_MODA = 0, IT_WQ = 1, IT_WUK = 5, IT_CKV = 9, IT_WUV = 41, IT_WO = 45, IT_X = 49  , IT_DOWN = 53, NITEMS = 55,
       NEVER = 63,
       SF0 = 64,
       PF0 = 80,
       EB_UNIT0 = 96, MBB = 103,
       EB_WQ = 104, EB_WUK, QT, QB, JD };

enum { MP_WQ = 0, MP_WUK, MP_CKV, MP_MODB, MP_WUV, MP_WO, MP_GATE, MP_UP, MP_DOWN, NMAPS };
struct First { const uint8_t* w[2]; const __nv_bfloat16* v[2]; };
struct Maps { CUtensorMap m[NMAPS]; uint32_t sched[3][72]; };

enum { B_HA = 0,
       B_MB = 6,
       B_RD = 7,
       B_E2 = 8,
       B_QA = 16,
       B_ML = 32,
       B_E5 = 64,
       B_E3 = 80,
       B_PR = 96,
       B_TR = 100 };
constexpr int G_E1 = 1 << 19;
constexpr int G_TR = B_TR * 4096;
__device__ __align__(1024) uint32_t g_scratch[(8 << 20) / 4];

#define TRACE(slot) do {} while (0)
#define TRACE_Q(slot) do {} while (0)
#define TRACE_GT(slot) do {} while (0)

#define CLK(var, cond) do {} while (0)
#define CLKD(var, cond, dep) do {} while (0)
#define TK(i) do {} while (0)
#define TKD(i, dep) do {} while (0)
__device__ __forceinline__ uint32_t s2u(const void* p) { return (uint32_t)__cvta_generic_to_shared(p); }
__device__ __forceinline__ void mbar_init(uint32_t b, int c) { asm volatile("mbarrier.init.shared::cta.b64 [%0], %1;" :: "r"(b), "r"(c) : "memory"); }
__device__ __forceinline__ void mbar_expect(uint32_t b, uint32_t bytes) { asm volatile("mbarrier.arrive.expect_tx.shared::cta.b64 _, [%0], %1;" :: "r"(b), "r"(bytes) : "memory"); }
__device__ __forceinline__ void mbar_arrive(uint32_t b) { asm volatile("mbarrier.arrive.shared::cta.b64 _, [%0];" :: "r"(b) : "memory"); }
__device__ __forceinline__ void mbar_wait(uint32_t b, uint32_t ph) {
    asm volatile("{\n.reg .pred p;\nW: mbarrier.try_wait.parity.shared::cta.b64 p, [%0], %1;\n@!p bra W;\n}" :: "r"(b), "r"(ph) : "memory");
}
__device__ __forceinline__ void mbar_waitb(uint32_t b, uint32_t ph) {
    asm volatile("{\n.reg .pred p;\n.reg .u32 n;\nmov.u32 n, 0;\n"
                 "W: mbarrier.try_wait.parity.shared::cta.b64 p, [%0], %1;\n@p bra D;\n"
                 "add.u32 n, n, 1;\nsetp.lt.u32 p, n, 0x100000;\n@p bra W;\ntrap;\nD:\n}" :: "r"(b), "r"(ph) : "memory");
}
__device__ __forceinline__ uint32_t mbar_test(uint32_t b, uint32_t ph) {
    uint32_t ok;
    asm volatile("{\n.reg .pred p;\nmbarrier.test_wait.parity.shared::cta.b64 p, [%1], %2;\nselp.u32 %0, 1, 0, p;\n}" : "=r"(ok) : "r"(b), "r"(ph) : "memory");
    return ok;
}
__device__ __forceinline__ void bar_sync(int id, int n) { asm volatile("bar.sync %0, %1;" :: "r"(id), "r"(n) : "memory"); }
__device__ __forceinline__ void bar_arrive(int id, int n) { asm volatile("bar.arrive %0, %1;" :: "r"(id), "r"(n) : "memory"); }
__device__ __forceinline__ uint32_t peer_addr(uint32_t a, uint32_t rank) { uint32_t r; asm("mapa.shared::cluster.u32 %0, %1, %2;" : "=r"(r) : "r"(a), "r"(rank)); return r; }
__device__ __forceinline__ void st_async1(uint32_t a, float x, uint32_t bar) {
    asm volatile("st.async.weak.shared::cluster.mbarrier::complete_tx::bytes.f32 [%0], %1, [%2];" :: "r"(a), "f"(x), "r"(bar) : "memory");
}
__device__ __forceinline__ void st_async2(uint32_t a, float x, float y, uint32_t bar) {
    asm volatile("st.async.weak.shared::cluster.mbarrier::complete_tx::bytes.v2.f32 [%0], {%1, %2}, [%3];" :: "r"(a), "f"(x), "f"(y), "r"(bar) : "memory");
}
__device__ __forceinline__ uint32_t gtime() { uint32_t t; asm volatile("mov.u32 %0, %%globaltimer_lo;" : "=r"(t)); return t; }
__device__ __forceinline__ void fence_gpu() { asm volatile("fence.acq_rel.gpu;" ::: "memory"); }

__device__ __forceinline__ uint32_t enc(uint32_t b) { uint32_t r; asm("max.u32 %0, %1, 1;" : "=r"(r) : "r"(b)); return r; }
__device__ __forceinline__ uint32_t encf(float f) { return enc(__float_as_uint(f)); }
__device__ __forceinline__ void st_x1(uint32_t* p, uint32_t v) { asm volatile("st.relaxed.gpu.global.u32 [%0], %1;" :: "l"(p), "r"(v) : "memory"); }
__device__ __forceinline__ void st_x4(void* p, uint32_t a, uint32_t b, uint32_t c, uint32_t d) {
    asm volatile("st.relaxed.gpu.global.v4.u32 [%0], {%1, %2, %3, %4};" :: "l"(p), "r"(a), "r"(b), "r"(c), "r"(d) : "memory");
}
__device__ __forceinline__ void st2_x1(uint32_t* p, uint32_t v) { st_x1(p, v); st_x1(p + 1024, v); }
__device__ __forceinline__ void st2_x4(uint32_t* p, uint32_t a, uint32_t b, uint32_t c, uint32_t d) { st_x4(p, a, b, c, d); st_x4(p + 1024, a, b, c, d); }
__device__ __forceinline__ int near_off(int b, uint32_t cls) { return b * 4096 + (((__popc(b & 0x2C) ^ cls) & 1) << 10); }
__device__ __forceinline__ void ld_x(uint32_t& v, const void* p) { asm volatile("ld.relaxed.gpu.global.u32 %0, [%1];" : "=r"(v) : "l"(p) : "memory"); }
__device__ __forceinline__ void ld_x(uint4& v, const void* p) {
    asm volatile("ld.relaxed.gpu.global.v4.u32 {%0, %1, %2, %3}, [%4];" : "=r"(v.x), "=r"(v.y), "=r"(v.z), "=r"(v.w) : "l"(p) : "memory");
}
__device__ __forceinline__ void ld_x(uint2& v, const void* p) { asm volatile("ld.relaxed.gpu.global.v2.u32 {%0, %1}, [%2];" : "=r"(v.x), "=r"(v.y) : "l"(p) : "memory"); }
__device__ __forceinline__ uint32_t minw(uint32_t v) { return v; }
__device__ __forceinline__ uint32_t minw(const uint2& v) { return min(v.x, v.y); }
__device__ __forceinline__ uint32_t minw(const uint4& v) { return min(__vimin3_u32(v.x, v.y, v.z), v.w); }
template <int N> __device__ __forceinline__ uint32_t mint(const uint32_t* m) {
    if constexpr (N == 1) return m[0];
    else if constexpr (N == 2) return min(m[0], m[1]);
    else return __vimin3_u32(mint<(N + 2) / 3>(m), mint<(N + 1) / 3>(m + (N + 2) / 3), mint<N / 3>(m + (N + 2) / 3 + (N + 1) / 3));
}

template <int STRIDE, int S4 = 4 * STRIDE, typename T, int N>
__device__ __forceinline__ void poll_start(T (&v)[N], const void* base) {
#pragma unroll
    for (int i = 0; i < N; i++) ld_x(v[i], (const uint8_t*)base + (i & 3) * STRIDE + (i >> 2) * S4);
}
struct Nop { __device__ void operator()() const {} };
template <int STRIDE, int SLEEP, bool STARTED = false, int S4 = 4 * STRIDE, typename T, int N, typename F = Nop>
__device__ __forceinline__ void poll(T (&v)[N], const void* base, F idle = F()) {
    if (!STARTED) { poll_start<STRIDE, S4>(v, base); idle(); }
#pragma unroll 1
    for (uint32_t it = 0;; it++) {
        uint32_t m[N];
#pragma unroll
        for (int i = 0; i < N; i++) m[i] = minw(v[i]);
        if (__all_sync(0xffffffffu, mint<N>(m) != 0)) break;
        if (SLEEP && it > 0) __nanosleep(SLEEP);
#pragma unroll
        for (int i = 0; i < N; i++) if (!m[i]) ld_x(v[i], (const uint8_t*)base + (i & 3) * STRIDE + (i >> 2) * S4);
        idle();
        if (it > SPIN_LIMIT) __trap();
    }
}

__device__ __forceinline__ void movx(uint32_t& d, uint32_t x) { asm volatile("mov.b32 %0, %1;" : "=r"(d) : "r"(x)); }
__device__ __forceinline__ void movx(uint2& d, const uint2& x) { movx(d.x, x.x); movx(d.y, x.y); }
__device__ __forceinline__ void movx(uint4& d, const uint4& x) { movx(d.x, x.x); movx(d.y, x.y); movx(d.z, x.z); movx(d.w, x.w); }
template <typename T, int N> struct Poll2 {
    T v[2][N];
    template <int STRIDE, typename F = Nop>
    __device__ __forceinline__ void run(T (&r)[N], const void* base, F idle = F()) {
        auto ok = [&](const T (&x)[N]) {
            uint32_t m[N];
#pragma unroll
            for (int i = 0; i < N; i++) m[i] = minw(x[i]);
            return __all_sync(0xffffffffu, mint<N>(m) != 0);
        };
        auto again = [&](T (&x)[N]) {
#pragma unroll
            for (int i = 0; i < N; i++) if (!minw(x[i])) ld_x(x[i], (const uint8_t*)base + i * STRIDE);
        };
#pragma unroll
        for (int i = 0; i < N; i++) { v[0][i] = r[i]; v[1][i] = r[i]; }
        uint32_t t0, t1;
        asm volatile("mov.u32 %0, %%clock;" : "=r"(t0));
        again(v[0]);
        idle();
        do { asm volatile("mov.u32 %0, %%clock;" : "=r"(t1)); } while (__any_sync(0xffffffffu, t1 - t0 < P2_GAP));
#pragma unroll 1
        for (uint32_t it = 0;; it++) {
            again(v[1]);
            if (ok(v[0])) {
#pragma unroll
                for (int i = 0; i < N; i++) movx(r[i], v[0][i]);
                break;
            }
            again(v[0]);
            idle();
            if (it > SPIN_LIMIT) __trap();
            if (ok(v[1])) {
#pragma unroll
                for (int i = 0; i < N; i++) movx(r[i], v[1][i]);
                break;
            }
        }
    }
    __device__ __forceinline__ void settle() const {
        uint32_t m[2 * N];
#pragma unroll
        for (int i = 0; i < 2 * N; i++) m[i] = minw(v[i / N][i % N]);
        asm volatile("{\n.reg .pred p;\nsetp.eq.u32 p, %0, 0xffffffff;\n@p nanosleep.u32 0;\n}" :: "r"(mint<2 * N>(m)));
    }
};

__device__ __forceinline__ float bflo(uint32_t w) { return __uint_as_float(w << 16); }
__device__ __forceinline__ float bfhi(uint32_t w) { return __uint_as_float(w & 0xffff0000u); }
__device__ __forceinline__ uint32_t pack2(float lo, float hi) {
    uint32_t r; asm("cvt.rn.bf16x2.f32 %0, %1, %2;" : "=r"(r) : "f"(hi), "f"(lo)); return r;
}
__device__ __forceinline__ float rbf(float x) { return __uint_as_float(pack2(0.f, x)); }
__device__ __forceinline__ float sumlo(const uint32_t (&v)[8]) { return ((bflo(v[0]) + bflo(v[1])) + (bflo(v[2]) + bflo(v[3]))) + ((bflo(v[4]) + bflo(v[5])) + (bflo(v[6]) + bflo(v[7]))); }
__device__ __forceinline__ float sumhi(const uint32_t (&v)[8]) { return ((bfhi(v[0]) + bfhi(v[1])) + (bfhi(v[2]) + bfhi(v[3]))) + ((bfhi(v[4]) + bfhi(v[5])) + (bfhi(v[6]) + bfhi(v[7]))); }
__device__ __forceinline__ float ex2(float x) { float r; asm("ex2.approx.ftz.f32 %0, %1;" : "=f"(r) : "f"(x)); return r; }
__device__ __forceinline__ float shx(float v, int m) { return __shfl_xor_sync(0xffffffffu, v, m); }
__device__ __forceinline__ uint4 lds128(uint32_t a) { uint4 v; asm volatile("ld.shared.v4.u32 {%0, %1, %2, %3}, [%4];" : "=r"(v.x), "=r"(v.y), "=r"(v.z), "=r"(v.w) : "r"(a) : "memory"); return v; }
__device__ __forceinline__ uint32_t lds32(uint32_t a) { uint32_t v; asm volatile("ld.shared.u32 %0, [%1];" : "=r"(v) : "r"(a) : "memory"); return v; }
__device__ __forceinline__ void sts32(uint32_t a, uint32_t v) { asm volatile("st.shared.u32 [%0], %1;" :: "r"(a), "r"(v) : "memory"); }
__device__ __forceinline__ void sts16(uint32_t a, uint32_t v) { asm volatile("st.shared.u16 [%0], %1;" :: "r"(a), "h"((uint16_t)v) : "memory"); }
__device__ __forceinline__ int frag_off(int k) { return (k >> 5) * 64 + ((k >> 1) & 3) * 16 + ((k >> 4) & 1) * 8 + ((k >> 3) & 1) * 4 + (k & 1) * 2; }

template <bool TRANS>
__device__ __forceinline__ uint4 ldsm(uint32_t a) {
    uint4 r;
    if (TRANS) asm volatile("ldmatrix.sync.aligned.m8n8.x4.trans.shared.b16 {%0, %1, %2, %3}, [%4];" : "=r"(r.x), "=r"(r.y), "=r"(r.z), "=r"(r.w) : "r"(a) : "memory");
    else asm volatile("ldmatrix.sync.aligned.m8n8.x4.shared.b16 {%0, %1, %2, %3}, [%4];" : "=r"(r.x), "=r"(r.y), "=r"(r.z), "=r"(r.w) : "r"(a) : "memory");
    return r;
}
__device__ __forceinline__ void mma(float (&c)[4], uint32_t a0, uint32_t a1, uint32_t a2, uint32_t a3, uint32_t b0, uint32_t b1) {
    asm volatile("mma.sync.aligned.m16n8k16.row.col.f32.bf16.bf16.f32 {%0,%1,%2,%3}, {%4,%5,%6,%7}, {%8,%9}, {%0,%1,%2,%3};"
                 : "+f"(c[0]), "+f"(c[1]), "+f"(c[2]), "+f"(c[3]) : "r"(a0), "r"(a1), "r"(a2), "r"(a3), "r"(b0), "r"(b1));
}
template <bool TRANS, typename F>
__device__ __forceinline__ void load8(uint4 (&a)[8], F addr) {
    __syncwarp();
#pragma unroll
    for (int s = 0; s < 8; s++) a[s] = ldsm<TRANS>(addr(s));
}
__device__ __forceinline__ void mma8(float (&c)[4], const uint4 (&a)[8], const uint4 (&b)[4]) {
    float e[4][4];
#pragma unroll
    for (int s = 0; s < 8; s++) {
        if (s < 4) e[s][0] = e[s][1] = e[s][2] = e[s][3] = 0.f;
        mma(e[s & 3], a[s].x, a[s].y, a[s].z, a[s].w, (s & 1) ? b[s >> 1].z : b[s >> 1].x, (s & 1) ? b[s >> 1].w : b[s >> 1].y);
    }
#pragma unroll
    for (int i = 0; i < 4; i++) c[i] = (e[0][i] + e[1][i]) + (e[2][i] + e[3][i]);
}
__device__ __forceinline__ void ldfrag(uint4 (&b)[4], uint32_t a) {
    asm volatile("ld.shared.v4.u32 {%0,%1,%2,%3}, [%16];\nld.shared.v4.u32 {%4,%5,%6,%7}, [%16+64];\n"
                 "ld.shared.v4.u32 {%8,%9,%10,%11}, [%16+128];\nld.shared.v4.u32 {%12,%13,%14,%15}, [%16+192];\n"
                 : "=r"(b[0].x), "=r"(b[0].y), "=r"(b[0].z), "=r"(b[0].w), "=r"(b[1].x), "=r"(b[1].y), "=r"(b[1].z), "=r"(b[1].w),
                   "=r"(b[2].x), "=r"(b[2].y), "=r"(b[2].z), "=r"(b[2].w), "=r"(b[3].x), "=r"(b[3].y), "=r"(b[3].z), "=r"(b[3].w) : "r"(a) : "memory");
}
__device__ __forceinline__ void pin(uint32_t& x) { asm volatile("" : "+r"(x)); }
template <typename T> __device__ __forceinline__ void pin(T*& x) { asm volatile("" : "+l"(x)); }
__device__ __forceinline__ float4 ldsf4(uint32_t a) { const uint4 v = lds128(a); return make_float4(__uint_as_float(v.x), __uint_as_float(v.y), __uint_as_float(v.z), __uint_as_float(v.w)); }
__device__ __forceinline__ float sum4(const float4& f) { return (f.x + f.y) + (f.z + f.w); }
__device__ __forceinline__ void stsf(uint32_t a, float v) { sts32(a, __float_as_uint(v)); }

__device__ __forceinline__ void wg_fence() { asm volatile("wgmma.fence.sync.aligned;" ::: "memory"); }
__device__ __forceinline__ void wg_commit() { asm volatile("wgmma.commit_group.sync.aligned;" ::: "memory"); }
__device__ __forceinline__ void wg_wait1() { asm volatile("wgmma.wait_group.sync.aligned 1;" ::: "memory"); }
__device__ __forceinline__ void wg_wait0() { asm volatile("wgmma.wait_group.sync.aligned 0;" ::: "memory"); }
#define R8(o) "+f"(d[o]), "+f"(d[o + 1]), "+f"(d[o + 2]), "+f"(d[o + 3]), "+f"(d[o + 4]), "+f"(d[o + 5]), "+f"(d[o + 6]), "+f"(d[o + 7])
__device__ __forceinline__ void wgmma_rs_n32(float (&d)[16], const uint4& a, uint64_t db, int acc) {
    asm volatile("{\n.reg .pred p;\nsetp.ne.b32 p, %21, 0;\n"
        "wgmma.mma_async.sync.aligned.m64n32k16.f32.bf16.bf16 "
        "{%0,%1,%2,%3,%4,%5,%6,%7,%8,%9,%10,%11,%12,%13,%14,%15}, {%16,%17,%18,%19}, %20, p, 1, 1, 0;\n}"
        : R8(0), R8(8) : "r"(a.x), "r"(a.y), "r"(a.z), "r"(a.w), "l"(db), "r"(acc));
}
#define PV_LO "{%0,%1,%2,%3,%4,%5,%6,%7,%8,%9,%10,%11,%12,%13,%14,%15,%16,%17,%18,%19,%20,%21,%22,%23,%24,%25,%26,%27,%28,%29,%30,%31,%32,%33,%34,%35,%36,%37,%38,%39,%40,%41,%42,%43,%44,%45,%46,%47,%48,%49,%50,%51,%52,%53,%54,%55,%56,%57,%58,%59,%60,%61,%62,%63}, "
#define PV_HI "{%64,%65,%66,%67,%68,%69,%70,%71,%72,%73,%74,%75,%76,%77,%78,%79,%80,%81,%82,%83,%84,%85,%86,%87,%88,%89,%90,%91,%92,%93,%94,%95,%96,%97,%98,%99,%100,%101,%102,%103,%104,%105,%106,%107,%108,%109,%110,%111,%112,%113,%114,%115,%116,%117,%118,%119,%120,%121,%122,%123,%124,%125,%126,%127}, "
__device__ __forceinline__ void wgmma_pv(float (&d)[128], const uint4& a, uint32_t blo, int acc) {
    asm volatile("{\n.reg .pred p;\n.reg .b32 u0, u1, u2, u3, t;\n.reg .b64 d0, d1, d2, d3;\nsetp.ne.b32 p, %133, 0;\n"
        "mov.b64 d0, {%132, 0x40000100};\nadd.u32 t, %132, 512;\nmov.b64 d1, {t, 0x40000100};\n"
        "add.u32 t, %132, 128;\nmov.b64 d2, {t, 0x40000100};\nadd.u32 t, %132, 640;\nmov.b64 d3, {t, 0x40000100};\n"
        "wgmma.fence.sync.aligned;\n"
        "wgmma.mma_async.sync.aligned.m64n128k16.f32.bf16.bf16 " PV_LO "{%128, u0, %129, u1}, d0, p, 1, 1, 1;\n"
        "wgmma.mma_async.sync.aligned.m64n128k16.f32.bf16.bf16 " PV_LO "{%130, u2, %131, u3}, d1, 1, 1, 1, 1;\n"
        "wgmma.commit_group.sync.aligned;\n"
        "wgmma.mma_async.sync.aligned.m64n128k16.f32.bf16.bf16 " PV_HI "{%128, u0, %129, u1}, d2, p, 1, 1, 1;\n"
        "wgmma.mma_async.sync.aligned.m64n128k16.f32.bf16.bf16 " PV_HI "{%130, u2, %131, u3}, d3, 1, 1, 1, 1;\n"
        "wgmma.commit_group.sync.aligned;\n}"
        : R8(0), R8(8), R8(16), R8(24), R8(32), R8(40), R8(48), R8(56), R8(64), R8(72), R8(80), R8(88), R8(96), R8(104), R8(112), R8(120)
        : "r"(a.x), "r"(a.y), "r"(a.z), "r"(a.w), "r"(blo), "r"(acc) : "memory");
}

template <int NW>
__device__ __forceinline__ void ln_stats(float s, float q, float sh, float* scr, int w, int lane, int bar, float& mean_b, float& sd_b) {
#pragma unroll
    for (int o = 16; o; o >>= 1) { s += shx(s, o); q += shx(q, o); }
    constexpr float n = 512.f / NW;
    if (lane == 0) { scr[w] = sh + s * (1.f / n); scr[NW + w] = q - s * s * (1.f / n); }
    bar_sync(bar, NW * 32);
    float mu = 0.f, m2 = 0.f;
#pragma unroll
    for (int i = 0; i < NW; i++) { mu += scr[i]; m2 += scr[NW + i]; }
    mu *= 1.f / NW;
#pragma unroll
    for (int i = 0; i < NW; i++) { const float d = scr[i] - mu; m2 = fmaf(n * d, d, m2); }
    mean_b = rbf(mu);
    sd_b = rbf(sqrtf(rbf(rbf(fmaxf(m2, 0.f) * (1.f / 512.f)) + 1e-5f)));
}
__device__ __forceinline__ float ln_mod(float x, float mean_b, float sd_b, float c, float s) {
    return rbf(rbf(__fdividef(rbf(x - mean_b), sd_b)) * rbf(1.f + c)) + s;
}

__global__ void __cluster_dims__(2, 1, 1) __launch_bounds__(NTHREADS, 1)
fused_kernel(const __grid_constant__ First F, __nv_bfloat16* __restrict__ out, uint32_t* __restrict__ gs, const __grid_constant__ Maps M) {
    extern __shared__ __align__(1024) uint8_t sm[];
    const uint32_t sb = s2u(sm);
    const int tid = threadIdx.x, lane = tid & 31;
    const int j = blockIdx.x, rk = j & 1;
    const int g = lane >> 2, t = lane & 3;
    const int r8 = lane & 7, lb3 = (lane >> 3) & 1, lb4 = lane >> 4;
    const uint64_t pol = 0x12F0000000000000ull;
    uint32_t in1 = 0, in2 = 0;
    {
        auto cpa = [&](uint32_t d, const uint8_t* s) {
            asm volatile("cp.async.cg.shared.global.L2::cache_hint.L2::128B [%0], [%1], 16, %2;" :: "r"(d), "l"(s), "l"(pol) : "memory");
        };
        const uint32_t ut = threadIdx.x, uj = blockIdx.x;
        const uint8_t* w = F.w[ut >= 128];
        if (ut < 128) {
            const uint32_t dq = (sb + ut * 16) ^ ((ut * 2) & 0x70);
            const uint8_t* sq = w + (uint32_t)(((uj & 1) * 256 + (ut >> 3)) * 8192 + (uj >> 1) * 128 + (ut & 7) * 16);
#pragma unroll
            for (int i = 0; i < 4 * NCP; i++) cpa(dq + 4 * 32768 + i * 2048, sq + i * 131072);
        } else if (ut < 384) {
            const uint32_t dm = (sb + ut * 16) ^ ((ut * 2) & 0x10);
            const uint8_t* sa = w + (uint32_t)(((uj >> 5) * 128 + (ut >> 1) - 64) * 6144 + (uj & 31) * 32 + (ut & 1) * 16);
            asm volatile("cp.async.cg.shared.global.L2::cache_hint" MODA_PF " [%0], [%1], 16, %2;" :: "r"(dm + SM_XA - 2048), "l"(sa), "l"(pol) : "memory");
            asm volatile("cp.async.cg.shared.global.L2::cache_hint" MODA_PF " [%0], [%1], 16, %2;" :: "r"(dm + SM_XA + 2048), "l"(sa + 1024), "l"(pol) : "memory");
        }
        else if (ut == 480 && uj < 16 * XC_LATE) asm volatile("prefetch.global.L2 [%0];" :: "l"(F.v[(uj >> 3) & 1] + (uj & 7) * 64));
    }
    const int warp = __shfl_sync(0xffffffffu, tid >> 5, 0);
    const __nv_bfloat16* const xin = F.v[0];
    uint32_t* const pl = gs + (warp < 2 ? (B_PR + (j >> 5)) * 4096 + (j & 31) * 32 : G_E1 + j * 8192) + (warp & 1) * 1024 + lane;
    auto small_loads = [&]() {
        if (warp < 4) { in1 = *(const uint32_t*)(xin + 2 * tid); in2 = *(const uint32_t*)(xin + 256 + 2 * tid); }
        else if (warp < 12) in1 = *(const uint32_t*)(F.v[1] + 2 * (tid - 128));
    };
    if (!XC_LATE) small_loads();
    if (warp < 4) st_x1(pl, 1u);
    auto BAR = [&](int i) -> uint32_t { return sb + SM_BAR + i * 8; };
    const uint32_t a16 = (r8 + 8 * lb4) * 32 + ((lb3 ^ (r8 >> 2)) * 16);
    const uint32_t a128 = (r8 + 8 * lb4) * 128 + ((((warp & 3) * 2 + lb3) ^ r8) * 16);
    auto ldcls = [&]() -> uint32_t { return *(const volatile uint32_t*)(sm + SM_CLS); };
    auto clear_head = [&]() {
        st2_x1(gs + (B_HA + ((j >> 4) & 1) * 2 + lb4) * 4096 + (j >> 5) * 256 + (j & 15) * 16 + (lane & 15), 0u);
        st2_x4(gs + (B_QA + rk * 8 + ((j >> 1) & 1) * 4 + (j >> 5)) * 4096 + g * 128 + ((j >> 2) & 7) * 16 + t * 4, 0u, 0u, 0u, 0u);
        if (lane < 8) st2_x1(gs + B_RD * 4096 + j * 8 + lane, 0u);
    };
    auto tma = [&](uint32_t dst, int mp, uint32_t bar, int c0, int c1, int c2, int c3) {
        asm volatile("{\n.reg .pred p;\nelect.sync _|p, 0xffffffff;\n"
                     "@p cp.async.bulk.tensor.4d.shared::cluster.global.mbarrier::complete_tx::bytes.L2::cache_hint [%0], [%1, {%3, %4, %5, %6}], [%2], %7;\n}"
                     :: "r"(dst), "l"(&M.m[mp]), "r"(bar), "r"(c0), "r"(c1), "r"(c2), "r"(c3), "l"(pol) : "memory");
    };
    if (warp <= 12 || warp == 15) {
        const int grp = warp == 12 ? 0 : warp == 15 ? 13 : warp + 1;
        const uint32_t cnt = grp < 10 ? 1 : grp < 13 ? 4 : 8;
        if (lane == 0) {
#pragma unroll
            for (int i = 0; i < 8; i++) mbar_init(BAR(grp * 8 + i), (i < 2 && grp == 0) ? (i ? 128 : 256) : cnt);
        }
        __syncwarp();
        if (grp < 10 && lane < 8 && (grp || lane > NCP)) mbar_expect(BAR(grp * 8 + lane), grp >= 8 ? 4096 : grp * 8 + lane < IT_X ? 8192 : 16384);
        asm volatile("fence.mbarrier_init.release.cluster;" ::: "memory");
        __syncwarp();
        if (warp == 12) {
#pragma unroll
            for (int i = NCP + 1; i < W0; i++) tma(sb + (15 + i) * 8192, MP_WQ, BAR(i), 0, rk * 256 + (i - 1) * 64, j >> 1, 0);
        }
    } else if (warp == 13) {
        if (lane < NMAPS) asm volatile("prefetch.tensormap [%0];" :: "l"(&M.m[lane]) : "memory");
    } else if (warp == 14 && PREZERO) {
        clear_head();
    }
    __syncthreads();
    if (XC_LATE) small_loads();
    if (warp < 12) asm volatile("cp.async.mbarrier.arrive.noinc.shared::cta.b64 [%0];" :: "r"(BAR(warp < 4)) : "memory");
    asm volatile("barrier.cluster.arrive.relaxed.aligned;" ::: "memory");

    if (warp >= 12) {
    asm volatile("setmaxnreg.dec.sync.aligned.u32 56;");
    if (warp == 12) {
        static_assert(W0 > NCP && W0 <= 5 && NCP >= 1 && NCP <= 4, "W0");
        const uint32_t* sched = M.sched[j < NFF ? 0 : j < J_RED ? 1 : 2];
        uint32_t e = sched[W0];
        uint32_t tn = gtime() + sched[1];
        const uint32_t tau = sched[0];
#pragma unroll 1
        for (int i = W0; e; i++) {
            const uint32_t en = sched[i + 1];
            const int id = e & 63, w0 = (e >> 11) & 127, w1 = (e >> 18) & 127;
            int mp, c0 = 0, c1 = 0, c2 = 0, c3 = 0;
            tn += tau;
            if (id < IT_CKV) { const int k = id - IT_WQ; mp = MP_WQ + (k >> 2); c1 = rk * 256 + (k & 3) * 64; c2 = j >> 1; }
            else if (id < IT_WUV) { const int k = id - IT_CKV; mp = MP_CKV; c2 = rk * 4; c3 = (k * 64 + (j >> 1)) * 2; }
            else if (id < IT_WO) { mp = MP_WUV; c1 = (j & 3) * 32 + (id - IT_WUV) * 128; c2 = (j >> 2) * 2; }
            else if (id < IT_X) { mp = MP_WO; c0 = (j & 7) * 64; c1 = (j >> 3) * 256 + (id - IT_WO) * 64; }
            else if (id < IT_DOWN) {
                if (j >= J_END) break;
                const int k = id - IT_X;
                mp = j < NFF ? MP_GATE + (k >> 1) : MP_MODB; c0 = (j >> 1) * 64 + (j < NFF ? 0 : 1024 - NFF * 32); c1 = rk * 256 + (k & 1) * 128;
            } else {
                if (id == NEVER) { e = en; continue; }
                mp = MP_DOWN; c1 = j * 32; c2 = (id - IT_DOWN) * 4;
            }
            if (w0) mbar_wait(BAR(w0 - 1), 0);
            const int w2 = e >> 25;
            if (w2) {
                mbar_wait(BAR(w2 - 1), 0);
                while (!__any_sync(0xffffffffu, mbar_test(BAR(w1 - 1), 0) | ((int)(gtime() - tn) > 0))) {}
            } else if (w1) mbar_wait(BAR(w1 - 1), 0);
            tma(sb + ((e >> 6) & 31) * 8192, mp, BAR(id), c0, c1, c2, c3);
            e = en;
        }
    } else if (warp == 13) {
#pragma unroll
        for (int i = 0; i < 2; i++) st2_x4(gs + (B_ML + rk * 16 + i * 8 + g) * 4096 + (j >> 1) * 16 + t * 4, 0u, 0u, 0u, 0u);
        if (lane < 16) st2_x4(gs + (B_E2 + (j >> 4)) * 4096 + (j & 15) * 64 + lane * 4, 0u, 0u, 0u, 0u);
        st2_x1(gs + (B_E3 + (j >> 5)) * 4096 + (j & 31) * 32 + lane, 0u);
        if (lane < 8) st2_x1(gs + B_MB * 4096 + j * 8 + lane, 0u);
        if (j < NFF) {
#pragma unroll
            for (int i = 0; i < 2; i++) st2_x4(gs + (B_E5 + i * 8 + g) * 4096 + j * 16 + t * 4, 0u, 0u, 0u, 0u);
        }
        bar_sync(9, 64);
        const uint32_t cs = ldcls();
#pragma unroll 1
        for (int i = 0; i < 32; i++) {
            st_x4(gs + G_E1 + j * 8192 + (i >> 3) * 2048 + ((((cs >> 1) ^ (i >> 3)) & 1) << 10) + (i & 7) * 128 + lane * 4, 0u, 0u, 0u, 0u);
            __nanosleep(JAN_SLEEP);
        }
        fence_gpu();
        if (lane < 8) st2_x1(gs + B_RD * 4096 + j * 8 + lane, 1u + (cs >> 1));
        if (lane == 0) TRACE(41);
        uint32_t rd[4];
        mbar_wait(BAR(IT_CKV + RD_ITEM), 0);
        poll<1024, RD_SLEEP>(rd, gs + near_off(B_RD, cs) + lane * 8);
#pragma unroll
        for (int i = 0; i < 4; i++) {
            const uint32_t m = __ballot_sync(0xffffffffu, rd[i] == 2u);
            if (lane == 0) sts32(sb + SM_CLS + 16 + i * 4, m);
        }
        __syncwarp();
        if (lane < 8) mbar_arrive(BAR(JD));
        if (lane == 0) TRACE(42);
    } else if (warp == 14) {
        uint2 ml[2];
        mbar_waitb(BAR(JD), 0);
        const uint32_t cls = ldcls();
        mbar_waitb(BAR(PF0 + 2 * NUNITS - 1), 0);
        __nanosleep(ML_DELAY);
        Poll2<uint2, 2> pm2;
        if (P2 & 1) { ml[0] = ml[1] = make_uint2(0u, 0u); pm2.run<64>(ml, gs + near_off(B_ML + (j >> 2), cls) + lane * 32); }
        else poll<64, ML_SLEEP>(ml, gs + near_off(B_ML + (j >> 2), cls) + lane * 32);
        if (!E1_DIRECT) bar_arrive(3, 288);
        if (lane == 0) TRACE_Q(37);
        const float m0 = __uint_as_float(ml[0].x), m1 = __uint_as_float(ml[1].x);
        const int mi = __float_as_int(fmaxf(m0, m1));
        const int mr = __reduce_max_sync(0xffffffffu, mi ^ ((mi >> 31) & 0x7fffffff));
        const float mm = __int_as_float(mr ^ ((mr >> 31) & 0x7fffffff));
        const uint32_t w0 = pack2(ex2(m0 - mm), 0.f), w1 = pack2(ex2(m1 - mm), 0.f);
        const uint32_t wa = sb + SM_W + (lane >> 3) * 64 + (lane & 1) * 32 + ((lane >> 1) & 3) * 4;
        sts32(wa, w0 * 0x10001u); sts32(wa + 16, w1 * 0x10001u);
        bar_arrive(8, 288);
        float L = bflo(w0) * __uint_as_float(ml[0].y) + bflo(w1) * __uint_as_float(ml[1].y);
#pragma unroll
        for (int o = 16; o; o >>= 1) L += shx(L, o);
        if (lane == 0) *(float*)(sm + SM_FQ) = __frcp_rn(L);
        if (lane == 0) TRACE(10);
        if (P2 & 1) pm2.settle();
        bar_sync(4, 288);
        clear_head();
        if (j < NFF) {
            uint32_t ya = sb + SM_Y + lane * 16, sa = peer_addr(sb + SM_RED + 2048 + rk * 8, lane & 1), tb = peer_addr(BAR(QB), lane & 1);
            pin(ya); pin(sa); pin(tb);
            bar_sync(7, 288);
            const float4 y0 = ldsf4(ya), y1 = ldsf4(ya + 512);
            float s = sum4(y0) + sum4(y1);
            float q = (fmaf(y0.x, y0.x, y0.y * y0.y) + fmaf(y0.z, y0.z, y0.w * y0.w)) + (fmaf(y1.x, y1.x, y1.y * y1.y) + fmaf(y1.z, y1.z, y1.w * y1.w));
#pragma unroll
            for (int o = 16; o; o >>= 1) { s += shx(s, o); q += shx(q, o); }
            if (lane < 2) st_async2(sa, s, q, tb);
        }
    } else if (warp == 15) {
        mbar_waitb(BAR(IT_X - 1), 0);
        if (j < J_END) mbar_waitb(BAR(j < NFF ? NITEMS - 1 : MBB), 0);
    }
    } else if (warp < 4) {
        float* scr = (float*)(sm + SM_SCR);
        uint32_t cls;
        {
            uint2 ha[8];
            {
                uint32_t best = 0xffffffffu;
#pragma unroll
                for (int i = 0; i < NPROBE; i++) {
                    uint32_t t0, t1, o;
                    asm volatile("mov.u32 %0, %%clock;" : "=r"(t0));
                    asm volatile("atom.relaxed.gpu.global.exch.b32 %0, [%1], %2;" : "=r"(o) : "l"(pl), "r"(2u + i) : "memory");
                    asm volatile("{\n.reg .pred p;\nsetp.ne.u32 p, %1, 0x1234567;\nmov.u32 %0, 0;\n@p mov.u32 %0, %%clock;\n}" : "=r"(t1) : "r"(o));
                    best = min(best, t1 - t0);
                }
                if (lane == 0) scr[16 + warp] = __uint_as_float(best);
            }
            const float sh = __shfl_sync(0xffffffffu, bflo(in1), 0);
            const float v0 = bflo(in1) - sh, v1 = bfhi(in1) - sh, v2 = bflo(in2) - sh, v3 = bfhi(in2) - sh;
            float mb, sd;
            ln_stats<4>((v0 + v1) + (v2 + v3), (v0 * v0 + v1 * v1) + (v2 * v2 + v3 * v3), sh, scr, warp, lane, 2, mb, sd);
            if (!rk) in2 = in1;
            const uint4 lt = *(const uint4*)(scr + 16);
            cls = NUMA ? ((lt.y < lt.x) ^ (__popc((B_PR + (j >> 5)) & 0x2C) & 1)) | (lt.w < lt.z) << 1 : 0;
            if (warp == 0) { if (lane == 0) sts32(sb + SM_CLS, cls); bar_arrive(9, 64); }
            if (tid == 0) TRACE(38);
            asm volatile("barrier.cluster.wait.aligned;" ::: "memory");
            mbar_wait(BAR(IT_MODA), 0);
            __nanosleep(HA_DELAY);
            poll<1024, H_SLEEP, false, 16384>(ha, gs + near_off(B_HA + rk * 2, cls) + 2 * tid);
            auto rsum = [](uint32_t a, uint32_t b, uint32_t c, uint32_t d) { return rbf((__uint_as_float(a) + __uint_as_float(b)) + (__uint_as_float(c) + __uint_as_float(d))); };
            sts32(sb + SM_FV + frag_off(2 * tid),
                  pack2(ln_mod(bflo(in2), mb, sd, rsum(ha[4].x, ha[5].x, ha[6].x, ha[7].x), rsum(ha[0].x, ha[1].x, ha[2].x, ha[3].x)),
                        ln_mod(bfhi(in2), mb, sd, rsum(ha[4].y, ha[5].y, ha[6].y, ha[7].y), rsum(ha[0].y, ha[1].y, ha[2].y, ha[3].y))));
            bar_arrive(5, 384);
            mbar_wait(BAR(QB), 0);
            if (tid < 64) {
                const float* qx = (const float*)(sm + SM_QX) + tid;
                sts16(sb + SM_FQ + frag_off(tid), pack2((qx[0] + qx[64]) + (qx[128] + qx[192]), 0.f));
            }
            bar_arrive(6, 384);
        }
        asm volatile("setmaxnreg.inc.sync.aligned.u32 168;");
        float acc[128];
        float M = 0.f;
        uint32_t pa = sb + SM_XA + warp * 512 + lane * 16, ma = sb + SM_MX + (warp * 8 + g) * 4, pf = BAR(PF0);
        uint32_t blo = __reduce_or_sync(0xffffffffu, (((sb + SM_U) & 0x3FFFFu) >> 4) | 0x400000u);
        uint32_t* e1[4];
#pragma unroll
        for (int i = 0; i < 4; i++) e1[i] = gs + G_E1 + (warp * 8 + g) * 4 * 8192 + (rk * 2 + (j >> 6)) * 2048 + ((j >> 1) & 31) * 32 + t * 4;
        uint32_t ck[10] = {0, 0, 0, 0, 0, 0, 0, 0, 0, 0};
#pragma unroll 1
        for (int h = 0; h < 2 * NUNITS; h++) {
            CLK(ck[0], h == 2 * TU); CLK(ck[5], h == 2 * TU + 1);
            mbar_wait(pf, 0);
            CLK(ck[1], h == 2 * TU); CLK(ck[6], h == 2 * TU + 1);
            const float m = __uint_as_float(lds32(ma));
            const uint4 pn = lds128(pa);
            wg_wait0();
#pragma unroll
            for (int i = 0; i < 128; i++) asm volatile("" : "+f"(acc[i]) :: "memory");
            CLK(ck[2], h == 2 * TU); CLK(ck[7], h == 2 * TU + 1);
            if (h == 0) M = m;
            uint32_t b2 = 0x3f803f80u;
            if (__builtin_expect(__any_sync(0xffffffffu, m != M), 0)) {
                const float Mn = fmaxf(M, m), alpha = ex2(M - Mn), beta = ex2(m - Mn);
                M = Mn;
                b2 = pack2(beta, beta);
#pragma unroll
                for (int jj = 0; jj < 32; jj++) { acc[4 * jj] *= alpha; acc[4 * jj + 1] *= alpha; }
            }
            auto mul2 = [](uint32_t x, uint32_t y) { uint32_t r; asm("mul.rn.bf16x2 %0, %1, %2;" : "=r"(r) : "r"(x), "r"(y)); return r; };
            const uint4 p = make_uint4(mul2(pn.x, b2), mul2(pn.y, b2), mul2(pn.z, b2), mul2(pn.w, b2));
            if (tid == 0 && (h & 1)) TRACE_Q(48 + (h >> 1));
            CLK(ck[3], h == 2 * TU); CLK(ck[8], h == 2 * TU + 1);
            wgmma_pv(acc, p, blo, h);
            CLK(ck[4], h == 2 * TU); CLK(ck[9], h == 2 * TU + 1);
            if (lane == 0 && h > 0 && !(h & 1)) mbar_arrive(BAR(EB_UNIT0 + (h >> 1) - 1));
            blo += h == 11 ? -11 * 1024 : 1024;
            pa += (h == 5 || h == 11) ? -5 * 2048 : 2048;
            ma += 128; pf += 8;
            if (h == 2 * NUNITS - 3) {
                mbar_wait(BAR(JD), 0);
                const uint32_t hm = (*(const uint32_t*)(sm + SM_CLS + 16 + warp * 4) >> (g * 4)) ^ ((j >> 6) ? 15u : 0u);
#pragma unroll
                for (int i = 0; i < 4; i++) e1[i] += ((hm >> i) & 1) << 10;
            }
        }
#pragma unroll
        for (int vv = 0; vv < 2; vv++) {
            if (vv && M == 1.f) __trap();
            if (vv) wg_wait0(); else wg_wait1();
#pragma unroll
            for (int i = 0; i < 64; i++) asm volatile("" : "+f"(acc[vv * 64 + i]) :: "memory");
            if (tid == 0 && !vv) TRACE_Q(63);
#pragma unroll
            for (int i = 0; i < 4; i++) {
                const float* a = &acc[vv * 64 + i * 16];
                st_x4(e1[i] + i * 8192 + vv * 16, enc(pack2(a[0], a[1])), enc(pack2(a[4], a[5])), enc(pack2(a[8], a[9])), enc(pack2(a[12], a[13])));
            }
        }
        if (tid == 0) TRACE_Q(17);
        if (j >= NFF && j < J_END) {
            uint4 a[8], b[4];
            float c[4], e[4];
            const bool own = (warp >> 1) == rk;
            const uint32_t xa = sb + SM_FV + (warp & 1) * 64 + g * 8;
            if (lane == 0) mbar_expect(BAR(MBB), own ? 64 : 0);
#pragma unroll
            for (int i = 0; i < 2; i++) {
                ldfrag(b, sb + SM_FS + rk * 512 + i * 256 + t * 16);
                mbar_wait(BAR(IT_X + i), 0);
                const uint32_t ab = sb + SM_U + B_X * 32768 + i * 16384 + a128;
                load8<true>(a, [&](int s) { return ab + s * 2048; });
                mma8(i ? e : c, a, b);
            }
            c[0] += e[0]; c[2] += e[2];
            if (!own) {
                if (t == 0) st_async2(peer_addr(xa, rk ^ 1), c[0], c[2], peer_addr(BAR(MBB), rk ^ 1));
            } else {
                mbar_wait(BAR(MBB), 0);
                const float2 pp = *(const float2*)(sm + (xa - sb));
                const float mine = t ? c[2] + pp.y : c[0] + pp.x, other = shx(mine, 4);
                const uint32_t w = (warp & 1) * 8 + t * 4 + (g >> 1), val = enc(pack2(mine, other));
                if (t < 2 && !(g & 1)) {
                    if (j < J_RED) st2_x1(gs + B_MB * 4096 + (j - NFF) * 16 + w, val);
                    else sts32(sb + SM_FV + 256 + w * 4, val);
                }
                if (j >= J_RED) bar_arrive(7, 320);
                if (lane == 0) TRACE(11);
            }
        }
    } else {
        const int u8 = tid - 128, w8 = warp - 4;
        const int v = w8 >> 2, wq4 = w8 & 3;
        {
            const float c0 = bflo(in1), c1 = bfhi(in1);
            sts32(sb + SM_FS + frag_off(2 * u8), pack2(__fdividef(c0, 1.f + __expf(-c0)), __fdividef(c1, 1.f + __expf(-c1))));
        }
        bar_sync(1, 256);
        asm volatile("barrier.cluster.wait.aligned;" ::: "memory");
        uint4 a[8], b[4]; float c[4];
        if (w8 < 2) {
            ldfrag(b, sb + SM_FS + (j >> 5) * 256 + t * 16);
            mbar_wait(BAR(IT_MODA), 0);
            if (u8 == 0) TRACE(12);
            const uint32_t ab = sb + SM_XA + w8 * 4096 + a16;
            load8<true>(a, [&](int s) { return ab + s * 512; });
            mma8(c, a, b);
            if (t < 2) st2_x1(gs + (B_HA + ((j >> 4) & 1) * 2 + w8) * 4096 + (j >> 5) * 256 + (j & 15) * 16 + t * 8 + g, encf(t ? c[2] : c[0]));
        }
        {
            mbar_wait(BAR(IT_WQ + 2 * v <= NCP ? 1 : IT_WQ + 2 * v), 0); mbar_wait(BAR(IT_WQ + 2 * v + 1 <= NCP ? 1 : IT_WQ + 2 * v + 1), 0);
            const uint32_t ab = sb + SM_U + 4 * 32768 + v * 16384 + a128;
            load8<true>(a, [&](int s) { return ab + s * 2048; });
            if (lane == 0) mbar_arrive(BAR(EB_WQ));
            bar_sync(5, 384);
            if (u8 == 0) TRACE(13);
            ldfrag(b, sb + SM_FV + v * 256 + t * 16);
            mma8(c, a, b);
            if (t < 2) {
                const float qv = t ? c[2] : c[0];
                const uint32_t qa_ = sb + SM_QX + ((rk * 2 + v) * 64 + wq4 * 16 + t * 8 + g) * 4;
                asm volatile("st.async.weak.shared::cluster.mbarrier::complete_tx::bytes.f32 [%0], %1, [%2];"
                             :: "r"(peer_addr(qa_, rk ^ 1)), "f"(qv), "r"(peer_addr(BAR(QB), rk ^ 1)) : "memory");
                sts32(qa_, __float_as_uint(qv));
            }
            __syncwarp();
            if (lane == 0) mbar_expect(BAR(QB), 64);
        }
        {
            mbar_wait(BAR(IT_WUK + v), 0); mbar_wait(BAR(IT_WUK + v + 2), 0);
            const uint32_t ab = sb + SM_U + 5 * 32768 + (w8 * 16 + r8 + 8 * lb3) * 128;
            const uint32_t x16 = (lb4 ^ r8) * 16;
            load8<false>(a, [&](int s) { return ab + (s & 1) * 16384 + (x16 ^ ((s >> 1) * 32)); });
            bar_sync(6, 384);
            if (u8 == 0) TRACE(14);
            b[0] = lds128(sb + SM_FQ + t * 16); b[1] = lds128(sb + SM_FQ + 64 + t * 16);
            float e[4] = {0.f, 0.f, 0.f, 0.f};
            c[0] = c[1] = c[2] = c[3] = 0.f;
#pragma unroll
            for (int k = 0; k < 4; k++) {
                const uint32_t b0 = (k & 1) ? b[k >> 1].z : b[k >> 1].x, b1 = (k & 1) ? b[k >> 1].w : b[k >> 1].y;
                mma(c, a[2 * k].x, a[2 * k].y, a[2 * k].z, a[2 * k].w, b0, b1);
                mma(e, a[2 * k + 1].x, a[2 * k + 1].y, a[2 * k + 1].z, a[2 * k + 1].w, b0, b1);
            }
            const float mine = ((t & 1) ? ((t & 2) ? e[2] : e[0]) : ((t & 2) ? c[2] : c[0])) * 0.12751743f;
            const float other = shx(mine, 4);
            if (!(g & 1)) st2_x1(gs + (B_QA + rk * 8 + ((j >> 1) & 1) * 4 + (j >> 5)) * 4096 + w8 * 128 + ((j >> 2) & 7) * 16 + (g >> 1) * 4 + t, enc(pack2(mine, other)));
            if (u8 == 0) TRACE(15);
        }
        const uint32_t cls = ldcls();
        __nanosleep(QA_DELAY);
        {
            uint4 qb[8];
            const uint32_t* pq = gs + near_off(B_QA + rk * 8 + wq4, cls) + lane * 4;
            const uint32_t* pq2 = gs + near_off(B_QA + rk * 8 + 4 + wq4, cls) + lane * 4;
            if (lane == 0) {
                mbar_expect(BAR(QT), 4096);
                asm volatile("cp.async.bulk.shared::cluster.global.mbarrier::complete_tx::bytes [%0], [%1], 4096, [%2];"
                             :: "r"(sb + SM_U + 5 * 32768 + w8 * 4096), "l"(gs + near_off(B_QA + rk * 8 + w8, cls)), "r"(BAR(QT)) : "memory");
            }
            const uint32_t qs = sb + SM_U + 5 * 32768 + wq4 * 4096 + lane * 16;
            mbar_wait(BAR(QT), 0);
#pragma unroll
            for (int i = 0; i < 8; i++) { a[i] = lds128(qs + i * 512); qb[i] = lds128(qs + 16384 + i * 512); }
            poll<512, QA_SLEEP, true>(a, pq);
            poll<512, QA_SLEEP, true>(qb, pq2);
            if (lane == 0) mbar_arrive(BAR(EB_WUK));
            auto add2 = [](uint32_t x, uint32_t y) { uint32_t r; asm("add.rn.bf16x2 %0, %1, %2;" : "=r"(r) : "r"(x), "r"(y)); return r; };
#pragma unroll
            for (int i = 0; i < 8; i++) a[i] = make_uint4(add2(a[i].x, qb[i].x), add2(a[i].y, qb[i].y), add2(a[i].z, qb[i].z), add2(a[i].w, qb[i].w));
        }
        if (u8 == 0) TRACE(8);
        {
            float m = -INFINITY, l = 0.f;
            uint32_t xl = sb + SM_XB + w8 * 2048 + lane * 16, xr = peer_addr(xl, rk ^ 1), bsr = peer_addr(BAR(SF0 + v), rk ^ 1);
            uint32_t pa = sb + SM_XA + v * 2048 + wq4 * 512 + lane * 16, ma = sb + SM_MX + v * 128 + (wq4 * 8 + g) * 4;
            uint32_t fb = BAR(IT_CKV + v * 2), sf = BAR(SF0 + v);
            uint32_t dlo = __reduce_or_sync(0xffffffffu, (((sb + SM_U + v * 16384) & 0x3FFFFu) >> 4) | 0x10000u);
            uint32_t ck[9] = {0, 0, 0, 0, 0, 0, 0, 0, 0};
            if (STAG && v) __nanosleep(STAG);
#pragma unroll 1
            for (int n = 0; n < NUNITS; n++) {
                CLK(ck[0], n == TU); CLK(ck[8], n == TU + 1);
                float d[2][16], sc[8];
#pragma unroll
                for (int i = 0; i < 2; i++) {
                    mbar_wait(fb + i * 8, 0);
                    if (i == 0) CLK(ck[1], n == TU);
                    wg_fence();
#pragma unroll
                    for (int s = 0; s < 8; s++) wgmma_rs_n32(d[i], a[s], (0x40000080ull << 32) | (dlo + i * 512 + (s >> 2) * 64 + (s & 3) * 2), s);
                    wg_commit();
                }
                CLK(ck[2], n == TU);
#pragma unroll
                for (int i = 0; i < 2; i++) {
                    if (i) wg_wait0(); else wg_wait1();
#pragma unroll
                    for (int k = 0; k < 16; k++) asm volatile("" : "+f"(d[i][k]) :: "memory");
                    sc[4 * i] = d[i][0] + d[i][6]; sc[4 * i + 1] = d[i][1] + d[i][7]; sc[4 * i + 2] = d[i][8] + d[i][14]; sc[4 * i + 3] = d[i][9] + d[i][15];
                    asm volatile("st.async.weak.shared::cluster.mbarrier::complete_tx::bytes.v4.f32 [%0], {%1, %2, %3, %4}, [%5];"
                                 :: "r"(xr + i * 1024), "f"(sc[4 * i]), "f"(sc[4 * i + 1]), "f"(sc[4 * i + 2]), "f"(sc[4 * i + 3]), "r"(bsr) : "memory");
                }
                CLK(ck[3], n == TU);
                if (u8 == 128) TRACE_Q(56 + (n < 6 ? n : -40));
                if (n >= 3) mbar_wait(BAR(EB_UNIT0 + n - 3), 0);
                dlo += n == 5 ? -5 * 2048 : 2048;
                fb += 32; xr ^= 512; bsr += 16;
                pin(fb); pin(xr); pin(bsr);
                CLK(ck[4], n == TU);
                mbar_wait(sf, 0);
                CLK(ck[5], n == TU);
                const float4 x = ldsf4(xl), y = ldsf4(xl + 1024);
                sc[0] += x.x; sc[1] += x.y; sc[2] += x.z; sc[3] += x.w; sc[4] += y.x; sc[5] += y.y; sc[6] += y.z; sc[7] += y.w;
                float pr[8];
#pragma unroll
                for (int i = 0; i < 8; i++) pr[i] = ex2(sc[i] - m);
                float mx = fmaxf(fmaxf(fmaxf(sc[0], sc[1]), fmaxf(sc[2], sc[3])), fmaxf(fmaxf(sc[4], sc[5]), fmaxf(sc[6], sc[7])));
                if (__builtin_expect(__any_sync(0xffffffffu, mx > m), 0)) {
                    mx = fmaxf(mx, shx(mx, 1));
                    mx = fmaxf(mx, shx(mx, 2));
                    const float mn = fmaxf(m, ceilf(mx * 0.0625f) * 16.f);
                    l *= ex2(m - mn);
                    m = mn;
#pragma unroll
                    for (int i = 0; i < 8; i++) pr[i] = ex2(sc[i] - m);
                }
                CLK(ck[6], n == TU);
                stsf(ma, m);
                asm volatile("st.shared.v4.u32 [%0], {%1, %2, %3, %4};" :: "r"(pa), "r"(pack2(pr[0], pr[1])), "r"(pack2(pr[2], pr[3])),
                             "r"(pack2(pr[4], pr[5])), "r"(pack2(pr[6], pr[7])) : "memory");
                __syncwarp();
                if (lane == 0) mbar_arrive(sf + (PF0 - SF0) * 8);
                CLK(ck[7], n == TU);
                l += ((pr[0] + pr[1]) + (pr[2] + pr[3])) + ((pr[4] + pr[5]) + (pr[6] + pr[7]));
                xl ^= 512; sf += 16; ma += 256; pa += (n == 2 || n == 5) ? -8192 : 4096;
            }
            l += shx(l, 1);
            l += shx(l, 2);
            float2* mlx = (float2*)(sm + SM_MX + 2048) + wq4 * 8 + g;
            if (v == 0) { *mlx = make_float2(m, l); bar_arrive(11, 256); }
            else {
                mbar_wait(BAR(JD), 0);
                bar_sync(11, 256);
                const float2 o = *mlx;
                const float mn = fmaxf(m, o.x);
                l = l * ex2(m - mn) + o.y * ex2(o.x - mn);
                if ((wq4 >> 1) == rk) st_x4(gs + (B_ML + wq4 * 8 + g) * 4096 + (t >> 1) * 1024 + (j >> 1) * 16 + (t & 1) * 4, encf(mn), encf(l), 1u, 1u);
            }
        }
        asm volatile("setmaxnreg.inc.sync.aligned.u32 144;");
        const int pi = j < NFF ? rk * 128 + w8 * 16 + (lane & 15) : ((j - J_RED) & 15) * 16 + v * 8 + lb4 * 4 + wq4;
        const uint32_t xw = *(const uint32_t*)(xin + 2 * pi);
        uint32_t rl = sb + SM_RED + lane * 16;
        {
#pragma unroll 1
            for (int i = 0; i < 4; i++) mbar_wait(BAR(IT_WUV + i), 0);
            const uint32_t ab = sb + SM_U + B_WUV * 32768 + v * 4096 + a128;
            load8<true>(a, [&](int s) { return ab + (s >> 1) * 8192 + (s & 1) * 2048; });
            uint32_t pa = sb + SM_PB + wq4 * 320 + frag_off(64 * v + 32 * (g >> 2) + 16 * (t & 1) + 8 * (t >> 1) + 2 * (g & 3));
            uint32_t fa = sb + SM_PB + g * 320 + t * 16, ra = sb + SM_RED + w8 * 288 + g * 16 + t * 4;
            uint32_t rb = sb + SM_RED + (((u8 >> 2) & 12) + t) * 144 + (g & 3) * 32;
            const uint32_t* pe = gs + G_E1 + j * 8192 + (w8 >> 1) * 2048 + ((((cls >> 1) ^ (w8 >> 1)) & 1) << 10) + (((w8 & 1) * 16 + t) * 8 + g) * 4;
            uint32_t* p2 = gs + (B_E2 + (j >> 4)) * 4096 + (u8 >> 6) * 1024 + (j & 12) * 64 + (u8 & 48) * 4 + (j & 3) * 16 + (u8 & 15);
            pin(pa); pin(fa); pin(ra); pin(rb); pin(rl); pin(pe); pin(p2);
            uint4 pv[4];
            bar_sync(3, 288);
            TK(0);
            poll_start<512>(pv, pe);
            bar_sync(8, 288);
            const uint4 wa = lds128(sb + SM_W + (wq4 * 4 + t) * 16);
            const uint32_t mk = (g & 1) ? 0xffff0000u : 0x0000ffffu, m0 = (g & 2) ? 0u : mk, m1 = (g & 2) ? mk : 0u;
            uint32_t wb[8] = {wa.x & m0, wa.x & m1, wa.y & m0, wa.y & m1, wa.z & m0, wa.z & m1, wa.w & m0, wa.w & m1};
#pragma unroll
            for (int i = 0; i < 8; i++) pin(wb[i]);
            poll<512, E1_SLEEP, true>(pv, pe);
            if (u8 == 0) TRACE_Q(18);
            TK(1);
            float e[4][4];
#pragma unroll
            for (int i = 0; i < 4; i++) {
                e[i][0] = e[i][1] = e[i][2] = e[i][3] = 0.f;
                mma(e[i], pv[i].x, pv[i].y, pv[i].z, pv[i].w, wb[2 * i], wb[2 * i + 1]);
            }
            const float r0 = (t & 2) ? (e[0][2] + e[1][2]) + (e[2][2] + e[3][2]) : (e[0][0] + e[1][0]) + (e[2][0] + e[3][0]);
            const float r1 = (t & 2) ? (e[0][3] + e[1][3]) + (e[2][3] + e[3][3]) : (e[0][1] + e[1][1]) + (e[2][1] + e[3][1]);
            const uint32_t hi = pack2(r0, r1);
            sts32(pa, hi); sts32(pa + 1280, pack2(r0 - bflo(hi), r1 - bfhi(hi)));
            TK(2);
            bar_sync(1, 256);
            TK(3);
            if (u8 == 0) TRACE(19);
            ldfrag(b, fa);
            mma8(c, a, b);
            stsf(ra, c[0] + c[1]); stsf(ra + 144, c[2] + c[3]);
            TK(4);
            bar_sync(4, 288);
            TK(5);
            if (w8 < 4) {
                const float inv = *(const float*)(sm + SM_FQ);
                st_x1(p2, enc(pack2(sum4(ldsf4(rb)) * inv, sum4(ldsf4(rb + 16)) * inv)));
            }
            TK(6);
            if (u8 == 0) TRACE(20);
        }
        uint32_t mb[3] = {0u, 0u, 0u};
        const uint32_t* pm = gs + near_off(B_MB, cls) + pi;
        pin(pm);
        if (j < NFF) poll_start<1024>(mb, pm);
        {
            const uint32_t nz = lb4 ? 0x80008000u : 0u;
#pragma unroll
            for (int i = 0; i < 4; i++) b[i] = make_uint4(nz, nz, nz, nz);
            const bool early = __all_sync(0xffffffffu, mbar_test(BAR(IT_WO + 2 * v), 0) & mbar_test(BAR(IT_WO + 2 * v + 1), 0));
            const uint32_t ab = sb + SM_U + B_WO * 32768 + v * 16384 + a128;
            if (early) load8<true>(a, [&](int s) { return ab + s * 2048; });
            uint32_t ra = sb + SM_R3 + (wq4 * 16 + g) * 16 + v * 8 + t * 4, rb = sb + SM_R3 + lane * 32;
            uint32_t* p3 = gs + (B_E3 + ((j >> 2) & 1) * 2 + (j >> 6)) * 4096 + w8 * 1024 + ((j >> 3) & 7) * 128 + (j & 3) * 32 + lane;
            pin(ra); pin(rb); pin(p3);
            TK(7);
            Poll2<uint4, 4> p2;
            if (P2 & 2) p2.run<256>(b, gs + near_off(B_E2 + (j >> 4), cls) + (((j >> 3) & 1) * 2 + v) * 256 + lane * 4);
            else poll<256, E2_SLEEP, true>(b, gs + near_off(B_E2 + (j >> 4), cls) + (((j >> 3) & 1) * 2 + v) * 256 + lane * 4);
            if (!early) { mbar_wait(BAR(IT_WO + 2 * v), 0); mbar_wait(BAR(IT_WO + 2 * v + 1), 0); load8<true>(a, [&](int s) { return ab + s * 2048; }); }
            TK(8);
            if (u8 == 0) TRACE(21);
            mma8(c, a, b);
            if (t < 2) { stsf(ra, c[0] + c[1]); stsf(ra + 128, c[2] + c[3]); }
            TK(9);
            bar_sync(1, 256);
            TK(10);
            if (w8 < 2) st_x1(p3, enc(pack2(sum4(ldsf4(rb)), sum4(ldsf4(rb + 16)))));
            if (P2 & 2) p2.settle();
            TK(11);
            if (u8 == 0) TRACE(22);
        }
        if (j < NFF) {
            const uint32_t* p3 = gs + near_off(B_E3 + rk * 2 + lb4, cls) + (pi & 127);
            uint32_t za = sb + SM_FZ + lb4 * 576 + frag_off(w8 * 32 + (lane & 15) * 2);
            uint32_t fa = sb + SM_FZ + (g & 3) * 576 + lb4 * 256 + t * 16, ya = sb + SM_Y + u8 * 4;
            poll<1024, MB_SLEEP, true>(mb, pm);
            const uint32_t kk = pack2(1.f + bflo(mb[2]), 1.f + bfhi(mb[2]));
            sts32(za + 2 * 576, lb4 ? mb[1] : kk);
            uint32_t e3[8] = {0u, 0u, 0u, 0u, 0u, 0u, 0u, 0u};
            uint32_t ra = peer_addr(sb + SM_RED + (rk * 2 + v) * 512 + ((wq4 & 1) * 16 + (t >> 1) * 8 + g) * 16 + (t & 1) * 8, wq4 >> 1), tbo = peer_addr(BAR(QB), wq4 >> 1);
            uint32_t ad = sb + SM_U + B_DN * 32768 + w8 * 4096 + (r8 + 8 * lb4) * 128 + (lb3 ^ r8) * 16;
            uint32_t* p5 = gs + (B_E5 + w8 * 2 + (t >> 1)) * 4096 + j * 16 + (t & 1) * 8 + g;
            pin(za); pin(fa); pin(ya); pin(ra); pin(tbo); pin(ad); pin(p5);
            if (lane == 0) mbar_expect(BAR(QB), 258);
            uint4 a2[8];
            TK(12);
            const uint32_t gb = BAR(IT_X + v * 2), ab = sb + SM_U + (B_X + v) * 32768 + a128;
            bool early = false, early2 = false;
            auto ldw = [&]() {
                if (!early) {
                    early = __all_sync(0xffffffffu, mbar_test(gb, 0));
                    if (early) load8<true>(a, [&](int s) { return ab + s * 2048; });
                }
                if (!early2) {
                    early2 = __all_sync(0xffffffffu, mbar_test(gb + 8, 0));
                    if (early2) load8<true>(a2, [&](int s) { return ab + 16384 + s * 2048; });
                }
            };
            Poll2<uint32_t, 8> p2;
            if (P2 & 4) p2.run<512>(e3, p3, ldw); else poll<512, 0, true>(e3, p3, ldw);
            TK(13);
            if (u8 == 0) TRACE(23);
            const float s0 = sumlo(e3), s1 = sumhi(e3);
            const float y0 = fmaf(bflo(mb[0]), s0 + shx(s0, 16), bflo(xw)), y1 = fmaf(bfhi(mb[0]), s1 + shx(s1, 16), bfhi(xw));
            stsf(ya, lb4 ? y1 : y0);
            const float z0 = y0 * bflo(kk), z1 = y1 * bfhi(kk);
            const uint32_t zh = pack2(z0, z1);
            sts32(za, lb4 ? pack2(z0 - bflo(zh), z1 - bfhi(zh)) : zh);
            TK(14);
            bar_sync(7, 288);
            TK(15);
            if (u8 == 0) TRACE(24);
            ldfrag(b, fa);
            if (!early) { mbar_wait(gb, 0); load8<true>(a, [&](int s) { return ab + s * 2048; }); }
            if (!early2) { mbar_wait(gb + 8, 0); load8<true>(a2, [&](int s) { return ab + 16384 + s * 2048; }); }
            {
                float e[4][4];
#pragma unroll
                for (int s = 0; s < 16; s++) {
                    const uint4& x = (s & 2) ? a2[(s >> 2) * 2 + (s & 1)] : a[(s >> 2) * 2 + (s & 1)];
                    const uint4& y = b[s >> 2];
                    if (s < 4) e[s][0] = e[s][1] = e[s][2] = e[s][3] = 0.f;
                    mma(e[s & 3], x.x, x.y, x.z, x.w, (s & 1) ? y.z : y.x, (s & 1) ? y.w : y.y);
                }
                const bool hi = t >> 1;
                const float k0 = hi ? e[2][2] + e[3][2] : e[0][0] + e[1][0], k1 = hi ? e[2][3] + e[3][3] : e[0][1] + e[1][1];
                const float o0 = hi ? e[2][0] + e[3][0] : e[0][2] + e[1][2], o1 = hi ? e[2][1] + e[3][1] : e[0][3] + e[1][3];
                TKD(16, o0);
                st_async2(ra, k0 + shx(o0, 2), k1 + shx(o1, 2), tbo);
            }
            if (P2 & 4) p2.settle();
            TK(17);
            const bool early5 = __all_sync(0xffffffffu, mbar_test(BAR(IT_DOWN + v), 0));
            if (early5) load8<true>(a, [&](int s) { return (ad ^ ((s & 3) * 32)) + (s >> 2) * 2048; });
            TK(18);
            mbar_wait(BAR(QB), 1);
            TK(19);
            if (u8 == 0) TRACE(25);
            const float4 st = ldsf4(sb + SM_RED + 2048);
            const float4 f0 = ldsf4(rl), f1 = ldsf4(rl + 512), f2 = ldsf4(rl + 1024), f3 = ldsf4(rl + 1536);
            const float mu = (st.x + st.z) * (1.f / 512.f);
            float rstd;
            asm("rsqrt.approx.ftz.f32 %0, %1;" : "=f"(rstd) : "f"(fmaxf(fmaf(-mu, mu, (st.y + st.w) * (1.f / 512.f)), 0.f) + 1e-5f));
            const float gg = fmaf(rstd, fmaf(-mu, f0.z + f2.z, (f0.x + f0.y) + (f2.x + f2.y)), f0.w + f2.w);
            const float uu = fmaf(rstd, fmaf(-mu, f1.z + f3.z, (f1.x + f1.y) + (f3.x + f3.y)), f1.w + f3.w);
            TKD(20, gg);
            const float hh = __fdividef(gg * uu, 1.f + ex2(-gg * fmaf(gg * gg, 0.10294324f, 2.3022082f)));
            uint32_t hb[4];
#pragma unroll
            for (int i = 0; i < 4; i++) hb[i] = pack2(__shfl_sync(0xffffffffu, hh, 2 * t + 8 * i), __shfl_sync(0xffffffffu, hh, 2 * t + 8 * i + 1));
            TKD(21, __uint_as_float(hb[3]));
            if (!early5) { mbar_wait(BAR(IT_DOWN + v), 0); load8<true>(a, [&](int s) { return (ad ^ ((s & 3) * 32)) + (s >> 2) * 2048; }); }
            uint32_t res = 0;
#pragma unroll
            for (int k = 0; k < 4; k++) {
                c[0] = c[1] = c[2] = c[3] = 0.f;
                mma(c, a[k].x, a[k].y, a[k].z, a[k].w, hb[0], hb[1]);
                mma(c, a[k + 4].x, a[k + 4].y, a[k + 4].z, a[k + 4].w, hb[2], hb[3]);
                if (t == k) res = pack2(c[0], c[2]);
            }
            st2_x1(p5, enc(res));
            TK(22);
            if (u8 == 0) { TRACE(27); TRACE_GT(47); }
        } else if (j >= J_RED && j < J_END) {
            uint32_t ga[1], e3[1];
            poll<0, MB_SLEEP>(ga, pm);
            poll<0, 100>(e3, gs + near_off(B_E3 + (pi >> 7) * 2 + lb3, cls) + r8 * 128 + (pi & 127));
            float y0 = bflo(e3[0]), y1 = bfhi(e3[0]);
#pragma unroll
            for (int o = 8; o; o >>= 1) { y0 += shx(y0, o); y1 += shx(y1, o); }
            y0 = fmaf(bflo(ga[0]), y0, bflo(xw)); y1 = fmaf(bfhi(ga[0]), y1, bfhi(xw));
            bar_sync(7, 320);
            const uint32_t gb = lds32(sb + SM_FV + 256 + (pi & 15) * 4);
            uint32_t* po = (uint32_t*)out + pi;
            pin(po);
            const uint32_t nz = lane < NFF / 2 ? 0u : 0x80008000u;
            uint2 yv[2] = {make_uint2(nz, nz), make_uint2(nz, nz)};
            Poll2<uint2, 2> p2;
            if (P2 & 8) p2.run<NFF * 32>(yv, gs + near_off(B_E5 + j - J_RED, cls) + lane * 16 + w8 * 2);
            else poll<NFF * 32, E5_SLEEP, true>(yv, gs + near_off(B_E5 + j - J_RED, cls) + lane * 16 + w8 * 2);
            if (u8 == 0) TRACE(26);
            const float l0 = bflo(yv[0].x) + bflo(yv[1].x), h0 = bfhi(yv[0].x) + bfhi(yv[1].x);
            const float l1 = bflo(yv[0].y) + bflo(yv[1].y), h1 = bfhi(yv[0].y) + bfhi(yv[1].y);
            float s0 = (lb4 ? h0 : l0) + shx(lb4 ? l0 : h0, 16), s1 = (lb4 ? h1 : l1) + shx(lb4 ? l1 : h1, 16);
#pragma unroll
            for (int o = 8; o; o >>= 1) { s0 += shx(s0, o); s1 += shx(s1, o); }
            if (!(lane & 15)) *po = pack2(fmaf(bflo(gb), s0, y0), fmaf(bfhi(gb), s1, y1));
            if (P2 & 8) p2.settle();
            if (u8 == 0) TRACE(27);
        }
    }
}

typedef CUresult (*EncFn)(CUtensorMap*, CUtensorMapDataType, cuuint32_t, void*, const cuuint64_t*, const cuuint64_t*,
                          const cuuint32_t*, const cuuint32_t*, CUtensorMapInterleave, CUtensorMapSwizzle,
                          CUtensorMapL2promotion, CUtensorMapFloatOOBfill);

void make_map(EncFn enc_fn, CUtensorMap* m, const void* p, cuuint64_t d0, cuuint64_t d1, cuuint64_t d2, cuuint64_t d3,
              cuuint64_t s1, cuuint64_t s2, cuuint64_t s3, cuuint32_t b0, cuuint32_t b1, cuuint32_t b2, cuuint32_t b3, CUtensorMapSwizzle sw) {
    const cuuint64_t dims[4] = {d0, d1, d2, d3}, strides[3] = {s1, s2, s3};
    const cuuint32_t box[4] = {b0, b1, b2, b3}, es[4] = {1, 1, 1, 1};
    enc_fn(m, CU_TENSOR_MAP_DATA_TYPE_BFLOAT16, 4, (void*)p, dims, strides, box, es,
           CU_TENSOR_MAP_INTERLEAVE_NONE, sw, CU_TENSOR_MAP_L2_PROMOTION_L2_64B, CU_TENSOR_MAP_FLOAT_OOB_FILL_NONE);
}

uint32_t* scratch = nullptr;

struct Tune { const char* win; const char* late; int tau, t_off; const char* tail[3][3]; };
Tune tune = {"66666666655555555555555555555555555555555",
             "00000000000000000000999999999999999999999", 315, -200,
             {{"VVVVOOOOguguDD", "55554444345666", "00000000000000"},
              {"VVVVMMOOOO", "5555555555", "0000000000"},
              {"VVVVOOOO......MM", "55554444000000zz", "0000000000000088"}}};
bool ready = false;

}

extern "C" void kernel_launch(void* const* d_in, const int* in_sizes, int n_in, void* d_out, int out_size) {
    (void)in_sizes; (void)n_in; (void)out_size;
    static Maps maps;
    static const void* cached[12] = {};
    bool same = ready;
    for (int i = 0; i < 12 && same; i++) same = cached[i] == d_in[i];
    if (!same) {
        void* fn = nullptr;
        cudaDriverEntryPointQueryResult qr;
        cudaGetDriverEntryPoint("cuTensorMapEncodeTiled", &fn, cudaEnableDefault, &qr);
        EncFn e = (EncFn)fn;
        const CUtensorMapSwizzle S128 = CU_TENSOR_MAP_SWIZZLE_128B;
        make_map(e, &maps.m[MP_WQ], d_in[2], 64, 512, 64, 1, 8192, 128, 8192, 64, 64, 1, 1, S128);
        make_map(e, &maps.m[MP_WUK], d_in[3], 64, 512, 64, 1, 8192, 128, 8192, 64, 64, 1, 1, S128);
        make_map(e, &maps.m[MP_CKV], d_in[1], 64, 8, 8, 4096, 1024, 128, 8192, 64, 8, 4, 2, S128);
        make_map(e, &maps.m[MP_MODB], d_in[11], 3072, 512, 1, 1, 6144, 6144, 6144, 64, 128, 1, 1, S128);
        make_map(e, &maps.m[MP_WUV], d_in[4], 64, 512, 64, 1, 8192, 128, 8192, 64, 32, 2, 1, S128);
        make_map(e, &maps.m[MP_WO], d_in[5], 512, 4096, 1, 1, 1024, 1024, 1024, 64, 64, 1, 1, S128);
        make_map(e, &maps.m[MP_GATE], d_in[7], 1792, 512, 1, 1, 3584, 3584, 3584, 64, 128, 1, 1, S128);
        make_map(e, &maps.m[MP_UP], d_in[8], 1792, 512, 1, 1, 3584, 3584, 3584, 64, 128, 1, 1, S128);
        make_map(e, &maps.m[MP_DOWN], d_in[9], 64, 1792, 8, 1, 1024, 128, 1024, 64, 32, 4, 1, S128);
        for (int r = 0; r < 3; r++) {
            int ids[72], real[72], nreal = 0, cnt[128] = {};
            uint32_t* sc = maps.sched[r];
            auto dig = [](char ch) { return ch >= 'a' ? ch - 'a' + 10 : ch - '0'; };
            for (int i = 0; i < 72; i++) sc[i] = 0;
            for (int i = 0;; i++) {
                int id = i, buf, dep, w, wl;
                if (i < IT_WUV) {
                    const int u = (i - IT_CKV) >> 2;
                    buf = i < IT_CKV ? 4 + ((i - 1) >> 2) : u % 6;
                    dep = i < IT_CKV || u < 4 ? -1 : u < 6 ? EB_WQ + u - 4 : EB_UNIT0 + u - 6;
                    w = dig(tune.win[i]); wl = dig(tune.late[i]);
                } else {
                    const char ch = tune.tail[r][0][i - IT_WUV];
                    if (!ch) break;
                    if (ch == '.') { sc[i] = NEVER; continue; }
                    buf = ch == 'V' ? B_WUV : ch == 'O' ? B_WO : ch == 'D' ? B_DN : ch == 'u' ? B_X + 1 : B_X;
                    id = (ch == 'V' ? IT_WUV : ch == 'O' ? IT_WO : ch == 'D' ? IT_DOWN : ch == 'u' ? IT_X + 2 : IT_X) + cnt[(int)ch]++;
                    dep = EB_UNIT0 + (buf < 2 ? buf + 6 : buf);
                    w = dig(tune.tail[r][1][i - IT_WUV]); wl = dig(tune.tail[r][2][i - IT_WUV]);
                }
                if (id < IT_X ? (id - 1) & 3 : (id - IT_X) & 1) dep = -1;
                ids[i] = id;
                auto back = [&](int d) { const int k = nreal - d; return k < 0 ? 0 : (ids[real[k]] && ids[real[k]] <= NCP ? 1 : ids[real[k]]) + 1; };
                sc[i] = id | (buf * 4 + (id < IT_X ? (id - 1) & 3 : ((id - IT_X) & 1) * 2)) << 6 | (dep + 1) << 11 | (w > 32 ? NEVER + 1 : back(w)) << 18 | (wl ? back(wl) : 0) << 25;
                real[nreal++] = i;
            }
            sc[0] = tune.tau; sc[1] = tune.t_off;
        }
        cudaGetSymbolAddress((void**)&scratch, g_scratch);
        scratch = (uint32_t*)(((uintptr_t)scratch + (2u << 20) - 1) & ~(uintptr_t)((2u << 20) - 1));
        cudaFuncSetAttribute(fused_kernel, cudaFuncAttributeMaxDynamicSharedMemorySize, SM_TOTAL);
        for (int i = 0; i < 12; i++) cached[i] = d_in[i];
        ready = true;
    }
    const First f = {{(const uint8_t*)d_in[2], (const uint8_t*)d_in[11]}, {(const __nv_bfloat16*)d_in[0], (const __nv_bfloat16*)d_in[10]}};
    fused_kernel<<<NCTA, NTHREADS, SM_TOTAL>>>(f, (__nv_bfloat16*)d_out, scratch, maps);
}
```

```cpp
#include <cuda_runtime.h>
#include <cuda_bf16.h>
#include <cuda.h>
#include <stdint.h>

namespace {

constexpr int NCTA = 128;
constexpr int NTHREADS = 512;
constexpr int NUNITS = 8;
constexpr int NFF = 56, J_RED = 104, J_END = 120;
constexpr uint32_t SPIN_LIMIT = 1u << 22;

#define E5_DELAY 0
#define P2 0
#define P2_GAP 250
#define XC_LATE 4
#define MODA_PF ".L2::128B"
#define PREZERO 1
#define E1_DIRECT 0
#define STAG 300
#define TU 2
#define NUMA 1
#define NPROBE 3
#define NCP 2
#define W0 4
#define RD_ITEM 15
#define JAN_SLEEP 100
#define RD_SLEEP 400
#define HA_DELAY 200
#define H_SLEEP 100
#define QA_DELAY 600
#define QA_SLEEP 200
#define ML_DELAY 300
#define ML_SLEEP 50
#define E1_SLEEP 50
#define E2_SLEEP 0
#define E3_SLEEP 0
#define E5_SLEEP 0
#define MB_SLEEP 100
constexpr int B_WUV = 2, B_WO = 3, B_X = 4  , B_DN = 0;

constexpr int SM_U = 0;
constexpr int SM_XA = 6 * 32768;
constexpr int SM_XB = SM_XA + 12288;
constexpr int SM_MX = SM_XB + 16384;
constexpr int SM_FZ = SM_XB + 8192;
constexpr int SM_PB = SM_XB;
constexpr int SM_R3 = SM_XB + 2560;
constexpr int SM_Y = SM_XB + 12288;
constexpr int SM_RED = SM_XB + 4096;
constexpr int SM_FS = SM_XB + 20480;
constexpr int SM_FV = SM_FS + 1024;
constexpr int SM_QX = SM_XA + 8192;
constexpr int SM_FQ = SM_FV + 512;
constexpr int SM_CLS = SM_FQ + 128;
constexpr int SM_W = SM_FQ + 256;
constexpr int SM_SCR = SM_XA + 9216;
constexpr int SM_TR = SM_XB + 19456;
constexpr int SM_BAR = SM_W + 256;
constexpr int SM_TOTAL = SM_BAR + 1024;
static_assert(SM_TOTAL <= 232448, "smem");

enum { IT_MODA = 0, IT_WQ = 1, IT_WUK = 5, IT_CKV = 9, IT_WUV = 41, IT_WO = 45, IT_X = 49  , IT_DOWN = 53, NITEMS = 55,
       NEVER = 63,
       SF0 = 64,
       PF0 = 80,
       EB_UNIT0 = 96, MBB = 103,
       EB_WQ = 104, EB_WUK, QT, QB, JD };

enum { MP_WQ = 0, MP_WUK, MP_CKV, MP_MODB, MP_WUV, MP_WO, MP_GATE, MP_UP, MP_DOWN, NMAPS };
struct First { const uint8_t* w[2]; const __nv_bfloat16* v[2]; };
struct Maps { CUtensorMap m[NMAPS]; uint32_t sched[3][72]; };

enum { B_HA = 0,
       B_MB = 6,
       B_RD = 7,
       B_E2 = 8,
       B_QA = 16,
       B_ML = 32,
       B_E5 = 64,
       B_E3 = 80,
       B_PR = 96,
       B_TR = 100 };
constexpr int G_E1 = 1 << 19;
constexpr int G_TR = B_TR * 4096;
__device__ __align__(1024) uint32_t g_scratch[(8 << 20) / 4];

#define TRACE(slot) do {} while (0)
#define TRACE_Q(slot) do {} while (0)
#define TRACE_GT(slot) do {} while (0)

#define CLK(var, cond) do {} while (0)
#define CLKD(var, cond, dep) do {} while (0)
#define TK(i) do {} while (0)
#define TKD(i, dep) do {} while (0)
__device__ __forceinline__ uint32_t s2u(const void* p) { return (uint32_t)__cvta_generic_to_shared(p); }
__device__ __forceinline__ void mbar_init(uint32_t b, int c) { asm volatile("mbarrier.init.shared::cta.b64 [%0], %1;" :: "r"(b), "r"(c) : "memory"); }
__device__ __forceinline__ void mbar_expect(uint32_t b, uint32_t bytes) { asm volatile("mbarrier.arrive.expect_tx.shared::cta.b64 _, [%0], %1;" :: "r"(b), "r"(bytes) : "memory"); }
__device__ __forceinline__ void mbar_arrive(uint32_t b) { asm volatile("mbarrier.arrive.shared::cta.b64 _, [%0];" :: "r"(b) : "memory"); }
__device__ __forceinline__ void mbar_wait(uint32_t b, uint32_t ph) {
    asm volatile("{\n.reg .pred p;\nW: mbarrier.try_wait.parity.shared::cta.b64 p, [%0], %1;\n@!p bra W;\n}" :: "r"(b), "r"(ph) : "memory");
}
__device__ __forceinline__ void mbar_waitb(uint32_t b, uint32_t ph) {
    asm volatile("{\n.reg .pred p;\n.reg .u32 n;\nmov.u32 n, 0;\n"
                 "W: mbarrier.try_wait.parity.shared::cta.b64 p, [%0], %1;\n@p bra D;\n"
                 "add.u32 n, n, 1;\nsetp.lt.u32 p, n, 0x100000;\n@p bra W;\ntrap;\nD:\n}" :: "r"(b), "r"(ph) : "memory");
}
__device__ __forceinline__ uint32_t mbar_test(uint32_t b, uint32_t ph) {
    uint32_t ok;
    asm volatile("{\n.reg .pred p;\nmbarrier.test_wait.parity.shared::cta.b64 p, [%1], %2;\nselp.u32 %0, 1, 0, p;\n}" : "=r"(ok) : "r"(b), "r"(ph) : "memory");
    return ok;
}
__device__ __forceinline__ void bar_sync(int id, int n) { asm volatile("bar.sync %0, %1;" :: "r"(id), "r"(n) : "memory"); }
__device__ __forceinline__ void bar_arrive(int id, int n) { asm volatile("bar.arrive %0, %1;" :: "r"(id), "r"(n) : "memory"); }
__device__ __forceinline__ uint32_t peer_addr(uint32_t a, uint32_t rank) { uint32_t r; asm("mapa.shared::cluster.u32 %0, %1, %2;" : "=r"(r) : "r"(a), "r"(rank)); return r; }
__device__ __forceinline__ void st_async1(uint32_t a, float x, uint32_t bar) {
    asm volatile("st.async.weak.shared::cluster.mbarrier::complete_tx::bytes.f32 [%0], %1, [%2];" :: "r"(a), "f"(x), "r"(bar) : "memory");
}
__device__ __forceinline__ void st_async2(uint32_t a, float x, float y, uint32_t bar) {
    asm volatile("st.async.weak.shared::cluster.mbarrier::complete_tx::bytes.v2.f32 [%0], {%1, %2}, [%3];" :: "r"(a), "f"(x), "f"(y), "r"(bar) : "memory");
}
__device__ __forceinline__ uint32_t gtime() { uint32_t t; asm volatile("mov.u32 %0, %%globaltimer_lo;" : "=r"(t)); return t; }
__device__ __forceinline__ void fence_gpu() { asm volatile("fence.acq_rel.gpu;" ::: "memory"); }

__device__ __forceinline__ uint32_t enc(uint32_t b) { uint32_t r; asm("max.u32 %0, %1, 1;" : "=r"(r) : "r"(b)); return r; }
__device__ __forceinline__ uint32_t encf(float f) { return enc(__float_as_uint(f)); }
__device__ __forceinline__ void st_x1(uint32_t* p, uint32_t v) { asm volatile("st.relaxed.gpu.global.u32 [%0], %1;" :: "l"(p), "r"(v) : "memory"); }
__device__ __forceinline__ void st_x4(void* p, uint32_t a, uint32_t b, uint32_t c, uint32_t d) {
    asm volatile("st.relaxed.gpu.global.v4.u32 [%0], {%1, %2, %3, %4};" :: "l"(p), "r"(a), "r"(b), "r"(c), "r"(d) : "memory");
}
__device__ __forceinline__ void st2_x1(uint32_t* p, uint32_t v) { st_x1(p, v); st_x1(p + 1024, v); }
__device__ __forceinline__ void st2_x4(uint32_t* p, uint32_t a, uint32_t b, uint32_t c, uint32_t d) { st_x4(p, a, b, c, d); st_x4(p + 1024, a, b, c, d); }
__device__ __forceinline__ int near_off(int b, uint32_t cls) { return b * 4096 + (((__popc(b & 0x2C) ^ cls) & 1) << 10); }
__device__ __forceinline__ void ld_x(uint32_t& v, const void* p) { asm volatile("ld.relaxed.gpu.global.u32 %0, [%1];" : "=r"(v) : "l"(p) : "memory"); }
__device__ __forceinline__ void ld_x(uint4& v, const void* p) {
    asm volatile("ld.relaxed.gpu.global.v4.u32 {%0, %1, %2, %3}, [%4];" : "=r"(v.x), "=r"(v.y), "=r"(v.z), "=r"(v.w) : "l"(p) : "memory");
}
__device__ __forceinline__ void ld_x(uint2& v, const void* p) { asm volatile("ld.relaxed.gpu.global.v2.u32 {%0, %1}, [%2];" : "=r"(v.x), "=r"(v.y) : "l"(p) : "memory"); }
__device__ __forceinline__ uint32_t minw(uint32_t v) { return v; }
__device__ __forceinline__ uint32_t minw(const uint2& v) { return min(v.x, v.y); }
__device__ __forceinline__ uint32_t minw(const uint4& v) { return min(__vimin3_u32(v.x, v.y, v.z), v.w); }
template <int N> __device__ __forceinline__ uint32_t mint(const uint32_t* m) {
    if constexpr (N == 1) return m[0];
    else if constexpr (N == 2) return min(m[0], m[1]);
    else return __vimin3_u32(mint<(N + 2) / 3>(m), mint<(N + 1) / 3>(m + (N + 2) / 3), mint<N / 3>(m + (N + 2) / 3 + (N + 1) / 3));
}

template <int STRIDE, int S4 = 4 * STRIDE, typename T, int N>
__device__ __forceinline__ void poll_start(T (&v)[N], const void* base) {
#pragma unroll
    for (int i = 0; i < N; i++) ld_x(v[i], (const uint8_t*)base + (i & 3) * STRIDE + (i >> 2) * S4);
}
struct Nop { __device__ void operator()() const {} };
template <int STRIDE, int SLEEP, bool STARTED = false, int S4 = 4 * STRIDE, typename T, int N, typename F = Nop>
__device__ __forceinline__ void poll(T (&v)[N], const void* base, F idle = F()) {
    if (!STARTED) { poll_start<STRIDE, S4>(v, base); idle(); }
#pragma unroll 1
    for (uint32_t it = 0;; it++) {
        uint32_t m[N];
#pragma unroll
        for (int i = 0; i < N; i++) m[i] = minw(v[i]);
        if (__all_sync(0xffffffffu, mint<N>(m) != 0)) break;
        if (SLEEP && it > 0) __nanosleep(SLEEP);
#pragma unroll
        for (int i = 0; i < N; i++) if (!m[i]) ld_x(v[i], (const uint8_t*)base + (i & 3) * STRIDE + (i >> 2) * S4);
        idle();
        if (it > SPIN_LIMIT) __trap();
    }
}

__device__ __forceinline__ void movx(uint32_t& d, uint32_t x) { asm volatile("mov.b32 %0, %1;" : "=r"(d) : "r"(x)); }
__device__ __forceinline__ void movx(uint2& d, const uint2& x) { movx(d.x, x.x); movx(d.y, x.y); }
__device__ __forceinline__ void movx(uint4& d, const uint4& x) { movx(d.x, x.x); movx(d.y, x.y); movx(d.z, x.z); movx(d.w, x.w); }
template <typename T, int N> struct Poll2 {
    T v[2][N];
    template <int STRIDE, typename F = Nop>
    __device__ __forceinline__ void run(T (&r)[N], const void* base, F idle = F()) {
        auto ok = [&](const T (&x)[N]) {
            uint32_t m[N];
#pragma unroll
            for (int i = 0; i < N; i++) m[i] = minw(x[i]);
            return __all_sync(0xffffffffu, mint<N>(m) != 0);
        };
        auto again = [&](T (&x)[N]) {
#pragma unroll
            for (int i = 0; i < N; i++) if (!minw(x[i])) ld_x(x[i], (const uint8_t*)base + i * STRIDE);
        };
#pragma unroll
        for (int i = 0; i < N; i++) { v[0][i] = r[i]; v[1][i] = r[i]; }
        uint32_t t0, t1;
        asm volatile("mov.u32 %0, %%clock;" : "=r"(t0));
        again(v[0]);
        idle();
        do { asm volatile("mov.u32 %0, %%clock;" : "=r"(t1)); } while (__any_sync(0xffffffffu, t1 - t0 < P2_GAP));
#pragma unroll 1
        for (uint32_t it = 0;; it++) {
            again(v[1]);
            if (ok(v[0])) {
#pragma unroll
                for (int i = 0; i < N; i++) movx(r[i], v[0][i]);
                break;
            }
            again(v[0]);
            idle();
            if (it > SPIN_LIMIT) __trap();
            if (ok(v[1])) {
#pragma unroll
                for (int i = 0; i < N; i++) movx(r[i], v[1][i]);
                break;
            }
        }
    }
    __device__ __forceinline__ void settle() const {
        uint32_t m[2 * N];
#pragma unroll
        for (int i = 0; i < 2 * N; i++) m[i] = minw(v[i / N][i % N]);
        asm volatile("{\n.reg .pred p;\nsetp.eq.u32 p, %0, 0xffffffff;\n@p nanosleep.u32 0;\n}" :: "r"(mint<2 * N>(m)));
    }
};

__device__ __forceinline__ float bflo(uint32_t w) { return __uint_as_float(w << 16); }
__device__ __forceinline__ float bfhi(uint32_t w) { return __uint_as_float(w & 0xffff0000u); }
__device__ __forceinline__ uint32_t pack2(float lo, float hi) {
    uint32_t r; asm("cvt.rn.bf16x2.f32 %0, %1, %2;" : "=r"(r) : "f"(hi), "f"(lo)); return r;
}
__device__ __forceinline__ float rbf(float x) { return __uint_as_float(pack2(0.f, x)); }
__device__ __forceinline__ float sumlo(const uint32_t (&v)[8]) { return ((bflo(v[0]) + bflo(v[1])) + (bflo(v[2]) + bflo(v[3]))) + ((bflo(v[4]) + bflo(v[5])) + (bflo(v[6]) + bflo(v[7]))); }
__device__ __forceinline__ float sumhi(const uint32_t (&v)[8]) { return ((bfhi(v[0]) + bfhi(v[1])) + (bfhi(v[2]) + bfhi(v[3]))) + ((bfhi(v[4]) + bfhi(v[5])) + (bfhi(v[6]) + bfhi(v[7]))); }
__device__ __forceinline__ float ex2(float x) { float r; asm("ex2.approx.ftz.f32 %0, %1;" : "=f"(r) : "f"(x)); return r; }
__device__ __forceinline__ float shx(float v, int m) { return __shfl_xor_sync(0xffffffffu, v, m); }
__device__ __forceinline__ uint4 lds128(uint32_t a) { uint4 v; asm volatile("ld.shared.v4.u32 {%0, %1, %2, %3}, [%4];" : "=r"(v.x), "=r"(v.y), "=r"(v.z), "=r"(v.w) : "r"(a) : "memory"); return v; }
__device__ __forceinline__ uint32_t lds32(uint32_t a) { uint32_t v; asm volatile("ld.shared.u32 %0, [%1];" : "=r"(v) : "r"(a) : "memory"); return v; }
__device__ __forceinline__ void sts32(uint32_t a, uint32_t v) { asm volatile("st.shared.u32 [%0], %1;" :: "r"(a), "r"(v) : "memory"); }
__device__ __forceinline__ void sts16(uint32_t a, uint32_t v) { asm volatile("st.shared.u16 [%0], %1;" :: "r"(a), "h"((uint16_t)v) : "memory"); }
__device__ __forceinline__ int frag_off(int k) { return (k >> 5) * 64 + ((k >> 1) & 3) * 16 + ((k >> 4) & 1) * 8 + ((k >> 3) & 1) * 4 + (k & 1) * 2; }

template <bool TRANS>
__device__ __forceinline__ uint4 ldsm(uint32_t a) {
    uint4 r;
    if (TRANS) asm volatile("ldmatrix.sync.aligned.m8n8.x4.trans.shared.b16 {%0, %1, %2, %3}, [%4];" : "=r"(r.x), "=r"(r.y), "=r"(r.z), "=r"(r.w) : "r"(a) : "memory");
    else asm volatile("ldmatrix.sync.aligned.m8n8.x4.shared.b16 {%0, %1, %2, %3}, [%4];" : "=r"(r.x), "=r"(r.y), "=r"(r.z), "=r"(r.w) : "r"(a) : "memory");
    return r;
}
__device__ __forceinline__ void mma(float (&c)[4], uint32_t a0, uint32_t a1, uint32_t a2, uint32_t a3, uint32_t b0, uint32_t b1) {
    asm volatile("mma.sync.aligned.m16n8k16.row.col.f32.bf16.bf16.f32 {%0,%1,%2,%3}, {%4,%5,%6,%7}, {%8,%9}, {%0,%1,%2,%3};"
                 : "+f"(c[0]), "+f"(c[1]), "+f"(c[2]), "+f"(c[3]) : "r"(a0), "r"(a1), "r"(a2), "r"(a3), "r"(b0), "r"(b1));
}
template <bool TRANS, typename F>
__device__ __forceinline__ void load8(uint4 (&a)[8], F addr) {
    __syncwarp();
#pragma unroll
    for (int s = 0; s < 8; s++) a[s] = ldsm<TRANS>(addr(s));
}
__device__ __forceinline__ void mma8(float (&c)[4], const uint4 (&a)[8], const uint4 (&b)[4]) {
    float e[4][4];
#pragma unroll
    for (int s = 0; s < 8; s++) {
        if (s < 4) e[s][0] = e[s][1] = e[s][2] = e[s][3] = 0.f;
        mma(e[s & 3], a[s].x, a[s].y, a[s].z, a[s].w, (s & 1) ? b[s >> 1].z : b[s >> 1].x, (s & 1) ? b[s >> 1].w : b[s >> 1].y);
    }
#pragma unroll
    for (int i = 0; i < 4; i++) c[i] = (e[0][i] + e[1][i]) + (e[2][i] + e[3][i]);
}
__device__ __forceinline__ void ldfrag(uint4 (&b)[4], uint32_t a) {
    asm volatile("ld.shared.v4.u32 {%0,%1,%2,%3}, [%16];\nld.shared.v4.u32 {%4,%5,%6,%7}, [%16+64];\n"
                 "ld.shared.v4.u32 {%8,%9,%10,%11}, [%16+128];\nld.shared.v4.u32 {%12,%13,%14,%15}, [%16+192];\n"
                 : "=r"(b[0].x), "=r"(b[0].y), "=r"(b[0].z), "=r"(b[0].w), "=r"(b[1].x), "=r"(b[1].y), "=r"(b[1].z), "=r"(b[1].w),
                   "=r"(b[2].x), "=r"(b[2].y), "=r"(b[2].z), "=r"(b[2].w), "=r"(b[3].x), "=r"(b[3].y), "=r"(b[3].z), "=r"(b[3].w) : "r"(a) : "memory");
}
__device__ __forceinline__ void pin(uint32_t& x) { asm volatile("" : "+r"(x)); }
template <typename T> __device__ __forceinline__ void pin(T*& x) { asm volatile("" : "+l"(x)); }
__device__ __forceinline__ float4 ldsf4(uint32_t a) { const uint4 v = lds128(a); return make_float4(__uint_as_float(v.x), __uint_as_float(v.y), __uint_as_float(v.z), __uint_as_float(v.w)); }
__device__ __forceinline__ float sum4(const float4& f) { return (f.x + f.y) + (f.z + f.w); }
__device__ __forceinline__ void stsf(uint32_t a, float v) { sts32(a, __float_as_uint(v)); }

__device__ __forceinline__ void wg_fence() { asm volatile("wgmma.fence.sync.aligned;" ::: "memory"); }
__device__ __forceinline__ void wg_commit() { asm volatile("wgmma.commit_group.sync.aligned;" ::: "memory"); }
__device__ __forceinline__ void wg_wait1() { asm volatile("wgmma.wait_group.sync.aligned 1;" ::: "memory"); }
__device__ __forceinline__ void wg_wait0() { asm volatile("wgmma.wait_group.sync.aligned 0;" ::: "memory"); }
#define R8(o) "+f"(d[o]), "+f"(d[o + 1]), "+f"(d[o + 2]), "+f"(d[o + 3]), "+f"(d[o + 4]), "+f"(d[o + 5]), "+f"(d[o + 6]), "+f"(d[o + 7])
__device__ __forceinline__ void wgmma_rs_n32(float (&d)[16], const uint4& a, uint64_t db, int acc) {
    asm volatile("{\n.reg .pred p;\nsetp.ne.b32 p, %21, 0;\n"
        "wgmma.mma_async.sync.aligned.m64n32k16.f32.bf16.bf16 "
        "{%0,%1,%2,%3,%4,%5,%6,%7,%8,%9,%10,%11,%12,%13,%14,%15}, {%16,%17,%18,%19}, %20, p, 1, 1, 0;\n}"
        : R8(0), R8(8) : "r"(a.x), "r"(a.y), "r"(a.z), "r"(a.w), "l"(db), "r"(acc));
}
#define PV_LO "{%0,%1,%2,%3,%4,%5,%6,%7,%8,%9,%10,%11,%12,%13,%14,%15,%16,%17,%18,%19,%20,%21,%22,%23,%24,%25,%26,%27,%28,%29,%30,%31,%32,%33,%34,%35,%36,%37,%38,%39,%40,%41,%42,%43,%44,%45,%46,%47,%48,%49,%50,%51,%52,%53,%54,%55,%56,%57,%58,%59,%60,%61,%62,%63}, "
#define PV_HI "{%64,%65,%66,%67,%68,%69,%70,%71,%72,%73,%74,%75,%76,%77,%78,%79,%80,%81,%82,%83,%84,%85,%86,%87,%88,%89,%90,%91,%92,%93,%94,%95,%96,%97,%98,%99,%100,%101,%102,%103,%104,%105,%106,%107,%108,%109,%110,%111,%112,%113,%114,%115,%116,%117,%118,%119,%120,%121,%122,%123,%124,%125,%126,%127}, "
__device__ __forceinline__ void wgmma_pv(float (&d)[128], const uint4& a, uint32_t blo, int acc) {
    asm volatile("{\n.reg .pred p;\n.reg .b32 u0, u1, u2, u3, t;\n.reg .b64 d0, d1, d2, d3;\nsetp.ne.b32 p, %133, 0;\n"
        "mov.b64 d0, {%132, 0x40000100};\nadd.u32 t, %132, 512;\nmov.b64 d1, {t, 0x40000100};\n"
        "add.u32 t, %132, 128;\nmov.b64 d2, {t, 0x40000100};\nadd.u32 t, %132, 640;\nmov.b64 d3, {t, 0x40000100};\n"
        "wgmma.fence.sync.aligned;\n"
        "wgmma.mma_async.sync.aligned.m64n128k16.f32.bf16.bf16 " PV_LO "{%128, u0, %129, u1}, d0, p, 1, 1, 1;\n"
        "wgmma.mma_async.sync.aligned.m64n128k16.f32.bf16.bf16 " PV_LO "{%130, u2, %131, u3}, d1, 1, 1, 1, 1;\n"
        "wgmma.commit_group.sync.aligned;\n"
        "wgmma.mma_async.sync.aligned.m64n128k16.f32.bf16.bf16 " PV_HI "{%128, u0, %129, u1}, d2, p, 1, 1, 1;\n"
        "wgmma.mma_async.sync.aligned.m64n128k16.f32.bf16.bf16 " PV_HI "{%130, u2, %131, u3}, d3, 1, 1, 1, 1;\n"
        "wgmma.commit_group.sync.aligned;\n}"
        : R8(0), R8(8), R8(16), R8(24), R8(32), R8(40), R8(48), R8(56), R8(64), R8(72), R8(80), R8(88), R8(96), R8(104), R8(112), R8(120)
        : "r"(a.x), "r"(a.y), "r"(a.z), "r"(a.w), "r"(blo), "r"(acc) : "memory");
}

template <int NW>
__device__ __forceinline__ void ln_stats(float s, float q, float sh, float* scr, int w, int lane, int bar, float& mean_b, float& sd_b) {
#pragma unroll
    for (int o = 16; o; o >>= 1) { s += shx(s, o); q += shx(q, o); }
    constexpr float n = 512.f / NW;
    if (lane == 0) { scr[w] = sh + s * (1.f / n); scr[NW + w] = q - s * s * (1.f / n); }
    bar_sync(bar, NW * 32);
    float mu = 0.f, m2 = 0.f;
#pragma unroll
    for (int i = 0; i < NW; i++) { mu += scr[i]; m2 += scr[NW + i]; }
    mu *= 1.f / NW;
#pragma unroll
    for (int i = 0; i < NW; i++) { const float d = scr[i] - mu; m2 = fmaf(n * d, d, m2); }
    mean_b = rbf(mu);
    sd_b = rbf(sqrtf(rbf(rbf(fmaxf(m2, 0.f) * (1.f / 512.f)) + 1e-5f)));
}
__device__ __forceinline__ float ln_mod(float x, float mean_b, float sd_b, float c, float s) {
    return rbf(rbf(__fdividef(rbf(x - mean_b), sd_b)) * rbf(1.f + c)) + s;
}

__global__ void __cluster_dims__(2, 1, 1) __launch_bounds__(NTHREADS, 1)
fused_kernel(const __grid_constant__ First F, __nv_bfloat16* __restrict__ out, uint32_t* __restrict__ gs, const __grid_constant__ Maps M) {
    extern __shared__ __align__(1024) uint8_t sm[];
    const uint32_t sb = s2u(sm);
    const int tid = threadIdx.x, lane = tid & 31;
    const int j = blockIdx.x, rk = j & 1;
    const int g = lane >> 2, t = lane & 3;
    const int r8 = lane & 7, lb3 = (lane >> 3) & 1, lb4 = lane >> 4;
    const uint64_t pol = 0x12F0000000000000ull;
    uint32_t in1 = 0, in2 = 0;
    {
        auto cpa = [&](uint32_t d, const uint8_t* s) {
            asm volatile("cp.async.cg.shared.global.L2::cache_hint.L2::128B [%0], [%1], 16, %2;" :: "r"(d), "l"(s), "l"(pol) : "memory");
        };
        const uint32_t ut = threadIdx.x, uj = blockIdx.x;
        const uint8_t* w = F.w[ut >= 128];
        if (ut < 128) {
            const uint32_t dq = (sb + ut * 16) ^ ((ut * 2) & 0x70);
            const uint8_t* sq = w + (uint32_t)(((uj & 1) * 256 + (ut >> 3)) * 8192 + (uj >> 1) * 128 + (ut & 7) * 16);
#pragma unroll
            for (int i = 0; i < 4 * NCP; i++) cpa(dq + 4 * 32768 + i * 2048, sq + i * 131072);
        } else if (ut < 384) {
            const uint32_t dm = (sb + ut * 16) ^ ((ut * 2) & 0x10);
            const uint8_t* sa = w + (uint32_t)(((uj >> 5) * 128 + (ut >> 1) - 64) * 6144 + (uj & 31) * 32 + (ut & 1) * 16);
            asm volatile("cp.async.cg.shared.global.L2::cache_hint" MODA_PF " [%0], [%1], 16, %2;" :: "r"(dm + SM_XA - 2048), "l"(sa), "l"(pol) : "memory");
            asm volatile("cp.async.cg.shared.global.L2::cache_hint" MODA_PF " [%0], [%1], 16, %2;" :: "r"(dm + SM_XA + 2048), "l"(sa + 1024), "l"(pol) : "memory");
        }
        else if (ut == 480 && uj < 16 * XC_LATE) asm volatile("prefetch.global.L2 [%0];" :: "l"(F.v[(uj >> 3) & 1] + (uj & 7) * 64));
    }
    const int warp = __shfl_sync(0xffffffffu, tid >> 5, 0);
    const __nv_bfloat16* const xin = F.v[0];
    uint32_t* const pl = gs + (warp < 2 ? (B_PR + (j >> 5)) * 4096 + (j & 31) * 32 : G_E1 + j * 8192) + (warp & 1) * 1024 + lane;
    auto small_loads = [&]() {
        if (warp < 4) { in1 = *(const uint32_t*)(xin + 2 * tid); in2 = *(const uint32_t*)(xin + 256 + 2 * tid); }
        else if (warp < 12) in1 = *(const uint32_t*)(F.v[1] + 2 * (tid - 128));
    };
    if (!XC_LATE) small_loads();
    if (warp < 4) st_x1(pl, 1u);
    auto BAR = [&](int i) -> uint32_t { return sb + SM_BAR + i * 8; };
    const uint32_t a16 = (r8 + 8 * lb4) * 32 + ((lb3 ^ (r8 >> 2)) * 16);
    const uint32_t a128 = (r8 + 8 * lb4) * 128 + ((((warp & 3) * 2 + lb3) ^ r8) * 16);
    auto ldcls = [&]() -> uint32_t { return *(const volatile uint32_t*)(sm + SM_CLS); };
    auto clear_head = [&]() {
        st2_x1(gs + (B_HA + ((j >> 4) & 1) * 2 + lb4) * 4096 + (j >> 5) * 256 + (j & 15) * 16 + (lane & 15), 0u);
        st2_x4(gs + (B_QA + rk * 8 + ((j >> 1) & 1) * 4 + (j >> 5)) * 4096 + g * 128 + ((j >> 2) & 7) * 16 + t * 4, 0u, 0u, 0u, 0u);
        if (lane < 8) st2_x1(gs + B_RD * 4096 + j * 8 + lane, 0u);
    };
    auto tma = [&](uint32_t dst, int mp, uint32_t bar, int c0, int c1, int c2, int c3) {
        asm volatile("{\n.reg .pred p;\nelect.sync _|p, 0xffffffff;\n"
                     "@p cp.async.bulk.tensor.4d.shared::cluster.global.mbarrier::complete_tx::bytes.L2::cache_hint [%0], [%1, {%3, %4, %5, %6}], [%2], %7;\n}"
                     :: "r"(dst), "l"(&M.m[mp]), "r"(bar), "r"(c0), "r"(c1), "r"(c2), "r"(c3), "l"(pol) : "memory");
    };
    if (warp <= 12 || warp == 15) {
        const int grp = warp == 12 ? 0 : warp == 15 ? 13 : warp + 1;
        const uint32_t cnt = grp < 10 ? 1 : grp < 13 ? 4 : 8;
        if (lane == 0) {
#pragma unroll
            for (int i = 0; i < 8; i++) mbar_init(BAR(grp * 8 + i), (i < 2 && grp == 0) ? (i ? 128 : 256) : cnt);
        }
        __syncwarp();
        if (grp < 10 && lane < 8 && (grp || lane > NCP)) mbar_expect(BAR(grp * 8 + lane), grp >= 8 ? 4096 : grp * 8 + lane < IT_X ? 8192 : 16384);
        asm volatile("fence.mbarrier_init.release.cluster;" ::: "memory");
        __syncwarp();
        if (warp == 12) {
#pragma unroll
            for (int i = NCP + 1; i < W0; i++) tma(sb + (15 + i) * 8192, MP_WQ, BAR(i), 0, rk * 256 + (i - 1) * 64, j >> 1, 0);
        }
    } else if (warp == 13) {
        if (lane < NMAPS) asm volatile("prefetch.tensormap [%0];" :: "l"(&M.m[lane]) : "memory");
    } else if (warp == 14 && PREZERO) {
        clear_head();
    }
    __syncthreads();
    if (XC_LATE) small_loads();
    if (warp < 12) asm volatile("cp.async.mbarrier.arrive.noinc.shared::cta.b64 [%0];" :: "r"(BAR(warp < 4)) : "memory");
    asm volatile("barrier.cluster.arrive.relaxed.aligned;" ::: "memory");

    if (warp >= 12) {
    asm volatile("setmaxnreg.dec.sync.aligned.u32 56;");
    if (warp == 12) {
        static_assert(W0 > NCP && W0 <= 5 && NCP >= 1 && NCP <= 4, "W0");
        const uint32_t* sched = M.sched[j < NFF ? 0 : j < J_RED ? 1 : 2];
        uint32_t e = sched[W0];
        uint32_t tn = gtime() + sched[1];
        const uint32_t tau = sched[0];
#pragma unroll 1
        for (int i = W0; e; i++) {
            const uint32_t en = sched[i + 1];
            const int id = e & 63, w0 = (e >> 11) & 127, w1 = (e >> 18) & 127;
            int mp, c0 = 0, c1 = 0, c2 = 0, c3 = 0;
            tn += tau;
            if (id < IT_CKV) { const int k = id - IT_WQ; mp = MP_WQ + (k >> 2); c1 = rk * 256 + (k & 3) * 64; c2 = j >> 1; }
            else if (id < IT_WUV) { const int k = id - IT_CKV; mp = MP_CKV; c2 = rk * 4; c3 = (k * 64 + (j >> 1)) * 2; }
            else if (id < IT_WO) { mp = MP_WUV; c1 = (j & 3) * 32 + (id - IT_WUV) * 128; c2 = (j >> 2) * 2; }
            else if (id < IT_X) { mp = MP_WO; c0 = (j & 7) * 64; c1 = (j >> 3) * 256 + (id - IT_WO) * 64; }
            else if (id < IT_DOWN) {
                if (j >= J_END) break;
                const int k = id - IT_X;
                mp = j < NFF ? MP_GATE + (k >> 1) : MP_MODB; c0 = (j >> 1) * 64 + (j < NFF ? 0 : 1024 - NFF * 32); c1 = rk * 256 + (k & 1) * 128;
            } else {
                if (id == NEVER) { e = en; continue; }
                mp = MP_DOWN; c1 = j * 32; c2 = (id - IT_DOWN) * 4;
            }
            if (w0) mbar_wait(BAR(w0 - 1), 0);
            const int w2 = e >> 25;
            if (w2) {
                mbar_wait(BAR(w2 - 1), 0);
                while (!__any_sync(0xffffffffu, mbar_test(BAR(w1 - 1), 0) | ((int)(gtime() - tn) > 0))) {}
            } else if (w1) mbar_wait(BAR(w1 - 1), 0);
            tma(sb + ((e >> 6) & 31) * 8192, mp, BAR(id), c0, c1, c2, c3);
            e = en;
        }
    } else if (warp == 13) {
#pragma unroll
        for (int i = 0; i < 2; i++) st_x4(gs + (B_ML + rk * 16 + i * 8 + g) * 4096 + (t >> 1) * 1024 + (j >> 1) * 8 + (t & 1) * 4, 0u, 0u, 0u, 0u);
        if (lane < 16) st2_x4(gs + (B_E2 + (j >> 4)) * 4096 + (j & 15) * 64 + lane * 4, 0u, 0u, 0u, 0u);
        st2_x1(gs + (B_E3 + (j >> 5)) * 4096 + (j & 31) * 32 + lane, 0u);
        if (lane < 8) st2_x1(gs + B_MB * 4096 + j * 8 + lane, 0u);
        if (j < NFF) {
#pragma unroll
            for (int i = 0; i < 2; i++) st2_x4(gs + (B_E5 + i * 8 + g) * 4096 + j * 16 + t * 4, 0u, 0u, 0u, 0u);
        }
        bar_sync(9, 64);
        const uint32_t cs = ldcls();
#pragma unroll 1
        for (int i = 0; i < 32; i++) {
            st_x4(gs + G_E1 + j * 8192 + (i >> 3) * 2048 + ((((cs >> 1) ^ (i >> 3)) & 1) << 10) + (i & 7) * 128 + lane * 4, 0u, 0u, 0u, 0u);
            __nanosleep(JAN_SLEEP);
        }
        fence_gpu();
        if (lane < 8) st2_x1(gs + B_RD * 4096 + j * 8 + lane, 1u + (cs >> 1));
        if (lane == 0) TRACE(41);
        uint32_t rd[4];
        mbar_wait(BAR(IT_CKV + RD_ITEM), 0);
        poll<1024, RD_SLEEP>(rd, gs + near_off(B_RD, cs) + lane * 8);
#pragma unroll
        for (int i = 0; i < 4; i++) {
            const uint32_t m = __ballot_sync(0xffffffffu, rd[i] == 2u);
            if (lane == 0) sts32(sb + SM_CLS + 16 + i * 4, m);
        }
        __syncwarp();
        if (lane < 8) mbar_arrive(BAR(JD));
        if (lane == 0) TRACE(42);
    } else if (warp == 14) {
        uint2 ml[2];
        mbar_waitb(BAR(JD), 0);
        const uint32_t cls = ldcls();
        mbar_waitb(BAR(PF0 + 2 * NUNITS - 1), 0);
        __nanosleep(ML_DELAY);
        Poll2<uint2, 2> pm2;
        if (P2 & 1) { ml[0] = ml[1] = make_uint2(0u, 0u); pm2.run<1024>(ml, gs + near_off(B_ML + (j >> 2), cls) + lane * 8); }
        else poll<1024, ML_SLEEP>(ml, gs + near_off(B_ML + (j >> 2), cls) + lane * 8);
        if (!E1_DIRECT) bar_arrive(3, 288);
        if (lane == 0) TRACE_Q(37);
        const float m0 = __uint_as_float(ml[0].x), m1 = __uint_as_float(ml[1].x);
        const int mi = __float_as_int(fmaxf(m0, m1));
        const int mr = __reduce_max_sync(0xffffffffu, mi ^ ((mi >> 31) & 0x7fffffff));
        const float mm = __int_as_float(mr ^ ((mr >> 31) & 0x7fffffff));
        const uint32_t w0 = pack2(ex2(m0 - mm), 0.f), w1 = pack2(ex2(m1 - mm), 0.f);
        const uint32_t wa = sb + SM_W + lb4 * 64 + t * 16 + (g & 3) * 4;
        sts32(wa, w0 * 0x10001u); sts32(wa + 128, w1 * 0x10001u);
        bar_arrive(8, 288);
        float L = bflo(w0) * __uint_as_float(ml[0].y) + bflo(w1) * __uint_as_float(ml[1].y);
#pragma unroll
        for (int o = 16; o; o >>= 1) L += shx(L, o);
        if (lane == 0) *(float*)(sm + SM_FQ) = __frcp_rn(L);
        if (lane == 0) TRACE(10);
        if (P2 & 1) pm2.settle();
        bar_sync(4, 288);
        clear_head();
        if (j < NFF) {
            uint32_t ya = sb + SM_Y + lane * 16, sa = peer_addr(sb + SM_RED + 2048 + rk * 8, lane & 1), tb = peer_addr(BAR(QB), lane & 1);
            pin(ya); pin(sa); pin(tb);
            bar_sync(7, 288);
            const float4 y0 = ldsf4(ya), y1 = ldsf4(ya + 512);
            float s = sum4(y0) + sum4(y1);
            float q = (fmaf(y0.x, y0.x, y0.y * y0.y) + fmaf(y0.z, y0.z, y0.w * y0.w)) + (fmaf(y1.x, y1.x, y1.y * y1.y) + fmaf(y1.z, y1.z, y1.w * y1.w));
#pragma unroll
            for (int o = 16; o; o >>= 1) { s += shx(s, o); q += shx(q, o); }
            if (lane < 2) st_async2(sa, s, q, tb);
        }
    } else if (warp == 15) {
        mbar_waitb(BAR(IT_X - 1), 0);
        if (j < J_END) mbar_waitb(BAR(j < NFF ? NITEMS - 1 : MBB), 0);
    }
    } else if (warp < 4) {
        float* scr = (float*)(sm + SM_SCR);
        uint32_t cls;
        {
            uint2 ha[8];
            {
                uint32_t best = 0xffffffffu;
#pragma unroll
                for (int i = 0; i < NPROBE; i++) {
                    uint32_t t0, t1, o;
                    asm volatile("mov.u32 %0, %%clock;" : "=r"(t0));
                    asm volatile("atom.relaxed.gpu.global.exch.b32 %0, [%1], %2;" : "=r"(o) : "l"(pl), "r"(2u + i) : "memory");
                    asm volatile("{\n.reg .pred p;\nsetp.ne.u32 p, %1, 0x1234567;\nmov.u32 %0, 0;\n@p mov.u32 %0, %%clock;\n}" : "=r"(t1) : "r"(o));
                    best = min(best, t1 - t0);
                }
                if (lane == 0) scr[16 + warp] = __uint_as_float(best);
            }
            const float sh = __shfl_sync(0xffffffffu, bflo(in1), 0);
            const float v0 = bflo(in1) - sh, v1 = bfhi(in1) - sh, v2 = bflo(in2) - sh, v3 = bfhi(in2) - sh;
            float mb, sd;
            ln_stats<4>((v0 + v1) + (v2 + v3), (v0 * v0 + v1 * v1) + (v2 * v2 + v3 * v3), sh, scr, warp, lane, 2, mb, sd);
            if (!rk) in2 = in1;
            const uint4 lt = *(const uint4*)(scr + 16);
            cls = NUMA ? ((lt.y < lt.x) ^ (__popc((B_PR + (j >> 5)) & 0x2C) & 1)) | (lt.w < lt.z) << 1 : 0;
            if (warp == 0) { if (lane == 0) sts32(sb + SM_CLS, cls); bar_arrive(9, 64); }
            if (tid == 0) TRACE(38);
            asm volatile("barrier.cluster.wait.aligned;" ::: "memory");
            mbar_wait(BAR(IT_MODA), 0);
            __nanosleep(HA_DELAY);
            poll<1024, H_SLEEP, false, 16384>(ha, gs + near_off(B_HA + rk * 2, cls) + 2 * tid);
            auto rsum = [](uint32_t a, uint32_t b, uint32_t c, uint32_t d) { return rbf((__uint_as_float(a) + __uint_as_float(b)) + (__uint_as_float(c) + __uint_as_float(d))); };
            sts32(sb + SM_FV + frag_off(2 * tid),
                  pack2(ln_mod(bflo(in2), mb, sd, rsum(ha[4].x, ha[5].x, ha[6].x, ha[7].x), rsum(ha[0].x, ha[1].x, ha[2].x, ha[3].x)),
                        ln_mod(bfhi(in2), mb, sd, rsum(ha[4].y, ha[5].y, ha[6].y, ha[7].y), rsum(ha[0].y, ha[1].y, ha[2].y, ha[3].y))));
            bar_arrive(5, 384);
            mbar_wait(BAR(QB), 0);
            if (tid < 64) {
                const float* qx = (const float*)(sm + SM_QX) + tid;
                sts16(sb + SM_FQ + frag_off(tid), pack2((qx[0] + qx[64]) + (qx[128] + qx[192]), 0.f));
            }
            bar_arrive(6, 384);
        }
        asm volatile("setmaxnreg.inc.sync.aligned.u32 168;");
        float acc[128];
        float M = 0.f;
        uint32_t pa = sb + SM_XA + warp * 512 + lane * 16, ma = sb + SM_MX + (warp * 8 + g) * 4, pf = BAR(PF0);
        uint32_t blo = __reduce_or_sync(0xffffffffu, (((sb + SM_U) & 0x3FFFFu) >> 4) | 0x400000u);
        uint32_t* e1[4];
#pragma unroll
        for (int i = 0; i < 4; i++) e1[i] = gs + G_E1 + (warp * 8 + g) * 4 * 8192 + (rk * 2 + (j >> 6)) * 2048 + ((j >> 1) & 31) * 32 + t * 4;
        uint32_t ck[10] = {0, 0, 0, 0, 0, 0, 0, 0, 0, 0};
#pragma unroll 1
        for (int h = 0; h < 2 * NUNITS; h++) {
            CLK(ck[0], h == 2 * TU); CLK(ck[5], h == 2 * TU + 1);
            mbar_wait(pf, 0);
            CLK(ck[1], h == 2 * TU); CLK(ck[6], h == 2 * TU + 1);
            const float m = __uint_as_float(lds32(ma));
            const uint4 pn = lds128(pa);
            wg_wait0();
#pragma unroll
            for (int i = 0; i < 128; i++) asm volatile("" : "+f"(acc[i]) :: "memory");
            CLK(ck[2], h == 2 * TU); CLK(ck[7], h == 2 * TU + 1);
            if (h == 0) M = m;
            uint32_t b2 = 0x3f803f80u;
            if (__builtin_expect(__any_sync(0xffffffffu, m != M), 0)) {
                const float Mn = fmaxf(M, m), alpha = ex2(M - Mn), beta = ex2(m - Mn);
                M = Mn;
                b2 = pack2(beta, beta);
#pragma unroll
                for (int jj = 0; jj < 32; jj++) { acc[4 * jj] *= alpha; acc[4 * jj + 1] *= alpha; }
            }
            auto mul2 = [](uint32_t x, uint32_t y) { uint32_t r; asm("mul.rn.bf16x2 %0, %1, %2;" : "=r"(r) : "r"(x), "r"(y)); return r; };
            const uint4 p = make_uint4(mul2(pn.x, b2), mul2(pn.y, b2), mul2(pn.z, b2), mul2(pn.w, b2));
            if (tid == 0 && (h & 1)) TRACE_Q(48 + (h >> 1));
            CLK(ck[3], h == 2 * TU); CLK(ck[8], h == 2 * TU + 1);
            wgmma_pv(acc, p, blo, h);
            CLK(ck[4], h == 2 * TU); CLK(ck[9], h == 2 * TU + 1);
            if (lane == 0 && h > 0 && !(h & 1)) mbar_arrive(BAR(EB_UNIT0 + (h >> 1) - 1));
            blo += h == 11 ? -11 * 1024 : 1024;
            pa += (h == 5 || h == 11) ? -5 * 2048 : 2048;
            ma += 128; pf += 8;
            if (h == 2 * NUNITS - 3) {
                mbar_wait(BAR(JD), 0);
                const uint32_t hm = (*(const uint32_t*)(sm + SM_CLS + 16 + warp * 4) >> (g * 4)) ^ ((j >> 6) ? 15u : 0u);
#pragma unroll
                for (int i = 0; i < 4; i++) e1[i] += ((hm >> i) & 1) << 10;
            }
        }
#pragma unroll
        for (int vv = 0; vv < 2; vv++) {
            if (vv && M == 1.f) __trap();
            if (vv) wg_wait0(); else wg_wait1();
#pragma unroll
            for (int i = 0; i < 64; i++) asm volatile("" : "+f"(acc[vv * 64 + i]) :: "memory");
            if (tid == 0 && !vv) TRACE_Q(63);
#pragma unroll
            for (int i = 0; i < 4; i++) {
                const float* a = &acc[vv * 64 + i * 16];
                st_x4(e1[i] + i * 8192 + vv * 16, enc(pack2(a[0], a[1])), enc(pack2(a[4], a[5])), enc(pack2(a[8], a[9])), enc(pack2(a[12], a[13])));
            }
        }
        if (tid == 0) TRACE_Q(17);
        if (j >= NFF && j < J_END) {
            uint4 a[8], b[4];
            float c[4], e[4];
            const bool own = (warp >> 1) == rk;
            const uint32_t xa = sb + SM_FV + (warp & 1) * 64 + g * 8;
            if (lane == 0) mbar_expect(BAR(MBB), own ? 64 : 0);
#pragma unroll
            for (int i = 0; i < 2; i++) {
                ldfrag(b, sb + SM_FS + rk * 512 + i * 256 + t * 16);
                mbar_wait(BAR(IT_X + i), 0);
                const uint32_t ab = sb + SM_U + B_X * 32768 + i * 16384 + a128;
                load8<true>(a, [&](int s) { return ab + s * 2048; });
                mma8(i ? e : c, a, b);
            }
            c[0] += e[0]; c[2] += e[2];
            if (!own) {
                if (t == 0) st_async2(peer_addr(xa, rk ^ 1), c[0], c[2], peer_addr(BAR(MBB), rk ^ 1));
            } else {
                mbar_wait(BAR(MBB), 0);
                const float2 pp = *(const float2*)(sm + (xa - sb));
                const float mine = t ? c[2] + pp.y : c[0] + pp.x, other = shx(mine, 4);
                const uint32_t w = (warp & 1) * 8 + t * 4 + (g >> 1), val = enc(pack2(mine, other));
                if (t < 2 && !(g & 1)) {
                    if (j < J_RED) st2_x1(gs + B_MB * 4096 + (j - NFF) * 16 + w, val);
                    else sts32(sb + SM_FV + 256 + w * 4, val);
                }
                if (j >= J_RED) bar_arrive(7, 320);
                if (lane == 0) TRACE(11);
            }
        }
    } else {
        const int u8 = tid - 128, w8 = warp - 4;
        const int v = w8 >> 2, wq4 = w8 & 3;
        {
            const float c0 = bflo(in1), c1 = bfhi(in1);
            sts32(sb + SM_FS + frag_off(2 * u8), pack2(__fdividef(c0, 1.f + __expf(-c0)), __fdividef(c1, 1.f + __expf(-c1))));
        }
        bar_sync(1, 256);
        asm volatile("barrier.cluster.wait.aligned;" ::: "memory");
        uint4 a[8], b[4]; float c[4];
        if (w8 < 2) {
            ldfrag(b, sb + SM_FS + (j >> 5) * 256 + t * 16);
            mbar_wait(BAR(IT_MODA), 0);
            if (u8 == 0) TRACE(12);
            const uint32_t ab = sb + SM_XA + w8 * 4096 + a16;
            load8<true>(a, [&](int s) { return ab + s * 512; });
            mma8(c, a, b);
            if (t < 2) st2_x1(gs + (B_HA + ((j >> 4) & 1) * 2 + w8) * 4096 + (j >> 5) * 256 + (j & 15) * 16 + t * 8 + g, encf(t ? c[2] : c[0]));
        }
        {
            mbar_wait(BAR(IT_WQ + 2 * v <= NCP ? 1 : IT_WQ + 2 * v), 0); mbar_wait(BAR(IT_WQ + 2 * v + 1 <= NCP ? 1 : IT_WQ + 2 * v + 1), 0);
            const uint32_t ab = sb + SM_U + 4 * 32768 + v * 16384 + a128;
            load8<true>(a, [&](int s) { return ab + s * 2048; });
            if (lane == 0) mbar_arrive(BAR(EB_WQ));
            bar_sync(5, 384);
            if (u8 == 0) TRACE(13);
            ldfrag(b, sb + SM_FV + v * 256 + t * 16);
            mma8(c, a, b);
            if (t < 2) {
                const float qv = t ? c[2] : c[0];
                const uint32_t qa_ = sb + SM_QX + ((rk * 2 + v) * 64 + wq4 * 16 + t * 8 + g) * 4;
                asm volatile("st.async.weak.shared::cluster.mbarrier::complete_tx::bytes.f32 [%0], %1, [%2];"
                             :: "r"(peer_addr(qa_, rk ^ 1)), "f"(qv), "r"(peer_addr(BAR(QB), rk ^ 1)) : "memory");
                sts32(qa_, __float_as_uint(qv));
            }
            __syncwarp();
            if (lane == 0) mbar_expect(BAR(QB), 64);
        }
        {
            mbar_wait(BAR(IT_WUK + v), 0); mbar_wait(BAR(IT_WUK + v + 2), 0);
            const uint32_t ab = sb + SM_U + 5 * 32768 + (w8 * 16 + r8 + 8 * lb3) * 128;
            const uint32_t x16 = (lb4 ^ r8) * 16;
            load8<false>(a, [&](int s) { return ab + (s & 1) * 16384 + (x16 ^ ((s >> 1) * 32)); });
            bar_sync(6, 384);
            if (u8 == 0) TRACE(14);
            b[0] = lds128(sb + SM_FQ + t * 16); b[1] = lds128(sb + SM_FQ + 64 + t * 16);
            float e[4] = {0.f, 0.f, 0.f, 0.f};
            c[0] = c[1] = c[2] = c[3] = 0.f;
#pragma unroll
            for (int k = 0; k < 4; k++) {
                const uint32_t b0 = (k & 1) ? b[k >> 1].z : b[k >> 1].x, b1 = (k & 1) ? b[k >> 1].w : b[k >> 1].y;
                mma(c, a[2 * k].x, a[2 * k].y, a[2 * k].z, a[2 * k].w, b0, b1);
                mma(e, a[2 * k + 1].x, a[2 * k + 1].y, a[2 * k + 1].z, a[2 * k + 1].w, b0, b1);
            }
            const float mine = ((t & 1) ? ((t & 2) ? e[2] : e[0]) : ((t & 2) ? c[2] : c[0])) * 0.12751743f;
            const float other = shx(mine, 4);
            if (!(g & 1)) st2_x1(gs + (B_QA + rk * 8 + ((j >> 1) & 1) * 4 + (j >> 5)) * 4096 + w8 * 128 + ((j >> 2) & 7) * 16 + (g >> 1) * 4 + t, enc(pack2(mine, other)));
            if (u8 == 0) TRACE(15);
        }
        const uint32_t cls = ldcls();
        __nanosleep(QA_DELAY);
        {
            uint4 qb[8];
            const uint32_t* pq = gs + near_off(B_QA + rk * 8 + wq4, cls) + lane * 4;
            const uint32_t* pq2 = gs + near_off(B_QA + rk * 8 + 4 + wq4, cls) + lane * 4;
            if (lane == 0) {
                mbar_expect(BAR(QT), 4096);
                asm volatile("cp.async.bulk.shared::cluster.global.mbarrier::complete_tx::bytes [%0], [%1], 4096, [%2];"
                             :: "r"(sb + SM_U + 5 * 32768 + w8 * 4096), "l"(gs + near_off(B_QA + rk * 8 + w8, cls)), "r"(BAR(QT)) : "memory");
            }
            const uint32_t qs = sb + SM_U + 5 * 32768 + wq4 * 4096 + lane * 16;
            mbar_wait(BAR(QT), 0);
#pragma unroll
            for (int i = 0; i < 8; i++) { a[i] = lds128(qs + i * 512); qb[i] = lds128(qs + 16384 + i * 512); }
            poll<512, QA_SLEEP, true>(a, pq);
            poll<512, QA_SLEEP, true>(qb, pq2);
            if (lane == 0) mbar_arrive(BAR(EB_WUK));
            auto add2 = [](uint32_t x, uint32_t y) { uint32_t r; asm("add.rn.bf16x2 %0, %1, %2;" : "=r"(r) : "r"(x), "r"(y)); return r; };
#pragma unroll
            for (int i = 0; i < 8; i++) a[i] = make_uint4(add2(a[i].x, qb[i].x), add2(a[i].y, qb[i].y), add2(a[i].z, qb[i].z), add2(a[i].w, qb[i].w));
        }
        if (u8 == 0) TRACE(8);
        {
            float m = -INFINITY, l = 0.f;
            uint32_t xl = sb + SM_XB + w8 * 2048 + lane * 16, xr = peer_addr(xl, rk ^ 1), bsr = peer_addr(BAR(SF0 + v), rk ^ 1);
            uint32_t pa = sb + SM_XA + v * 2048 + wq4 * 512 + lane * 16, ma = sb + SM_MX + v * 128 + (wq4 * 8 + g) * 4;
            uint32_t fb = BAR(IT_CKV + v * 2), sf = BAR(SF0 + v);
            uint32_t dlo = __reduce_or_sync(0xffffffffu, (((sb + SM_U + v * 16384) & 0x3FFFFu) >> 4) | 0x10000u);
            uint32_t ck[9] = {0, 0, 0, 0, 0, 0, 0, 0, 0};
            if (STAG && v) __nanosleep(STAG);
#pragma unroll 1
            for (int n = 0; n < NUNITS; n++) {
                CLK(ck[0], n == TU); CLK(ck[8], n == TU + 1);
                float d[2][16], sc[8];
#pragma unroll
                for (int i = 0; i < 2; i++) {
                    mbar_wait(fb + i * 8, 0);
                    if (i == 0) CLK(ck[1], n == TU);
                    wg_fence();
#pragma unroll
                    for (int s = 0; s < 8; s++) wgmma_rs_n32(d[i], a[s], (0x40000080ull << 32) | (dlo + i * 512 + (s >> 2) * 64 + (s & 3) * 2), s);
                    wg_commit();
                }
                CLK(ck[2], n == TU);
#pragma unroll
                for (int i = 0; i < 2; i++) {
                    if (i) wg_wait0(); else wg_wait1();
#pragma unroll
                    for (int k = 0; k < 16; k++) asm volatile("" : "+f"(d[i][k]) :: "memory");
                    sc[4 * i] = d[i][0] + d[i][6]; sc[4 * i + 1] = d[i][1] + d[i][7]; sc[4 * i + 2] = d[i][8] + d[i][14]; sc[4 * i + 3] = d[i][9] + d[i][15];
                    asm volatile("st.async.weak.shared::cluster.mbarrier::complete_tx::bytes.v4.f32 [%0], {%1, %2, %3, %4}, [%5];"
                                 :: "r"(xr + i * 1024), "f"(sc[4 * i]), "f"(sc[4 * i + 1]), "f"(sc[4 * i + 2]), "f"(sc[4 * i + 3]), "r"(bsr) : "memory");
                }
                CLK(ck[3], n == TU);
                if (u8 == 128) TRACE_Q(56 + (n < 6 ? n : -40));
                if (n >= 3) mbar_wait(BAR(EB_UNIT0 + n - 3), 0);
                dlo += n == 5 ? -5 * 2048 : 2048;
                fb += 32; xr ^= 512; bsr += 16;
                pin(fb); pin(xr); pin(bsr);
                CLK(ck[4], n == TU);
                mbar_wait(sf, 0);
                CLK(ck[5], n == TU);
                const float4 x = ldsf4(xl), y = ldsf4(xl + 1024);
                sc[0] += x.x; sc[1] += x.y; sc[2] += x.z; sc[3] += x.w; sc[4] += y.x; sc[5] += y.y; sc[6] += y.z; sc[7] += y.w;
                float pr[8];
#pragma unroll
                for (int i = 0; i < 8; i++) pr[i] = ex2(sc[i] - m);
                float mx = fmaxf(fmaxf(fmaxf(sc[0], sc[1]), fmaxf(sc[2], sc[3])), fmaxf(fmaxf(sc[4], sc[5]), fmaxf(sc[6], sc[7])));
                if (__builtin_expect(__any_sync(0xffffffffu, mx > m), 0)) {
                    mx = fmaxf(mx, shx(mx, 1));
                    mx = fmaxf(mx, shx(mx, 2));
                    const float mn = fmaxf(m, ceilf(mx * 0.0625f) * 16.f);
                    l *= ex2(m - mn);
                    m = mn;
#pragma unroll
                    for (int i = 0; i < 8; i++) pr[i] = ex2(sc[i] - m);
                }
                CLK(ck[6], n == TU);
                stsf(ma, m);
                asm volatile("st.shared.v4.u32 [%0], {%1, %2, %3, %4};" :: "r"(pa), "r"(pack2(pr[0], pr[1])), "r"(pack2(pr[2], pr[3])),
                             "r"(pack2(pr[4], pr[5])), "r"(pack2(pr[6], pr[7])) : "memory");
                __syncwarp();
                if (lane == 0) mbar_arrive(sf + (PF0 - SF0) * 8);
                CLK(ck[7], n == TU);
                l += ((pr[0] + pr[1]) + (pr[2] + pr[3])) + ((pr[4] + pr[5]) + (pr[6] + pr[7]));
                xl ^= 512; sf += 16; ma += 256; pa += (n == 2 || n == 5) ? -8192 : 4096;
            }
            l += shx(l, 1);
            l += shx(l, 2);
            float2* mlx = (float2*)(sm + SM_MX + 2048) + wq4 * 8 + g;
            if (v == 0) { *mlx = make_float2(m, l); bar_arrive(11, 256); }
            else {
                mbar_wait(BAR(JD), 0);
                bar_sync(11, 256);
                const float2 o = *mlx;
                const float mn = fmaxf(m, o.x);
                l = l * ex2(m - mn) + o.y * ex2(o.x - mn);
                if ((wq4 >> 1) == rk) st_x4(gs + (B_ML + wq4 * 8 + g) * 4096 + (t >> 1) * 1024 + (j >> 1) * 8 + (t & 1) * 4, encf(mn), encf(l), 1u, 1u);
            }
        }
        asm volatile("setmaxnreg.inc.sync.aligned.u32 144;");
        const int pi = j < NFF ? rk * 128 + w8 * 16 + (lane & 15) : ((j - J_RED) & 15) * 16 + v * 8 + lb4 * 4 + wq4;
        const uint32_t xw = *(const uint32_t*)(xin + 2 * pi);
        uint32_t rl = sb + SM_RED + lane * 16;
        {
#pragma unroll 1
            for (int i = 0; i < 4; i++) mbar_wait(BAR(IT_WUV + i), 0);
            const uint32_t ab = sb + SM_U + B_WUV * 32768 + v * 4096 + a128;
            load8<true>(a, [&](int s) { return ab + (s >> 1) * 8192 + (s & 1) * 2048; });
            uint32_t pa = sb + SM_PB + wq4 * 320 + frag_off(64 * v + 32 * (g >> 2) + 16 * (t & 1) + 8 * (t >> 1) + 2 * (g & 3));
            uint32_t fa = sb + SM_PB + g * 320 + t * 16, ra = sb + SM_RED + w8 * 288 + g * 16 + t * 4;
            uint32_t rb = sb + SM_RED + (((u8 >> 2) & 12) + t) * 144 + (g & 3) * 32;
            const uint32_t* pe = gs + G_E1 + j * 8192 + (w8 >> 1) * 2048 + ((((cls >> 1) ^ (w8 >> 1)) & 1) << 10) + (((w8 & 1) * 16 + t) * 8 + g) * 4;
            uint32_t* p2 = gs + (B_E2 + (j >> 4)) * 4096 + (u8 >> 6) * 1024 + (j & 12) * 64 + (u8 & 48) * 4 + (j & 3) * 16 + (u8 & 15);
            pin(pa); pin(fa); pin(ra); pin(rb); pin(rl); pin(pe); pin(p2);
            uint4 pv[4];
            bar_sync(3, 288);
            TK(0);
            poll_start<512>(pv, pe);
            bar_sync(8, 288);
            const uint4 wa = lds128(sb + SM_W + (wq4 * 4 + t) * 16);
            const uint32_t mk = (g & 1) ? 0xffff0000u : 0x0000ffffu, m0 = (g & 2) ? 0u : mk, m1 = (g & 2) ? mk : 0u;
            uint32_t wb[8] = {wa.x & m0, wa.x & m1, wa.y & m0, wa.y & m1, wa.z & m0, wa.z & m1, wa.w & m0, wa.w & m1};
#pragma unroll
            for (int i = 0; i < 8; i++) pin(wb[i]);
            poll<512, E1_SLEEP, true>(pv, pe);
            if (u8 == 0) TRACE_Q(18);
            TK(1);
            float e[4][4];
#pragma unroll
            for (int i = 0; i < 4; i++) {
                e[i][0] = e[i][1] = e[i][2] = e[i][3] = 0.f;
                mma(e[i], pv[i].x, pv[i].y, pv[i].z, pv[i].w, wb[2 * i], wb[2 * i + 1]);
            }
            const float r0 = (t & 2) ? (e[0][2] + e[1][2]) + (e[2][2] + e[3][2]) : (e[0][0] + e[1][0]) + (e[2][0] + e[3][0]);
            const float r1 = (t & 2) ? (e[0][3] + e[1][3]) + (e[2][3] + e[3][3]) : (e[0][1] + e[1][1]) + (e[2][1] + e[3][1]);
            const uint32_t hi = pack2(r0, r1);
            sts32(pa, hi); sts32(pa + 1280, pack2(r0 - bflo(hi), r1 - bfhi(hi)));
            TK(2);
            bar_sync(1, 256);
            TK(3);
            if (u8 == 0) TRACE(19);
            ldfrag(b, fa);
            mma8(c, a, b);
            stsf(ra, c[0] + c[1]); stsf(ra + 144, c[2] + c[3]);
            TK(4);
            bar_sync(4, 288);
            TK(5);
            if (w8 < 4) {
                const float inv = *(const float*)(sm + SM_FQ);
                st_x1(p2, enc(pack2(sum4(ldsf4(rb)) * inv, sum4(ldsf4(rb + 16)) * inv)));
            }
            TK(6);
            if (u8 == 0) TRACE(20);
        }
        uint32_t mb[3] = {0u, 0u, 0u};
        const uint32_t* pm = gs + near_off(B_MB, cls) + pi;
        pin(pm);
        if (j < NFF) poll_start<1024>(mb, pm);
        {
            const uint32_t nz = lb4 ? 0x80008000u : 0u;
#pragma unroll
            for (int i = 0; i < 4; i++) b[i] = make_uint4(nz, nz, nz, nz);
            const bool early = __all_sync(0xffffffffu, mbar_test(BAR(IT_WO + 2 * v), 0) & mbar_test(BAR(IT_WO + 2 * v + 1), 0));
            const uint32_t ab = sb + SM_U + B_WO * 32768 + v * 16384 + a128;
            if (early) load8<true>(a, [&](int s) { return ab + s * 2048; });
            uint32_t ra = sb + SM_R3 + (wq4 * 16 + g) * 16 + v * 8 + t * 4, rb = sb + SM_R3 + lane * 32;
            uint32_t* p3 = gs + (B_E3 + ((j >> 1) & 3)) * 4096 + w8 * 1024 + (rk * 2 + lb4) * 256 + (j >> 3) * 16 + (lane & 15);
            pin(ra); pin(rb); pin(p3);
            TK(7);
            Poll2<uint4, 4> p2;
            if (P2 & 2) p2.run<256>(b, gs + near_off(B_E2 + (j >> 4), cls) + (((j >> 3) & 1) * 2 + v) * 256 + lane * 4);
            else poll<256, E2_SLEEP, true>(b, gs + near_off(B_E2 + (j >> 4), cls) + (((j >> 3) & 1) * 2 + v) * 256 + lane * 4);
            if (!early) { mbar_wait(BAR(IT_WO + 2 * v), 0); mbar_wait(BAR(IT_WO + 2 * v + 1), 0); load8<true>(a, [&](int s) { return ab + s * 2048; }); }
            TK(8);
            if (u8 == 0) TRACE(21);
            mma8(c, a, b);
            if (t < 2) { stsf(ra, c[0] + c[1]); stsf(ra + 128, c[2] + c[3]); }
            TK(9);
            bar_sync(1, 256);
            TK(10);
            if (w8 < 2) st_x1(p3, enc(pack2(sum4(ldsf4(rb)), sum4(ldsf4(rb + 16)))));
            if (P2 & 2) p2.settle();
            TK(11);
            if (u8 == 0) TRACE(22);
        }
        if (j < NFF) {
            const uint32_t* p3 = gs + near_off(B_E3 + rk * 2 + v, cls) + wq4 * 256 + lane;
            uint32_t za = sb + SM_FZ + lb4 * 576 + frag_off(w8 * 32 + (lane & 15) * 2);
            uint32_t fa = sb + SM_FZ + (g & 3) * 576 + lb4 * 256 + t * 16, ya = sb + SM_Y + u8 * 4;
            poll<1024, MB_SLEEP, true>(mb, pm);
            const uint32_t kk = pack2(1.f + bflo(mb[2]), 1.f + bfhi(mb[2]));
            sts32(za + 2 * 576, lb4 ? mb[1] : kk);
            uint32_t e3[8] = {0u, 0u, 0u, 0u, 0u, 0u, 0u, 0u};
            uint32_t ra = peer_addr(sb + SM_RED + (rk * 2 + v) * 512 + ((wq4 & 1) * 16 + (t >> 1) * 8 + g) * 16 + (t & 1) * 8, wq4 >> 1), tbo = peer_addr(BAR(QB), wq4 >> 1);
            uint32_t ad = sb + SM_U + B_DN * 32768 + w8 * 4096 + (r8 + 8 * lb4) * 128 + (lb3 ^ r8) * 16;
            uint32_t* p5 = gs + (B_E5 + w8 * 2 + (t >> 1)) * 4096 + j * 16 + (t & 1) * 8 + g;
            pin(za); pin(fa); pin(ya); pin(ra); pin(tbo); pin(ad); pin(p5);
            if (lane == 0) mbar_expect(BAR(QB), 258);
            uint4 a2[8];
            TK(12);
            const uint32_t gb = BAR(IT_X + v * 2), ab = sb + SM_U + (B_X + v) * 32768 + a128;
            bool early = false, early2 = false;
            auto ldw = [&]() {
                if (!early) {
                    early = __all_sync(0xffffffffu, mbar_test(gb, 0));
                    if (early) load8<true>(a, [&](int s) { return ab + s * 2048; });
                }
                if (!early2) {
                    early2 = __all_sync(0xffffffffu, mbar_test(gb + 8, 0));
                    if (early2) load8<true>(a2, [&](int s) { return ab + 16384 + s * 2048; });
                }
            };
            Poll2<uint32_t, 8> p2;
            if (P2 & 4) p2.run<128>(e3, p3, ldw); else poll<128, E3_SLEEP, true>(e3, p3, ldw);
            TK(13);
            if (u8 == 0) TRACE(23);
            const float s0 = sumlo(e3), s1 = sumhi(e3);
            const float y0 = fmaf(bflo(mb[0]), s0 + shx(s0, 16), bflo(xw)), y1 = fmaf(bfhi(mb[0]), s1 + shx(s1, 16), bfhi(xw));
            stsf(ya, lb4 ? y1 : y0);
            const float z0 = y0 * bflo(kk), z1 = y1 * bfhi(kk);
            const uint32_t zh = pack2(z0, z1);
            sts32(za, lb4 ? pack2(z0 - bflo(zh), z1 - bfhi(zh)) : zh);
            TK(14);
            bar_sync(7, 288);
            TK(15);
            if (u8 == 0) TRACE(24);
            ldfrag(b, fa);
            if (!early) { mbar_wait(gb, 0); load8<true>(a, [&](int s) { return ab + s * 2048; }); }
            if (!early2) { mbar_wait(gb + 8, 0); load8<true>(a2, [&](int s) { return ab + 16384 + s * 2048; }); }
            {
                float e[4][4];
#pragma unroll
                for (int s = 0; s < 16; s++) {
                    const uint4& x = (s & 2) ? a2[(s >> 2) * 2 + (s & 1)] : a[(s >> 2) * 2 + (s & 1)];
                    const uint4& y = b[s >> 2];
                    if (s < 4) e[s][0] = e[s][1] = e[s][2] = e[s][3] = 0.f;
                    mma(e[s & 3], x.x, x.y, x.z, x.w, (s & 1) ? y.z : y.x, (s & 1) ? y.w : y.y);
                }
                const bool hi = t >> 1;
                const float k0 = hi ? e[2][2] + e[3][2] : e[0][0] + e[1][0], k1 = hi ? e[2][3] + e[3][3] : e[0][1] + e[1][1];
                const float o0 = hi ? e[2][0] + e[3][0] : e[0][2] + e[1][2], o1 = hi ? e[2][1] + e[3][1] : e[0][3] + e[1][3];
                TKD(16, o0);
                st_async2(ra, k0 + shx(o0, 2), k1 + shx(o1, 2), tbo);
            }
            if (P2 & 4) p2.settle();
            TK(17);
            const bool early5 = __all_sync(0xffffffffu, mbar_test(BAR(IT_DOWN + v), 0));
            if (early5) load8<true>(a, [&](int s) { return (ad ^ ((s & 3) * 32)) + (s >> 2) * 2048; });
            TK(18);
            mbar_wait(BAR(QB), 1);
            TK(19);
            if (u8 == 0) TRACE(25);
            const float4 st = ldsf4(sb + SM_RED + 2048);
            const float4 f0 = ldsf4(rl), f1 = ldsf4(rl + 512), f2 = ldsf4(rl + 1024), f3 = ldsf4(rl + 1536);
            const float mu = (st.x + st.z) * (1.f / 512.f);
            float rstd;
            asm("rsqrt.approx.ftz.f32 %0, %1;" : "=f"(rstd) : "f"(fmaxf(fmaf(-mu, mu, (st.y + st.w) * (1.f / 512.f)), 0.f) + 1e-5f));
            const float gg = fmaf(rstd, fmaf(-mu, f0.z + f2.z, (f0.x + f0.y) + (f2.x + f2.y)), f0.w + f2.w);
            const float uu = fmaf(rstd, fmaf(-mu, f1.z + f3.z, (f1.x + f1.y) + (f3.x + f3.y)), f1.w + f3.w);
            TKD(20, gg);
            const float hh = __fdividef(gg * uu, 1.f + ex2(-gg * fmaf(gg * gg, 0.10294324f, 2.3022082f)));
            uint32_t hb[4];
#pragma unroll
            for (int i = 0; i < 4; i++) hb[i] = pack2(__shfl_sync(0xffffffffu, hh, 2 * t + 8 * i), __shfl_sync(0xffffffffu, hh, 2 * t + 8 * i + 1));
            TKD(21, __uint_as_float(hb[3]));
            if (!early5) { mbar_wait(BAR(IT_DOWN + v), 0); load8<true>(a, [&](int s) { return (ad ^ ((s & 3) * 32)) + (s >> 2) * 2048; }); }
            uint32_t res = 0;
#pragma unroll
            for (int k = 0; k < 4; k++) {
                c[0] = c[1] = c[2] = c[3] = 0.f;
                mma(c, a[k].x, a[k].y, a[k].z, a[k].w, hb[0], hb[1]);
                mma(c, a[k + 4].x, a[k + 4].y, a[k + 4].z, a[k + 4].w, hb[2], hb[3]);
                if (t == k) res = pack2(c[0], c[2]);
            }
            st2_x1(p5, enc(res));
            TK(22);
            if (u8 == 0) { TRACE(27); TRACE_GT(47); }
        } else if (j >= J_RED && j < J_END) {
            uint32_t ga[1], e3[1];
            poll<0, MB_SLEEP>(ga, pm);
            poll<0, 100>(e3, gs + near_off(B_E3 + (pi >> 6), cls) + (pi & 48) * 16 + (lane & 15) * 16 + (pi & 15));
            if (E5_DELAY) __nanosleep(E5_DELAY);
            float y0 = bflo(e3[0]), y1 = bfhi(e3[0]);
#pragma unroll
            for (int o = 8; o; o >>= 1) { y0 += shx(y0, o); y1 += shx(y1, o); }
            y0 = fmaf(bflo(ga[0]), y0, bflo(xw)); y1 = fmaf(bfhi(ga[0]), y1, bfhi(xw));
            bar_sync(7, 320);
            const uint32_t gb = lds32(sb + SM_FV + 256 + (pi & 15) * 4);
            uint32_t* po = (uint32_t*)out + pi;
            pin(po);
            const uint32_t nz = lane < NFF / 2 ? 0u : 0x80008000u;
            uint2 yv[2] = {make_uint2(nz, nz), make_uint2(nz, nz)};
            Poll2<uint2, 2> p2;
            if (P2 & 8) p2.run<NFF * 32>(yv, gs + near_off(B_E5 + j - J_RED, cls) + lane * 16 + w8 * 2);
            else poll<NFF * 32, E5_SLEEP, true>(yv, gs + near_off(B_E5 + j - J_RED, cls) + lane * 16 + w8 * 2);
            if (u8 == 0) TRACE(26);
            const float l0 = bflo(yv[0].x) + bflo(yv[1].x), h0 = bfhi(yv[0].x) + bfhi(yv[1].x);
            const float l1 = bflo(yv[0].y) + bflo(yv[1].y), h1 = bfhi(yv[0].y) + bfhi(yv[1].y);
            float s0 = (lb4 ? h0 : l0) + shx(lb4 ? l0 : h0, 16), s1 = (lb4 ? h1 : l1) + shx(lb4 ? l1 : h1, 16);
#pragma unroll
            for (int o = 8; o; o >>= 1) { s0 += shx(s0, o); s1 += shx(s1, o); }
            if (!(lane & 15)) *po = pack2(fmaf(bflo(gb), s0, y0), fmaf(bfhi(gb), s1, y1));
            if (P2 & 8) p2.settle();
            if (u8 == 0) TRACE(27);
        }
    }
}

typedef CUresult (*EncFn)(CUtensorMap*, CUtensorMapDataType, cuuint32_t, void*, const cuuint64_t*, const cuuint64_t*,
                          const cuuint32_t*, const cuuint32_t*, CUtensorMapInterleave, CUtensorMapSwizzle,
                          CUtensorMapL2promotion, CUtensorMapFloatOOBfill);

void make_map(EncFn enc_fn, CUtensorMap* m, const void* p, cuuint64_t d0, cuuint64_t d1, cuuint64_t d2, cuuint64_t d3,
              cuuint64_t s1, cuuint64_t s2, cuuint64_t s3, cuuint32_t b0, cuuint32_t b1, cuuint32_t b2, cuuint32_t b3, CUtensorMapSwizzle sw) {
    const cuuint64_t dims[4] = {d0, d1, d2, d3}, strides[3] = {s1, s2, s3};
    const cuuint32_t box[4] = {b0, b1, b2, b3}, es[4] = {1, 1, 1, 1};
    enc_fn(m, CU_TENSOR_MAP_DATA_TYPE_BFLOAT16, 4, (void*)p, dims, strides, box, es,
           CU_TENSOR_MAP_INTERLEAVE_NONE, sw, CU_TENSOR_MAP_L2_PROMOTION_L2_64B, CU_TENSOR_MAP_FLOAT_OOB_FILL_NONE);
}

uint32_t* scratch = nullptr;

struct Tune { const char* win; const char* late; int tau, t_off; const char* tail[3][3]; };
Tune tune = {"66666666655555555555555555555555555555555",
             "00000000000000000000999999999999999999999", 315, -200,
             {{"VVVVOOOOguguDD", "55554444345666", "00000000000000"},
              {"VVVVMMOOOO", "5555555555", "0000000000"},
              {"VVVVOOOO......MM", "55554444000000zz", "0000000000000088"}}};
bool ready = false;

}

extern "C" void kernel_launch(void* const* d_in, const int* in_sizes, int n_in, void* d_out, int out_size) {
    (void)in_sizes; (void)n_in; (void)out_size;
    static Maps maps;
    static const void* cached[12] = {};
    bool same = ready;
    for (int i = 0; i < 12 && same; i++) same = cached[i] == d_in[i];
    if (!same) {
        void* fn = nullptr;
        cudaDriverEntryPointQueryResult qr;
        cudaGetDriverEntryPoint("cuTensorMapEncodeTiled", &fn, cudaEnableDefault, &qr);
        EncFn e = (EncFn)fn;
        const CUtensorMapSwizzle S128 = CU_TENSOR_MAP_SWIZZLE_128B;
        make_map(e, &maps.m[MP_WQ], d_in[2], 64, 512, 64, 1, 8192, 128, 8192, 64, 64, 1, 1, S128);
        make_map(e, &maps.m[MP_WUK], d_in[3], 64, 512, 64, 1, 8192, 128, 8192, 64, 64, 1, 1, S128);
        make_map(e, &maps.m[MP_CKV], d_in[1], 64, 8, 8, 4096, 1024, 128, 8192, 64, 8, 4, 2, S128);
        make_map(e, &maps.m[MP_MODB], d_in[11], 3072, 512, 1, 1, 6144, 6144, 6144, 64, 128, 1, 1, S128);
        make_map(e, &maps.m[MP_WUV], d_in[4], 64, 512, 64, 1, 8192, 128, 8192, 64, 32, 2, 1, S128);
        make_map(e, &maps.m[MP_WO], d_in[5], 512, 4096, 1, 1, 1024, 1024, 1024, 64, 64, 1, 1, S128);
        make_map(e, &maps.m[MP_GATE], d_in[7], 1792, 512, 1, 1, 3584, 3584, 3584, 64, 128, 1, 1, S128);
        make_map(e, &maps.m[MP_UP], d_in[8], 1792, 512, 1, 1, 3584, 3584, 3584, 64, 128, 1, 1, S128);
        make_map(e, &maps.m[MP_DOWN], d_in[9], 64, 1792, 8, 1, 1024, 128, 1024, 64, 32, 4, 1, S128);
        for (int r = 0; r < 3; r++) {
            int ids[72], real[72], nreal = 0, cnt[128] = {};
            uint32_t* sc = maps.sched[r];
            auto dig = [](char ch) { return ch >= 'a' ? ch - 'a' + 10 : ch - '0'; };
            for (int i = 0; i < 72; i++) sc[i] = 0;
            for (int i = 0;; i++) {
                int id = i, buf, dep, w, wl;
                if (i < IT_WUV) {
                    const int u = (i - IT_CKV) >> 2;
                    buf = i < IT_CKV ? 4 + ((i - 1) >> 2) : u % 6;
                    dep = i < IT_CKV || u < 4 ? -1 : u < 6 ? EB_WQ + u - 4 : EB_UNIT0 + u - 6;
                    w = dig(tune.win[i]); wl = dig(tune.late[i]);
                } else {
                    const char ch = tune.tail[r][0][i - IT_WUV];
                    if (!ch) break;
                    if (ch == '.') { sc[i] = NEVER; continue; }
                    buf = ch == 'V' ? B_WUV : ch == 'O' ? B_WO : ch == 'D' ? B_DN : ch == 'u' ? B_X + 1 : B_X;
                    id = (ch == 'V' ? IT_WUV : ch == 'O' ? IT_WO : ch == 'D' ? IT_DOWN : ch == 'u' ? IT_X + 2 : IT_X) + cnt[(int)ch]++;
                    dep = EB_UNIT0 + (buf < 2 ? buf + 6 : buf);
                    w = dig(tune.tail[r][1][i - IT_WUV]); wl = dig(tune.tail[r][2][i - IT_WUV]);
                }
                if (id < IT_X ? (id - 1) & 3 : (id - IT_X) & 1) dep = -1;
                ids[i] = id;
                auto back = [&](int d) { const int k = nreal - d; return k < 0 ? 0 : (ids[real[k]] && ids[real[k]] <= NCP ? 1 : ids[real[k]]) + 1; };
                sc[i] = id | (buf * 4 + (id < IT_X ? (id - 1) & 3 : ((id - IT_X) & 1) * 2)) << 6 | (dep + 1) << 11 | (w > 32 ? NEVER + 1 : back(w)) << 18 | (wl ? back(wl) : 0) << 25;
                real[nreal++] = i;
            }
            sc[0] = tune.tau; sc[1] = tune.t_off;
        }
        cudaGetSymbolAddress((void**)&scratch, g_scratch);
        scratch = (uint32_t*)(((uintptr_t)scratch + (2u << 20) - 1) & ~(uintptr_t)((2u << 20) - 1));
        cudaFuncSetAttribute(fused_kernel, cudaFuncAttributeMaxDynamicSharedMemorySize, SM_TOTAL);
        for (int i = 0; i < 12; i++) cached[i] = d_in[i];
        ready = true;
    }
    const First f = {{(const uint8_t*)d_in[2], (const uint8_t*)d_in[11]}, {(const __nv_bfloat16*)d_in[0], (const __nv_bfloat16*)d_in[10]}};
    fused_kernel<<<NCTA, NTHREADS, SM_TOTAL>>>(f, (__nv_bfloat16*)d_out, scratch, maps);
}
```

```cpp
#include <cuda_runtime.h>
#include <cuda_bf16.h>
#include <cuda.h>
#include <stdint.h>

namespace {

constexpr int NCTA = 128;
constexpr int NTHREADS = 512;
constexpr int NUNITS = 8;
constexpr int NFF = 56, J_RED = 104, J_END = 120;
constexpr uint32_t SPIN_LIMIT = 1u << 22;

#define PINSB 0
#define E5_DELAY 0
#define P2 0
#define P2_GAP 250
#define XC_LATE 4
#define MODA_PF ".L2::128B"
#define PREZERO 1
#define E1_EARLY 50
#define STAG 300
#define TU 2
#define NUMA 1
#define NPROBE 3
#define NCP 2
#define W0 4
#define RD_ITEM 15
#define JAN_SLEEP 100
#define RD_SLEEP 400
#define HA_DELAY 200
#define H_SLEEP 100
#define QA_DELAY 600
#define QA_SLEEP 200
#define ML_DELAY 300
#define ML_SLEEP 50
#define E1_SLEEP 50
#define E2_SLEEP 0
#define E3_SLEEP 0
#define E5_SLEEP 0
#define MB_SLEEP 100
constexpr int B_WUV = 2, B_WO = 3, B_X = 4  , B_DN = 0;

constexpr int SM_U = 0;
constexpr int SM_XA = 6 * 32768;
constexpr int SM_XB = SM_XA + 12288;
constexpr int SM_MX = SM_XB + 16384;
constexpr int SM_FZ = SM_XB + 8192;
constexpr int SM_PB = SM_XB;
constexpr int SM_R3 = SM_XB + 2560;
constexpr int SM_Y = SM_XB + 12288;
constexpr int SM_RED = SM_XB + 4096;
constexpr int SM_FS = SM_XB + 20480;
constexpr int SM_FV = SM_FS + 1024;
constexpr int SM_QX = SM_XA + 8192;
constexpr int SM_FQ = SM_FV + 512;
constexpr int SM_CLS = SM_FQ + 128;
constexpr int SM_W = SM_FQ + 256;
constexpr int SM_SCR = SM_XA + 9216;
constexpr int SM_TR = SM_XB + 19456;
constexpr int SM_BAR = SM_W + 256;
constexpr int SM_TOTAL = SM_BAR + 1024;
static_assert(SM_TOTAL <= 232448, "smem");

enum { IT_MODA = 0, IT_WQ = 1, IT_WUK = 5, IT_CKV = 9, IT_WUV = 41, IT_WO = 45, IT_X = 49  , IT_DOWN = 53, NITEMS = 55,
       NEVER = 63,
       SF0 = 64,
       PF0 = 80,
       EB_UNIT0 = 96, MBB = 103,
       EB_WQ = 104, EB_WUK, QT, QB, JD };

enum { MP_WQ = 0, MP_WUK, MP_CKV, MP_MODB, MP_WUV, MP_WO, MP_GATE, MP_UP, MP_DOWN, NMAPS };
struct First { const uint8_t* w[2]; const __nv_bfloat16* v[2]; };
struct Maps { CUtensorMap m[NMAPS]; uint32_t sched[3][72]; };

enum { B_HA = 0,
       B_MB = 6,
       B_RD = 7,
       B_E2 = 8,
       B_QA = 16,
       B_ML = 32,
       B_E5 = 64,
       B_E3 = 80,
       B_PR = 96,
       B_TR = 100 };
constexpr int G_E1 = 1 << 19;
constexpr int G_TR = B_TR * 4096;
__device__ __align__(1024) uint32_t g_scratch[(8 << 20) / 4];

#define TRACE(slot) do {} while (0)
#define TRACE_Q(slot) do {} while (0)
#define TRACE_GT(slot) do {} while (0)

#define CLK(var, cond) do {} while (0)
#define CLKD(var, cond, dep) do {} while (0)
#define TK(i) do {} while (0)
#define TKD(i, dep) do {} while (0)
__device__ __forceinline__ uint32_t s2u(const void* p) { return (uint32_t)__cvta_generic_to_shared(p); }
__device__ __forceinline__ void mbar_init(uint32_t b, int c) { asm volatile("mbarrier.init.shared::cta.b64 [%0], %1;" :: "r"(b), "r"(c) : "memory"); }
__device__ __forceinline__ void mbar_expect(uint32_t b, uint32_t bytes) { asm volatile("mbarrier.arrive.expect_tx.shared::cta.b64 _, [%0], %1;" :: "r"(b), "r"(bytes) : "memory"); }
__device__ __forceinline__ void mbar_arrive(uint32_t b) { asm volatile("mbarrier.arrive.shared::cta.b64 _, [%0];" :: "r"(b) : "memory"); }
__device__ __forceinline__ void mbar_wait(uint32_t b, uint32_t ph) {
    asm volatile("{\n.reg .pred p;\nW: mbarrier.try_wait.parity.shared::cta.b64 p, [%0], %1;\n@!p bra W;\n}" :: "r"(b), "r"(ph) : "memory");
}
__device__ __forceinline__ void mbar_waitb(uint32_t b, uint32_t ph) {
    asm volatile("{\n.reg .pred p;\n.reg .u32 n;\nmov.u32 n, 0;\n"
                 "W: mbarrier.try_wait.parity.shared::cta.b64 p, [%0], %1;\n@p bra D;\n"
                 "add.u32 n, n, 1;\nsetp.lt.u32 p, n, 0x100000;\n@p bra W;\ntrap;\nD:\n}" :: "r"(b), "r"(ph) : "memory");
}
__device__ __forceinline__ uint32_t mbar_test(uint32_t b, uint32_t ph) {
    uint32_t ok;
    asm volatile("{\n.reg .pred p;\nmbarrier.test_wait.parity.shared::cta.b64 p, [%1], %2;\nselp.u32 %0, 1, 0, p;\n}" : "=r"(ok) : "r"(b), "r"(ph) : "memory");
    return ok;
}
__device__ __forceinline__ void bar_sync(int id, int n) { asm volatile("bar.sync %0, %1;" :: "r"(id), "r"(n) : "memory"); }
__device__ __forceinline__ void bar_arrive(int id, int n) { asm volatile("bar.arrive %0, %1;" :: "r"(id), "r"(n) : "memory"); }
__device__ __forceinline__ uint32_t peer_addr(uint32_t a, uint32_t rank) { uint32_t r; asm("mapa.shared::cluster.u32 %0, %1, %2;" : "=r"(r) : "r"(a), "r"(rank)); return r; }
__device__ __forceinline__ void st_async1(uint32_t a, float x, uint32_t bar) {
    asm volatile("st.async.weak.shared::cluster.mbarrier::complete_tx::bytes.f32 [%0], %1, [%2];" :: "r"(a), "f"(x), "r"(bar) : "memory");
}
__device__ __forceinline__ void st_async2(uint32_t a, float x, float y, uint32_t bar) {
    asm volatile("st.async.weak.shared::cluster.mbarrier::complete_tx::bytes.v2.f32 [%0], {%1, %2}, [%3];" :: "r"(a), "f"(x), "f"(y), "r"(bar) : "memory");
}
__device__ __forceinline__ uint32_t gtime() { uint32_t t; asm volatile("mov.u32 %0, %%globaltimer_lo;" : "=r"(t)); return t; }
__device__ __forceinline__ void fence_gpu() { asm volatile("fence.acq_rel.gpu;" ::: "memory"); }

__device__ __forceinline__ uint32_t enc(uint32_t b) { uint32_t r; asm("max.u32 %0, %1, 1;" : "=r"(r) : "r"(b)); return r; }
__device__ __forceinline__ uint32_t encf(float f) { return enc(__float_as_uint(f)); }
__device__ __forceinline__ void st_x1(uint32_t* p, uint32_t v) { asm volatile("st.relaxed.gpu.global.u32 [%0], %1;" :: "l"(p), "r"(v) : "memory"); }
__device__ __forceinline__ void st_x4(void* p, uint32_t a, uint32_t b, uint32_t c, uint32_t d) {
    asm volatile("st.relaxed.gpu.global.v4.u32 [%0], {%1, %2, %3, %4};" :: "l"(p), "r"(a), "r"(b), "r"(c), "r"(d) : "memory");
}
__device__ __forceinline__ void st2_x1(uint32_t* p, uint32_t v) { st_x1(p, v); st_x1(p + 1024, v); }
__device__ __forceinline__ void st2_x4(uint32_t* p, uint32_t a, uint32_t b, uint32_t c, uint32_t d) { st_x4(p, a, b, c, d); st_x4(p + 1024, a, b, c, d); }
__device__ __forceinline__ int near_off(int b, uint32_t cls) { return b * 4096 + (((__popc(b & 0x2C) ^ cls) & 1) << 10); }
__device__ __forceinline__ void ld_x(uint32_t& v, const void* p) { asm volatile("ld.relaxed.gpu.global.u32 %0, [%1];" : "=r"(v) : "l"(p) : "memory"); }
__device__ __forceinline__ void ld_x(uint4& v, const void* p) {
    asm volatile("ld.relaxed.gpu.global.v4.u32 {%0, %1, %2, %3}, [%4];" : "=r"(v.x), "=r"(v.y), "=r"(v.z), "=r"(v.w) : "l"(p) : "memory");
}
__device__ __forceinline__ void ld_x(uint2& v, const void* p) { asm volatile("ld.relaxed.gpu.global.v2.u32 {%0, %1}, [%2];" : "=r"(v.x), "=r"(v.y) : "l"(p) : "memory"); }
__device__ __forceinline__ uint32_t minw(uint32_t v) { return v; }
__device__ __forceinline__ uint32_t minw(const uint2& v) { return min(v.x, v.y); }
__device__ __forceinline__ uint32_t minw(const uint4& v) { return min(__vimin3_u32(v.x, v.y, v.z), v.w); }
template <int N> __device__ __forceinline__ uint32_t mint(const uint32_t* m) {
    if constexpr (N == 1) return m[0];
    else if constexpr (N == 2) return min(m[0], m[1]);
    else return __vimin3_u32(mint<(N + 2) / 3>(m), mint<(N + 1) / 3>(m + (N + 2) / 3), mint<N / 3>(m + (N + 2) / 3 + (N + 1) / 3));
}

template <int STRIDE, int S4 = 4 * STRIDE, typename T, int N>
__device__ __forceinline__ void poll_start(T (&v)[N], const void* base) {
#pragma unroll
    for (int i = 0; i < N; i++) ld_x(v[i], (const uint8_t*)base + (i & 3) * STRIDE + (i >> 2) * S4);
}
struct Nop { __device__ void operator()() const {} };
template <int STRIDE, int SLEEP, bool STARTED = false, int S4 = 4 * STRIDE, typename T, int N, typename F = Nop>
__device__ __forceinline__ void poll(T (&v)[N], const void* base, F idle = F()) {
    if (!STARTED) { poll_start<STRIDE, S4>(v, base); idle(); }
#pragma unroll 1
    for (uint32_t it = 0;; it++) {
        uint32_t m[N];
#pragma unroll
        for (int i = 0; i < N; i++) m[i] = minw(v[i]);
        if (__all_sync(0xffffffffu, mint<N>(m) != 0)) break;
        if (SLEEP && it > 0) __nanosleep(SLEEP);
#pragma unroll
        for (int i = 0; i < N; i++) if (!m[i]) ld_x(v[i], (const uint8_t*)base + (i & 3) * STRIDE + (i >> 2) * S4);
        idle();
        if (it > SPIN_LIMIT) __trap();
    }
}

__device__ __forceinline__ void movx(uint32_t& d, uint32_t x) { asm volatile("mov.b32 %0, %1;" : "=r"(d) : "r"(x)); }
__device__ __forceinline__ void movx(uint2& d, const uint2& x) { movx(d.x, x.x); movx(d.y, x.y); }
__device__ __forceinline__ void movx(uint4& d, const uint4& x) { movx(d.x, x.x); movx(d.y, x.y); movx(d.z, x.z); movx(d.w, x.w); }
template <typename T, int N> struct Poll2 {
    T v[2][N];
    template <int STRIDE, typename F = Nop>
    __device__ __forceinline__ void run(T (&r)[N], const void* base, F idle = F()) {
        auto ok = [&](const T (&x)[N]) {
            uint32_t m[N];
#pragma unroll
            for (int i = 0; i < N; i++) m[i] = minw(x[i]);
            return __all_sync(0xffffffffu, mint<N>(m) != 0);
        };
        auto again = [&](T (&x)[N]) {
#pragma unroll
            for (int i = 0; i < N; i++) if (!minw(x[i])) ld_x(x[i], (const uint8_t*)base + i * STRIDE);
        };
#pragma unroll
        for (int i = 0; i < N; i++) { v[0][i] = r[i]; v[1][i] = r[i]; }
        uint32_t t0, t1;
        asm volatile("mov.u32 %0, %%clock;" : "=r"(t0));
        again(v[0]);
        idle();
        do { asm volatile("mov.u32 %0, %%clock;" : "=r"(t1)); } while (__any_sync(0xffffffffu, t1 - t0 < P2_GAP));
#pragma unroll 1
        for (uint32_t it = 0;; it++) {
            again(v[1]);
            if (ok(v[0])) {
#pragma unroll
                for (int i = 0; i < N; i++) movx(r[i], v[0][i]);
                break;
            }
            again(v[0]);
            idle();
            if (it > SPIN_LIMIT) __trap();
            if (ok(v[1])) {
#pragma unroll
                for (int i = 0; i < N; i++) movx(r[i], v[1][i]);
                break;
            }
        }
    }
    __device__ __forceinline__ void settle() const {
        uint32_t m[2 * N];
#pragma unroll
        for (int i = 0; i < 2 * N; i++) m[i] = minw(v[i / N][i % N]);
        asm volatile("{\n.reg .pred p;\nsetp.eq.u32 p, %0, 0xffffffff;\n@p nanosleep.u32 0;\n}" :: "r"(mint<2 * N>(m)));
    }
};

__device__ __forceinline__ float bflo(uint32_t w) { return __uint_as_float(w << 16); }
__device__ __forceinline__ float bfhi(uint32_t w) { return __uint_as_float(w & 0xffff0000u); }
__device__ __forceinline__ uint32_t pack2(float lo, float hi) {
    uint32_t r; asm("cvt.rn.bf16x2.f32 %0, %1, %2;" : "=r"(r) : "f"(hi), "f"(lo)); return r;
}
__device__ __forceinline__ float rbf(float x) { return __uint_as_float(pack2(0.f, x)); }
__device__ __forceinline__ float sumlo(const uint32_t (&v)[8]) { return ((bflo(v[0]) + bflo(v[1])) + (bflo(v[2]) + bflo(v[3]))) + ((bflo(v[4]) + bflo(v[5])) + (bflo(v[6]) + bflo(v[7]))); }
__device__ __forceinline__ float sumhi(const uint32_t (&v)[8]) { return ((bfhi(v[0]) + bfhi(v[1])) + (bfhi(v[2]) + bfhi(v[3]))) + ((bfhi(v[4]) + bfhi(v[5])) + (bfhi(v[6]) + bfhi(v[7]))); }
__device__ __forceinline__ float ex2(float x) { float r; asm("ex2.approx.ftz.f32 %0, %1;" : "=f"(r) : "f"(x)); return r; }
__device__ __forceinline__ float shx(float v, int m) { return __shfl_xor_sync(0xffffffffu, v, m); }
__device__ __forceinline__ uint4 lds128(uint32_t a) { uint4 v; asm volatile("ld.shared.v4.u32 {%0, %1, %2, %3}, [%4];" : "=r"(v.x), "=r"(v.y), "=r"(v.z), "=r"(v.w) : "r"(a) : "memory"); return v; }
__device__ __forceinline__ uint32_t lds32(uint32_t a) { uint32_t v; asm volatile("ld.shared.u32 %0, [%1];" : "=r"(v) : "r"(a) : "memory"); return v; }
__device__ __forceinline__ void sts32(uint32_t a, uint32_t v) { asm volatile("st.shared.u32 [%0], %1;" :: "r"(a), "r"(v) : "memory"); }
__device__ __forceinline__ void sts16(uint32_t a, uint32_t v) { asm volatile("st.shared.u16 [%0], %1;" :: "r"(a), "h"((uint16_t)v) : "memory"); }
__device__ __forceinline__ int frag_off(int k) { return (k >> 5) * 64 + ((k >> 1) & 3) * 16 + ((k >> 4) & 1) * 8 + ((k >> 3) & 1) * 4 + (k & 1) * 2; }

template <bool TRANS>
__device__ __forceinline__ uint4 ldsm(uint32_t a) {
    uint4 r;
    if (TRANS) asm volatile("ldmatrix.sync.aligned.m8n8.x4.trans.shared.b16 {%0, %1, %2, %3}, [%4];" : "=r"(r.x), "=r"(r.y), "=r"(r.z), "=r"(r.w) : "r"(a) : "memory");
    else asm volatile("ldmatrix.sync.aligned.m8n8.x4.shared.b16 {%0, %1, %2, %3}, [%4];" : "=r"(r.x), "=r"(r.y), "=r"(r.z), "=r"(r.w) : "r"(a) : "memory");
    return r;
}
__device__ __forceinline__ void mma(float (&c)[4], uint32_t a0, uint32_t a1, uint32_t a2, uint32_t a3, uint32_t b0, uint32_t b1) {
    asm volatile("mma.sync.aligned.m16n8k16.row.col.f32.bf16.bf16.f32 {%0,%1,%2,%3}, {%4,%5,%6,%7}, {%8,%9}, {%0,%1,%2,%3};"
                 : "+f"(c[0]), "+f"(c[1]), "+f"(c[2]), "+f"(c[3]) : "r"(a0), "r"(a1), "r"(a2), "r"(a3), "r"(b0), "r"(b1));
}
template <bool TRANS, typename F>
__device__ __forceinline__ void load8(uint4 (&a)[8], F addr) {
    __syncwarp();
#pragma unroll
    for (int s = 0; s < 8; s++) a[s] = ldsm<TRANS>(addr(s));
}
__device__ __forceinline__ void mma8(float (&c)[4], const uint4 (&a)[8], const uint4 (&b)[4]) {
    float e[4][4];
#pragma unroll
    for (int s = 0; s < 8; s++) {
        if (s < 4) e[s][0] = e[s][1] = e[s][2] = e[s][3] = 0.f;
        mma(e[s & 3], a[s].x, a[s].y, a[s].z, a[s].w, (s & 1) ? b[s >> 1].z : b[s >> 1].x, (s & 1) ? b[s >> 1].w : b[s >> 1].y);
    }
#pragma unroll
    for (int i = 0; i < 4; i++) c[i] = (e[0][i] + e[1][i]) + (e[2][i] + e[3][i]);
}
__device__ __forceinline__ void ldfrag(uint4 (&b)[4], uint32_t a) {
    asm volatile("ld.shared.v4.u32 {%0,%1,%2,%3}, [%16];\nld.shared.v4.u32 {%4,%5,%6,%7}, [%16+64];\n"
                 "ld.shared.v4.u32 {%8,%9,%10,%11}, [%16+128];\nld.shared.v4.u32 {%12,%13,%14,%15}, [%16+192];\n"
                 : "=r"(b[0].x), "=r"(b[0].y), "=r"(b[0].z), "=r"(b[0].w), "=r"(b[1].x), "=r"(b[1].y), "=r"(b[1].z), "=r"(b[1].w),
                   "=r"(b[2].x), "=r"(b[2].y), "=r"(b[2].z), "=r"(b[2].w), "=r"(b[3].x), "=r"(b[3].y), "=r"(b[3].z), "=r"(b[3].w) : "r"(a) : "memory");
}
__device__ __forceinline__ void pin(uint32_t& x) { asm volatile("" : "+r"(x)); }
template <typename T> __device__ __forceinline__ void pin(T*& x) { asm volatile("" : "+l"(x)); }
__device__ __forceinline__ float4 ldsf4(uint32_t a) { const uint4 v = lds128(a); return make_float4(__uint_as_float(v.x), __uint_as_float(v.y), __uint_as_float(v.z), __uint_as_float(v.w)); }
__device__ __forceinline__ float sum4(const float4& f) { return (f.x + f.y) + (f.z + f.w); }
__device__ __forceinline__ void stsf(uint32_t a, float v) { sts32(a, __float_as_uint(v)); }

__device__ __forceinline__ void wg_fence() { asm volatile("wgmma.fence.sync.aligned;" ::: "memory"); }
__device__ __forceinline__ void wg_commit() { asm volatile("wgmma.commit_group.sync.aligned;" ::: "memory"); }
__device__ __forceinline__ void wg_wait1() { asm volatile("wgmma.wait_group.sync.aligned 1;" ::: "memory"); }
__device__ __forceinline__ void wg_wait0() { asm volatile("wgmma.wait_group.sync.aligned 0;" ::: "memory"); }
#define R8(o) "+f"(d[o]), "+f"(d[o + 1]), "+f"(d[o + 2]), "+f"(d[o + 3]), "+f"(d[o + 4]), "+f"(d[o + 5]), "+f"(d[o + 6]), "+f"(d[o + 7])
__device__ __forceinline__ void wgmma_rs_n32(float (&d)[16], const uint4& a, uint64_t db, int acc) {
    asm volatile("{\n.reg .pred p;\nsetp.ne.b32 p, %21, 0;\n"
        "wgmma.mma_async.sync.aligned.m64n32k16.f32.bf16.bf16 "
        "{%0,%1,%2,%3,%4,%5,%6,%7,%8,%9,%10,%11,%12,%13,%14,%15}, {%16,%17,%18,%19}, %20, p, 1, 1, 0;\n}"
        : R8(0), R8(8) : "r"(a.x), "r"(a.y), "r"(a.z), "r"(a.w), "l"(db), "r"(acc));
}
#define PV_LO "{%0,%1,%2,%3,%4,%5,%6,%7,%8,%9,%10,%11,%12,%13,%14,%15,%16,%17,%18,%19,%20,%21,%22,%23,%24,%25,%26,%27,%28,%29,%30,%31,%32,%33,%34,%35,%36,%37,%38,%39,%40,%41,%42,%43,%44,%45,%46,%47,%48,%49,%50,%51,%52,%53,%54,%55,%56,%57,%58,%59,%60,%61,%62,%63}, "
#define PV_HI "{%64,%65,%66,%67,%68,%69,%70,%71,%72,%73,%74,%75,%76,%77,%78,%79,%80,%81,%82,%83,%84,%85,%86,%87,%88,%89,%90,%91,%92,%93,%94,%95,%96,%97,%98,%99,%100,%101,%102,%103,%104,%105,%106,%107,%108,%109,%110,%111,%112,%113,%114,%115,%116,%117,%118,%119,%120,%121,%122,%123,%124,%125,%126,%127}, "
__device__ __forceinline__ void wgmma_pv(float (&d)[128], const uint4& a, uint32_t blo, int acc) {
    asm volatile("{\n.reg .pred p;\n.reg .b32 u0, u1, u2, u3, t;\n.reg .b64 d0, d1, d2, d3;\nsetp.ne.b32 p, %133, 0;\n"
        "mov.b64 d0, {%132, 0x40000100};\nadd.u32 t, %132, 512;\nmov.b64 d1, {t, 0x40000100};\n"
        "add.u32 t, %132, 128;\nmov.b64 d2, {t, 0x40000100};\nadd.u32 t, %132, 640;\nmov.b64 d3, {t, 0x40000100};\n"
        "wgmma.fence.sync.aligned;\n"
        "wgmma.mma_async.sync.aligned.m64n128k16.f32.bf16.bf16 " PV_LO "{%128, u0, %129, u1}, d0, p, 1, 1, 1;\n"
        "wgmma.mma_async.sync.aligned.m64n128k16.f32.bf16.bf16 " PV_LO "{%130, u2, %131, u3}, d1, 1, 1, 1, 1;\n"
        "wgmma.commit_group.sync.aligned;\n"
        "wgmma.mma_async.sync.aligned.m64n128k16.f32.bf16.bf16 " PV_HI "{%128, u0, %129, u1}, d2, p, 1, 1, 1;\n"
        "wgmma.mma_async.sync.aligned.m64n128k16.f32.bf16.bf16 " PV_HI "{%130, u2, %131, u3}, d3, 1, 1, 1, 1;\n"
        "wgmma.commit_group.sync.aligned;\n}"
        : R8(0), R8(8), R8(16), R8(24), R8(32), R8(40), R8(48), R8(56), R8(64), R8(72), R8(80), R8(88), R8(96), R8(104), R8(112), R8(120)
        : "r"(a.x), "r"(a.y), "r"(a.z), "r"(a.w), "r"(blo), "r"(acc) : "memory");
}

template <int NW>
__device__ __forceinline__ void ln_stats(float s, float q, float sh, float* scr, int w, int lane, int bar, float& mean_b, float& sd_b) {
#pragma unroll
    for (int o = 16; o; o >>= 1) { s += shx(s, o); q += shx(q, o); }
    constexpr float n = 512.f / NW;
    if (lane == 0) { scr[w] = sh + s * (1.f / n); scr[NW + w] = q - s * s * (1.f / n); }
    bar_sync(bar, NW * 32);
    float mu = 0.f, m2 = 0.f;
#pragma unroll
    for (int i = 0; i < NW; i++) { mu += scr[i]; m2 += scr[NW + i]; }
    mu *= 1.f / NW;
#pragma unroll
    for (int i = 0; i < NW; i++) { const float d = scr[i] - mu; m2 = fmaf(n * d, d, m2); }
    mean_b = rbf(mu);
    sd_b = rbf(sqrtf(rbf(rbf(fmaxf(m2, 0.f) * (1.f / 512.f)) + 1e-5f)));
}
__device__ __forceinline__ float ln_mod(float x, float mean_b, float sd_b, float c, float s) {
    return rbf(rbf(__fdividef(rbf(x - mean_b), sd_b)) * rbf(1.f + c)) + s;
}

__global__ void __cluster_dims__(2, 1, 1) __launch_bounds__(NTHREADS, 1)
fused_kernel(const __grid_constant__ First F, __nv_bfloat16* __restrict__ out, uint32_t* __restrict__ gs, const __grid_constant__ Maps M) {
    extern __shared__ __align__(1024) uint8_t sm[];
    const uint32_t sb0 = s2u(sm);
    const int tid = threadIdx.x, lane = tid & 31;
    const int j = blockIdx.x, rk = j & 1;
    const int g = lane >> 2, t = lane & 3;
    const int r8 = lane & 7, lb3 = (lane >> 3) & 1, lb4 = lane >> 4;
    const uint64_t pol = 0x12F0000000000000ull;
    uint32_t in1 = 0, in2 = 0;
    {
        auto cpa = [&](uint32_t d, const uint8_t* s) {
            asm volatile("cp.async.cg.shared.global.L2::cache_hint.L2::128B [%0], [%1], 16, %2;" :: "r"(d), "l"(s), "l"(pol) : "memory");
        };
        const uint32_t ut = threadIdx.x, uj = blockIdx.x;
        const uint8_t* w = F.w[ut >= 128];
        if (ut < 128) {
            const uint32_t dq = (sb0 + ut * 16) ^ ((ut * 2) & 0x70);
            const uint8_t* sq = w + (uint32_t)(((uj & 1) * 256 + (ut >> 3)) * 8192 + (uj >> 1) * 128 + (ut & 7) * 16);
#pragma unroll
            for (int i = 0; i < 4 * NCP; i++) cpa(dq + 4 * 32768 + i * 2048, sq + i * 131072);
        } else if (ut < 384) {
            const uint32_t dm = (sb0 + ut * 16) ^ ((ut * 2) & 0x10);
            const uint8_t* sa = w + (uint32_t)(((uj >> 5) * 128 + (ut >> 1) - 64) * 6144 + (uj & 31) * 32 + (ut & 1) * 16);
            asm volatile("cp.async.cg.shared.global.L2::cache_hint" MODA_PF " [%0], [%1], 16, %2;" :: "r"(dm + SM_XA - 2048), "l"(sa), "l"(pol) : "memory");
            asm volatile("cp.async.cg.shared.global.L2::cache_hint" MODA_PF " [%0], [%1], 16, %2;" :: "r"(dm + SM_XA + 2048), "l"(sa + 1024), "l"(pol) : "memory");
        }
        else if (ut == 480 && uj < 16 * XC_LATE) asm volatile("prefetch.global.L2 [%0];" :: "l"(F.v[(uj >> 3) & 1] + (uj & 7) * 64));
    }
    const int warp = __shfl_sync(0xffffffffu, tid >> 5, 0);
    const uint32_t sb = sb0;
    const __nv_bfloat16* const xin = F.v[0];
    uint32_t* const pl = gs + (warp < 2 ? (B_PR + (j >> 5)) * 4096 + (j & 31) * 32 : G_E1 + j * 8192) + (warp & 1) * 1024 + lane;
    auto small_loads = [&]() {
        if (warp < 4) { in1 = *(const uint32_t*)(xin + 2 * tid); in2 = *(const uint32_t*)(xin + 256 + 2 * tid); }
        else if (warp < 12) in1 = *(const uint32_t*)(F.v[1] + 2 * (tid - 128));
    };
    if (!XC_LATE) small_loads();
    if (warp < 4) st_x1(pl, 1u);
    auto BAR = [&](int i) -> uint32_t { return sb + SM_BAR + i * 8; };
    const uint32_t a16 = (r8 + 8 * lb4) * 32 + ((lb3 ^ (r8 >> 2)) * 16);
    const uint32_t a128 = (r8 + 8 * lb4) * 128 + ((((warp & 3) * 2 + lb3) ^ r8) * 16);
    auto ldcls = [&]() -> uint32_t { return *(const volatile uint32_t*)(sm + SM_CLS); };
    auto clear_head = [&]() {
        st2_x1(gs + (B_HA + ((j >> 4) & 1) * 2 + lb4) * 4096 + (j >> 5) * 256 + (j & 15) * 16 + (lane & 15), 0u);
        st2_x4(gs + (B_QA + rk * 8 + ((j >> 1) & 1) * 4 + (j >> 5)) * 4096 + g * 128 + ((j >> 2) & 7) * 16 + t * 4, 0u, 0u, 0u, 0u);
        if (lane < 8) st2_x1(gs + B_RD * 4096 + j * 8 + lane, 0u);
    };
    auto tma = [&](uint32_t dst, int mp, uint32_t bar, int c0, int c1, int c2, int c3) {
        asm volatile("{\n.reg .pred p;\nelect.sync _|p, 0xffffffff;\n"
                     "@p cp.async.bulk.tensor.4d.shared::cluster.global.mbarrier::complete_tx::bytes.L2::cache_hint [%0], [%1, {%3, %4, %5, %6}], [%2], %7;\n}"
                     :: "r"(dst), "l"(&M.m[mp]), "r"(bar), "r"(c0), "r"(c1), "r"(c2), "r"(c3), "l"(pol) : "memory");
    };
    if (warp <= 12 || warp == 15) {
        const int grp = warp == 12 ? 0 : warp == 15 ? 13 : warp + 1;
        const uint32_t cnt = grp < 10 ? 1 : grp < 13 ? 4 : 8;
        if (lane == 0) {
#pragma unroll
            for (int i = 0; i < 8; i++) mbar_init(BAR(grp * 8 + i), (i < 2 && grp == 0) ? (i ? 128 : 256) : cnt);
        }
        __syncwarp();
        if (grp < 10 && lane < 8 && (grp || lane > NCP)) mbar_expect(BAR(grp * 8 + lane), grp >= 8 ? 4096 : grp * 8 + lane < IT_X ? 8192 : 16384);
        asm volatile("fence.mbarrier_init.release.cluster;" ::: "memory");
        __syncwarp();
        if (warp == 12) {
#pragma unroll
            for (int i = NCP + 1; i < W0; i++) tma(sb + (15 + i) * 8192, MP_WQ, BAR(i), 0, rk * 256 + (i - 1) * 64, j >> 1, 0);
        }
    } else if (warp == 13) {
        if (lane < NMAPS) asm volatile("prefetch.tensormap [%0];" :: "l"(&M.m[lane]) : "memory");
    } else if (warp == 14 && PREZERO) {
        clear_head();
    }
    __syncthreads();
    if (XC_LATE) small_loads();
    if (warp < 12) asm volatile("cp.async.mbarrier.arrive.noinc.shared::cta.b64 [%0];" :: "r"(BAR(warp < 4)) : "memory");
    asm volatile("barrier.cluster.arrive.relaxed.aligned;" ::: "memory");

    if (warp >= 12) {
    asm volatile("setmaxnreg.dec.sync.aligned.u32 56;");
    if (warp == 12) {
        static_assert(W0 > NCP && W0 <= 5 && NCP >= 1 && NCP <= 4, "W0");
        const uint32_t* sched = M.sched[j < NFF ? 0 : j < J_RED ? 1 : 2];
        uint32_t e = sched[W0];
        uint32_t tn = gtime() + sched[1];
        const uint32_t tau = sched[0] + ((j & 2) ? sched[2] : -sched[2]);
#pragma unroll 1
        for (int i = W0; e; i++) {
            const uint32_t en = sched[i + 1];
            const int id = e & 63, w0 = (e >> 11) & 127, w1 = (e >> 18) & 127;
            int mp, c0 = 0, c1 = 0, c2 = 0, c3 = 0;
            tn += tau;
            if (id < IT_CKV) { const int k = id - IT_WQ; mp = MP_WQ + (k >> 2); c1 = rk * 256 + (k & 3) * 64; c2 = j >> 1; }
            else if (id < IT_WUV) { const int k = id - IT_CKV; mp = MP_CKV; c2 = rk * 4; c3 = (k * 64 + (j >> 1)) * 2; }
            else if (id < IT_WO) { mp = MP_WUV; c1 = (j & 3) * 32 + (id - IT_WUV) * 128; c2 = (j >> 2) * 2; }
            else if (id < IT_X) { mp = MP_WO; c0 = (j & 7) * 64; c1 = (j >> 3) * 256 + (id - IT_WO) * 64; }
            else if (id < IT_DOWN) {
                if (j >= J_END) break;
                const int k = id - IT_X;
                mp = j < NFF ? MP_GATE + (k >> 1) : MP_MODB; c0 = (j >> 1) * 64 + (j < NFF ? 0 : 1024 - NFF * 32); c1 = rk * 256 + (k & 1) * 128;
            } else {
                if (id == NEVER) { e = en; continue; }
                mp = MP_DOWN; c1 = j * 32; c2 = (id - IT_DOWN) * 4;
            }
            if (w0) mbar_wait(BAR(w0 - 1), 0);
            const int w2 = e >> 25;
            if (w2) {
                mbar_wait(BAR(w2 - 1), 0);
                while (!__any_sync(0xffffffffu, mbar_test(BAR(w1 - 1), 0) | ((int)(gtime() - tn) > 0))) {}
            } else if (w1) mbar_wait(BAR(w1 - 1), 0);
            tma(sb + ((e >> 6) & 31) * 8192, mp, BAR(id), c0, c1, c2, c3);
            e = en;
        }
    } else if (warp == 13) {
#pragma unroll
        for (int i = 0; i < 2; i++) st_x4(gs + (B_ML + rk * 16 + i * 8 + g) * 4096 + (t >> 1) * 1024 + (j >> 1) * 8 + (t & 1) * 4, 0u, 0u, 0u, 0u);
        if (lane < 16) st2_x4(gs + (B_E2 + (j >> 4)) * 4096 + (j & 15) * 64 + lane * 4, 0u, 0u, 0u, 0u);
        st2_x1(gs + (B_E3 + (j >> 5)) * 4096 + (j & 31) * 32 + lane, 0u);
        if (lane < 8) st2_x1(gs + B_MB * 4096 + j * 8 + lane, 0u);
        if (j < NFF) {
#pragma unroll
            for (int i = 0; i < 2; i++) st2_x4(gs + (B_E5 + i * 8 + g) * 4096 + j * 16 + t * 4, 0u, 0u, 0u, 0u);
        }
        bar_sync(9, 64);
        const uint32_t cs = ldcls();
#pragma unroll 1
        for (int i = 0; i < 32; i++) {
            st_x4(gs + G_E1 + j * 8192 + (i >> 3) * 2048 + ((((cs >> 1) ^ (i >> 3)) & 1) << 10) + (i & 7) * 128 + lane * 4, 0u, 0u, 0u, 0u);
            __nanosleep(JAN_SLEEP);
        }
        fence_gpu();
        if (lane < 8) st2_x1(gs + B_RD * 4096 + j * 8 + lane, 1u + (cs >> 1));
        if (lane == 0) TRACE(41);
        uint32_t rd[4];
        mbar_wait(BAR(IT_CKV + RD_ITEM), 0);
        poll<1024, RD_SLEEP>(rd, gs + near_off(B_RD, cs) + lane * 8);
#pragma unroll
        for (int i = 0; i < 4; i++) {
            const uint32_t m = __ballot_sync(0xffffffffu, rd[i] == 2u);
            if (lane == 0) sts32(sb + SM_CLS + 16 + i * 4, m);
        }
        __syncwarp();
        if (lane < 8) mbar_arrive(BAR(JD));
        if (lane == 0) TRACE(42);
    } else if (warp == 14) {
        uint2 ml[2];
        mbar_waitb(BAR(JD), 0);
        const uint32_t cls = ldcls();
        mbar_waitb(BAR(PF0 + 2 * NUNITS - 1), 0);
        __nanosleep(ML_DELAY);
        {
            const uint32_t* pl2 = gs + near_off(B_ML + (j >> 2), cls) + lane * 8;
            poll_start<1024>(ml, pl2);
            bool first = E1_EARLY;
#pragma unroll 1
            for (uint32_t it = 0;; it++) {
                const uint32_t m0 = minw(ml[0]), m1 = minw(ml[1]);
                const int n = __popc(__ballot_sync(0xffffffffu, m0 != 0)) + __popc(__ballot_sync(0xffffffffu, m1 != 0));
                if (first && n >= E1_EARLY) { bar_arrive(5, 288); first = false; }
                if (n == 64) break;
                if (!m0) ld_x(ml[0], pl2);
                if (!m1) ld_x(ml[1], pl2 + 256);
                if (it > SPIN_LIMIT) __trap();
            }
            bar_arrive(3, 288);
        }
        if (lane == 0) TRACE_Q(37);
        const float m0 = __uint_as_float(ml[0].x), m1 = __uint_as_float(ml[1].x);
        const int mi = __float_as_int(fmaxf(m0, m1));
        const int mr = __reduce_max_sync(0xffffffffu, mi ^ ((mi >> 31) & 0x7fffffff));
        const float mm = __int_as_float(mr ^ ((mr >> 31) & 0x7fffffff));
        const uint32_t w0 = pack2(ex2(m0 - mm), 0.f), w1 = pack2(ex2(m1 - mm), 0.f);
        const uint32_t wa = sb + SM_W + lb4 * 64 + t * 16 + (g & 3) * 4;
        sts32(wa, w0 * 0x10001u); sts32(wa + 128, w1 * 0x10001u);
        bar_arrive(8, 288);
        float L = bflo(w0) * __uint_as_float(ml[0].y) + bflo(w1) * __uint_as_float(ml[1].y);
#pragma unroll
        for (int o = 16; o; o >>= 1) L += shx(L, o);
        if (lane == 0) *(float*)(sm + SM_FQ) = __frcp_rn(L);
        if (lane == 0) TRACE(10);
        bar_sync(4, 288);
        clear_head();
        if (j < NFF) {
            uint32_t ya = sb + SM_Y + lane * 16, sa = peer_addr(sb + SM_RED + 2048 + rk * 8, lane & 1), tb = peer_addr(BAR(QB), lane & 1);
            pin(ya); pin(sa); pin(tb);
            bar_sync(7, 288);
            const float4 y0 = ldsf4(ya), y1 = ldsf4(ya + 512);
            float s = sum4(y0) + sum4(y1);
            float q = (fmaf(y0.x, y0.x, y0.y * y0.y) + fmaf(y0.z, y0.z, y0.w * y0.w)) + (fmaf(y1.x, y1.x, y1.y * y1.y) + fmaf(y1.z, y1.z, y1.w * y1.w));
#pragma unroll
            for (int o = 16; o; o >>= 1) { s += shx(s, o); q += shx(q, o); }
            if (lane < 2) st_async2(sa, s, q, tb);
        }
    } else if (warp == 15) {
        mbar_waitb(BAR(IT_X - 1), 0);
        if (j < J_END) mbar_waitb(BAR(j < NFF ? NITEMS - 1 : MBB), 0);
    }
    } else if (warp < 4) {
        float* scr = (float*)(sm + SM_SCR);
        uint32_t cls;
        {
            uint2 ha[8];
            {
                uint32_t best = 0xffffffffu;
#pragma unroll
                for (int i = 0; i < NPROBE; i++) {
                    uint32_t t0, t1, o;
                    asm volatile("mov.u32 %0, %%clock;" : "=r"(t0));
                    asm volatile("atom.relaxed.gpu.global.exch.b32 %0, [%1], %2;" : "=r"(o) : "l"(pl), "r"(2u + i) : "memory");
                    asm volatile("{\n.reg .pred p;\nsetp.ne.u32 p, %1, 0x1234567;\nmov.u32 %0, 0;\n@p mov.u32 %0, %%clock;\n}" : "=r"(t1) : "r"(o));
                    best = min(best, t1 - t0);
                }
                if (lane == 0) scr[16 + warp] = __uint_as_float(best);
            }
            const float sh = __shfl_sync(0xffffffffu, bflo(in1), 0);
            const float v0 = bflo(in1) - sh, v1 = bfhi(in1) - sh, v2 = bflo(in2) - sh, v3 = bfhi(in2) - sh;
            float mb, sd;
            ln_stats<4>((v0 + v1) + (v2 + v3), (v0 * v0 + v1 * v1) + (v2 * v2 + v3 * v3), sh, scr, warp, lane, 2, mb, sd);
            if (!rk) in2 = in1;
            const uint4 lt = *(const uint4*)(scr + 16);
            cls = NUMA ? ((lt.y < lt.x) ^ (__popc((B_PR + (j >> 5)) & 0x2C) & 1)) | (lt.w < lt.z) << 1 : 0;
            if (warp == 0) { if (lane == 0) sts32(sb + SM_CLS, cls); bar_arrive(9, 64); }
            if (tid == 0) TRACE(38);
            asm volatile("barrier.cluster.wait.aligned;" ::: "memory");
            mbar_wait(BAR(IT_MODA), 0);
            __nanosleep(HA_DELAY);
            poll<1024, H_SLEEP, false, 16384>(ha, gs + near_off(B_HA + rk * 2, cls) + 2 * tid);
            auto rsum = [](uint32_t a, uint32_t b, uint32_t c, uint32_t d) { return rbf((__uint_as_float(a) + __uint_as_float(b)) + (__uint_as_float(c) + __uint_as_float(d))); };
            sts32(sb + SM_FV + frag_off(2 * tid),
                  pack2(ln_mod(bflo(in2), mb, sd, rsum(ha[4].x, ha[5].x, ha[6].x, ha[7].x), rsum(ha[0].x, ha[1].x, ha[2].x, ha[3].x)),
                        ln_mod(bfhi(in2), mb, sd, rsum(ha[4].y, ha[5].y, ha[6].y, ha[7].y), rsum(ha[0].y, ha[1].y, ha[2].y, ha[3].y))));
            bar_arrive(5, 384);
            mbar_wait(BAR(QB), 0);
            if (tid < 64) {
                const float* qx = (const float*)(sm + SM_QX) + tid;
                sts16(sb + SM_FQ + frag_off(tid), pack2((qx[0] + qx[64]) + (qx[128] + qx[192]), 0.f));
            }
            bar_arrive(6, 384);
        }
        asm volatile("setmaxnreg.inc.sync.aligned.u32 168;");
        float acc[128];
        float M = 0.f;
        uint32_t pa = sb + SM_XA + warp * 512 + lane * 16, ma = sb + SM_MX + (warp * 8 + g) * 4, pf = BAR(PF0);
        uint32_t blo = __reduce_or_sync(0xffffffffu, (((sb + SM_U) & 0x3FFFFu) >> 4) | 0x400000u);
        uint32_t* e1[4];
#pragma unroll
        for (int i = 0; i < 4; i++) e1[i] = gs + G_E1 + (warp * 8 + g) * 4 * 8192 + (rk * 2 + (j >> 6)) * 2048 + ((j >> 1) & 31) * 32 + t * 4;
        uint32_t ck[10] = {0, 0, 0, 0, 0, 0, 0, 0, 0, 0};
#pragma unroll 1
        for (int h = 0; h < 2 * NUNITS; h++) {
            CLK(ck[0], h == 2 * TU); CLK(ck[5], h == 2 * TU + 1);
            mbar_wait(pf, 0);
            CLK(ck[1], h == 2 * TU); CLK(ck[6], h == 2 * TU + 1);
            const float m = __uint_as_float(lds32(ma));
            const uint4 pn = lds128(pa);
            wg_wait0();
#pragma unroll
            for (int i = 0; i < 128; i++) asm volatile("" : "+f"(acc[i]) :: "memory");
            CLK(ck[2], h == 2 * TU); CLK(ck[7], h == 2 * TU + 1);
            if (h == 0) M = m;
            uint32_t b2 = 0x3f803f80u;
            if (__builtin_expect(__any_sync(0xffffffffu, m != M), 0)) {
                const float Mn = fmaxf(M, m), alpha = ex2(M - Mn), beta = ex2(m - Mn);
                M = Mn;
                b2 = pack2(beta, beta);
#pragma unroll
                for (int jj = 0; jj < 32; jj++) { acc[4 * jj] *= alpha; acc[4 * jj + 1] *= alpha; }
            }
            auto mul2 = [](uint32_t x, uint32_t y) { uint32_t r; asm("mul.rn.bf16x2 %0, %1, %2;" : "=r"(r) : "r"(x), "r"(y)); return r; };
            const uint4 p = make_uint4(mul2(pn.x, b2), mul2(pn.y, b2), mul2(pn.z, b2), mul2(pn.w, b2));
            if (tid == 0 && (h & 1)) TRACE_Q(48 + (h >> 1));
            CLK(ck[3], h == 2 * TU); CLK(ck[8], h == 2 * TU + 1);
            wgmma_pv(acc, p, blo, h);
            CLK(ck[4], h == 2 * TU); CLK(ck[9], h == 2 * TU + 1);
            if (lane == 0 && h > 0 && !(h & 1)) mbar_arrive(BAR(EB_UNIT0 + (h >> 1) - 1));
            blo += h == 11 ? -11 * 1024 : 1024;
            pa += (h == 5 || h == 11) ? -5 * 2048 : 2048;
            ma += 128; pf += 8;
            if (h == 2 * NUNITS - 3) {
                mbar_wait(BAR(JD), 0);
                const uint32_t hm = (*(const uint32_t*)(sm + SM_CLS + 16 + warp * 4) >> (g * 4)) ^ ((j >> 6) ? 15u : 0u);
#pragma unroll
                for (int i = 0; i < 4; i++) e1[i] += ((hm >> i) & 1) << 10;
            }
        }
#pragma unroll
        for (int vv = 0; vv < 2; vv++) {
            if (vv && M == 1.f) __trap();
            if (vv) wg_wait0(); else wg_wait1();
#pragma unroll
            for (int i = 0; i < 64; i++) asm volatile("" : "+f"(acc[vv * 64 + i]) :: "memory");
            if (tid == 0 && !vv) TRACE_Q(63);
#pragma unroll
            for (int i = 0; i < 4; i++) {
                const float* a = &acc[vv * 64 + i * 16];
                st_x4(e1[i] + i * 8192 + vv * 16, enc(pack2(a[0], a[1])), enc(pack2(a[4], a[5])), enc(pack2(a[8], a[9])), enc(pack2(a[12], a[13])));
            }
        }
        if (tid == 0) TRACE_Q(17);
        if (j < NFF) {
            uint4 a[16];
            const uint32_t ad = sb + SM_U + B_DN * 32768 + warp * 8192 + (r8 + 8 * lb4) * 128 + (lb3 ^ r8) * 16;
            uint32_t rl = sb + SM_RED + lane * 16;
            uint32_t* p5 = gs + (B_E5 + warp * 4 + (t >> 1)) * 4096 + j * 16 + (t & 1) * 8 + g;
            pin(rl); pin(p5);
            mbar_wait(BAR(IT_DOWN + (warp >> 1)), 0);
#pragma unroll
            for (int s = 0; s < 16; s++) a[s] = ldsm<true>((ad ^ ((s & 3) * 32)) + (s >> 2) * 2048);
            TK(18);
            mbar_wait(BAR(QB), 1);
            TK(19);
            if (tid == 0) TRACE(25);
            const float4 st = ldsf4(sb + SM_RED + 2048);
            const float4 f0 = ldsf4(rl), f2 = ldsf4(rl + 1024), f1 = ldsf4(rl + 512), f3 = ldsf4(rl + 1536);
            const float mu = (st.x + st.z) * (1.f / 512.f);
            float rstd;
            asm("rsqrt.approx.ftz.f32 %0, %1;" : "=f"(rstd) : "f"(fmaxf(fmaf(-mu, mu, (st.y + st.w) * (1.f / 512.f)), 0.f) + 1e-5f));
            const float gg = fmaf(rstd, fmaf(-mu, f0.z + f2.z, (f0.x + f0.y) + (f2.x + f2.y)), f0.w + f2.w);
            const float uu = fmaf(rstd, fmaf(-mu, f1.z + f3.z, (f1.x + f1.y) + (f3.x + f3.y)), f1.w + f3.w);
            TKD(20, gg);
            const float hh = __fdividef(gg * uu, 1.f + ex2(-gg * fmaf(gg * gg, 0.10294324f, 2.3022082f)));
            uint32_t hb[4];
#pragma unroll
            for (int i = 0; i < 4; i++) hb[i] = pack2(__shfl_sync(0xffffffffu, hh, 2 * t + 8 * i), __shfl_sync(0xffffffffu, hh, 2 * t + 8 * i + 1));
            TKD(21, __uint_as_float(hb[3]));
#pragma unroll
            for (int i = 0; i < 2; i++) {
                uint32_t res = 0;
#pragma unroll
                for (int k = 0; k < 4; k++) {
                    float c[4] = {0.f, 0.f, 0.f, 0.f};
                    const uint4 &x = a[i * 8 + k], &y = a[i * 8 + k + 4];
                    mma(c, x.x, x.y, x.z, x.w, hb[0], hb[1]);
                    mma(c, y.x, y.y, y.z, y.w, hb[2], hb[3]);
                    if (t == k) res = pack2(c[0], c[2]);
                }
                st2_x1(p5 + i * 8192, enc(res));
            }
            TK(22);
            if (tid == 0) { TRACE(27); TRACE_GT(47); }
        } else if (j < J_END) {
            uint4 a[8], b[4];
            float c[4], e[4];
            const bool own = (warp >> 1) == rk;
            const uint32_t xa = sb + SM_FV + (warp & 1) * 64 + g * 8;
            if (lane == 0) mbar_expect(BAR(MBB), own ? 64 : 0);
#pragma unroll
            for (int i = 0; i < 2; i++) {
                ldfrag(b, sb + SM_FS + rk * 512 + i * 256 + t * 16);
                mbar_wait(BAR(IT_X + i), 0);
                const uint32_t ab = sb + SM_U + B_X * 32768 + i * 16384 + a128;
                load8<true>(a, [&](int s) { return ab + s * 2048; });
                mma8(i ? e : c, a, b);
            }
            c[0] += e[0]; c[2] += e[2];
            if (!own) {
                if (t == 0) st_async2(peer_addr(xa, rk ^ 1), c[0], c[2], peer_addr(BAR(MBB), rk ^ 1));
            } else {
                mbar_wait(BAR(MBB), 0);
                const float2 pp = *(const float2*)(sm + (xa - sb));
                const float mine = t ? c[2] + pp.y : c[0] + pp.x, other = shx(mine, 4);
                const uint32_t w = (warp & 1) * 8 + t * 4 + (g >> 1), val = enc(pack2(mine, other));
                if (t < 2 && !(g & 1)) {
                    if (j < J_RED) st2_x1(gs + B_MB * 4096 + (j - NFF) * 16 + w, val);
                    else sts32(sb + SM_FV + 256 + w * 4, val);
                }
                if (j >= J_RED) bar_arrive(7, 320);
                if (lane == 0) TRACE(11);
            }
        }
    } else {
        const int u8 = tid - 128, w8 = warp - 4;
        const int v = w8 >> 2, wq4 = w8 & 3;
        {
            const float c0 = bflo(in1), c1 = bfhi(in1);
            sts32(sb + SM_FS + frag_off(2 * u8), pack2(__fdividef(c0, 1.f + __expf(-c0)), __fdividef(c1, 1.f + __expf(-c1))));
        }
        bar_sync(1, 256);
        asm volatile("barrier.cluster.wait.aligned;" ::: "memory");
        uint4 a[8], b[4]; float c[4];
        if (w8 < 2) {
            ldfrag(b, sb + SM_FS + (j >> 5) * 256 + t * 16);
            mbar_wait(BAR(IT_MODA), 0);
            if (u8 == 0) TRACE(12);
            const uint32_t ab = sb + SM_XA + w8 * 4096 + a16;
            load8<true>(a, [&](int s) { return ab + s * 512; });
            mma8(c, a, b);
            if (t < 2) st2_x1(gs + (B_HA + ((j >> 4) & 1) * 2 + w8) * 4096 + (j >> 5) * 256 + (j & 15) * 16 + t * 8 + g, encf(t ? c[2] : c[0]));
        }
        {
            mbar_wait(BAR(IT_WQ + 2 * v <= NCP ? 1 : IT_WQ + 2 * v), 0); mbar_wait(BAR(IT_WQ + 2 * v + 1 <= NCP ? 1 : IT_WQ + 2 * v + 1), 0);
            const uint32_t ab = sb + SM_U + 4 * 32768 + v * 16384 + a128;
            load8<true>(a, [&](int s) { return ab + s * 2048; });
            if (lane == 0) mbar_arrive(BAR(EB_WQ));
            bar_sync(5, 384);
            if (u8 == 0) TRACE(13);
            ldfrag(b, sb + SM_FV + v * 256 + t * 16);
            mma8(c, a, b);
            if (t < 2) {
                const float qv = t ? c[2] : c[0];
                const uint32_t qa_ = sb + SM_QX + ((rk * 2 + v) * 64 + wq4 * 16 + t * 8 + g) * 4;
                asm volatile("st.async.weak.shared::cluster.mbarrier::complete_tx::bytes.f32 [%0], %1, [%2];"
                             :: "r"(peer_addr(qa_, rk ^ 1)), "f"(qv), "r"(peer_addr(BAR(QB), rk ^ 1)) : "memory");
                sts32(qa_, __float_as_uint(qv));
            }
            __syncwarp();
            if (lane == 0) mbar_expect(BAR(QB), 64);
        }
        {
            mbar_wait(BAR(IT_WUK + v), 0); mbar_wait(BAR(IT_WUK + v + 2), 0);
            const uint32_t ab = sb + SM_U + 5 * 32768 + (w8 * 16 + r8 + 8 * lb3) * 128;
            const uint32_t x16 = (lb4 ^ r8) * 16;
            load8<false>(a, [&](int s) { return ab + (s & 1) * 16384 + (x16 ^ ((s >> 1) * 32)); });
            bar_sync(6, 384);
            if (u8 == 0) TRACE(14);
            b[0] = lds128(sb + SM_FQ + t * 16); b[1] = lds128(sb + SM_FQ + 64 + t * 16);
            float e[4] = {0.f, 0.f, 0.f, 0.f};
            c[0] = c[1] = c[2] = c[3] = 0.f;
#pragma unroll
            for (int k = 0; k < 4; k++) {
                const uint32_t b0 = (k & 1) ? b[k >> 1].z : b[k >> 1].x, b1 = (k & 1) ? b[k >> 1].w : b[k >> 1].y;
                mma(c, a[2 * k].x, a[2 * k].y, a[2 * k].z, a[2 * k].w, b0, b1);
                mma(e, a[2 * k + 1].x, a[2 * k + 1].y, a[2 * k + 1].z, a[2 * k + 1].w, b0, b1);
            }
            const float mine = ((t & 1) ? ((t & 2) ? e[2] : e[0]) : ((t & 2) ? c[2] : c[0])) * 0.12751743f;
            const float other = shx(mine, 4);
            if (!(g & 1)) st2_x1(gs + (B_QA + rk * 8 + ((j >> 1) & 1) * 4 + (j >> 5)) * 4096 + w8 * 128 + ((j >> 2) & 7) * 16 + (g >> 1) * 4 + t, enc(pack2(mine, other)));
            if (u8 == 0) TRACE(15);
        }
        const uint32_t cls = ldcls();
        __nanosleep(QA_DELAY);
        {
            uint4 qb[8];
            const uint32_t* pq = gs + near_off(B_QA + rk * 8 + wq4, cls) + lane * 4;
            const uint32_t* pq2 = gs + near_off(B_QA + rk * 8 + 4 + wq4, cls) + lane * 4;
            if (lane == 0) {
                mbar_expect(BAR(QT), 4096);
                asm volatile("cp.async.bulk.shared::cluster.global.mbarrier::complete_tx::bytes [%0], [%1], 4096, [%2];"
                             :: "r"(sb + SM_U + 5 * 32768 + w8 * 4096), "l"(gs + near_off(B_QA + rk * 8 + w8, cls)), "r"(BAR(QT)) : "memory");
            }
            const uint32_t qs = sb + SM_U + 5 * 32768 + wq4 * 4096 + lane * 16;
            mbar_wait(BAR(QT), 0);
#pragma unroll
            for (int i = 0; i < 8; i++) { a[i] = lds128(qs + i * 512); qb[i] = lds128(qs + 16384 + i * 512); }
            poll<512, QA_SLEEP, true>(a, pq);
            poll<512, QA_SLEEP, true>(qb, pq2);
            if (lane == 0) mbar_arrive(BAR(EB_WUK));
            auto add2 = [](uint32_t x, uint32_t y) { uint32_t r; asm("add.rn.bf16x2 %0, %1, %2;" : "=r"(r) : "r"(x), "r"(y)); return r; };
#pragma unroll
            for (int i = 0; i < 8; i++) a[i] = make_uint4(add2(a[i].x, qb[i].x), add2(a[i].y, qb[i].y), add2(a[i].z, qb[i].z), add2(a[i].w, qb[i].w));
        }
        if (u8 == 0) TRACE(8);
        {
            float m = -INFINITY, l = 0.f;
            uint32_t xl = sb + SM_XB + w8 * 2048 + lane * 16, xr = peer_addr(xl, rk ^ 1), bsr = peer_addr(BAR(SF0 + v), rk ^ 1);
            uint32_t pa = sb + SM_XA + v * 2048 + wq4 * 512 + lane * 16, ma = sb + SM_MX + v * 128 + (wq4 * 8 + g) * 4;
            uint32_t fb = BAR(IT_CKV + v * 2), sf = BAR(SF0 + v);
            uint32_t dlo = __reduce_or_sync(0xffffffffu, (((sb + SM_U + v * 16384) & 0x3FFFFu) >> 4) | 0x10000u);
            uint32_t ck[9] = {0, 0, 0, 0, 0, 0, 0, 0, 0};
            if (STAG && v) __nanosleep(STAG);
#pragma unroll 1
            for (int n = 0; n < NUNITS; n++) {
                CLK(ck[0], n == TU); CLK(ck[8], n == TU + 1);
                float d[2][16], sc[8];
#pragma unroll
                for (int i = 0; i < 2; i++) {
                    mbar_wait(fb + i * 8, 0);
                    if (i == 0) CLK(ck[1], n == TU);
                    wg_fence();
#pragma unroll
                    for (int s = 0; s < 8; s++) wgmma_rs_n32(d[i], a[s], (0x40000080ull << 32) | (dlo + i * 512 + (s >> 2) * 64 + (s & 3) * 2), s);
                    wg_commit();
                }
                CLK(ck[2], n == TU);
#pragma unroll
                for (int i = 0; i < 2; i++) {
                    if (i) wg_wait0(); else wg_wait1();
#pragma unroll
                    for (int k = 0; k < 16; k++) asm volatile("" : "+f"(d[i][k]) :: "memory");
                    sc[4 * i] = d[i][0] + d[i][6]; sc[4 * i + 1] = d[i][1] + d[i][7]; sc[4 * i + 2] = d[i][8] + d[i][14]; sc[4 * i + 3] = d[i][9] + d[i][15];
                    asm volatile("st.async.weak.shared::cluster.mbarrier::complete_tx::bytes.v4.f32 [%0], {%1, %2, %3, %4}, [%5];"
                                 :: "r"(xr + i * 1024), "f"(sc[4 * i]), "f"(sc[4 * i + 1]), "f"(sc[4 * i + 2]), "f"(sc[4 * i + 3]), "r"(bsr) : "memory");
                }
                CLK(ck[3], n == TU);
                if (u8 == 128) TRACE_Q(56 + (n < 6 ? n : -40));
                if (n >= 3) mbar_wait(BAR(EB_UNIT0 + n - 3), 0);
                dlo += n == 5 ? -5 * 2048 : 2048;
                fb += 32; xr ^= 512; bsr += 16;
                pin(fb); pin(xr); pin(bsr);
                CLK(ck[4], n == TU);
                mbar_wait(sf, 0);
                CLK(ck[5], n == TU);
                const float4 x = ldsf4(xl), y = ldsf4(xl + 1024);
                sc[0] += x.x; sc[1] += x.y; sc[2] += x.z; sc[3] += x.w; sc[4] += y.x; sc[5] += y.y; sc[6] += y.z; sc[7] += y.w;
                float pr[8];
#pragma unroll
                for (int i = 0; i < 8; i++) pr[i] = ex2(sc[i] - m);
                float mx = fmaxf(fmaxf(fmaxf(sc[0], sc[1]), fmaxf(sc[2], sc[3])), fmaxf(fmaxf(sc[4], sc[5]), fmaxf(sc[6], sc[7])));
                if (__builtin_expect(__any_sync(0xffffffffu, mx > m), 0)) {
                    mx = fmaxf(mx, shx(mx, 1));
                    mx = fmaxf(mx, shx(mx, 2));
                    const float mn = fmaxf(m, ceilf(mx * 0.0625f) * 16.f);
                    l *= ex2(m - mn);
                    m = mn;
#pragma unroll
                    for (int i = 0; i < 8; i++) pr[i] = ex2(sc[i] - m);
                }
                CLK(ck[6], n == TU);
                stsf(ma, m);
                asm volatile("st.shared.v4.u32 [%0], {%1, %2, %3, %4};" :: "r"(pa), "r"(pack2(pr[0], pr[1])), "r"(pack2(pr[2], pr[3])),
                             "r"(pack2(pr[4], pr[5])), "r"(pack2(pr[6], pr[7])) : "memory");
                __syncwarp();
                if (lane == 0) mbar_arrive(sf + (PF0 - SF0) * 8);
                CLK(ck[7], n == TU);
                l += ((pr[0] + pr[1]) + (pr[2] + pr[3])) + ((pr[4] + pr[5]) + (pr[6] + pr[7]));
                xl ^= 512; sf += 16; ma += 256; pa += (n == 2 || n == 5) ? -8192 : 4096;
            }
            l += shx(l, 1);
            l += shx(l, 2);
            float2* mlx = (float2*)(sm + SM_MX + 2048) + wq4 * 8 + g;
            if (v == 0) { *mlx = make_float2(m, l); bar_arrive(11, 256); }
            else {
                mbar_wait(BAR(JD), 0);
                bar_sync(11, 256);
                const float2 o = *mlx;
                const float mn = fmaxf(m, o.x);
                l = l * ex2(m - mn) + o.y * ex2(o.x - mn);
                if ((wq4 >> 1) == rk) st_x4(gs + (B_ML + wq4 * 8 + g) * 4096 + (t >> 1) * 1024 + (j >> 1) * 8 + (t & 1) * 4, encf(mn), encf(l), 1u, 1u);
            }
        }
        asm volatile("setmaxnreg.inc.sync.aligned.u32 144;");
        const int pi = j < NFF ? rk * 128 + w8 * 16 + (lane & 15) : ((j - J_RED) & 15) * 16 + v * 8 + lb4 * 4 + wq4;
        const uint32_t xw = *(const uint32_t*)(xin + 2 * pi);
        {
#pragma unroll 1
            for (int i = 0; i < 4; i++) mbar_wait(BAR(IT_WUV + i), 0);
            const uint32_t ab = sb + SM_U + B_WUV * 32768 + v * 4096 + a128;
            load8<true>(a, [&](int s) { return ab + (s >> 1) * 8192 + (s & 1) * 2048; });
            uint32_t pa = sb + SM_PB + wq4 * 320 + frag_off(64 * v + 32 * (g >> 2) + 16 * (t & 1) + 8 * (t >> 1) + 2 * (g & 3));
            uint32_t fa = sb + SM_PB + g * 320 + t * 16, ra = sb + SM_RED + w8 * 288 + g * 16 + t * 4;
            uint32_t rb = sb + SM_RED + (u8 & 15) * 144 + ((u8 >> 4) & 3) * 32;
            const uint32_t* pe = gs + G_E1 + j * 8192 + (w8 >> 1) * 2048 + ((((cls >> 1) ^ (w8 >> 1)) & 1) << 10) + (((w8 & 1) * 16 + t) * 8 + g) * 4;
            uint32_t* p2 = gs + (B_E2 + (j >> 4)) * 4096 + (u8 >> 6) * 1024 + (j & 12) * 64 + (u8 & 12) * 16 + (j & 3) * 16 + ((u8 >> 2) & 12) + t;
            pin(pa); pin(fa); pin(ra); pin(rb); pin(pe); pin(p2);
            uint4 pv[4];
            if (E1_EARLY) { bar_sync(5, 288); poll_start<512>(pv, pe); }
            bar_sync(3, 288);
            TK(0);
            if (E1_EARLY) {
#pragma unroll
                for (int i = 0; i < 4; i++) if (!minw(pv[i])) ld_x(pv[i], pe + i * 128);
            } else poll_start<512>(pv, pe);
            bar_sync(8, 288);
            const uint4 wa = lds128(sb + SM_W + (wq4 * 4 + t) * 16);
            const uint32_t mk = (g & 1) ? 0xffff0000u : 0x0000ffffu, m0 = (g & 2) ? 0u : mk, m1 = (g & 2) ? mk : 0u;
            uint32_t wb[8] = {wa.x & m0, wa.x & m1, wa.y & m0, wa.y & m1, wa.z & m0, wa.z & m1, wa.w & m0, wa.w & m1};
#pragma unroll
            for (int i = 0; i < 8; i++) pin(wb[i]);
            poll<512, E1_SLEEP, true>(pv, pe);
            if (u8 == 0) TRACE_Q(18);
            TK(1);
            float e[4][4];
#pragma unroll
            for (int i = 0; i < 4; i++) {
                e[i][0] = e[i][1] = e[i][2] = e[i][3] = 0.f;
                mma(e[i], pv[i].x, pv[i].y, pv[i].z, pv[i].w, wb[2 * i], wb[2 * i + 1]);
            }
            const float r0 = (t & 2) ? (e[0][2] + e[1][2]) + (e[2][2] + e[3][2]) : (e[0][0] + e[1][0]) + (e[2][0] + e[3][0]);
            const float r1 = (t & 2) ? (e[0][3] + e[1][3]) + (e[2][3] + e[3][3]) : (e[0][1] + e[1][1]) + (e[2][1] + e[3][1]);
            const uint32_t hi = pack2(r0, r1);
            sts32(pa, hi); sts32(pa + 1280, pack2(r0 - bflo(hi), r1 - bfhi(hi)));
            TK(2);
            bar_sync(1, 256);
            TK(3);
            if (u8 == 0) TRACE(19);
            ldfrag(b, fa);
            mma8(c, a, b);
            stsf(ra, c[0] + c[1]); stsf(ra + 144, c[2] + c[3]);
            TK(4);
            bar_sync(4, 288);
            TK(5);
            if (w8 < 4) {
                const float inv = *(const float*)(sm + SM_FQ);
                st_x1(p2, enc(pack2(sum4(ldsf4(rb)) * inv, sum4(ldsf4(rb + 16)) * inv)));
            }
            TK(6);
            if (u8 == 0) TRACE(20);
        }
        uint32_t mb[3] = {0u, 0u, 0u};
        const uint32_t* pm = gs + near_off(B_MB, cls) + pi;
        pin(pm);
        if (j < NFF) poll_start<1024>(mb, pm);
        {
            const uint32_t nz = lb4 ? 0x80008000u : 0u;
#pragma unroll
            for (int i = 0; i < 4; i++) b[i] = make_uint4(nz, nz, nz, nz);
            const bool early = __all_sync(0xffffffffu, mbar_test(BAR(IT_WO + 2 * v), 0) & mbar_test(BAR(IT_WO + 2 * v + 1), 0));
            const uint32_t ab = sb + SM_U + B_WO * 32768 + v * 16384 + a128;
            if (early) load8<true>(a, [&](int s) { return ab + s * 2048; });
            uint32_t ra = sb + SM_R3 + (wq4 * 16 + g) * 16 + v * 8 + t * 4, rb = sb + SM_R3 + lane * 32;
            uint32_t* p3 = gs + (B_E3 + ((j >> 1) & 3)) * 4096 + w8 * 1024 + (rk * 2 + lb4) * 256 + (j >> 3) * 16 + (lane & 15);
            pin(ra); pin(rb); pin(p3);
            TK(7);
            Poll2<uint4, 4> p2;
            if (P2 & 2) p2.run<256>(b, gs + near_off(B_E2 + (j >> 4), cls) + (((j >> 3) & 1) * 2 + v) * 256 + lane * 4);
            else poll<256, E2_SLEEP, true>(b, gs + near_off(B_E2 + (j >> 4), cls) + (((j >> 3) & 1) * 2 + v) * 256 + lane * 4);
            if (!early) { mbar_wait(BAR(IT_WO + 2 * v), 0); mbar_wait(BAR(IT_WO + 2 * v + 1), 0); load8<true>(a, [&](int s) { return ab + s * 2048; }); }
            TK(8);
            if (u8 == 0) TRACE(21);
            mma8(c, a, b);
            if (t < 2) { stsf(ra, c[0] + c[1]); stsf(ra + 128, c[2] + c[3]); }
            TK(9);
            bar_sync(1, 256);
            TK(10);
            if (w8 < 2) st_x1(p3, enc(pack2(sum4(ldsf4(rb)), sum4(ldsf4(rb + 16)))));
            if (P2 & 2) p2.settle();
            TK(11);
            if (u8 == 0) TRACE(22);
        }
        if (j < NFF) {
            const uint32_t* p3 = gs + near_off(B_E3 + rk * 2 + v, cls) + wq4 * 256 + lane;
            uint32_t za = sb + SM_FZ + lb4 * 576 + frag_off(w8 * 32 + (lane & 15) * 2);
            uint32_t fa = sb + SM_FZ + (g & 3) * 576 + lb4 * 256 + t * 16, ya = sb + SM_Y + u8 * 4;
            poll<1024, MB_SLEEP, true>(mb, pm);
            const uint32_t kk = pack2(1.f + bflo(mb[2]), 1.f + bfhi(mb[2]));
            sts32(za + 2 * 576, lb4 ? mb[1] : kk);
            uint32_t e3[8] = {0u, 0u, 0u, 0u, 0u, 0u, 0u, 0u};
            uint32_t ra = peer_addr(sb + SM_RED + (rk * 2 + v) * 512 + ((wq4 & 1) * 16 + (t >> 1) * 8 + g) * 16 + (t & 1) * 8, wq4 >> 1), tbo = peer_addr(BAR(QB), wq4 >> 1);
            pin(za); pin(fa); pin(ya); pin(ra); pin(tbo);
            if (lane == 0) mbar_expect(BAR(QB), 258);
            uint4 a2[8];
            TK(12);
            const uint32_t gb = BAR(IT_X + v * 2), ab = sb + SM_U + (B_X + v) * 32768 + a128;
            bool early = false, early2 = false;
            auto ldw = [&]() {
                if (!early) {
                    early = __all_sync(0xffffffffu, mbar_test(gb, 0));
                    if (early) load8<true>(a, [&](int s) { return ab + s * 2048; });
                }
                if (!early2) {
                    early2 = __all_sync(0xffffffffu, mbar_test(gb + 8, 0));
                    if (early2) load8<true>(a2, [&](int s) { return ab + 16384 + s * 2048; });
                }
            };
            Poll2<uint32_t, 8> p2;
            if (P2 & 4) p2.run<128>(e3, p3, ldw); else poll<128, E3_SLEEP, true>(e3, p3, ldw);
            TK(13);
            if (u8 == 0) TRACE(23);
            const float s0 = sumlo(e3), s1 = sumhi(e3);
            const float y0 = fmaf(bflo(mb[0]), s0 + shx(s0, 16), bflo(xw)), y1 = fmaf(bfhi(mb[0]), s1 + shx(s1, 16), bfhi(xw));
            stsf(ya, lb4 ? y1 : y0);
            const float z0 = y0 * bflo(kk), z1 = y1 * bfhi(kk);
            const uint32_t zh = pack2(z0, z1);
            sts32(za, lb4 ? pack2(z0 - bflo(zh), z1 - bfhi(zh)) : zh);
            TK(14);
            bar_sync(7, 288);
            TK(15);
            if (u8 == 0) TRACE(24);
            ldfrag(b, fa);
            if (!early) { mbar_wait(gb, 0); load8<true>(a, [&](int s) { return ab + s * 2048; }); }
            if (!early2) { mbar_wait(gb + 8, 0); load8<true>(a2, [&](int s) { return ab + 16384 + s * 2048; }); }
            {
                float e[4][4];
#pragma unroll
                for (int s = 0; s < 16; s++) {
                    const uint4& x = (s & 2) ? a2[(s >> 2) * 2 + (s & 1)] : a[(s >> 2) * 2 + (s & 1)];
                    const uint4& y = b[s >> 2];
                    if (s < 4) e[s][0] = e[s][1] = e[s][2] = e[s][3] = 0.f;
                    mma(e[s & 3], x.x, x.y, x.z, x.w, (s & 1) ? y.z : y.x, (s & 1) ? y.w : y.y);
                }
                const bool hi = t >> 1;
                const float k0 = hi ? e[2][2] + e[3][2] : e[0][0] + e[1][0], k1 = hi ? e[2][3] + e[3][3] : e[0][1] + e[1][1];
                const float o0 = hi ? e[2][0] + e[3][0] : e[0][2] + e[1][2], o1 = hi ? e[2][1] + e[3][1] : e[0][3] + e[1][3];
                TKD(16, o0);
                st_async2(ra, k0 + shx(o0, 2), k1 + shx(o1, 2), tbo);
            }
            if (P2 & 4) p2.settle();
            TK(17);
        } else if (j >= J_RED && j < J_END) {
            uint32_t ga[1], e3[1];
            poll<0, MB_SLEEP>(ga, pm);
            poll<0, 100>(e3, gs + near_off(B_E3 + (pi >> 6), cls) + (pi & 48) * 16 + (lane & 15) * 16 + (pi & 15));
            if (E5_DELAY) __nanosleep(E5_DELAY);
            float y0 = bflo(e3[0]), y1 = bfhi(e3[0]);
#pragma unroll
            for (int o = 8; o; o >>= 1) { y0 += shx(y0, o); y1 += shx(y1, o); }
            y0 = fmaf(bflo(ga[0]), y0, bflo(xw)); y1 = fmaf(bfhi(ga[0]), y1, bfhi(xw));
            bar_sync(7, 320);
            const uint32_t gb = lds32(sb + SM_FV + 256 + (pi & 15) * 4);
            uint32_t* po = (uint32_t*)out + pi;
            pin(po);
            const uint32_t nz = lane < NFF / 2 ? 0u : 0x80008000u;
            uint2 yv[2] = {make_uint2(nz, nz), make_uint2(nz, nz)};
            Poll2<uint2, 2> p2;
            if (P2 & 8) p2.run<NFF * 32>(yv, gs + near_off(B_E5 + j - J_RED, cls) + lane * 16 + w8 * 2);
            else poll<NFF * 32, E5_SLEEP, true>(yv, gs + near_off(B_E5 + j - J_RED, cls) + lane * 16 + w8 * 2);
            if (u8 == 0) TRACE(26);
            const float l0 = bflo(yv[0].x) + bflo(yv[1].x), h0 = bfhi(yv[0].x) + bfhi(yv[1].x);
            const float l1 = bflo(yv[0].y) + bflo(yv[1].y), h1 = bfhi(yv[0].y) + bfhi(yv[1].y);
            float s0 = (lb4 ? h0 : l0) + shx(lb4 ? l0 : h0, 16), s1 = (lb4 ? h1 : l1) + shx(lb4 ? l1 : h1, 16);
#pragma unroll
            for (int o = 8; o; o >>= 1) { s0 += shx(s0, o); s1 += shx(s1, o); }
            if (!(lane & 15)) *po = pack2(fmaf(bflo(gb), s0, y0), fmaf(bfhi(gb), s1, y1));
            if (P2 & 8) p2.settle();
            if (u8 == 0) TRACE(27);
        }
    }
}

typedef CUresult (*EncFn)(CUtensorMap*, CUtensorMapDataType, cuuint32_t, void*, const cuuint64_t*, const cuuint64_t*,
                          const cuuint32_t*, const cuuint32_t*, CUtensorMapInterleave, CUtensorMapSwizzle,
                          CUtensorMapL2promotion, CUtensorMapFloatOOBfill);

void make_map(EncFn enc_fn, CUtensorMap* m, const void* p, cuuint64_t d0, cuuint64_t d1, cuuint64_t d2, cuuint64_t d3,
              cuuint64_t s1, cuuint64_t s2, cuuint64_t s3, cuuint32_t b0, cuuint32_t b1, cuuint32_t b2, cuuint32_t b3, CUtensorMapSwizzle sw) {
    const cuuint64_t dims[4] = {d0, d1, d2, d3}, strides[3] = {s1, s2, s3};
    const cuuint32_t box[4] = {b0, b1, b2, b3}, es[4] = {1, 1, 1, 1};
    enc_fn(m, CU_TENSOR_MAP_DATA_TYPE_BFLOAT16, 4, (void*)p, dims, strides, box, es,
           CU_TENSOR_MAP_INTERLEAVE_NONE, sw, CU_TENSOR_MAP_L2_PROMOTION_L2_64B, CU_TENSOR_MAP_FLOAT_OOB_FILL_NONE);
}

uint32_t* scratch = nullptr;

struct Tune { const char* win; const char* late; int tau, t_off; const char* tail[3][3]; int dtau; };
Tune tune = {"66666666655566677766666665555554444445544",
             "00000000000888888880999999bbbbbbbb9999999", 315, -200,
             {{"VVVVOOOOguguDD", "55544444346787", "00000000000000"},
              {"VVVVMMOOOO", "5555556655", "0000000008"},
              {"VVVVOOOO...MM", "44453334000zz", "0000000000088"}}, 0};
bool ready = false;

}

extern "C" void kernel_launch(void* const* d_in, const int* in_sizes, int n_in, void* d_out, int out_size) {
    (void)in_sizes; (void)n_in; (void)out_size;
    static Maps maps;
    static const void* cached[12] = {};
    bool same = ready;
    for (int i = 0; i < 12 && same; i++) same = cached[i] == d_in[i];
    if (!same) {
        void* fn = nullptr;
        cudaDriverEntryPointQueryResult qr;
        cudaGetDriverEntryPoint("cuTensorMapEncodeTiled", &fn, cudaEnableDefault, &qr);
        EncFn e = (EncFn)fn;
        const CUtensorMapSwizzle S128 = CU_TENSOR_MAP_SWIZZLE_128B;
        make_map(e, &maps.m[MP_WQ], d_in[2], 64, 512, 64, 1, 8192, 128, 8192, 64, 64, 1, 1, S128);
        make_map(e, &maps.m[MP_WUK], d_in[3], 64, 512, 64, 1, 8192, 128, 8192, 64, 64, 1, 1, S128);
        make_map(e, &maps.m[MP_CKV], d_in[1], 64, 8, 8, 4096, 1024, 128, 8192, 64, 8, 4, 2, S128);
        make_map(e, &maps.m[MP_MODB], d_in[11], 3072, 512, 1, 1, 6144, 6144, 6144, 64, 128, 1, 1, S128);
        make_map(e, &maps.m[MP_WUV], d_in[4], 64, 512, 64, 1, 8192, 128, 8192, 64, 32, 2, 1, S128);
        make_map(e, &maps.m[MP_WO], d_in[5], 512, 4096, 1, 1, 1024, 1024, 1024, 64, 64, 1, 1, S128);
        make_map(e, &maps.m[MP_GATE], d_in[7], 1792, 512, 1, 1, 3584, 3584, 3584, 64, 128, 1, 1, S128);
        make_map(e, &maps.m[MP_UP], d_in[8], 1792, 512, 1, 1, 3584, 3584, 3584, 64, 128, 1, 1, S128);
        make_map(e, &maps.m[MP_DOWN], d_in[9], 64, 1792, 8, 1, 1024, 128, 1024, 64, 32, 4, 1, S128);
        for (int r = 0; r < 3; r++) {
            int ids[72], real[72], nreal = 0, cnt[128] = {};
            uint32_t* sc = maps.sched[r];
            auto dig = [](char ch) { return ch >= 'a' ? ch - 'a' + 10 : ch - '0'; };
            for (int i = 0; i < 72; i++) sc[i] = 0;
            for (int i = 0;; i++) {
                int id = i, buf, dep, w, wl;
                if (i < IT_WUV) {
                    const int u = (i - IT_CKV) >> 2;
                    buf = i < IT_CKV ? 4 + ((i - 1) >> 2) : u % 6;
                    dep = i < IT_CKV || u < 4 ? -1 : u < 6 ? EB_WQ + u - 4 : EB_UNIT0 + u - 6;
                    w = dig(tune.win[i]); wl = dig(tune.late[i]);
                } else {
                    const char ch = tune.tail[r][0][i - IT_WUV];
                    if (!ch) break;
                    if (ch == '.') { sc[i] = NEVER; continue; }
                    buf = ch == 'V' ? B_WUV : ch == 'O' ? B_WO : ch == 'D' ? B_DN : ch == 'u' ? B_X + 1 : B_X;
                    id = (ch == 'V' ? IT_WUV : ch == 'O' ? IT_WO : ch == 'D' ? IT_DOWN : ch == 'u' ? IT_X + 2 : IT_X) + cnt[(int)ch]++;
                    dep = EB_UNIT0 + (buf < 2 ? buf + 6 : buf);
                    w = dig(tune.tail[r][1][i - IT_WUV]); wl = dig(tune.tail[r][2][i - IT_WUV]);
                }
                if (id < IT_X ? (id - 1) & 3 : (id - IT_X) & 1) dep = -1;
                ids[i] = id;
                auto back = [&](int d) { const int k = nreal - d; return k < 0 ? 0 : (ids[real[k]] && ids[real[k]] <= NCP ? 1 : ids[real[k]]) + 1; };
                sc[i] = id | (buf * 4 + (id < IT_X ? (id - 1) & 3 : ((id - IT_X) & 1) * 2)) << 6 | (dep + 1) << 11 | (w > 32 ? NEVER + 1 : back(w)) << 18 | (wl ? back(wl) : 0) << 25;
                real[nreal++] = i;
            }
            sc[0] = tune.tau; sc[1] = tune.t_off; sc[2] = tune.dtau;
        }
        cudaGetSymbolAddress((void**)&scratch, g_scratch);
        scratch = (uint32_t*)(((uintptr_t)scratch + (2u << 20) - 1) & ~(uintptr_t)((2u << 20) - 1));
        cudaFuncSetAttribute(fused_kernel, cudaFuncAttributeMaxDynamicSharedMemorySize, SM_TOTAL);
        for (int i = 0; i < 12; i++) cached[i] = d_in[i];
        ready = true;
    }
    const First f = {{(const uint8_t*)d_in[2], (const uint8_t*)d_in[11]}, {(const __nv_bfloat16*)d_in[0], (const __nv_bfloat16*)d_in[10]}};
    fused_kernel<<<NCTA, NTHREADS, SM_TOTAL>>>(f, (__nv_bfloat16*)d_out, scratch, maps);
}
```

```cpp
#include <cuda_runtime.h>
#include <cuda_bf16.h>
#include <cuda.h>
#include <stdint.h>

namespace {

constexpr int NCTA = 128;
constexpr int NTHREADS = 512;
constexpr int NUNITS = 8;
constexpr int NFF = 56, J_RED = 104, J_END = 120;
constexpr uint32_t SPIN_LIMIT = 1u << 22;

#define PINSB 0
#define E5_DELAY 0
#define XC_LATE 4
#define MODA_PF ".L2::128B"
#define PREZERO 1
#define E1_EARLY 50
#define STAG 300
#define TU 2
#define NUMA 1
#define NPROBE 3
#define NCP 2
#define W0 4
#define RD_ITEM 15
#define JAN_SLEEP 100
#define RD_SLEEP 400
#define HA_DELAY 200
#define H_SLEEP 100
#define QA_DELAY 600
#define QA_SLEEP 200
#define ML_DELAY 300
#define ML_SLEEP 50
#define E1_SLEEP 50
#define E2_SLEEP 0
#define E3_SLEEP 0
#define E5_SLEEP 0
#define MB_SLEEP 100
constexpr int B_WUV = 2, B_WO = 3, B_X = 4  , B_DN = 0;

constexpr int SM_U = 0;
constexpr int SM_XA = 6 * 32768;
constexpr int SM_XB = SM_XA + 12288;
constexpr int SM_MX = SM_XB + 16384;
constexpr int SM_FZ = SM_XB + 8192;
constexpr int SM_PB = SM_XB;
constexpr int SM_Y = SM_XB + 12288;
constexpr int SM_RED = SM_XB + 4096;
constexpr int SM_FS = SM_XB + 20480;
constexpr int SM_FV = SM_FS + 1024;
constexpr int SM_QX = SM_XA + 8192;
constexpr int SM_FQ = SM_FV + 512;
constexpr int SM_CLS = SM_FQ + 128;
constexpr int SM_W = SM_FQ + 256;
constexpr int SM_SCR = SM_XA + 9216;
constexpr int SM_TR = SM_XB + 19456;
constexpr int SM_BAR = SM_W + 256;
constexpr int SM_TOTAL = SM_BAR + 1024;
static_assert(SM_TOTAL <= 232448, "smem");

enum { IT_MODA = 0, IT_WQ = 1, IT_WUK = 5, IT_CKV = 9, IT_WUV = 41, IT_WO = 45, IT_X = 49  , IT_DOWN = 53, NITEMS = 55,
       NEVER = 63,
       SF0 = 64,
       PF0 = 80,
       EB_UNIT0 = 96, MBB = 103,
       EB_WQ = 104, EB_WUK, QT, QB, JD, WR };

enum { MP_WQ = 0, MP_WUK, MP_CKV, MP_MODB, MP_WUV, MP_WO, MP_GATE, MP_UP, MP_DOWN, NMAPS };
struct First { const uint8_t* w[2]; const __nv_bfloat16* v[2]; };
struct Maps { CUtensorMap m[NMAPS]; uint2 sched[3][56]; };

enum { B_HA = 0,
       B_MB = 6,
       B_RD = 7,
       B_E2 = 8,
       B_QA = 16,
       B_ML = 32,
       B_E5 = 64,
       B_E3 = 80,
       B_PR = 96,
       B_TR = 100 };
constexpr int G_E1 = 1 << 19;
constexpr int G_TR = B_TR * 4096;
__device__ __align__(1024) uint32_t g_scratch[(8 << 20) / 4];

#define TRACE(slot) do {} while (0)
#define TRACE_Q(slot) do {} while (0)
#define TRACE_GT(slot) do {} while (0)

#define CLK(var, cond) do {} while (0)
#define CLKD(var, cond, dep) do {} while (0)
#define TK(i) do {} while (0)
#define TKD(i, dep) do {} while (0)
__device__ __forceinline__ uint32_t s2u(const void* p) { return (uint32_t)__cvta_generic_to_shared(p); }
__device__ __forceinline__ void mbar_init(uint32_t b, int c) { asm volatile("mbarrier.init.shared::cta.b64 [%0], %1;" :: "r"(b), "r"(c) : "memory"); }
__device__ __forceinline__ void mbar_expect(uint32_t b, uint32_t bytes) { asm volatile("mbarrier.arrive.expect_tx.shared::cta.b64 _, [%0], %1;" :: "r"(b), "r"(bytes) : "memory"); }
__device__ __forceinline__ void mbar_arrive(uint32_t b) { asm volatile("mbarrier.arrive.shared::cta.b64 _, [%0];" :: "r"(b) : "memory"); }
__device__ __forceinline__ void mbar_wait(uint32_t b, uint32_t ph) {
    asm volatile("{\n.reg .pred p;\nW: mbarrier.try_wait.parity.shared::cta.b64 p, [%0], %1;\n@!p bra W;\n}" :: "r"(b), "r"(ph) : "memory");
}
__device__ __forceinline__ void mbar_waitb(uint32_t b, uint32_t ph) {
    asm volatile("{\n.reg .pred p;\n.reg .u32 n;\nmov.u32 n, 0;\n"
                 "W: mbarrier.try_wait.parity.shared::cta.b64 p, [%0], %1;\n@p bra D;\n"
                 "add.u32 n, n, 1;\nsetp.lt.u32 p, n, 0x100000;\n@p bra W;\ntrap;\nD:\n}" :: "r"(b), "r"(ph) : "memory");
}
__device__ __forceinline__ uint32_t mbar_test(uint32_t b, uint32_t ph) {
    uint32_t ok;
    asm volatile("{\n.reg .pred p;\nmbarrier.test_wait.parity.shared::cta.b64 p, [%1], %2;\nselp.u32 %0, 1, 0, p;\n}" : "=r"(ok) : "r"(b), "r"(ph) : "memory");
    return ok;
}
__device__ __forceinline__ void bar_sync(int id, int n) { asm volatile("bar.sync %0, %1;" :: "r"(id), "r"(n) : "memory"); }
__device__ __forceinline__ void bar_arrive(int id, int n) { asm volatile("bar.arrive %0, %1;" :: "r"(id), "r"(n) : "memory"); }
__device__ __forceinline__ uint32_t peer_addr(uint32_t a, uint32_t rank) { uint32_t r; asm("mapa.shared::cluster.u32 %0, %1, %2;" : "=r"(r) : "r"(a), "r"(rank)); return r; }
__device__ __forceinline__ void st_async1(uint32_t a, float x, uint32_t bar) {
    asm volatile("st.async.weak.shared::cluster.mbarrier::complete_tx::bytes.f32 [%0], %1, [%2];" :: "r"(a), "f"(x), "r"(bar) : "memory");
}
__device__ __forceinline__ void st_async2(uint32_t a, float x, float y, uint32_t bar) {
    asm volatile("st.async.weak.shared::cluster.mbarrier::complete_tx::bytes.v2.f32 [%0], {%1, %2}, [%3];" :: "r"(a), "f"(x), "f"(y), "r"(bar) : "memory");
}
__device__ __forceinline__ uint32_t gtime() { uint32_t t; asm volatile("mov.u32 %0, %%globaltimer_lo;" : "=r"(t)); return t; }
__device__ __forceinline__ void fence_gpu() { asm volatile("fence.acq_rel.gpu;" ::: "memory"); }

__device__ __forceinline__ uint32_t enc(uint32_t b) { uint32_t r; asm("max.u32 %0, %1, 1;" : "=r"(r) : "r"(b)); return r; }
__device__ __forceinline__ uint32_t encf(float f) { return enc(__float_as_uint(f)); }
__device__ __forceinline__ void st_x1(uint32_t* p, uint32_t v) { asm volatile("st.relaxed.gpu.global.u32 [%0], %1;" :: "l"(p), "r"(v) : "memory"); }
__device__ __forceinline__ void st_x4(void* p, uint32_t a, uint32_t b, uint32_t c, uint32_t d) {
    asm volatile("st.relaxed.gpu.global.v4.u32 [%0], {%1, %2, %3, %4};" :: "l"(p), "r"(a), "r"(b), "r"(c), "r"(d) : "memory");
}
__device__ __forceinline__ void st2_x1(uint32_t* p, uint32_t v) { st_x1(p, v); st_x1(p + 1024, v); }
__device__ __forceinline__ void st2_x4(uint32_t* p, uint32_t a, uint32_t b, uint32_t c, uint32_t d) { st_x4(p, a, b, c, d); st_x4(p + 1024, a, b, c, d); }
__device__ __forceinline__ int near_off(int b, uint32_t cls) { return b * 4096 + (((__popc(b & 0x2C) ^ cls) & 1) << 10); }
__device__ __forceinline__ void ld_x(uint32_t& v, const void* p) { asm volatile("ld.relaxed.gpu.global.u32 %0, [%1];" : "=r"(v) : "l"(p) : "memory"); }
__device__ __forceinline__ void ld_x(uint4& v, const void* p) {
    asm volatile("ld.relaxed.gpu.global.v4.u32 {%0, %1, %2, %3}, [%4];" : "=r"(v.x), "=r"(v.y), "=r"(v.z), "=r"(v.w) : "l"(p) : "memory");
}
__device__ __forceinline__ void ld_x(uint2& v, const void* p) { asm volatile("ld.relaxed.gpu.global.v2.u32 {%0, %1}, [%2];" : "=r"(v.x), "=r"(v.y) : "l"(p) : "memory"); }
__device__ __forceinline__ uint32_t minw(uint32_t v) { return v; }
__device__ __forceinline__ uint32_t minw(const uint2& v) { return min(v.x, v.y); }
__device__ __forceinline__ uint32_t minw(const uint4& v) { return min(__vimin3_u32(v.x, v.y, v.z), v.w); }
template <int N> __device__ __forceinline__ uint32_t mint(const uint32_t* m) {
    if constexpr (N == 1) return m[0];
    else if constexpr (N == 2) return min(m[0], m[1]);
    else return __vimin3_u32(mint<(N + 2) / 3>(m), mint<(N + 1) / 3>(m + (N + 2) / 3), mint<N / 3>(m + (N + 2) / 3 + (N + 1) / 3));
}

template <int STRIDE, int S4 = 4 * STRIDE, typename T, int N>
__device__ __forceinline__ void poll_start(T (&v)[N], const void* base) {
#pragma unroll
    for (int i = 0; i < N; i++) ld_x(v[i], (const uint8_t*)base + (i & 3) * STRIDE + (i >> 2) * S4);
}
struct Nop { __device__ void operator()() const {} };
template <int STRIDE, int SLEEP, bool STARTED = false, int S4 = 4 * STRIDE, typename T, int N, typename F = Nop>
__device__ __forceinline__ void poll(T (&v)[N], const void* base, F idle = F()) {
    if (!STARTED) { poll_start<STRIDE, S4>(v, base); idle(); }
#pragma unroll 1
    for (uint32_t it = 0;; it++) {
        uint32_t m[N];
#pragma unroll
        for (int i = 0; i < N; i++) m[i] = minw(v[i]);
        if (__all_sync(0xffffffffu, mint<N>(m) != 0)) break;
        if (SLEEP && it > 0) __nanosleep(SLEEP);
#pragma unroll
        for (int i = 0; i < N; i++) if (!m[i]) ld_x(v[i], (const uint8_t*)base + (i & 3) * STRIDE + (i >> 2) * S4);
        idle();
        if (it > SPIN_LIMIT) __trap();
    }
}

__device__ __forceinline__ float bflo(uint32_t w) { return __uint_as_float(w << 16); }
__device__ __forceinline__ float bfhi(uint32_t w) { return __uint_as_float(w & 0xffff0000u); }
__device__ __forceinline__ uint32_t pack2(float lo, float hi) {
    uint32_t r; asm("cvt.rn.bf16x2.f32 %0, %1, %2;" : "=r"(r) : "f"(hi), "f"(lo)); return r;
}
__device__ __forceinline__ float rbf(float x) { return __uint_as_float(pack2(0.f, x)); }
__device__ __forceinline__ float sumlo(const uint32_t (&v)[8]) { return ((bflo(v[0]) + bflo(v[1])) + (bflo(v[2]) + bflo(v[3]))) + ((bflo(v[4]) + bflo(v[5])) + (bflo(v[6]) + bflo(v[7]))); }
__device__ __forceinline__ float sumhi(const uint32_t (&v)[8]) { return ((bfhi(v[0]) + bfhi(v[1])) + (bfhi(v[2]) + bfhi(v[3]))) + ((bfhi(v[4]) + bfhi(v[5])) + (bfhi(v[6]) + bfhi(v[7]))); }
__device__ __forceinline__ float ex2(float x) { float r; asm("ex2.approx.ftz.f32 %0, %1;" : "=f"(r) : "f"(x)); return r; }
__device__ __forceinline__ float shx(float v, int m) { return __shfl_xor_sync(0xffffffffu, v, m); }
__device__ __forceinline__ uint4 lds128(uint32_t a) { uint4 v; asm volatile("ld.shared.v4.u32 {%0, %1, %2, %3}, [%4];" : "=r"(v.x), "=r"(v.y), "=r"(v.z), "=r"(v.w) : "r"(a) : "memory"); return v; }
__device__ __forceinline__ uint32_t lds32(uint32_t a) { uint32_t v; asm volatile("ld.shared.u32 %0, [%1];" : "=r"(v) : "r"(a) : "memory"); return v; }
__device__ __forceinline__ void sts32(uint32_t a, uint32_t v) { asm volatile("st.shared.u32 [%0], %1;" :: "r"(a), "r"(v) : "memory"); }
__device__ __forceinline__ void sts16(uint32_t a, uint32_t v) { asm volatile("st.shared.u16 [%0], %1;" :: "r"(a), "h"((uint16_t)v) : "memory"); }
__device__ __forceinline__ int frag_off(int k) { return (k >> 5) * 64 + ((k >> 1) & 3) * 16 + ((k >> 4) & 1) * 8 + ((k >> 3) & 1) * 4 + (k & 1) * 2; }

template <bool TRANS>
__device__ __forceinline__ uint4 ldsm(uint32_t a) {
    uint4 r;
    if (TRANS) asm volatile("ldmatrix.sync.aligned.m8n8.x4.trans.shared.b16 {%0, %1, %2, %3}, [%4];" : "=r"(r.x), "=r"(r.y), "=r"(r.z), "=r"(r.w) : "r"(a) : "memory");
    else asm volatile("ldmatrix.sync.aligned.m8n8.x4.shared.b16 {%0, %1, %2, %3}, [%4];" : "=r"(r.x), "=r"(r.y), "=r"(r.z), "=r"(r.w) : "r"(a) : "memory");
    return r;
}
__device__ __forceinline__ void mma(float (&c)[4], uint32_t a0, uint32_t a1, uint32_t a2, uint32_t a3, uint32_t b0, uint32_t b1) {
    asm volatile("mma.sync.aligned.m16n8k16.row.col.f32.bf16.bf16.f32 {%0,%1,%2,%3}, {%4,%5,%6,%7}, {%8,%9}, {%0,%1,%2,%3};"
                 : "+f"(c[0]), "+f"(c[1]), "+f"(c[2]), "+f"(c[3]) : "r"(a0), "r"(a1), "r"(a2), "r"(a3), "r"(b0), "r"(b1));
}
template <bool TRANS, typename F>
__device__ __forceinline__ void load8(uint4 (&a)[8], F addr) {
    __syncwarp();
#pragma unroll
    for (int s = 0; s < 8; s++) a[s] = ldsm<TRANS>(addr(s));
}
__device__ __forceinline__ void mma8(float (&c)[4], const uint4 (&a)[8], const uint4 (&b)[4]) {
    float e[4][4];
#pragma unroll
    for (int s = 0; s < 8; s++) {
        if (s < 4) e[s][0] = e[s][1] = e[s][2] = e[s][3] = 0.f;
        mma(e[s & 3], a[s].x, a[s].y, a[s].z, a[s].w, (s & 1) ? b[s >> 1].z : b[s >> 1].x, (s & 1) ? b[s >> 1].w : b[s >> 1].y);
    }
#pragma unroll
    for (int i = 0; i < 4; i++) c[i] = (e[0][i] + e[1][i]) + (e[2][i] + e[3][i]);
}
__device__ __forceinline__ void ldfrag(uint4 (&b)[4], uint32_t a) {
    asm volatile("ld.shared.v4.u32 {%0,%1,%2,%3}, [%16];\nld.shared.v4.u32 {%4,%5,%6,%7}, [%16+64];\n"
                 "ld.shared.v4.u32 {%8,%9,%10,%11}, [%16+128];\nld.shared.v4.u32 {%12,%13,%14,%15}, [%16+192];\n"
                 : "=r"(b[0].x), "=r"(b[0].y), "=r"(b[0].z), "=r"(b[0].w), "=r"(b[1].x), "=r"(b[1].y), "=r"(b[1].z), "=r"(b[1].w),
                   "=r"(b[2].x), "=r"(b[2].y), "=r"(b[2].z), "=r"(b[2].w), "=r"(b[3].x), "=r"(b[3].y), "=r"(b[3].z), "=r"(b[3].w) : "r"(a) : "memory");
}
__device__ __forceinline__ void quad_pair(float x, float y, int t, float& lo, float& hi) {
    const float k = ((t & 1) ? y : x) + shx((t & 1) ? x : y, 1);
    lo = k + shx(k, 2); hi = shx(k, 4) + shx(k, 6);
}
__device__ __forceinline__ void pin(uint32_t& x) { asm volatile("" : "+r"(x)); }
template <typename T> __device__ __forceinline__ void pin(T*& x) { asm volatile("" : "+l"(x)); }
__device__ __forceinline__ float4 ldsf4(uint32_t a) { const uint4 v = lds128(a); return make_float4(__uint_as_float(v.x), __uint_as_float(v.y), __uint_as_float(v.z), __uint_as_float(v.w)); }
__device__ __forceinline__ float sum4(const float4& f) { return (f.x + f.y) + (f.z + f.w); }
__device__ __forceinline__ void stsf(uint32_t a, float v) { sts32(a, __float_as_uint(v)); }

__device__ __forceinline__ void wg_fence() { asm volatile("wgmma.fence.sync.aligned;" ::: "memory"); }
__device__ __forceinline__ void wg_commit() { asm volatile("wgmma.commit_group.sync.aligned;" ::: "memory"); }
__device__ __forceinline__ void wg_wait1() { asm volatile("wgmma.wait_group.sync.aligned 1;" ::: "memory"); }
__device__ __forceinline__ void wg_wait0() { asm volatile("wgmma.wait_group.sync.aligned 0;" ::: "memory"); }
#define R8(o) "+f"(d[o]), "+f"(d[o + 1]), "+f"(d[o + 2]), "+f"(d[o + 3]), "+f"(d[o + 4]), "+f"(d[o + 5]), "+f"(d[o + 6]), "+f"(d[o + 7])
__device__ __forceinline__ void wgmma_rs_n32(float (&d)[16], const uint4& a, uint64_t db, int acc) {
    asm volatile("{\n.reg .pred p;\nsetp.ne.b32 p, %21, 0;\n"
        "wgmma.mma_async.sync.aligned.m64n32k16.f32.bf16.bf16 "
        "{%0,%1,%2,%3,%4,%5,%6,%7,%8,%9,%10,%11,%12,%13,%14,%15}, {%16,%17,%18,%19}, %20, p, 1, 1, 0;\n}"
        : R8(0), R8(8) : "r"(a.x), "r"(a.y), "r"(a.z), "r"(a.w), "l"(db), "r"(acc));
}
#define PV_LO "{%0,%1,%2,%3,%4,%5,%6,%7,%8,%9,%10,%11,%12,%13,%14,%15,%16,%17,%18,%19,%20,%21,%22,%23,%24,%25,%26,%27,%28,%29,%30,%31,%32,%33,%34,%35,%36,%37,%38,%39,%40,%41,%42,%43,%44,%45,%46,%47,%48,%49,%50,%51,%52,%53,%54,%55,%56,%57,%58,%59,%60,%61,%62,%63}, "
#define PV_HI "{%64,%65,%66,%67,%68,%69,%70,%71,%72,%73,%74,%75,%76,%77,%78,%79,%80,%81,%82,%83,%84,%85,%86,%87,%88,%89,%90,%91,%92,%93,%94,%95,%96,%97,%98,%99,%100,%101,%102,%103,%104,%105,%106,%107,%108,%109,%110,%111,%112,%113,%114,%115,%116,%117,%118,%119,%120,%121,%122,%123,%124,%125,%126,%127}, "
__device__ __forceinline__ void wgmma_pv(float (&d)[128], const uint4& a, uint32_t blo, int acc) {
    asm volatile("{\n.reg .pred p;\n.reg .b32 u0, u1, u2, u3, t;\n.reg .b64 d0, d1, d2, d3;\nsetp.ne.b32 p, %133, 0;\n"
        "mov.b64 d0, {%132, 0x40000100};\nadd.u32 t, %132, 512;\nmov.b64 d1, {t, 0x40000100};\n"
        "add.u32 t, %132, 128;\nmov.b64 d2, {t, 0x40000100};\nadd.u32 t, %132, 640;\nmov.b64 d3, {t, 0x40000100};\n"
        "wgmma.fence.sync.aligned;\n"
        "wgmma.mma_async.sync.aligned.m64n128k16.f32.bf16.bf16 " PV_LO "{%128, u0, %129, u1}, d0, p, 1, 1, 1;\n"
        "wgmma.mma_async.sync.aligned.m64n128k16.f32.bf16.bf16 " PV_LO "{%130, u2, %131, u3}, d1, 1, 1, 1, 1;\n"
        "wgmma.commit_group.sync.aligned;\n"
        "wgmma.mma_async.sync.aligned.m64n128k16.f32.bf16.bf16 " PV_HI "{%128, u0, %129, u1}, d2, p, 1, 1, 1;\n"
        "wgmma.mma_async.sync.aligned.m64n128k16.f32.bf16.bf16 " PV_HI "{%130, u2, %131, u3}, d3, 1, 1, 1, 1;\n"
        "wgmma.commit_group.sync.aligned;\n}"
        : R8(0), R8(8), R8(16), R8(24), R8(32), R8(40), R8(48), R8(56), R8(64), R8(72), R8(80), R8(88), R8(96), R8(104), R8(112), R8(120)
        : "r"(a.x), "r"(a.y), "r"(a.z), "r"(a.w), "r"(blo), "r"(acc) : "memory");
}

template <int NW>
__device__ __forceinline__ void ln_stats(float s, float q, float sh, float* scr, int w, int lane, int bar, float& mean_b, float& sd_b) {
#pragma unroll
    for (int o = 16; o; o >>= 1) { s += shx(s, o); q += shx(q, o); }
    constexpr float n = 512.f / NW;
    if (lane == 0) { scr[w] = sh + s * (1.f / n); scr[NW + w] = q - s * s * (1.f / n); }
    bar_sync(bar, NW * 32);
    float mu = 0.f, m2 = 0.f;
#pragma unroll
    for (int i = 0; i < NW; i++) { mu += scr[i]; m2 += scr[NW + i]; }
    mu *= 1.f / NW;
#pragma unroll
    for (int i = 0; i < NW; i++) { const float d = scr[i] - mu; m2 = fmaf(n * d, d, m2); }
    mean_b = rbf(mu);
    sd_b = rbf(sqrtf(rbf(rbf(fmaxf(m2, 0.f) * (1.f / 512.f)) + 1e-5f)));
}
__device__ __forceinline__ float ln_mod(float x, float mean_b, float sd_b, float c, float s) {
    return rbf(rbf(__fdividef(rbf(x - mean_b), sd_b)) * rbf(1.f + c)) + s;
}

__global__ void __cluster_dims__(2, 1, 1) __launch_bounds__(NTHREADS, 1)
fused_kernel(const __grid_constant__ First F, __nv_bfloat16* __restrict__ out, uint32_t* __restrict__ gs, const __grid_constant__ Maps M) {
    extern __shared__ __align__(1024) uint8_t sm[];
    const uint32_t sb0 = s2u(sm);
    const int tid = threadIdx.x, lane = tid & 31;
    const int j = blockIdx.x, rk = j & 1;
    const int g = lane >> 2, t = lane & 3;
    const int r8 = lane & 7, lb3 = (lane >> 3) & 1, lb4 = lane >> 4;
    const uint64_t pol = 0x12F0000000000000ull;
    uint32_t in1 = 0, in2 = 0;
    {
        auto cpa = [&](uint32_t d, const uint8_t* s) {
            asm volatile("cp.async.cg.shared.global.L2::cache_hint.L2::128B [%0], [%1], 16, %2;" :: "r"(d), "l"(s), "l"(pol) : "memory");
        };
        const uint32_t ut = threadIdx.x, uj = blockIdx.x;
        const uint8_t* w = F.w[ut >= 128];
        if (ut < 128) {
            const uint32_t dq = (sb0 + ut * 16) ^ ((ut * 2) & 0x70);
            const uint8_t* sq = w + (uint32_t)(((uj & 1) * 256 + (ut >> 3)) * 8192 + (uj >> 1) * 128 + (ut & 7) * 16);
#pragma unroll
            for (int i = 0; i < 4 * NCP; i++) cpa(dq + 4 * 32768 + i * 2048, sq + i * 131072);
        } else if (ut < 384) {
            const uint32_t dm = (sb0 + ut * 16) ^ ((ut * 2) & 0x10);
            const uint8_t* sa = w + (uint32_t)(((uj >> 5) * 128 + (ut >> 1) - 64) * 6144 + (uj & 31) * 32 + (ut & 1) * 16);
            asm volatile("cp.async.cg.shared.global.L2::cache_hint" MODA_PF " [%0], [%1], 16, %2;" :: "r"(dm + SM_XA - 2048), "l"(sa), "l"(pol) : "memory");
            asm volatile("cp.async.cg.shared.global.L2::cache_hint" MODA_PF " [%0], [%1], 16, %2;" :: "r"(dm + SM_XA + 2048), "l"(sa + 1024), "l"(pol) : "memory");
        }
        else if (ut == 480 && uj < 16 * XC_LATE) asm volatile("prefetch.global.L2 [%0];" :: "l"(F.v[(uj >> 3) & 1] + (uj & 7) * 64));
    }
    const int warp = __shfl_sync(0xffffffffu, tid >> 5, 0);
    const uint32_t sb = sb0;
    const __nv_bfloat16* const xin = F.v[0];
    uint32_t* const pl = gs + (warp < 2 ? (B_PR + (j >> 5)) * 4096 + (j & 31) * 32 : G_E1 + j * 8192) + (warp & 1) * 1024 + lane;
    auto small_loads = [&]() {
        if (warp < 4) { in1 = *(const uint32_t*)(xin + 2 * tid); in2 = *(const uint32_t*)(xin + 256 + 2 * tid); }
        else if (warp < 12) in1 = *(const uint32_t*)(F.v[1] + 2 * (tid - 128));
    };
    if (!XC_LATE) small_loads();
    if (warp < 4) st_x1(pl, 1u);
    auto BAR = [&](int i) -> uint32_t { return sb + SM_BAR + i * 8; };
    const uint32_t a16 = (r8 + 8 * lb4) * 32 + ((lb3 ^ (r8 >> 2)) * 16);
    const uint32_t a128 = (r8 + 8 * lb4) * 128 + ((((warp & 3) * 2 + lb3) ^ r8) * 16);
    auto ldcls = [&]() -> uint32_t { return *(const volatile uint32_t*)(sm + SM_CLS); };
    auto clear_head = [&]() {
        st2_x1(gs + (B_HA + ((j >> 4) & 1) * 2 + lb4) * 4096 + (j >> 5) * 256 + (j & 15) * 16 + (lane & 15), 0u);
        st2_x4(gs + (B_QA + rk * 8 + ((j >> 1) & 1) * 4 + (j >> 5)) * 4096 + g * 128 + ((j >> 2) & 7) * 16 + t * 4, 0u, 0u, 0u, 0u);
        if (lane < 8) st2_x1(gs + B_RD * 4096 + j * 8 + lane, 0u);
    };
    auto tma = [&](uint32_t dst, int mp, uint32_t bar, int c0, int c1, int c2, int c3) {
        asm volatile("{\n.reg .pred p;\nelect.sync _|p, 0xffffffff;\n"
                     "@p cp.async.bulk.tensor.4d.shared::cluster.global.mbarrier::complete_tx::bytes.L2::cache_hint [%0], [%1, {%3, %4, %5, %6}], [%2], %7;\n}"
                     :: "r"(dst), "l"(&M.m[mp]), "r"(bar), "r"(c0), "r"(c1), "r"(c2), "r"(c3), "l"(pol) : "memory");
    };
    if (warp <= 12 || warp == 15) {
        const int grp = warp == 12 ? 0 : warp == 15 ? 13 : warp + 1;
        const uint32_t cnt = grp < 10 ? 1 : grp < 13 ? 4 : 8;
        if (lane == 0) {
#pragma unroll
            for (int i = 0; i < 8; i++) mbar_init(BAR(grp * 8 + i), (i < 2 && grp == 0) ? (i ? 128 : 256) : cnt);
        }
        __syncwarp();
        if (grp < 10 && lane < 8 && (grp || lane > NCP)) mbar_expect(BAR(grp * 8 + lane), grp >= 8 ? 4096 : grp * 8 + lane < IT_X ? 8192 : 16384);
        asm volatile("fence.mbarrier_init.release.cluster;" ::: "memory");
        __syncwarp();
        if (warp == 12) {
#pragma unroll
            for (int i = NCP + 1; i < W0; i++) tma(sb + (15 + i) * 8192, MP_WQ, BAR(i), 0, rk * 256 + (i - 1) * 64, j >> 1, 0);
        }
    } else if (warp == 13) {
        if (lane < NMAPS) asm volatile("prefetch.tensormap [%0];" :: "l"(&M.m[lane]) : "memory");
    } else if (warp == 14 && PREZERO) {
        clear_head();
    }
    __syncthreads();
    if (XC_LATE) small_loads();
    if (warp < 12) asm volatile("cp.async.mbarrier.arrive.noinc.shared::cta.b64 [%0];" :: "r"(BAR(warp < 4)) : "memory");
    asm volatile("barrier.cluster.arrive.relaxed.aligned;" ::: "memory");

    if (warp >= 12) {
    asm volatile("setmaxnreg.dec.sync.aligned.u32 64;");
    if (warp == 12) {
        static_assert(W0 > NCP && W0 <= 5 && NCP >= 1 && NCP <= 4, "W0");
        const uint2* sched = M.sched[j < NFF ? 0 : j < J_RED ? 1 : 2];
        uint2 en = sched[W0];
        const uint32_t t0 = gtime();
#pragma unroll 1
        for (int i = W0; en.x; i++) {
            const uint32_t e = en.x, tn = t0 + en.y;
            en = sched[i + 1];
            const int id = e & 63, w0 = (e >> 11) & 127, w1 = (e >> 18) & 127;
            int mp, c0 = 0, c1 = 0, c2 = 0, c3 = 0;
            if (id < IT_CKV) { const int k = id - IT_WQ; mp = MP_WQ + (k >> 2); c1 = rk * 256 + (k & 3) * 64; c2 = j >> 1; }
            else if (id < IT_WUV) { const int k = id - IT_CKV; mp = MP_CKV; c2 = rk * 4; c3 = (k * 64 + (j >> 1)) * 2; }
            else if (id < IT_WO) { mp = MP_WUV; c1 = (j & 3) * 32 + (id - IT_WUV) * 128; c2 = (j >> 2) * 2; }
            else if (id < IT_X) { mp = MP_WO; c0 = (j & 7) * 64; c1 = (j >> 3) * 256 + (id - IT_WO) * 64; }
            else if (id < IT_DOWN) {
                if (j >= J_END) break;
                const int k = id - IT_X;
                mp = j < NFF ? MP_GATE + (k >> 1) : MP_MODB; c0 = (j >> 1) * 64 + (j < NFF ? 0 : 1024 - NFF * 32); c1 = rk * 256 + (k & 1) * 128;
            } else { mp = MP_DOWN; c1 = j * 32; c2 = (id - IT_DOWN) * 4; }
            if (w0) mbar_wait(BAR(w0 - 1), 0);
            const int w2 = e >> 25;
            if (w2) {
                mbar_wait(BAR(w2 - 1), 0);
                while (!__any_sync(0xffffffffu, mbar_test(BAR(w1 - 1), 0) | ((int)(gtime() - tn) > 0))) {}
            } else if (w1) mbar_wait(BAR(w1 - 1), 0);
            tma(sb + ((e >> 6) & 31) * 8192, mp, BAR(id), c0, c1, c2, c3);
        }
    } else if (warp == 13) {
#pragma unroll
        for (int i = 0; i < 2; i++) st_x4(gs + (B_ML + rk * 16 + i * 8 + g) * 4096 + (t >> 1) * 1024 + (j >> 1) * 8 + (t & 1) * 4, 0u, 0u, 0u, 0u);
        if (lane < 16) st2_x4(gs + (B_E2 + (j >> 4)) * 4096 + (j & 15) * 64 + lane * 4, 0u, 0u, 0u, 0u);
        st2_x1(gs + (B_E3 + (j >> 5)) * 4096 + (j & 31) * 32 + lane, 0u);
        if (lane < 8) st2_x1(gs + B_MB * 4096 + j * 8 + lane, 0u);
        if (j < NFF) {
#pragma unroll
            for (int i = 0; i < 2; i++) st2_x4(gs + (B_E5 + i * 8 + g) * 4096 + j * 16 + t * 4, 0u, 0u, 0u, 0u);
        }
        bar_sync(9, 64);
        const uint32_t cs = ldcls();
#pragma unroll 1
        for (int i = 0; i < 32; i++) {
            st_x4(gs + G_E1 + j * 8192 + (i >> 3) * 2048 + ((((cs >> 1) ^ (i >> 3)) & 1) << 10) + (i & 7) * 128 + lane * 4, 0u, 0u, 0u, 0u);
            __nanosleep(JAN_SLEEP);
        }
        fence_gpu();
        if (lane < 8) st2_x1(gs + B_RD * 4096 + j * 8 + lane, 1u + (cs >> 1));
        if (lane == 0) TRACE(41);
        uint32_t rd[4];
        mbar_wait(BAR(IT_CKV + RD_ITEM), 0);
        poll<1024, RD_SLEEP>(rd, gs + near_off(B_RD, cs) + lane * 8);
#pragma unroll
        for (int i = 0; i < 4; i++) {
            const uint32_t m = __ballot_sync(0xffffffffu, rd[i] == 2u);
            if (lane == 0) sts32(sb + SM_CLS + 16 + i * 4, m);
        }
        __syncwarp();
        if (lane < 8) mbar_arrive(BAR(JD));
        if (lane == 0) TRACE(42);
    } else if (warp == 14) {
        uint2 ml[2];
        mbar_waitb(BAR(JD), 0);
        const uint32_t cls = ldcls();
        mbar_waitb(BAR(PF0 + 2 * NUNITS - 1), 0);
        __nanosleep(ML_DELAY);
        {
            const uint32_t* pl2 = gs + near_off(B_ML + (j >> 2), cls) + lane * 8;
            poll_start<1024>(ml, pl2);
            bool first = true;
#pragma unroll 1
            for (uint32_t it = 0;; it++) {
                const uint32_t m0 = minw(ml[0]), m1 = minw(ml[1]);
                const int n = __popc(__ballot_sync(0xffffffffu, m0 != 0)) + __popc(__ballot_sync(0xffffffffu, m1 != 0));
                if (first && n >= E1_EARLY) { bar_arrive(3, 416); first = false; }
                if (n == 64) break;
                if (!m0) ld_x(ml[0], pl2);
                if (!m1) ld_x(ml[1], pl2 + 256);
                if (it > SPIN_LIMIT) __trap();
            }
        }
        if (lane == 0) TRACE_Q(37);
        const float m0 = __uint_as_float(ml[0].x), m1 = __uint_as_float(ml[1].x);
        const int mi = __float_as_int(fmaxf(m0, m1));
        const int mr = __reduce_max_sync(0xffffffffu, mi ^ ((mi >> 31) & 0x7fffffff));
        const float mm = __int_as_float(mr ^ ((mr >> 31) & 0x7fffffff));
        const uint32_t w0 = pack2(ex2(m0 - mm), 0.f), w1 = pack2(ex2(m1 - mm), 0.f);
        const uint32_t wa = sb + SM_W + lb4 * 64 + t * 16 + (g & 3) * 4;
        sts32(wa, w0 * 0x10001u); sts32(wa + 128, w1 * 0x10001u);
        __syncwarp();
        if (lane < 8) mbar_arrive(BAR(WR));
        float L = bflo(w0) * __uint_as_float(ml[0].y) + bflo(w1) * __uint_as_float(ml[1].y);
#pragma unroll
        for (int o = 16; o; o >>= 1) L += shx(L, o);
        if (lane == 0) *(float*)(sm + SM_FQ) = __frcp_rn(L);
        if (lane == 0) TRACE(10);
        bar_sync(4, 288);
        clear_head();
        if (j < NFF) {
            uint32_t ya = sb + SM_Y + lane * 16, sa = peer_addr(sb + SM_RED + 2048 + rk * 8, lane & 1), tb = peer_addr(BAR(QB), lane & 1);
            pin(ya); pin(sa); pin(tb);
            bar_sync(7, 288);
            const float4 y0 = ldsf4(ya), y1 = ldsf4(ya + 512);
            float s = sum4(y0) + sum4(y1);
            float q = (fmaf(y0.x, y0.x, y0.y * y0.y) + fmaf(y0.z, y0.z, y0.w * y0.w)) + (fmaf(y1.x, y1.x, y1.y * y1.y) + fmaf(y1.z, y1.z, y1.w * y1.w));
#pragma unroll
            for (int o = 16; o; o >>= 1) { s += shx(s, o); q += shx(q, o); }
            if (lane < 2) st_async2(sa, s, q, tb);
        }
    } else if (warp == 15) {
        mbar_waitb(BAR(IT_X - 1), 0);
        if (j < J_END) mbar_waitb(BAR(j < NFF ? NITEMS - 1 : MBB), 0);
    }
    } else if (warp < 4) {
        float* scr = (float*)(sm + SM_SCR);
        uint32_t cls;
        {
            uint2 ha[8];
            {
                uint32_t best = 0xffffffffu;
#pragma unroll
                for (int i = 0; i < NPROBE; i++) {
                    uint32_t t0, t1, o;
                    asm volatile("mov.u32 %0, %%clock;" : "=r"(t0));
                    asm volatile("atom.relaxed.gpu.global.exch.b32 %0, [%1], %2;" : "=r"(o) : "l"(pl), "r"(2u + i) : "memory");
                    asm volatile("{\n.reg .pred p;\nsetp.ne.u32 p, %1, 0x1234567;\nmov.u32 %0, 0;\n@p mov.u32 %0, %%clock;\n}" : "=r"(t1) : "r"(o));
                    best = min(best, t1 - t0);
                }
                if (lane == 0) scr[16 + warp] = __uint_as_float(best);
            }
            const float sh = __shfl_sync(0xffffffffu, bflo(in1), 0);
            const float v0 = bflo(in1) - sh, v1 = bfhi(in1) - sh, v2 = bflo(in2) - sh, v3 = bfhi(in2) - sh;
            float mb, sd;
            ln_stats<4>((v0 + v1) + (v2 + v3), (v0 * v0 + v1 * v1) + (v2 * v2 + v3 * v3), sh, scr, warp, lane, 2, mb, sd);
            if (!rk) in2 = in1;
            const uint4 lt = *(const uint4*)(scr + 16);
            cls = NUMA ? ((lt.y < lt.x) ^ (__popc((B_PR + (j >> 5)) & 0x2C) & 1)) | (lt.w < lt.z) << 1 : 0;
            if (warp == 0) { if (lane == 0) sts32(sb + SM_CLS, cls); bar_arrive(9, 64); }
            if (tid == 0) TRACE(38);
            asm volatile("barrier.cluster.wait.aligned;" ::: "memory");
            mbar_wait(BAR(IT_MODA), 0);
            __nanosleep(HA_DELAY);
            poll<1024, H_SLEEP, false, 16384>(ha, gs + near_off(B_HA + rk * 2, cls) + 2 * tid);
            auto rsum = [](uint32_t a, uint32_t b, uint32_t c, uint32_t d) { return rbf((__uint_as_float(a) + __uint_as_float(b)) + (__uint_as_float(c) + __uint_as_float(d))); };
            sts32(sb + SM_FV + frag_off(2 * tid),
                  pack2(ln_mod(bflo(in2), mb, sd, rsum(ha[4].x, ha[5].x, ha[6].x, ha[7].x), rsum(ha[0].x, ha[1].x, ha[2].x, ha[3].x)),
                        ln_mod(bfhi(in2), mb, sd, rsum(ha[4].y, ha[5].y, ha[6].y, ha[7].y), rsum(ha[0].y, ha[1].y, ha[2].y, ha[3].y))));
            bar_arrive(5, 384);
            mbar_wait(BAR(QB), 0);
            if (tid < 64) {
                const float* qx = (const float*)(sm + SM_QX) + tid;
                sts16(sb + SM_FQ + frag_off(tid), pack2((qx[0] + qx[64]) + (qx[128] + qx[192]), 0.f));
            }
            bar_arrive(6, 384);
        }
        asm volatile("setmaxnreg.inc.sync.aligned.u32 192;");
        float acc[128];
        float M = 0.f;
        uint32_t pa = sb + SM_XA + warp * 512 + lane * 16, ma = sb + SM_MX + (warp * 8 + g) * 4, pf = BAR(PF0);
        uint32_t blo = __reduce_or_sync(0xffffffffu, (((sb + SM_U) & 0x3FFFFu) >> 4) | 0x400000u);
        uint32_t* e1[4];
#pragma unroll
        for (int i = 0; i < 4; i++) e1[i] = gs + G_E1 + (warp * 8 + g) * 4 * 8192 + (rk * 2 + (j >> 6)) * 2048 + ((j >> 1) & 31) * 32 + t * 4;
        uint32_t ck[10] = {0, 0, 0, 0, 0, 0, 0, 0, 0, 0};
#pragma unroll 1
        for (int h = 0; h < 2 * NUNITS; h++) {
            CLK(ck[0], h == 2 * TU); CLK(ck[5], h == 2 * TU + 1);
            mbar_wait(pf, 0);
            CLK(ck[1], h == 2 * TU); CLK(ck[6], h == 2 * TU + 1);
            const float m = __uint_as_float(lds32(ma));
            const uint4 pn = lds128(pa);
            wg_wait0();
#pragma unroll
            for (int i = 0; i < 128; i++) asm volatile("" : "+f"(acc[i]) :: "memory");
            CLK(ck[2], h == 2 * TU); CLK(ck[7], h == 2 * TU + 1);
            if (h == 0) M = m;
            uint32_t b2 = 0x3f803f80u;
            if (__builtin_expect(__any_sync(0xffffffffu, m != M), 0)) {
                const float Mn = fmaxf(M, m), alpha = ex2(M - Mn), beta = ex2(m - Mn);
                M = Mn;
                b2 = pack2(beta, beta);
#pragma unroll
                for (int jj = 0; jj < 32; jj++) { acc[4 * jj] *= alpha; acc[4 * jj + 1] *= alpha; }
            }
            auto mul2 = [](uint32_t x, uint32_t y) { uint32_t r; asm("mul.rn.bf16x2 %0, %1, %2;" : "=r"(r) : "r"(x), "r"(y)); return r; };
            const uint4 p = make_uint4(mul2(pn.x, b2), mul2(pn.y, b2), mul2(pn.z, b2), mul2(pn.w, b2));
            if (tid == 0 && (h & 1)) TRACE_Q(48 + (h >> 1));
            CLK(ck[3], h == 2 * TU); CLK(ck[8], h == 2 * TU + 1);
            wgmma_pv(acc, p, blo, h);
            CLK(ck[4], h == 2 * TU); CLK(ck[9], h == 2 * TU + 1);
            if (lane == 0 && h > 0 && !(h & 1)) mbar_arrive(BAR(EB_UNIT0 + (h >> 1) - 1));
            blo += h == 11 ? -11 * 1024 : 1024;
            pa += (h == 5 || h == 11) ? -5 * 2048 : 2048;
            ma += 128; pf += 8;
            if (h == 2 * NUNITS - 3) {
                mbar_wait(BAR(JD), 0);
                const uint32_t hm = (*(const uint32_t*)(sm + SM_CLS + 16 + warp * 4) >> (g * 4)) ^ ((j >> 6) ? 15u : 0u);
#pragma unroll
                for (int i = 0; i < 4; i++) e1[i] += ((hm >> i) & 1) << 10;
            }
        }
#pragma unroll
        for (int vv = 0; vv < 2; vv++) {
            if (vv && M == 1.f) __trap();
            if (vv) wg_wait0(); else wg_wait1();
#pragma unroll
            for (int i = 0; i < 64; i++) asm volatile("" : "+f"(acc[vv * 64 + i]) :: "memory");
            if (tid == 0 && !vv) TRACE_Q(63);
#pragma unroll
            for (int i = 0; i < 4; i++) {
                const float* a = &acc[vv * 64 + i * 16];
                st_x4(e1[i] + i * 8192 + vv * 16, enc(pack2(a[0], a[1])), enc(pack2(a[4], a[5])), enc(pack2(a[8], a[9])), enc(pack2(a[12], a[13])));
            }
        }
        bar_arrive(3, 416);
        if (tid == 0) TRACE_Q(17);
        if (j < NFF) {
            uint4 a[16];
            const uint32_t ad = sb + SM_U + B_DN * 32768 + warp * 8192 + (r8 + 8 * lb4) * 128 + (lb3 ^ r8) * 16;
            uint32_t rl = sb + SM_RED + lane * 16;
            uint32_t* p5 = gs + (B_E5 + warp * 4 + (t >> 1)) * 4096 + j * 16 + (t & 1) * 8 + g;
            pin(rl); pin(p5);
            mbar_wait(BAR(IT_DOWN + (warp >> 1)), 0);
#pragma unroll
            for (int s = 0; s < 16; s++) a[s] = ldsm<true>((ad ^ ((s & 3) * 32)) + (s >> 2) * 2048);
            TK(18);
            mbar_wait(BAR(QB), 1);
            TK(19);
            if (tid == 0) TRACE(25);
            const float4 st = ldsf4(sb + SM_RED + 2048);
            const float4 f0 = ldsf4(rl), f2 = ldsf4(rl + 1024), f1 = ldsf4(rl + 512), f3 = ldsf4(rl + 1536);
            const float mu = (st.x + st.z) * (1.f / 512.f);
            float rstd;
            asm("rsqrt.approx.ftz.f32 %0, %1;" : "=f"(rstd) : "f"(fmaxf(fmaf(-mu, mu, (st.y + st.w) * (1.f / 512.f)), 0.f) + 1e-5f));
            const float gg = fmaf(rstd, fmaf(-mu, f0.z + f2.z, (f0.x + f0.y) + (f2.x + f2.y)), f0.w + f2.w);
            const float uu = fmaf(rstd, fmaf(-mu, f1.z + f3.z, (f1.x + f1.y) + (f3.x + f3.y)), f1.w + f3.w);
            TKD(20, gg);
            const float hh = __fdividef(gg * uu, 1.f + ex2(-gg * fmaf(gg * gg, 0.10294324f, 2.3022082f)));
            uint32_t hb[4];
#pragma unroll
            for (int i = 0; i < 4; i++) hb[i] = pack2(__shfl_sync(0xffffffffu, hh, 2 * t + 8 * i), __shfl_sync(0xffffffffu, hh, 2 * t + 8 * i + 1));
            TKD(21, __uint_as_float(hb[3]));
#pragma unroll
            for (int i = 0; i < 2; i++) {
                uint32_t res = 0;
#pragma unroll
                for (int k = 0; k < 4; k++) {
                    float c[4] = {0.f, 0.f, 0.f, 0.f};
                    const uint4 &x = a[i * 8 + k], &y = a[i * 8 + k + 4];
                    mma(c, x.x, x.y, x.z, x.w, hb[0], hb[1]);
                    mma(c, y.x, y.y, y.z, y.w, hb[2], hb[3]);
                    if (t == k) res = pack2(c[0], c[2]);
                }
                st2_x1(p5 + i * 8192, enc(res));
            }
            TK(22);
            if (tid == 0) { TRACE(27); TRACE_GT(47); }
        } else if (j < J_END) {
            uint4 a[8], b[4];
            float c[4], e[4];
            const bool own = (warp >> 1) == rk;
            const uint32_t xa = sb + SM_FV + (warp & 1) * 64 + g * 8;
            if (lane == 0) mbar_expect(BAR(MBB), own ? 64 : 0);
#pragma unroll
            for (int i = 0; i < 2; i++) {
                ldfrag(b, sb + SM_FS + rk * 512 + i * 256 + t * 16);
                mbar_wait(BAR(IT_X + i), 0);
                const uint32_t ab = sb + SM_U + B_X * 32768 + i * 16384 + a128;
                load8<true>(a, [&](int s) { return ab + s * 2048; });
                mma8(i ? e : c, a, b);
            }
            c[0] += e[0]; c[2] += e[2];
            if (!own) {
                if (t == 0) st_async2(peer_addr(xa, rk ^ 1), c[0], c[2], peer_addr(BAR(MBB), rk ^ 1));
            } else {
                mbar_wait(BAR(MBB), 0);
                const float2 pp = *(const float2*)(sm + (xa - sb));
                const float mine = t ? c[2] + pp.y : c[0] + pp.x, other = shx(mine, 4);
                const uint32_t w = (warp & 1) * 8 + t * 4 + (g >> 1), val = enc(pack2(mine, other));
                if (t < 2 && !(g & 1)) {
                    if (j < J_RED) st2_x1(gs + B_MB * 4096 + (j - NFF) * 16 + w, val);
                    else sts32(sb + SM_FV + 256 + w * 4, val);
                }
                if (j >= J_RED) bar_arrive(7, 320);
                if (lane == 0) TRACE(11);
            }
        }
    } else {
        const int u8 = tid - 128, w8 = warp - 4;
        const int v = w8 >> 2, wq4 = w8 & 3;
        {
            const float c0 = bflo(in1), c1 = bfhi(in1);
            sts32(sb + SM_FS + frag_off(2 * u8), pack2(__fdividef(c0, 1.f + __expf(-c0)), __fdividef(c1, 1.f + __expf(-c1))));
        }
        bar_sync(1, 256);
        asm volatile("barrier.cluster.wait.aligned;" ::: "memory");
        uint4 a[8], b[4]; float c[4];
        if (w8 < 2) {
            ldfrag(b, sb + SM_FS + (j >> 5) * 256 + t * 16);
            mbar_wait(BAR(IT_MODA), 0);
            if (u8 == 0) TRACE(12);
            const uint32_t ab = sb + SM_XA + w8 * 4096 + a16;
            load8<true>(a, [&](int s) { return ab + s * 512; });
            mma8(c, a, b);
            if (t < 2) st2_x1(gs + (B_HA + ((j >> 4) & 1) * 2 + w8) * 4096 + (j >> 5) * 256 + (j & 15) * 16 + t * 8 + g, encf(t ? c[2] : c[0]));
        }
        {
            mbar_wait(BAR(IT_WQ + 2 * v <= NCP ? 1 : IT_WQ + 2 * v), 0); mbar_wait(BAR(IT_WQ + 2 * v + 1 <= NCP ? 1 : IT_WQ + 2 * v + 1), 0);
            const uint32_t ab = sb + SM_U + 4 * 32768 + v * 16384 + a128;
            load8<true>(a, [&](int s) { return ab + s * 2048; });
            if (lane == 0) mbar_arrive(BAR(EB_WQ));
            bar_sync(5, 384);
            if (u8 == 0) TRACE(13);
            ldfrag(b, sb + SM_FV + v * 256 + t * 16);
            mma8(c, a, b);
            if (t < 2) {
                const float qv = t ? c[2] : c[0];
                const uint32_t qa_ = sb + SM_QX + ((rk * 2 + v) * 64 + wq4 * 16 + t * 8 + g) * 4;
                asm volatile("st.async.weak.shared::cluster.mbarrier::complete_tx::bytes.f32 [%0], %1, [%2];"
                             :: "r"(peer_addr(qa_, rk ^ 1)), "f"(qv), "r"(peer_addr(BAR(QB), rk ^ 1)) : "memory");
                sts32(qa_, __float_as_uint(qv));
            }
            __syncwarp();
            if (lane == 0) mbar_expect(BAR(QB), 64);
        }
        {
            mbar_wait(BAR(IT_WUK + v), 0); mbar_wait(BAR(IT_WUK + v + 2), 0);
            const uint32_t ab = sb + SM_U + 5 * 32768 + (w8 * 16 + r8 + 8 * lb3) * 128;
            const uint32_t x16 = (lb4 ^ r8) * 16;
            load8<false>(a, [&](int s) { return ab + (s & 1) * 16384 + (x16 ^ ((s >> 1) * 32)); });
            bar_sync(6, 384);
            if (u8 == 0) TRACE(14);
            b[0] = lds128(sb + SM_FQ + t * 16); b[1] = lds128(sb + SM_FQ + 64 + t * 16);
            float e[4] = {0.f, 0.f, 0.f, 0.f};
            c[0] = c[1] = c[2] = c[3] = 0.f;
#pragma unroll
            for (int k = 0; k < 4; k++) {
                const uint32_t b0 = (k & 1) ? b[k >> 1].z : b[k >> 1].x, b1 = (k & 1) ? b[k >> 1].w : b[k >> 1].y;
                mma(c, a[2 * k].x, a[2 * k].y, a[2 * k].z, a[2 * k].w, b0, b1);
                mma(e, a[2 * k + 1].x, a[2 * k + 1].y, a[2 * k + 1].z, a[2 * k + 1].w, b0, b1);
            }
            const float mine = ((t & 1) ? ((t & 2) ? e[2] : e[0]) : ((t & 2) ? c[2] : c[0])) * 0.12751743f;
            const float other = shx(mine, 4);
            if (!(g & 1)) st2_x1(gs + (B_QA + rk * 8 + ((j >> 1) & 1) * 4 + (j >> 5)) * 4096 + w8 * 128 + ((j >> 2) & 7) * 16 + (g >> 1) * 4 + t, enc(pack2(mine, other)));
            if (u8 == 0) TRACE(15);
        }
        const uint32_t cls = ldcls();
        __nanosleep(QA_DELAY);
        {
            uint4 qb[8];
            const uint32_t* pq = gs + near_off(B_QA + rk * 8 + wq4, cls) + lane * 4;
            const uint32_t* pq2 = gs + near_off(B_QA + rk * 8 + 4 + wq4, cls) + lane * 4;
            if (lane == 0) {
                mbar_expect(BAR(QT), 4096);
                asm volatile("cp.async.bulk.shared::cluster.global.mbarrier::complete_tx::bytes [%0], [%1], 4096, [%2];"
                             :: "r"(sb + SM_U + 5 * 32768 + w8 * 4096), "l"(gs + near_off(B_QA + rk * 8 + w8, cls)), "r"(BAR(QT)) : "memory");
            }
            const uint32_t qs = sb + SM_U + 5 * 32768 + wq4 * 4096 + lane * 16;
            mbar_wait(BAR(QT), 0);
#pragma unroll
            for (int i = 0; i < 8; i++) { a[i] = lds128(qs + i * 512); qb[i] = lds128(qs + 16384 + i * 512); }
            poll<512, QA_SLEEP, true>(a, pq);
            poll<512, QA_SLEEP, true>(qb, pq2);
            if (lane == 0) mbar_arrive(BAR(EB_WUK));
            auto add2 = [](uint32_t x, uint32_t y) { uint32_t r; asm("add.rn.bf16x2 %0, %1, %2;" : "=r"(r) : "r"(x), "r"(y)); return r; };
#pragma unroll
            for (int i = 0; i < 8; i++) a[i] = make_uint4(add2(a[i].x, qb[i].x), add2(a[i].y, qb[i].y), add2(a[i].z, qb[i].z), add2(a[i].w, qb[i].w));
        }
        if (u8 == 0) TRACE(8);
        {
            float m = -INFINITY, l = 0.f;
            uint32_t xl = sb + SM_XB + w8 * 2048 + lane * 16, xr = peer_addr(xl, rk ^ 1), bsr = peer_addr(BAR(SF0 + v), rk ^ 1);
            uint32_t pa = sb + SM_XA + v * 2048 + wq4 * 512 + lane * 16, ma = sb + SM_MX + v * 128 + (wq4 * 8 + g) * 4;
            uint32_t fb = BAR(IT_CKV + v * 2), sf = BAR(SF0 + v);
            uint32_t dlo = __reduce_or_sync(0xffffffffu, (((sb + SM_U + v * 16384) & 0x3FFFFu) >> 4) | 0x10000u);
            uint32_t ck[9] = {0, 0, 0, 0, 0, 0, 0, 0, 0};
            if (STAG && v) __nanosleep(STAG);
#pragma unroll 1
            for (int n = 0; n < NUNITS; n++) {
                CLK(ck[0], n == TU); CLK(ck[8], n == TU + 1);
                float d[2][16], sc[8];
#pragma unroll
                for (int i = 0; i < 2; i++) {
                    mbar_wait(fb + i * 8, 0);
                    if (i == 0) CLK(ck[1], n == TU);
                    wg_fence();
#pragma unroll
                    for (int s = 0; s < 8; s++) wgmma_rs_n32(d[i], a[s], (0x40000080ull << 32) | (dlo + i * 512 + (s >> 2) * 64 + (s & 3) * 2), s);
                    wg_commit();
                }
                CLK(ck[2], n == TU);
#pragma unroll
                for (int i = 0; i < 2; i++) {
                    if (i) wg_wait0(); else wg_wait1();
#pragma unroll
                    for (int k = 0; k < 16; k++) asm volatile("" : "+f"(d[i][k]) :: "memory");
                    sc[4 * i] = d[i][0] + d[i][6]; sc[4 * i + 1] = d[i][1] + d[i][7]; sc[4 * i + 2] = d[i][8] + d[i][14]; sc[4 * i + 3] = d[i][9] + d[i][15];
                    asm volatile("st.async.weak.shared::cluster.mbarrier::complete_tx::bytes.v4.f32 [%0], {%1, %2, %3, %4}, [%5];"
                                 :: "r"(xr + i * 1024), "f"(sc[4 * i]), "f"(sc[4 * i + 1]), "f"(sc[4 * i + 2]), "f"(sc[4 * i + 3]), "r"(bsr) : "memory");
                }
                CLK(ck[3], n == TU);
                if (u8 == 128) TRACE_Q(56 + (n < 6 ? n : -40));
                if (n >= 3) mbar_wait(BAR(EB_UNIT0 + n - 3), 0);
                dlo += n == 5 ? -5 * 2048 : 2048;
                fb += 32; xr ^= 512; bsr += 16;
                pin(fb); pin(xr); pin(bsr);
                CLK(ck[4], n == TU);
                mbar_wait(sf, 0);
                CLK(ck[5], n == TU);
                const float4 x = ldsf4(xl), y = ldsf4(xl + 1024);
                sc[0] += x.x; sc[1] += x.y; sc[2] += x.z; sc[3] += x.w; sc[4] += y.x; sc[5] += y.y; sc[6] += y.z; sc[7] += y.w;
                float pr[8];
#pragma unroll
                for (int i = 0; i < 8; i++) pr[i] = ex2(sc[i] - m);
                float mx = fmaxf(fmaxf(fmaxf(sc[0], sc[1]), fmaxf(sc[2], sc[3])), fmaxf(fmaxf(sc[4], sc[5]), fmaxf(sc[6], sc[7])));
                if (__builtin_expect(__any_sync(0xffffffffu, mx > m), 0)) {
                    mx = fmaxf(mx, shx(mx, 1));
                    mx = fmaxf(mx, shx(mx, 2));
                    const float mn = fmaxf(m, ceilf(mx * 0.0625f) * 16.f);
                    l *= ex2(m - mn);
                    m = mn;
#pragma unroll
                    for (int i = 0; i < 8; i++) pr[i] = ex2(sc[i] - m);
                }
                CLK(ck[6], n == TU);
                stsf(ma, m);
                asm volatile("st.shared.v4.u32 [%0], {%1, %2, %3, %4};" :: "r"(pa), "r"(pack2(pr[0], pr[1])), "r"(pack2(pr[2], pr[3])),
                             "r"(pack2(pr[4], pr[5])), "r"(pack2(pr[6], pr[7])) : "memory");
                __syncwarp();
                if (lane == 0) mbar_arrive(sf + (PF0 - SF0) * 8);
                CLK(ck[7], n == TU);
                l += ((pr[0] + pr[1]) + (pr[2] + pr[3])) + ((pr[4] + pr[5]) + (pr[6] + pr[7]));
                xl ^= 512; sf += 16; ma += 256; pa += (n == 2 || n == 5) ? -8192 : 4096;
            }
            l += shx(l, 1);
            l += shx(l, 2);
            float2* mlx = (float2*)(sm + SM_MX + 2048) + wq4 * 8 + g;
            if (v == 0) { *mlx = make_float2(m, l); bar_arrive(11, 256); }
            else {
                mbar_wait(BAR(JD), 0);
                bar_sync(11, 256);
                const float2 o = *mlx;
                const float mn = fmaxf(m, o.x);
                l = l * ex2(m - mn) + o.y * ex2(o.x - mn);
                if ((wq4 >> 1) == rk) st_x4(gs + (B_ML + wq4 * 8 + g) * 4096 + (t >> 1) * 1024 + (j >> 1) * 8 + (t & 1) * 4, encf(mn), encf(l), 1u, 1u);
            }
        }
        const int pi = j < NFF ? rk * 128 + w8 * 16 + (lane & 15) : ((j - J_RED) & 15) * 16 + v * 8 + lb4 * 4 + wq4;
        const uint32_t xw = *(const uint32_t*)(xin + 2 * pi);
        {
            const uint32_t ab = sb + SM_U + B_WUV * 32768 + v * 4096 + a128;
            uint32_t pa = sb + SM_PB + wq4 * 320 + frag_off(64 * v + 32 * (g >> 2) + 16 * (t & 1) + 8 * (t >> 1) + 2 * (g & 3));
            uint32_t fa = sb + SM_PB + g * 320 + t * 16;
            const uint32_t* pe = gs + G_E1 + j * 8192 + (w8 >> 1) * 2048 + ((((cls >> 1) ^ (w8 >> 1)) & 1) << 10) + (((w8 & 1) * 16 + t) * 8 + g) * 4;
            uint32_t* p2 = gs + (B_E2 + (j >> 4)) * 4096 + (t >> 1) * 1024 + (j & 12) * 64 + w8 * 32 + (j & 3) * 8 + (g & 6) + (t & 1);
            pin(pa); pin(fa); pin(pe); pin(p2);
            const uint32_t mk = (g & 1) ? 0xffff0000u : 0x0000ffffu, m0 = (g & 2) ? 0u : mk, m1 = (g & 2) ? mk : 0u;
            uint4 pv[4], wa;
            bool hv = false, hw = false;
            bar_sync(3, 416);
            TK(0);
            pv[0] = pv[1] = pv[2] = pv[3] = make_uint4(0u, 0u, 0u, 0u);
            poll<512, E1_SLEEP, true>(pv, pe, [&]() {
                if (!hv) {
                    hv = __all_sync(0xffffffffu, mbar_test(BAR(IT_WUV + t), 0));
                    if (hv) load8<true>(a, [&](int s) { return ab + (s >> 1) * 8192 + (s & 1) * 2048; });
                }
                if (!hw) {
                    hw = __all_sync(0xffffffffu, mbar_test(BAR(WR), 0));
                    if (hw) wa = lds128(sb + SM_W + (wq4 * 4 + t) * 16);
                }
            });
            if (lane == 0) TRACE_Q(48 + w8);
            if (!hw) { mbar_wait(BAR(WR), 0); wa = lds128(sb + SM_W + (wq4 * 4 + t) * 16); }
            const uint32_t wb[8] = {wa.x & m0, wa.x & m1, wa.y & m0, wa.y & m1, wa.z & m0, wa.z & m1, wa.w & m0, wa.w & m1};
            if (u8 == 0) TRACE_Q(18);
            TK(1);
            float e[4][4];
#pragma unroll
            for (int i = 0; i < 4; i++) {
                e[i][0] = e[i][1] = e[i][2] = e[i][3] = 0.f;
                mma(e[i], pv[i].x, pv[i].y, pv[i].z, pv[i].w, wb[2 * i], wb[2 * i + 1]);
            }
            const float r0 = (t & 2) ? (e[0][2] + e[1][2]) + (e[2][2] + e[3][2]) : (e[0][0] + e[1][0]) + (e[2][0] + e[3][0]);
            const float r1 = (t & 2) ? (e[0][3] + e[1][3]) + (e[2][3] + e[3][3]) : (e[0][1] + e[1][1]) + (e[2][1] + e[3][1]);
            const uint32_t hi = pack2(r0, r1);
            sts32(pa, hi); sts32(pa + 1280, pack2(r0 - bflo(hi), r1 - bfhi(hi)));
            if (!hv) {
#pragma unroll 1
                for (int i = 0; i < 4; i++) mbar_wait(BAR(IT_WUV + i), 0);
                load8<true>(a, [&](int s) { return ab + (s >> 1) * 8192 + (s & 1) * 2048; });
            }
            TK(2);
            bar_sync(4, 288);
            TK(3);
            if (u8 == 0) TRACE(19);
            ldfrag(b, fa);
            const float inv = __uint_as_float(lds32(sb + SM_FQ));
            mma8(c, a, b);
            TK(4); TK(5);
            float lo, hi2;
            quad_pair(c[0] + c[1], c[2] + c[3], t, lo, hi2);
            if (!(g & 1)) st_x1(p2, enc(pack2(lo * inv, hi2 * inv)));
            TK(6);
            if (u8 == 0) TRACE(20);
        }
        uint32_t mb[3] = {0u, 0u, 0u};
        const uint32_t* pm = gs + near_off(B_MB, cls) + pi;
        pin(pm);
        if (j < NFF) poll_start<1024>(mb, pm);
        uint4 a2[8];
        TK(7); TK(8); TK(9); TK(10);
        if (v == 0) {
            const uint32_t ab = sb + SM_U + B_WO * 32768 + a128;
            uint32_t* p3 = gs + (B_E3 + ((j >> 1) & 3)) * 4096 + (t >> 1) * 1024 + (rk * 2 + (wq4 >> 1)) * 256 + (j >> 3) * 16 + (wq4 & 1) * 8 + (t & 1) * 4 + (g >> 1);
            pin(p3);
            uint2 bb[8];
#pragma unroll
            for (int i = 0; i < 8; i++) bb[i] = make_uint2(0u, 0u);
            bool ho = false;
            auto ldo = [&]() { load8<true>(a, [&](int s) { return ab + s * 2048; }); load8<true>(a2, [&](int s) { return ab + 16384 + s * 2048; }); };
            TK(7);
            poll<128, E2_SLEEP, true>(bb, gs + near_off(B_E2 + (j >> 4), cls) + (((j >> 3) & 1) * 2 + lb4) * 256 + (lane & 15) * 2, [&]() {
                if (!ho) {
                    ho = __all_sync(0xffffffffu, mbar_test(BAR(IT_WO + t), 0));
                    if (ho) ldo();
                }
            });
            if (!ho) {
#pragma unroll 1
                for (int i = 0; i < 4; i++) mbar_wait(BAR(IT_WO + i), 0);
                ldo();
            }
            TK(8);
            if (u8 == 0) TRACE(21);
            float e[4][4];
#pragma unroll
            for (int s = 0; s < 16; s++) {
                const uint4& x = (s & 2) ? a2[(s >> 2) * 2 + (s & 1)] : a[(s >> 2) * 2 + (s & 1)];
                const uint2& y = bb[(s >> 2) * 2 + (s & 1)];
                if (s < 4) e[s][0] = e[s][1] = e[s][2] = e[s][3] = 0.f;
                mma(e[s & 3], x.x, x.y, x.z, x.w, y.x, y.y);
            }
            TK(9); TK(10);
            float lo, hi;
            quad_pair((t & 2) ? (e[2][0] + e[3][0]) + (e[2][1] + e[3][1]) : (e[0][0] + e[1][0]) + (e[0][1] + e[1][1]),
                      (t & 2) ? (e[2][2] + e[3][2]) + (e[2][3] + e[3][3]) : (e[0][2] + e[1][2]) + (e[0][3] + e[1][3]), t, lo, hi);
            if (!(g & 1)) st_x1(p3, enc(pack2(lo, hi)));
            bar_arrive(1, 256);
            if (u8 == 0) TRACE(22);
        } else bar_sync(1, 256);
        TK(11);
        if (j < NFF) {
            const uint32_t* p3 = gs + near_off(B_E3 + rk * 2 + v, cls) + wq4 * 256 + lane;
            uint32_t za = sb + SM_FZ + lb4 * 576 + frag_off(w8 * 32 + (lane & 15) * 2);
            uint32_t fa = sb + SM_FZ + (g & 3) * 576 + lb4 * 256 + t * 16, ya = sb + SM_Y + u8 * 4;
            poll<1024, MB_SLEEP, true>(mb, pm);
            const uint32_t kk = pack2(1.f + bflo(mb[2]), 1.f + bfhi(mb[2]));
            sts32(za + 2 * 576, lb4 ? mb[1] : kk);
            uint32_t e3[8] = {0u, 0u, 0u, 0u, 0u, 0u, 0u, 0u};
            uint32_t ra = peer_addr(sb + SM_RED + (rk * 2 + v) * 512 + ((wq4 & 1) * 16 + (t >> 1) * 8 + g) * 16 + (t & 1) * 8, wq4 >> 1), tbo = peer_addr(BAR(QB), wq4 >> 1);
            pin(za); pin(fa); pin(ya); pin(ra); pin(tbo);
            if (lane == 0) mbar_expect(BAR(QB), 258);
            TK(12);
            const uint32_t gb = BAR(IT_X + v * 2), ab = sb + SM_U + (B_X + v) * 32768 + a128;
            bool early = false, early2 = false;
            auto ldw = [&]() {
                if (!early) {
                    early = __all_sync(0xffffffffu, mbar_test(gb, 0));
                    if (early) load8<true>(a, [&](int s) { return ab + s * 2048; });
                }
                if (!early2) {
                    early2 = __all_sync(0xffffffffu, mbar_test(gb + 8, 0));
                    if (early2) load8<true>(a2, [&](int s) { return ab + 16384 + s * 2048; });
                }
            };
            poll<128, E3_SLEEP, true>(e3, p3, ldw);
            TK(13);
            if (u8 == 0) TRACE(23);
            const float s0 = sumlo(e3), s1 = sumhi(e3);
            const float y0 = fmaf(bflo(mb[0]), s0 + shx(s0, 16), bflo(xw)), y1 = fmaf(bfhi(mb[0]), s1 + shx(s1, 16), bfhi(xw));
            stsf(ya, lb4 ? y1 : y0);
            const float z0 = y0 * bflo(kk), z1 = y1 * bfhi(kk);
            const uint32_t zh = pack2(z0, z1);
            sts32(za, lb4 ? pack2(z0 - bflo(zh), z1 - bfhi(zh)) : zh);
            TK(14);
            bar_sync(7, 288);
            TK(15);
            if (u8 == 0) TRACE(24);
            ldfrag(b, fa);
            if (!early) { mbar_wait(gb, 0); load8<true>(a, [&](int s) { return ab + s * 2048; }); }
            if (!early2) { mbar_wait(gb + 8, 0); load8<true>(a2, [&](int s) { return ab + 16384 + s * 2048; }); }
            {
                float e[4][4];
#pragma unroll
                for (int s = 0; s < 16; s++) {
                    const uint4& x = (s & 2) ? a2[(s >> 2) * 2 + (s & 1)] : a[(s >> 2) * 2 + (s & 1)];
                    const uint4& y = b[s >> 2];
                    if (s < 4) e[s][0] = e[s][1] = e[s][2] = e[s][3] = 0.f;
                    mma(e[s & 3], x.x, x.y, x.z, x.w, (s & 1) ? y.z : y.x, (s & 1) ? y.w : y.y);
                }
                const bool hi = t >> 1;
                const float k0 = hi ? e[2][2] + e[3][2] : e[0][0] + e[1][0], k1 = hi ? e[2][3] + e[3][3] : e[0][1] + e[1][1];
                const float o0 = hi ? e[2][0] + e[3][0] : e[0][2] + e[1][2], o1 = hi ? e[2][1] + e[3][1] : e[0][3] + e[1][3];
                TKD(16, o0);
                st_async2(ra, k0 + shx(o0, 2), k1 + shx(o1, 2), tbo);
            }
            TK(17);
        } else if (j >= J_RED && j < J_END) {
            uint32_t ga[1], e3[1];
            poll<0, MB_SLEEP>(ga, pm);
            poll<0, 100>(e3, gs + near_off(B_E3 + (pi >> 6), cls) + (pi & 48) * 16 + (lane & 15) * 16 + (pi & 15));
            if (E5_DELAY) __nanosleep(E5_DELAY);
            float y0 = bflo(e3[0]), y1 = bfhi(e3[0]);
#pragma unroll
            for (int o = 8; o; o >>= 1) { y0 += shx(y0, o); y1 += shx(y1, o); }
            y0 = fmaf(bflo(ga[0]), y0, bflo(xw)); y1 = fmaf(bfhi(ga[0]), y1, bfhi(xw));
            bar_sync(7, 320);
            const uint32_t gb = lds32(sb + SM_FV + 256 + (pi & 15) * 4);
            uint32_t* po = (uint32_t*)out + pi;
            pin(po);
            const uint32_t nz = lane < NFF / 2 ? 0u : 0x80008000u;
            uint2 yv[2] = {make_uint2(nz, nz), make_uint2(nz, nz)};
            poll<NFF * 32, E5_SLEEP, true>(yv, gs + near_off(B_E5 + j - J_RED, cls) + lane * 16 + w8 * 2);
            if (u8 == 0) TRACE(26);
            const float l0 = bflo(yv[0].x) + bflo(yv[1].x), h0 = bfhi(yv[0].x) + bfhi(yv[1].x);
            const float l1 = bflo(yv[0].y) + bflo(yv[1].y), h1 = bfhi(yv[0].y) + bfhi(yv[1].y);
            float s0 = (lb4 ? h0 : l0) + shx(lb4 ? l0 : h0, 16), s1 = (lb4 ? h1 : l1) + shx(lb4 ? l1 : h1, 16);
#pragma unroll
            for (int o = 8; o; o >>= 1) { s0 += shx(s0, o); s1 += shx(s1, o); }
            if (!(lane & 15)) *po = pack2(fmaf(bflo(gb), s0, y0), fmaf(bfhi(gb), s1, y1));
            if (u8 == 0) TRACE(27);
        }
    }
}

typedef CUresult (*EncFn)(CUtensorMap*, CUtensorMapDataType, cuuint32_t, void*, const cuuint64_t*, const cuuint64_t*,
                          const cuuint32_t*, const cuuint32_t*, CUtensorMapInterleave, CUtensorMapSwizzle,
                          CUtensorMapL2promotion, CUtensorMapFloatOOBfill);

void make_map(EncFn enc_fn, CUtensorMap* m, const void* p, cuuint64_t d0, cuuint64_t d1, cuuint64_t d2, cuuint64_t d3,
              cuuint64_t s1, cuuint64_t s2, cuuint64_t s3, cuuint32_t b0, cuuint32_t b1, cuuint32_t b2, cuuint32_t b3, CUtensorMapSwizzle sw) {
    const cuuint64_t dims[4] = {d0, d1, d2, d3}, strides[3] = {s1, s2, s3};
    const cuuint32_t box[4] = {b0, b1, b2, b3}, es[4] = {1, 1, 1, 1};
    enc_fn(m, CU_TENSOR_MAP_DATA_TYPE_BFLOAT16, 4, (void*)p, dims, strides, box, es,
           CU_TENSOR_MAP_INTERLEAVE_NONE, sw, CU_TENSOR_MAP_L2_PROMOTION_L2_64B, CU_TENSOR_MAP_FLOAT_OOB_FILL_NONE);
}

uint32_t* scratch = nullptr;

struct Tune { const char* win; const char* late; int tau, t_off; const char* tail[3][4]; };
Tune tune = {"66666666555556666666665555443222222222222",
             "000000000009999999999999999aaaaaaaaaaaaaa", 318, -240,
             {{"VVVVOOOOguguDD", "zzzzzzzzzzzzzz", "88888888888864", "aaaaaaaaiaaaza"},
              {"VVMVMVOOOO", "zzzzzzzzzz", "8888888888", "aa5555aaaa"},
              {"VVVVOOOOMM", "zzzzzzzzzz", "8888888888", "aaaacaaazo"}}};
bool ready = false;

}

extern "C" void kernel_launch(void* const* d_in, const int* in_sizes, int n_in, void* d_out, int out_size) {
    (void)in_sizes; (void)n_in; (void)out_size;
    static Maps maps;
    static const void* cached[12] = {};
    bool same = ready;
    for (int i = 0; i < 12 && same; i++) same = cached[i] == d_in[i];
    if (!same) {
        void* fn = nullptr;
        cudaDriverEntryPointQueryResult qr;
        cudaGetDriverEntryPoint("cuTensorMapEncodeTiled", &fn, cudaEnableDefault, &qr);
        EncFn e = (EncFn)fn;
        const CUtensorMapSwizzle S128 = CU_TENSOR_MAP_SWIZZLE_128B;
        make_map(e, &maps.m[MP_WQ], d_in[2], 64, 512, 64, 1, 8192, 128, 8192, 64, 64, 1, 1, S128);
        make_map(e, &maps.m[MP_WUK], d_in[3], 64, 512, 64, 1, 8192, 128, 8192, 64, 64, 1, 1, S128);
        make_map(e, &maps.m[MP_CKV], d_in[1], 64, 8, 8, 4096, 1024, 128, 8192, 64, 8, 4, 2, S128);
        make_map(e, &maps.m[MP_MODB], d_in[11], 3072, 512, 1, 1, 6144, 6144, 6144, 64, 128, 1, 1, S128);
        make_map(e, &maps.m[MP_WUV], d_in[4], 64, 512, 64, 1, 8192, 128, 8192, 64, 32, 2, 1, S128);
        make_map(e, &maps.m[MP_WO], d_in[5], 512, 4096, 1, 1, 1024, 1024, 1024, 64, 64, 1, 1, S128);
        make_map(e, &maps.m[MP_GATE], d_in[7], 1792, 512, 1, 1, 3584, 3584, 3584, 64, 128, 1, 1, S128);
        make_map(e, &maps.m[MP_UP], d_in[8], 1792, 512, 1, 1, 3584, 3584, 3584, 64, 128, 1, 1, S128);
        make_map(e, &maps.m[MP_DOWN], d_in[9], 64, 1792, 8, 1, 1024, 128, 1024, 64, 32, 4, 1, S128);
        for (int r = 0; r < 3; r++) {
            int ids[56], cnt[128] = {}, tn = tune.t_off - (W0 - 1) * tune.tau;
            uint2* sc = maps.sched[r];
            auto dig = [](char ch) { return ch >= 'a' ? ch - 'a' + 10 : ch - '0'; };
            for (int i = 0; i < 56; i++) sc[i] = make_uint2(0u, 0u);
            for (int i = 0;; i++) {
                int id = i, buf, dep, w, wl;
                if (i < IT_WUV) {
                    const int u = (i - IT_CKV) >> 2;
                    buf = i < IT_CKV ? 4 + ((i - 1) >> 2) : u % 6;
                    dep = i < IT_CKV || u < 4 ? -1 : u < 6 ? EB_WQ + u - 4 : EB_UNIT0 + u - 6;
                    w = dig(tune.win[i]); wl = dig(tune.late[i]);
                    if (i) tn += tune.tau;
                } else {
                    const char ch = tune.tail[r][0][i - IT_WUV];
                    if (!ch) break;
                    buf = ch == 'V' ? B_WUV : ch == 'O' ? B_WO : ch == 'D' ? B_DN : ch == 'u' ? B_X + 1 : B_X;
                    id = (ch == 'V' ? IT_WUV : ch == 'O' ? IT_WO : ch == 'D' ? IT_DOWN : ch == 'u' ? IT_X + 2 : IT_X) + cnt[(int)ch]++;
                    dep = EB_UNIT0 + (buf < 2 ? buf + 6 : buf);
                    w = dig(tune.tail[r][1][i - IT_WUV]); wl = dig(tune.tail[r][2][i - IT_WUV]);
                    tn += 32 * dig(tune.tail[r][3][i - IT_WUV]);
                }
                if (id < IT_X ? (id - 1) & 3 : (id - IT_X) & 1) dep = -1;
                ids[i] = id;
                auto back = [&](int d) { return i < d ? 0 : (ids[i - d] && ids[i - d] <= NCP ? 1 : ids[i - d]) + 1; };
                sc[i].x = id | (buf * 4 + (id < IT_X ? (id - 1) & 3 : ((id - IT_X) & 1) * 2)) << 6 | (dep + 1) << 11 | (w > 32 ? NEVER + 1 : back(w)) << 18 | (wl ? back(wl) : 0) << 25;
                sc[i].y = tn;
            }
        }
        cudaGetSymbolAddress((void**)&scratch, g_scratch);
        scratch = (uint32_t*)(((uintptr_t)scratch + (2u << 20) - 1) & ~(uintptr_t)((2u << 20) - 1));
        cudaFuncSetAttribute(fused_kernel, cudaFuncAttributeMaxDynamicSharedMemorySize, SM_TOTAL);
        for (int i = 0; i < 12; i++) cached[i] = d_in[i];
        ready = true;
    }
    const First f = {{(const uint8_t*)d_in[2], (const uint8_t*)d_in[11]}, {(const __nv_bfloat16*)d_in[0], (const __nv_bfloat16*)d_in[10]}};
    fused_kernel<<<NCTA, NTHREADS, SM_TOTAL>>>(f, (__nv_bfloat16*)d_out, scratch, maps);
}
```

```cpp
#include <cuda_runtime.h>
#include <cuda_bf16.h>
#include <cuda.h>
#include <stdint.h>
#include <limits.h>

namespace {

constexpr int NCTA = 128;
constexpr int NTHREADS = 512;
constexpr int NUNITS = 8;
constexpr int NFF = 56, J_RED = 104, J_END = 120;
constexpr uint32_t SPIN_LIMIT = 1u << 22;

#define DMODE 1
#define SPLIT4 1
#define WHATIF 0
#define PINSB 0
#define E5_DELAY 0
#define XC_LATE 4
#define MODA_PF ".L2::128B"
#define PREZERO 1
#define E1_EARLY 50
#define STAG 300
#define TU 2
#define NUMA 1
#define NPROBE 3
#define NCP 2
#define W0 4
#define RD_ITEM 15
#define JAN_SLEEP 100
#define RD_SLEEP 400
#define HA_DELAY 200
#define H_SLEEP 100
#define QA_DELAY 600
#define QA_SLEEP 200
#define ML_DELAY 300
#define ML_SLEEP 50
#define E1_SLEEP 50
#define E2_SLEEP 0
#define E3_SLEEP 0
#define E5_SLEEP 0
#define MB_SLEEP 100
constexpr int B_WUV = 2, B_WO = 3, B_X = 4  , B_DN = 0;

constexpr int SM_U = 0;
constexpr int SM_XA = 6 * 32768;
constexpr int SM_XB = SM_XA + 12288;
constexpr int SM_MX = SM_XB + 16384;
constexpr int SM_FZ = SM_XB + 8192;
constexpr int SM_PB = SM_XB;
constexpr int SM_Y = SM_XB + 12288;
constexpr int SM_RED = SM_XB + 4096;
constexpr int SM_FS = SM_XB + 20480;
constexpr int SM_FV = SM_FS + 1024;
constexpr int SM_QX = SM_XA + 8192;
constexpr int SM_FQ = SM_FV + 512;
constexpr int SM_CLS = SM_FQ + 128;
constexpr int SM_W = SM_FQ + 256;
constexpr int SM_W2 = SM_MX + 2304;
constexpr int SM_SCR = SM_XA + 9216;
constexpr int SM_TR = SM_XB + 19456;
constexpr int SM_BAR = SM_W + 256;
constexpr int SM_TOTAL = SM_BAR + 1024;
static_assert(SM_TOTAL <= 232448, "smem");

enum { IT_MODA = 0, IT_WQ = 1, IT_WUK = 5, IT_CKV = 9, IT_WUV = 41, IT_WO = 45, IT_X = 49  , IT_DOWN = 53, NITEMS = 55,
       NEVER = 63,
       SF0 = 64,
       PF0 = 80,
       EB_UNIT0 = 96, MBB = 103,
       EB_WQ = 104, EB_WUK, QT, QB, JD, WR };

enum { MP_WQ = 0, MP_WUK, MP_CKV, MP_MODB, MP_WUV, MP_WO, MP_GATE, MP_UP, MP_DOWN, NMAPS };
struct First { const uint8_t* w[2]; const __nv_bfloat16* v[2]; };
struct Maps { CUtensorMap m[NMAPS]; uint2 sched[3][56]; };

enum { B_HA = 0,
       B_MB = 6,
       B_RD = 7,
       B_E2 = 8,
       B_QA = 16,
       B_ML = 32,
       B_E5 = 64,
       B_E3 = 80,
       B_PR = 96,
       B_TR = 100 };
constexpr int G_E1 = 1 << 19;
constexpr int G_TR = B_TR * 4096;
__device__ __align__(1024) uint32_t g_scratch[(8 << 20) / 4];

#define TRACE(slot) do {} while (0)
#define TRACE_Q(slot) do {} while (0)
#define TRACE_GT(slot) do {} while (0)

#define CLK(var, cond) do {} while (0)
#define CLKD(var, cond, dep) do {} while (0)
#define TK(i) do {} while (0)
#define TKD(i, dep) do {} while (0)
__device__ __forceinline__ uint32_t s2u(const void* p) { return (uint32_t)__cvta_generic_to_shared(p); }
__device__ __forceinline__ void mbar_init(uint32_t b, int c) { asm volatile("mbarrier.init.shared::cta.b64 [%0], %1;" :: "r"(b), "r"(c) : "memory"); }
__device__ __forceinline__ void mbar_expect(uint32_t b, uint32_t bytes) { asm volatile("mbarrier.arrive.expect_tx.shared::cta.b64 _, [%0], %1;" :: "r"(b), "r"(bytes) : "memory"); }
__device__ __forceinline__ void mbar_arrive(uint32_t b) { asm volatile("mbarrier.arrive.shared::cta.b64 _, [%0];" :: "r"(b) : "memory"); }
__device__ __forceinline__ void mbar_wait(uint32_t b, uint32_t ph) {
    asm volatile("{\n.reg .pred p;\nW: mbarrier.try_wait.parity.shared::cta.b64 p, [%0], %1;\n@!p bra W;\n}" :: "r"(b), "r"(ph) : "memory");
}
__device__ __forceinline__ void mbar_waitb(uint32_t b, uint32_t ph) {
    asm volatile("{\n.reg .pred p;\n.reg .u32 n;\nmov.u32 n, 0;\n"
                 "W: mbarrier.try_wait.parity.shared::cta.b64 p, [%0], %1;\n@p bra D;\n"
                 "add.u32 n, n, 1;\nsetp.lt.u32 p, n, 0x100000;\n@p bra W;\ntrap;\nD:\n}" :: "r"(b), "r"(ph) : "memory");
}
__device__ __forceinline__ uint32_t mbar_test(uint32_t b, uint32_t ph) {
    uint32_t ok;
    asm volatile("{\n.reg .pred p;\nmbarrier.test_wait.parity.shared::cta.b64 p, [%1], %2;\nselp.u32 %0, 1, 0, p;\n}" : "=r"(ok) : "r"(b), "r"(ph) : "memory");
    return ok;
}
__device__ __forceinline__ void bar_sync(int id, int n) { asm volatile("bar.sync %0, %1;" :: "r"(id), "r"(n) : "memory"); }
__device__ __forceinline__ void bar_arrive(int id, int n) { asm volatile("bar.arrive %0, %1;" :: "r"(id), "r"(n) : "memory"); }
__device__ __forceinline__ uint32_t peer_addr(uint32_t a, uint32_t rank) { uint32_t r; asm("mapa.shared::cluster.u32 %0, %1, %2;" : "=r"(r) : "r"(a), "r"(rank)); return r; }
__device__ __forceinline__ void st_async1(uint32_t a, float x, uint32_t bar) {
    asm volatile("st.async.weak.shared::cluster.mbarrier::complete_tx::bytes.f32 [%0], %1, [%2];" :: "r"(a), "f"(x), "r"(bar) : "memory");
}
__device__ __forceinline__ void st_async2(uint32_t a, float x, float y, uint32_t bar) {
    asm volatile("st.async.weak.shared::cluster.mbarrier::complete_tx::bytes.v2.f32 [%0], {%1, %2}, [%3];" :: "r"(a), "f"(x), "f"(y), "r"(bar) : "memory");
}
__device__ __forceinline__ uint32_t gtime() { uint32_t t; asm volatile("mov.u32 %0, %%globaltimer_lo;" : "=r"(t)); return t; }
__device__ __forceinline__ void fence_gpu() { asm volatile("fence.acq_rel.gpu;" ::: "memory"); }

__device__ __forceinline__ uint32_t enc(uint32_t b) { uint32_t r; asm("max.u32 %0, %1, 1;" : "=r"(r) : "r"(b)); return r; }
__device__ __forceinline__ uint32_t encf(float f) { return enc(__float_as_uint(f)); }
__device__ __forceinline__ void st_x1(uint32_t* p, uint32_t v) { asm volatile("st.relaxed.gpu.global.u32 [%0], %1;" :: "l"(p), "r"(v) : "memory"); }
__device__ __forceinline__ void st_x4(void* p, uint32_t a, uint32_t b, uint32_t c, uint32_t d) {
    asm volatile("st.relaxed.gpu.global.v4.u32 [%0], {%1, %2, %3, %4};" :: "l"(p), "r"(a), "r"(b), "r"(c), "r"(d) : "memory");
}
__device__ __forceinline__ void st2_x1(uint32_t* p, uint32_t v) { st_x1(p, v); st_x1(p + 1024, v); }
__device__ __forceinline__ void st2_x4(uint32_t* p, uint32_t a, uint32_t b, uint32_t c, uint32_t d) { st_x4(p, a, b, c, d); st_x4(p + 1024, a, b, c, d); }
__device__ __forceinline__ int near_off(int b, uint32_t cls) { return b * 4096 + (((__popc(b & 0x2C) ^ cls) & 1) << 10); }
__device__ __forceinline__ void ld_x(uint32_t& v, const void* p) { asm volatile("ld.relaxed.gpu.global.u32 %0, [%1];" : "=r"(v) : "l"(p) : "memory"); }
__device__ __forceinline__ void ld_x(uint4& v, const void* p) {
    asm volatile("ld.relaxed.gpu.global.v4.u32 {%0, %1, %2, %3}, [%4];" : "=r"(v.x), "=r"(v.y), "=r"(v.z), "=r"(v.w) : "l"(p) : "memory");
}
__device__ __forceinline__ void ld_x(uint2& v, const void* p) { asm volatile("ld.relaxed.gpu.global.v2.u32 {%0, %1}, [%2];" : "=r"(v.x), "=r"(v.y) : "l"(p) : "memory"); }
__device__ __forceinline__ uint32_t minw(uint32_t v) { return v; }
__device__ __forceinline__ uint32_t minw(const uint2& v) { return min(v.x, v.y); }
__device__ __forceinline__ uint32_t minw(const uint4& v) { return min(__vimin3_u32(v.x, v.y, v.z), v.w); }
template <int N> __device__ __forceinline__ uint32_t mint(const uint32_t* m) {
    if constexpr (N == 1) return m[0];
    else if constexpr (N == 2) return min(m[0], m[1]);
    else return __vimin3_u32(mint<(N + 2) / 3>(m), mint<(N + 1) / 3>(m + (N + 2) / 3), mint<N / 3>(m + (N + 2) / 3 + (N + 1) / 3));
}

template <int STRIDE, int S4 = 4 * STRIDE, typename T, int N>
__device__ __forceinline__ void poll_start(T (&v)[N], const void* base) {
#pragma unroll
    for (int i = 0; i < N; i++) ld_x(v[i], (const uint8_t*)base + (i & 3) * STRIDE + (i >> 2) * S4);
}
struct Nop { __device__ void operator()() const {} };
template <int STRIDE, int SLEEP, bool STARTED = false, int S4 = 4 * STRIDE, typename T, int N, typename F = Nop>
__device__ __forceinline__ void poll(T (&v)[N], const void* base, F idle = F()) {
    if (!STARTED) { poll_start<STRIDE, S4>(v, base); idle(); }
#pragma unroll 1
    for (uint32_t it = 0;; it++) {
        uint32_t m[N];
#pragma unroll
        for (int i = 0; i < N; i++) m[i] = minw(v[i]);
        if (__all_sync(0xffffffffu, mint<N>(m) != 0)) break;
        if (SLEEP && it > 0) __nanosleep(SLEEP);
#pragma unroll
        for (int i = 0; i < N; i++) if (!m[i]) ld_x(v[i], (const uint8_t*)base + (i & 3) * STRIDE + (i >> 2) * S4);
        idle();
        if (it > SPIN_LIMIT) __trap();
    }
}

__device__ __forceinline__ float bflo(uint32_t w) { return __uint_as_float(w << 16); }
__device__ __forceinline__ float bfhi(uint32_t w) { return __uint_as_float(w & 0xffff0000u); }
__device__ __forceinline__ uint32_t pack2(float lo, float hi) {
    uint32_t r; asm("cvt.rn.bf16x2.f32 %0, %1, %2;" : "=r"(r) : "f"(hi), "f"(lo)); return r;
}
__device__ __forceinline__ float rbf(float x) { return __uint_as_float(pack2(0.f, x)); }
__device__ __forceinline__ float sumlo(const uint32_t (&v)[8]) { return ((bflo(v[0]) + bflo(v[1])) + (bflo(v[2]) + bflo(v[3]))) + ((bflo(v[4]) + bflo(v[5])) + (bflo(v[6]) + bflo(v[7]))); }
__device__ __forceinline__ float sumhi(const uint32_t (&v)[8]) { return ((bfhi(v[0]) + bfhi(v[1])) + (bfhi(v[2]) + bfhi(v[3]))) + ((bfhi(v[4]) + bfhi(v[5])) + (bfhi(v[6]) + bfhi(v[7]))); }
__device__ __forceinline__ float ex2(float x) { float r; asm("ex2.approx.ftz.f32 %0, %1;" : "=f"(r) : "f"(x)); return r; }
__device__ __forceinline__ float shx(float v, int m) { return __shfl_xor_sync(0xffffffffu, v, m); }
__device__ __forceinline__ uint4 lds128(uint32_t a) { uint4 v; asm volatile("ld.shared.v4.u32 {%0, %1, %2, %3}, [%4];" : "=r"(v.x), "=r"(v.y), "=r"(v.z), "=r"(v.w) : "r"(a) : "memory"); return v; }
__device__ __forceinline__ uint32_t lds32(uint32_t a) { uint32_t v; asm volatile("ld.shared.u32 %0, [%1];" : "=r"(v) : "r"(a) : "memory"); return v; }
__device__ __forceinline__ void sts32(uint32_t a, uint32_t v) { asm volatile("st.shared.u32 [%0], %1;" :: "r"(a), "r"(v) : "memory"); }
__device__ __forceinline__ void sts16(uint32_t a, uint32_t v) { asm volatile("st.shared.u16 [%0], %1;" :: "r"(a), "h"((uint16_t)v) : "memory"); }
__device__ __forceinline__ int frag_off(int k) { return (k >> 5) * 64 + ((k >> 1) & 3) * 16 + ((k >> 4) & 1) * 8 + ((k >> 3) & 1) * 4 + (k & 1) * 2; }

template <bool TRANS>
__device__ __forceinline__ uint4 ldsm(uint32_t a) {
    uint4 r;
    if (TRANS) asm volatile("ldmatrix.sync.aligned.m8n8.x4.trans.shared.b16 {%0, %1, %2, %3}, [%4];" : "=r"(r.x), "=r"(r.y), "=r"(r.z), "=r"(r.w) : "r"(a) : "memory");
    else asm volatile("ldmatrix.sync.aligned.m8n8.x4.shared.b16 {%0, %1, %2, %3}, [%4];" : "=r"(r.x), "=r"(r.y), "=r"(r.z), "=r"(r.w) : "r"(a) : "memory");
    return r;
}
__device__ __forceinline__ void mma(float (&c)[4], uint32_t a0, uint32_t a1, uint32_t a2, uint32_t a3, uint32_t b0, uint32_t b1) {
    asm volatile("mma.sync.aligned.m16n8k16.row.col.f32.bf16.bf16.f32 {%0,%1,%2,%3}, {%4,%5,%6,%7}, {%8,%9}, {%0,%1,%2,%3};"
                 : "+f"(c[0]), "+f"(c[1]), "+f"(c[2]), "+f"(c[3]) : "r"(a0), "r"(a1), "r"(a2), "r"(a3), "r"(b0), "r"(b1));
}
template <bool TRANS, typename F>
__device__ __forceinline__ void load8(uint4 (&a)[8], F addr) {
    __syncwarp();
#pragma unroll
    for (int s = 0; s < 8; s++) a[s] = ldsm<TRANS>(addr(s));
}
__device__ __forceinline__ void mma8(float (&c)[4], const uint4 (&a)[8], const uint4 (&b)[4]) {
    float e[4][4];
#pragma unroll
    for (int s = 0; s < 8; s++) {
        if (s < 4) e[s][0] = e[s][1] = e[s][2] = e[s][3] = 0.f;
        mma(e[s & 3], a[s].x, a[s].y, a[s].z, a[s].w, (s & 1) ? b[s >> 1].z : b[s >> 1].x, (s & 1) ? b[s >> 1].w : b[s >> 1].y);
    }
#pragma unroll
    for (int i = 0; i < 4; i++) c[i] = (e[0][i] + e[1][i]) + (e[2][i] + e[3][i]);
}
__device__ __forceinline__ void ldfrag(uint4 (&b)[4], uint32_t a) {
    asm volatile("ld.shared.v4.u32 {%0,%1,%2,%3}, [%16];\nld.shared.v4.u32 {%4,%5,%6,%7}, [%16+64];\n"
                 "ld.shared.v4.u32 {%8,%9,%10,%11}, [%16+128];\nld.shared.v4.u32 {%12,%13,%14,%15}, [%16+192];\n"
                 : "=r"(b[0].x), "=r"(b[0].y), "=r"(b[0].z), "=r"(b[0].w), "=r"(b[1].x), "=r"(b[1].y), "=r"(b[1].z), "=r"(b[1].w),
                   "=r"(b[2].x), "=r"(b[2].y), "=r"(b[2].z), "=r"(b[2].w), "=r"(b[3].x), "=r"(b[3].y), "=r"(b[3].z), "=r"(b[3].w) : "r"(a) : "memory");
}
__device__ __forceinline__ void quad_pair(float x, float y, int t, float& lo, float& hi) {
    const float k = ((t & 1) ? y : x) + shx((t & 1) ? x : y, 1);
    lo = k + shx(k, 2); hi = shx(k, 4) + shx(k, 6);
}
__device__ __forceinline__ void pin(uint32_t& x) { asm volatile("" : "+r"(x)); }
template <typename T> __device__ __forceinline__ void pin(T*& x) { asm volatile("" : "+l"(x)); }
__device__ __forceinline__ float4 ldsf4(uint32_t a) { const uint4 v = lds128(a); return make_float4(__uint_as_float(v.x), __uint_as_float(v.y), __uint_as_float(v.z), __uint_as_float(v.w)); }
__device__ __forceinline__ float sum4(const float4& f) { return (f.x + f.y) + (f.z + f.w); }
__device__ __forceinline__ void stsf(uint32_t a, float v) { sts32(a, __float_as_uint(v)); }

__device__ __forceinline__ void wg_fence() { asm volatile("wgmma.fence.sync.aligned;" ::: "memory"); }
__device__ __forceinline__ void wg_commit() { asm volatile("wgmma.commit_group.sync.aligned;" ::: "memory"); }
__device__ __forceinline__ void wg_wait1() { asm volatile("wgmma.wait_group.sync.aligned 1;" ::: "memory"); }
__device__ __forceinline__ void wg_wait0() { asm volatile("wgmma.wait_group.sync.aligned 0;" ::: "memory"); }
#define R8(o) "+f"(d[o]), "+f"(d[o + 1]), "+f"(d[o + 2]), "+f"(d[o + 3]), "+f"(d[o + 4]), "+f"(d[o + 5]), "+f"(d[o + 6]), "+f"(d[o + 7])
__device__ __forceinline__ void wgmma_rs_n32(float (&d)[16], const uint4& a, uint64_t db, int acc) {
    asm volatile("{\n.reg .pred p;\nsetp.ne.b32 p, %21, 0;\n"
        "wgmma.mma_async.sync.aligned.m64n32k16.f32.bf16.bf16 "
        "{%0,%1,%2,%3,%4,%5,%6,%7,%8,%9,%10,%11,%12,%13,%14,%15}, {%16,%17,%18,%19}, %20, p, 1, 1, 0;\n}"
        : R8(0), R8(8) : "r"(a.x), "r"(a.y), "r"(a.z), "r"(a.w), "l"(db), "r"(acc));
}
#define PV_LO "{%0,%1,%2,%3,%4,%5,%6,%7,%8,%9,%10,%11,%12,%13,%14,%15,%16,%17,%18,%19,%20,%21,%22,%23,%24,%25,%26,%27,%28,%29,%30,%31,%32,%33,%34,%35,%36,%37,%38,%39,%40,%41,%42,%43,%44,%45,%46,%47,%48,%49,%50,%51,%52,%53,%54,%55,%56,%57,%58,%59,%60,%61,%62,%63}, "
#define PV_HI "{%64,%65,%66,%67,%68,%69,%70,%71,%72,%73,%74,%75,%76,%77,%78,%79,%80,%81,%82,%83,%84,%85,%86,%87,%88,%89,%90,%91,%92,%93,%94,%95,%96,%97,%98,%99,%100,%101,%102,%103,%104,%105,%106,%107,%108,%109,%110,%111,%112,%113,%114,%115,%116,%117,%118,%119,%120,%121,%122,%123,%124,%125,%126,%127}, "
__device__ __forceinline__ void wgmma_pv(float (&d)[128], const uint4& a, uint32_t blo, int acc) {
    asm volatile("{\n.reg .pred p;\n.reg .b32 u0, u1, u2, u3, t;\n.reg .b64 d0, d1, d2, d3;\nsetp.ne.b32 p, %133, 0;\n"
        "mov.b64 d0, {%132, 0x40000100};\nadd.u32 t, %132, 512;\nmov.b64 d1, {t, 0x40000100};\n"
        "add.u32 t, %132, 128;\nmov.b64 d2, {t, 0x40000100};\nadd.u32 t, %132, 640;\nmov.b64 d3, {t, 0x40000100};\n"
        "wgmma.fence.sync.aligned;\n"
        "wgmma.mma_async.sync.aligned.m64n128k16.f32.bf16.bf16 " PV_LO "{%128, u0, %129, u1}, d0, p, 1, 1, 1;\n"
        "wgmma.mma_async.sync.aligned.m64n128k16.f32.bf16.bf16 " PV_LO "{%130, u2, %131, u3}, d1, 1, 1, 1, 1;\n"
        "wgmma.commit_group.sync.aligned;\n"
        "wgmma.mma_async.sync.aligned.m64n128k16.f32.bf16.bf16 " PV_HI "{%128, u0, %129, u1}, d2, p, 1, 1, 1;\n"
        "wgmma.mma_async.sync.aligned.m64n128k16.f32.bf16.bf16 " PV_HI "{%130, u2, %131, u3}, d3, 1, 1, 1, 1;\n"
        "wgmma.commit_group.sync.aligned;\n}"
        : R8(0), R8(8), R8(16), R8(24), R8(32), R8(40), R8(48), R8(56), R8(64), R8(72), R8(80), R8(88), R8(96), R8(104), R8(112), R8(120)
        : "r"(a.x), "r"(a.y), "r"(a.z), "r"(a.w), "r"(blo), "r"(acc) : "memory");
}

template <int NW>
__device__ __forceinline__ void ln_stats(float s, float q, float sh, float* scr, int w, int lane, int bar, float& mean_b, float& sd_b) {
#pragma unroll
    for (int o = 16; o; o >>= 1) { s += shx(s, o); q += shx(q, o); }
    constexpr float n = 512.f / NW;
    if (lane == 0) { scr[w] = sh + s * (1.f / n); scr[NW + w] = q - s * s * (1.f / n); }
    bar_sync(bar, NW * 32);
    float mu = 0.f, m2 = 0.f;
#pragma unroll
    for (int i = 0; i < NW; i++) { mu += scr[i]; m2 += scr[NW + i]; }
    mu *= 1.f / NW;
#pragma unroll
    for (int i = 0; i < NW; i++) { const float d = scr[i] - mu; m2 = fmaf(n * d, d, m2); }
    mean_b = rbf(mu);
    sd_b = rbf(sqrtf(rbf(rbf(fmaxf(m2, 0.f) * (1.f / 512.f)) + 1e-5f)));
}
__device__ __forceinline__ float ln_mod(float x, float mean_b, float sd_b, float c, float s) {
    return rbf(rbf(__fdividef(rbf(x - mean_b), sd_b)) * rbf(1.f + c)) + s;
}

__global__ void __cluster_dims__(2, 1, 1) __launch_bounds__(NTHREADS, 1)
fused_kernel(const __grid_constant__ First F, __nv_bfloat16* __restrict__ out, uint32_t* __restrict__ gs, const __grid_constant__ Maps M) {
    extern __shared__ __align__(1024) uint8_t sm[];
    const uint32_t sb0 = s2u(sm);
    const int tid = threadIdx.x, lane = tid & 31;
    const int j = blockIdx.x, rk = j & 1;
    const int g = lane >> 2, t = lane & 3;
    const int r8 = lane & 7, lb3 = (lane >> 3) & 1, lb4 = lane >> 4;
    const uint64_t pol = 0x12F0000000000000ull;
    uint32_t in1 = 0, in2 = 0;
    {
        auto cpa = [&](uint32_t d, const uint8_t* s) {
            asm volatile("cp.async.cg.shared.global.L2::cache_hint.L2::128B [%0], [%1], 16, %2;" :: "r"(d), "l"(s), "l"(pol) : "memory");
        };
        const uint32_t ut = threadIdx.x, uj = blockIdx.x;
        const uint8_t* w = F.w[ut >= 128];
        if (ut < 128) {
            const uint32_t dq = (sb0 + ut * 16) ^ ((ut * 2) & 0x70);
            const uint8_t* sq = w + (uint32_t)(((uj & 1) * 256 + (ut >> 3)) * 8192 + (uj >> 1) * 128 + (ut & 7) * 16);
#pragma unroll
            for (int i = 0; i < 4 * NCP; i++) cpa(dq + 4 * 32768 + i * 2048, sq + i * 131072);
        } else if (ut < 384) {
            const uint32_t dm = (sb0 + ut * 16) ^ ((ut * 2) & 0x10);
            const uint8_t* sa = w + (uint32_t)(((uj >> 5) * 128 + (ut >> 1) - 64) * 6144 + (uj & 31) * 32 + (ut & 1) * 16);
            asm volatile("cp.async.cg.shared.global.L2::cache_hint" MODA_PF " [%0], [%1], 16, %2;" :: "r"(dm + SM_XA - 2048), "l"(sa), "l"(pol) : "memory");
            asm volatile("cp.async.cg.shared.global.L2::cache_hint" MODA_PF " [%0], [%1], 16, %2;" :: "r"(dm + SM_XA + 2048), "l"(sa + 1024), "l"(pol) : "memory");
        }
        else if (ut == 480 && uj < 16 * XC_LATE) asm volatile("prefetch.global.L2 [%0];" :: "l"(F.v[(uj >> 3) & 1] + (uj & 7) * 64));
    }
    const int warp = __shfl_sync(0xffffffffu, tid >> 5, 0);
    const uint32_t sb = sb0;
    const __nv_bfloat16* const xin = F.v[0];
    uint32_t* const pl = gs + (warp < 2 ? (B_PR + (j >> 5)) * 4096 + (j & 31) * 32 : G_E1 + j * 8192) + (warp & 1) * 1024 + lane;
    auto small_loads = [&]() {
        if (warp < 4) { in1 = *(const uint32_t*)(xin + 2 * tid); in2 = *(const uint32_t*)(xin + 256 + 2 * tid); }
        else if (warp < 12) in1 = *(const uint32_t*)(F.v[1] + 2 * (tid - 128));
    };
    if (!XC_LATE) small_loads();
    if (warp < 4) st_x1(pl, 1u);
    auto BAR = [&](int i) -> uint32_t { return sb + SM_BAR + i * 8; };
    const uint32_t a16 = (r8 + 8 * lb4) * 32 + ((lb3 ^ (r8 >> 2)) * 16);
    const uint32_t a128 = (r8 + 8 * lb4) * 128 + ((((warp & 3) * 2 + lb3) ^ r8) * 16);
    auto ldcls = [&]() -> uint32_t { return *(const volatile uint32_t*)(sm + SM_CLS); };
    auto clear_head = [&]() {
        st2_x1(gs + (B_HA + ((j >> 4) & 1) * 2 + lb4) * 4096 + (j >> 5) * 256 + (j & 15) * 16 + (lane & 15), 0u);
        st2_x4(gs + (B_QA + rk * 8 + ((j >> 1) & 1) * 4 + (j >> 5)) * 4096 + g * 128 + ((j >> 2) & 7) * 16 + t * 4, 0u, 0u, 0u, 0u);
        if (lane < 8) st2_x1(gs + B_RD * 4096 + j * 8 + lane, 0u);
    };
    auto tma = [&](uint32_t dst, int mp, uint32_t bar, int c0, int c1, int c2, int c3) {
        asm volatile("{\n.reg .pred p;\nelect.sync _|p, 0xffffffff;\n"
                     "@p cp.async.bulk.tensor.4d.shared::cluster.global.mbarrier::complete_tx::bytes.L2::cache_hint [%0], [%1, {%3, %4, %5, %6}], [%2], %7;\n}"
                     :: "r"(dst), "l"(&M.m[mp]), "r"(bar), "r"(c0), "r"(c1), "r"(c2), "r"(c3), "l"(pol) : "memory");
    };
    if (warp <= 12 || warp == 15) {
        const int grp = warp == 12 ? 0 : warp == 15 ? 13 : warp + 1;
        const uint32_t cnt = grp < 10 ? 1 : grp < 13 ? 4 : 8;
        if (lane == 0) {
#pragma unroll
            for (int i = 0; i < 8; i++) mbar_init(BAR(grp * 8 + i), (i < 2 && grp == 0) ? (i ? 128 : 256) : cnt);
        }
        __syncwarp();
        if (grp < 10 && lane < 8 && (grp || lane > NCP)) mbar_expect(BAR(grp * 8 + lane), grp >= 8 ? 4096 : grp * 8 + lane < IT_X ? 8192 : 16384);
        asm volatile("fence.mbarrier_init.release.cluster;" ::: "memory");
        __syncwarp();
        if (warp == 12) {
#pragma unroll
            for (int i = NCP + 1; i < W0; i++) tma(sb + (15 + i) * 8192, MP_WQ, BAR(i), 0, rk * 256 + (i - 1) * 64, j >> 1, 0);
        }
    } else if (warp == 13) {
        if (lane < NMAPS) asm volatile("prefetch.tensormap [%0];" :: "l"(&M.m[lane]) : "memory");
    } else if (warp == 14 && PREZERO) {
        clear_head();
    }
    __syncthreads();
    if (XC_LATE) small_loads();
    if (warp < 12) asm volatile("cp.async.mbarrier.arrive.noinc.shared::cta.b64 [%0];" :: "r"(BAR(warp < 4)) : "memory");
    asm volatile("barrier.cluster.arrive.relaxed.aligned;" ::: "memory");

    if (warp >= 12) {
    asm volatile("setmaxnreg.dec.sync.aligned.u32 64;");
    if (warp == 12) {
        static_assert(W0 > NCP && W0 <= 5 && NCP >= 1 && NCP <= 4, "W0");
        const uint2* sched = M.sched[j < NFF ? 0 : j < J_RED ? 1 : 2];
        uint2 en = sched[W0];
        const uint32_t t0 = gtime();
#pragma unroll 1
        for (int i = W0; en.x; i++) {
            const uint32_t e = en.x, tn = t0 + en.y;
            en = sched[i + 1];
            const int id = e & 63, w0 = (e >> 11) & 127, w1 = (e >> 18) & 127;
            int mp, c0 = 0, c1 = 0, c2 = 0, c3 = 0;
            if (id < IT_CKV) { const int k = id - IT_WQ; mp = MP_WQ + (k >> 2); c1 = rk * 256 + (k & 3) * 64; c2 = j >> 1; }
            else if (id < IT_WUV) { const int k = id - IT_CKV; mp = MP_CKV; c2 = rk * 4; c3 = (k * 64 + (j >> 1)) * 2; }
            else if (id < IT_WO) { mp = MP_WUV; c1 = (j & 3) * 32 + (id - IT_WUV) * 128; c2 = (j >> 2) * 2; }
            else if (id < IT_X) { mp = MP_WO; c0 = (j & 7) * 64; c1 = (j >> 3) * 256 + (id - IT_WO) * 64; }
            else if (id < IT_DOWN) {
                if (j >= J_END) break;
                const int k = id - IT_X;
                mp = j < NFF ? MP_GATE + (k >> 1) : MP_MODB; c0 = (j >> 1) * 64 + (j < NFF ? 0 : 1024 - NFF * 32); c1 = rk * 256 + (k & 1) * 128;
            } else { mp = MP_DOWN; c1 = j * 32; c2 = (id - IT_DOWN) * 4; }
            if (w0) mbar_wait(BAR(w0 - 1), 0);
            const int w2 = e >> 25;
            if (w2) {
                mbar_wait(BAR(w2 - 1), 0);
                while (!__any_sync(0xffffffffu, mbar_test(BAR(w1 - 1), 0) | ((int)(gtime() - tn) > 0))) {}
            } else if (w1) mbar_wait(BAR(w1 - 1), 0);
            tma(sb + ((e >> 6) & 31) * 8192, mp, BAR(id), c0, c1, c2, c3);
        }
    } else if (warp == 13) {
#pragma unroll
        for (int i = 0; i < 2; i++) st_x4(gs + (B_ML + rk * 16 + i * 8 + g) * 4096 + (t >> 1) * 1024 + (j >> 1) * 8 + (t & 1) * 4, 0u, 0u, 0u, 0u);
        if (lane < 16) st2_x4(gs + (B_E2 + (j >> 4)) * 4096 + (j & 15) * 64 + lane * 4, 0u, 0u, 0u, 0u);
        st2_x1(gs + (B_E3 + (j >> 5)) * 4096 + (j & 31) * 32 + lane, 0u);
        if (lane < 8) st2_x1(gs + B_MB * 4096 + j * 8 + lane, 0u);
        if (j < NFF) {
#pragma unroll
            for (int i = 0; i < 2; i++) st2_x4(gs + (B_E5 + i * 8 + g) * 4096 + j * 16 + t * 4, 0u, 0u, 0u, 0u);
        }
        bar_sync(9, 64);
        const uint32_t cs = ldcls();
#pragma unroll 1
        for (int i = 0; i < 32; i++) {
            st_x4(gs + G_E1 + j * 8192 + (i >> 3) * 2048 + ((((cs >> 1) ^ (i >> 3)) & 1) << 10) + (i & 7) * 128 + lane * 4, 0u, 0u, 0u, 0u);
            __nanosleep(JAN_SLEEP);
        }
        fence_gpu();
        if (lane < 8) st2_x1(gs + B_RD * 4096 + j * 8 + lane, 1u + (cs >> 1));
        if (lane == 0) TRACE(41);
        uint32_t rd[4];
        mbar_wait(BAR(IT_CKV + RD_ITEM), 0);
        poll<1024, RD_SLEEP>(rd, gs + near_off(B_RD, cs) + lane * 8);
#pragma unroll
        for (int i = 0; i < 4; i++) {
            const uint32_t m = __ballot_sync(0xffffffffu, rd[i] == 2u);
            if (lane == 0) sts32(sb + SM_CLS + 16 + i * 4, m);
        }
        __syncwarp();
        if (lane < 8) mbar_arrive(BAR(JD));
        if (lane == 0) TRACE(42);
    } else if (warp == 14) {
        uint2 ml[2];
        mbar_waitb(BAR(JD), 0);
        const uint32_t cls = ldcls();
        mbar_waitb(BAR(PF0 + 2 * NUNITS - 1), 0);
        __nanosleep(ML_DELAY);
        const uint32_t* pl2 = gs + near_off(B_ML + (j >> 2), cls) + lane * 8;
        const uint32_t wa = sb + SM_W + lb4 * 64 + t * 16 + (g & 3) * 4;
        poll_start<1024>(ml, pl2);
        uint32_t w0 = 0, w1 = 0, redo = 0;
        bool first = true;
#pragma unroll 1
        for (uint32_t it = 0;; it++) {
            const bool p0 = minw(ml[0]) != 0, p1 = minw(ml[1]) != 0;
            const int n = __popc(__ballot_sync(0xffffffffu, p0)) + __popc(__ballot_sync(0xffffffffu, p1));
            const uint32_t x0 = ml[0].x, x1 = ml[1].x;
            if (n < 64) {
                if (!p0) ld_x(ml[0], pl2);
                if (!p1) ld_x(ml[1], pl2 + 256);
            }
            if (n == 64 || (first && n >= E1_EARLY)) {
                auto ord = [](int x) { return x ^ ((x >> 31) & 0x7fffffff); };
                const int o0 = ord(x0), o1 = ord(x1);
                const float mm = __int_as_float(ord(__reduce_max_sync(0xffffffffu, max(p0 ? o0 : INT_MIN, p1 ? o1 : INT_MIN))));
                const float lo = __int_as_float(ord(__reduce_min_sync(0xffffffffu, min(p0 ? o0 : INT_MAX, p1 ? o1 : INT_MAX))));
                const uint32_t v0 = pack2(ex2((p0 ? __uint_as_float(x0) : lo) - mm), 0.f), v1 = pack2(ex2((p1 ? __uint_as_float(x1) : lo) - mm), 0.f);
                redo = !first && __any_sync(0xffffffffu, v0 != w0 || v1 != w1);
                w0 = v0; w1 = v1;
                sts32(wa + redo * (SM_W2 - SM_W), w0 * 0x10001u); sts32(wa + redo * (SM_W2 - SM_W) + 128, w1 * 0x10001u);
                if (first) bar_arrive(3, 416);
                first = false;
                if (n == 64) break;
            }
            if (it > SPIN_LIMIT) __trap();
        }
        if (lane == 0) TRACE_Q(37);
        float L = bflo(w0) * __uint_as_float(ml[0].y) + bflo(w1) * __uint_as_float(ml[1].y);
#pragma unroll
        for (int o = 16; o; o >>= 1) L += shx(L, o);
        if (lane == 0) *(float2*)(sm + SM_FQ) = make_float2(__frcp_rn(L), __uint_as_float(redo));
        __syncwarp();
        if (lane < 8) mbar_arrive(BAR(WR));
        if (lane == 0) TRACE(10);
        bar_sync(4, 288);
        clear_head();
        if (j < NFF) {
            uint32_t ya = sb + SM_Y + lane * 16, sa = peer_addr(sb + SM_RED + 2048 + rk * 8, lane & 1), tb = peer_addr(BAR(MBB), lane & 1);
            pin(ya); pin(sa); pin(tb);
            bar_sync(7, 288);
            const float4 y0 = ldsf4(ya), y1 = ldsf4(ya + 512);
            float s = sum4(y0) + sum4(y1);
            float q = (fmaf(y0.x, y0.x, y0.y * y0.y) + fmaf(y0.z, y0.z, y0.w * y0.w)) + (fmaf(y1.x, y1.x, y1.y * y1.y) + fmaf(y1.z, y1.z, y1.w * y1.w));
#pragma unroll
            for (int o = 16; o; o >>= 1) { s += shx(s, o); q += shx(q, o); }
            if (lane < 2) st_async2(sa, s, q, tb);
        }
    } else if (warp == 15) {
        mbar_waitb(BAR(IT_X - 1), 0);
        if (j < J_END) mbar_waitb(BAR(j < NFF ? NITEMS - 1 : MBB), 0);
    }
    } else if (warp < 4) {
        float* scr = (float*)(sm + SM_SCR);
        uint32_t cls;
        {
            uint2 ha[8];
            {
                uint32_t best = 0xffffffffu;
#pragma unroll
                for (int i = 0; i < NPROBE; i++) {
                    uint32_t t0, t1, o;
                    asm volatile("mov.u32 %0, %%clock;" : "=r"(t0));
                    asm volatile("atom.relaxed.gpu.global.exch.b32 %0, [%1], %2;" : "=r"(o) : "l"(pl), "r"(2u + i) : "memory");
                    asm volatile("{\n.reg .pred p;\nsetp.ne.u32 p, %1, 0x1234567;\nmov.u32 %0, 0;\n@p mov.u32 %0, %%clock;\n}" : "=r"(t1) : "r"(o));
                    best = min(best, t1 - t0);
                }
                if (lane == 0) scr[16 + warp] = __uint_as_float(best);
            }
            const float sh = __shfl_sync(0xffffffffu, bflo(in1), 0);
            const float v0 = bflo(in1) - sh, v1 = bfhi(in1) - sh, v2 = bflo(in2) - sh, v3 = bfhi(in2) - sh;
            float mb, sd;
            ln_stats<4>((v0 + v1) + (v2 + v3), (v0 * v0 + v1 * v1) + (v2 * v2 + v3 * v3), sh, scr, warp, lane, 2, mb, sd);
            if (!rk) in2 = in1;
            const uint4 lt = *(const uint4*)(scr + 16);
            cls = NUMA ? ((lt.y < lt.x) ^ (__popc((B_PR + (j >> 5)) & 0x2C) & 1)) | (lt.w < lt.z) << 1 : 0;
            if (warp == 0) { if (lane == 0) sts32(sb + SM_CLS, cls); bar_arrive(9, 64); }
            if (tid == 0) TRACE(38);
            asm volatile("barrier.cluster.wait.aligned;" ::: "memory");
            mbar_wait(BAR(IT_MODA), 0);
            __nanosleep(HA_DELAY);
            poll<1024, H_SLEEP, false, 16384>(ha, gs + near_off(B_HA + rk * 2, cls) + 2 * tid);
            auto rsum = [](uint32_t a, uint32_t b, uint32_t c, uint32_t d) { return rbf((__uint_as_float(a) + __uint_as_float(b)) + (__uint_as_float(c) + __uint_as_float(d))); };
            sts32(sb + SM_FV + frag_off(2 * tid),
                  pack2(ln_mod(bflo(in2), mb, sd, rsum(ha[4].x, ha[5].x, ha[6].x, ha[7].x), rsum(ha[0].x, ha[1].x, ha[2].x, ha[3].x)),
                        ln_mod(bfhi(in2), mb, sd, rsum(ha[4].y, ha[5].y, ha[6].y, ha[7].y), rsum(ha[0].y, ha[1].y, ha[2].y, ha[3].y))));
            bar_arrive(5, 384);
            mbar_wait(BAR(QB), 0);
            if (tid < 64) {
                const float* qx = (const float*)(sm + SM_QX) + tid;
                sts16(sb + SM_FQ + frag_off(tid), pack2((qx[0] + qx[64]) + (qx[128] + qx[192]), 0.f));
            }
            bar_arrive(6, 384);
        }
        asm volatile("setmaxnreg.inc.sync.aligned.u32 192;");
        float acc[128];
        float M = 0.f;
        uint32_t pa = sb + SM_XA + warp * 512 + lane * 16, ma = sb + SM_MX + (warp * 8 + g) * 4, pf = BAR(PF0);
        uint32_t blo = __reduce_or_sync(0xffffffffu, (((sb + SM_U) & 0x3FFFFu) >> 4) | 0x400000u);
        uint32_t* e1[4];
#pragma unroll
        for (int i = 0; i < 4; i++) e1[i] = gs + G_E1 + (warp * 8 + g) * 4 * 8192 + (rk * 2 + (j >> 6)) * 2048 + ((j >> 1) & 31) * 32 + t * 4;
        uint32_t ck[10] = {0, 0, 0, 0, 0, 0, 0, 0, 0, 0};
#pragma unroll 1
        for (int h = 0; h < 2 * NUNITS; h++) {
            CLK(ck[0], h == 2 * TU); CLK(ck[5], h == 2 * TU + 1);
            mbar_wait(pf, 0);
            CLK(ck[1], h == 2 * TU); CLK(ck[6], h == 2 * TU + 1);
            const float m = __uint_as_float(lds32(ma));
            const uint4 pn = lds128(pa);
            wg_wait0();
#pragma unroll
            for (int i = 0; i < 128; i++) asm volatile("" : "+f"(acc[i]) :: "memory");
            CLK(ck[2], h == 2 * TU); CLK(ck[7], h == 2 * TU + 1);
            if (h == 0) M = m;
            uint32_t b2 = 0x3f803f80u;
            if (__builtin_expect(__any_sync(0xffffffffu, m != M), 0)) {
                const float Mn = fmaxf(M, m), alpha = ex2(M - Mn), beta = ex2(m - Mn);
                M = Mn;
                b2 = pack2(beta, beta);
#pragma unroll
                for (int jj = 0; jj < 32; jj++) { acc[4 * jj] *= alpha; acc[4 * jj + 1] *= alpha; }
            }
            auto mul2 = [](uint32_t x, uint32_t y) { uint32_t r; asm("mul.rn.bf16x2 %0, %1, %2;" : "=r"(r) : "r"(x), "r"(y)); return r; };
            const uint4 p = make_uint4(mul2(pn.x, b2), mul2(pn.y, b2), mul2(pn.z, b2), mul2(pn.w, b2));
            if (tid == 0 && (h & 1)) TRACE_Q(48 + (h >> 1));
            CLK(ck[3], h == 2 * TU); CLK(ck[8], h == 2 * TU + 1);
            wgmma_pv(acc, p, blo, h);
            CLK(ck[4], h == 2 * TU); CLK(ck[9], h == 2 * TU + 1);
            if (lane == 0 && h > 0 && !(h & 1)) mbar_arrive(BAR(EB_UNIT0 + (h >> 1) - 1));
            blo += h == 11 ? -11 * 1024 : 1024;
            pa += (h == 5 || h == 11) ? -5 * 2048 : 2048;
            ma += 128; pf += 8;
            if (h == 2 * NUNITS - 3) {
                mbar_wait(BAR(JD), 0);
                const uint32_t hm = (*(const uint32_t*)(sm + SM_CLS + 16 + warp * 4) >> (g * 4)) ^ ((j >> 6) ? 15u : 0u);
#pragma unroll
                for (int i = 0; i < 4; i++) e1[i] += ((hm >> i) & 1) << 10;
            }
        }
#pragma unroll
        for (int vv = 0; vv < 2; vv++) {
            if (vv && M == 1.f) __trap();
            if (vv) wg_wait0(); else wg_wait1();
#pragma unroll
            for (int i = 0; i < 64; i++) asm volatile("" : "+f"(acc[vv * 64 + i]) :: "memory");
            if (tid == 0 && !vv) TRACE_Q(63);
#pragma unroll
            for (int i = 0; i < 4; i++) {
                const float* a = &acc[vv * 64 + i * 16];
                if (!(WHATIF & 1) || vv) st_x4(e1[i] + i * 8192 + vv * 16, enc(pack2(a[0], a[1])), enc(pack2(a[4], a[5])), enc(pack2(a[8], a[9])), enc(pack2(a[12], a[13])));
            }
        }
        bar_arrive(3, 416);
        if (tid == 0) TRACE_Q(17);
        if (j < NFF) {
            uint4 a[16];
            const uint32_t ad = sb + SM_U + B_DN * 32768 + warp * 8192 + (r8 + 8 * lb4) * 128 + (lb3 ^ r8) * 16;
            uint32_t rl = sb + SM_RED + lane * 16;
            uint32_t* p5 = gs + (B_E5 + warp * 4 + (t >> 1)) * 4096 + j * 16 + (t & 1) * 8 + g;
            pin(rl); pin(p5);
            if (lane == 0) mbar_expect(BAR(MBB), 4);
            auto ldd = [&]() {
#pragma unroll
                for (int s = 0; s < 16; s++) a[s] = ldsm<true>((ad ^ ((s & 3) * 32)) + (s >> 2) * 2048);
            };
            const uint32_t db = BAR(IT_DOWN + (warp >> 1));
            bool hd = false;
            mbar_wait(BAR(MBB), 0);
            const float4 st = ldsf4(sb + SM_RED + 2048);
            hd = __all_sync(0xffffffffu, mbar_test(db, 0));
            if (hd) ldd();
            const float mu = (st.x + st.z) * (1.f / 512.f);
            float rstd;
            asm volatile("rsqrt.approx.ftz.f32 %0, %1;" : "=f"(rstd) : "f"(fmaxf(fmaf(-mu, mu, (st.y + st.w) * (1.f / 512.f)), 0.f) + 1e-5f));
            TK(18);
            mbar_wait(BAR(QB), 1);
            TK(19);
            if (tid == 0) TRACE(25);
            const float4 f0 = ldsf4(rl), f2 = ldsf4(rl + 1024), f1 = ldsf4(rl + 512), f3 = ldsf4(rl + 1536);
            const float gg = fmaf(rstd, fmaf(-mu, f0.z + f2.z, (f0.x + f0.y) + (f2.x + f2.y)), f0.w + f2.w);
            const float uu = fmaf(rstd, fmaf(-mu, f1.z + f3.z, (f1.x + f1.y) + (f3.x + f3.y)), f1.w + f3.w);
            TKD(20, gg);
            const float hh = __fdividef(gg * uu, 1.f + ex2(-gg * fmaf(gg * gg, 0.10294324f, 2.3022082f)));
            uint32_t hb[4];
#pragma unroll
            for (int i = 0; i < 4; i++) hb[i] = pack2(__shfl_sync(0xffffffffu, hh, 2 * t + 8 * i), __shfl_sync(0xffffffffu, hh, 2 * t + 8 * i + 1));
            TKD(21, __uint_as_float(hb[3]));
            if (!hd) { mbar_wait(db, 0); ldd(); }
#pragma unroll
            for (int i = 0; i < 2; i++) {
                uint32_t res = 0;
#pragma unroll
                for (int k = 0; k < 4; k++) {
                    float c[4] = {0.f, 0.f, 0.f, 0.f};
                    const uint4 &x = a[i * 8 + k], &y = a[i * 8 + k + 4];
                    mma(c, x.x, x.y, x.z, x.w, hb[0], hb[1]);
                    mma(c, y.x, y.y, y.z, y.w, hb[2], hb[3]);
                    if (t == k) res = pack2(c[0], c[2]);
                }
                st2_x1(p5 + i * 8192, enc(res));
            }
            TK(22);
            if (tid == 0) { TRACE(27); TRACE_GT(47); }
        } else if (j < J_END) {
            uint4 a[8], b[4];
            float c[4], e[4];
            const bool own = (warp >> 1) == rk;
            const uint32_t xa = sb + SM_FV + (warp & 1) * 64 + g * 8;
            if (lane == 0) mbar_expect(BAR(MBB), own ? 64 : 0);
#pragma unroll
            for (int i = 0; i < 2; i++) {
                ldfrag(b, sb + SM_FS + rk * 512 + i * 256 + t * 16);
                mbar_wait(BAR(IT_X + i), 0);
                const uint32_t ab = sb + SM_U + B_X * 32768 + i * 16384 + a128;
                load8<true>(a, [&](int s) { return ab + s * 2048; });
                mma8(i ? e : c, a, b);
            }
            c[0] += e[0]; c[2] += e[2];
            if (!own) {
                if (t == 0) st_async2(peer_addr(xa, rk ^ 1), c[0], c[2], peer_addr(BAR(MBB), rk ^ 1));
            } else {
                mbar_wait(BAR(MBB), 0);
                const float2 pp = *(const float2*)(sm + (xa - sb));
                const float mine = t ? c[2] + pp.y : c[0] + pp.x, other = shx(mine, 4);
                const uint32_t w = (warp & 1) * 8 + t * 4 + (g >> 1), val = enc(pack2(mine, other));
                if (t < 2 && !(g & 1)) {
                    if (j < J_RED) st2_x1(gs + B_MB * 4096 + (j - NFF) * 16 + w, val);
                    else sts32(sb + SM_FV + 256 + w * 4, val);
                }
                if (j >= J_RED) bar_arrive(7, 320);
                if (lane == 0) TRACE(11);
            }
        }
    } else {
        const int u8 = tid - 128, w8 = warp - 4;
        const int v = w8 >> 2, wq4 = w8 & 3;
        {
            const float c0 = bflo(in1), c1 = bfhi(in1);
            sts32(sb + SM_FS + frag_off(2 * u8), pack2(__fdividef(c0, 1.f + __expf(-c0)), __fdividef(c1, 1.f + __expf(-c1))));
        }
        bar_sync(1, 256);
        asm volatile("barrier.cluster.wait.aligned;" ::: "memory");
        uint4 a[8], b[4]; float c[4];
        if (w8 < 2) {
            ldfrag(b, sb + SM_FS + (j >> 5) * 256 + t * 16);
            mbar_wait(BAR(IT_MODA), 0);
            if (u8 == 0) TRACE(12);
            const uint32_t ab = sb + SM_XA + w8 * 4096 + a16;
            load8<true>(a, [&](int s) { return ab + s * 512; });
            mma8(c, a, b);
            if (t < 2) st2_x1(gs + (B_HA + ((j >> 4) & 1) * 2 + w8) * 4096 + (j >> 5) * 256 + (j & 15) * 16 + t * 8 + g, encf(t ? c[2] : c[0]));
        }
        {
            mbar_wait(BAR(IT_WQ + 2 * v <= NCP ? 1 : IT_WQ + 2 * v), 0); mbar_wait(BAR(IT_WQ + 2 * v + 1 <= NCP ? 1 : IT_WQ + 2 * v + 1), 0);
            const uint32_t ab = sb + SM_U + 4 * 32768 + v * 16384 + a128;
            load8<true>(a, [&](int s) { return ab + s * 2048; });
            if (lane == 0) mbar_arrive(BAR(EB_WQ));
            bar_sync(5, 384);
            if (u8 == 0) TRACE(13);
            ldfrag(b, sb + SM_FV + v * 256 + t * 16);
            mma8(c, a, b);
            if (t < 2) {
                const float qv = t ? c[2] : c[0];
                const uint32_t qa_ = sb + SM_QX + ((rk * 2 + v) * 64 + wq4 * 16 + t * 8 + g) * 4;
                asm volatile("st.async.weak.shared::cluster.mbarrier::complete_tx::bytes.f32 [%0], %1, [%2];"
                             :: "r"(peer_addr(qa_, rk ^ 1)), "f"(qv), "r"(peer_addr(BAR(QB), rk ^ 1)) : "memory");
                sts32(qa_, __float_as_uint(qv));
            }
            __syncwarp();
            if (lane == 0) mbar_expect(BAR(QB), 64);
        }
        {
            mbar_wait(BAR(IT_WUK + v), 0); mbar_wait(BAR(IT_WUK + v + 2), 0);
            const uint32_t ab = sb + SM_U + 5 * 32768 + (w8 * 16 + r8 + 8 * lb3) * 128;
            const uint32_t x16 = (lb4 ^ r8) * 16;
            load8<false>(a, [&](int s) { return ab + (s & 1) * 16384 + (x16 ^ ((s >> 1) * 32)); });
            bar_sync(6, 384);
            if (u8 == 0) TRACE(14);
            b[0] = lds128(sb + SM_FQ + t * 16); b[1] = lds128(sb + SM_FQ + 64 + t * 16);
            float e[4] = {0.f, 0.f, 0.f, 0.f};
            c[0] = c[1] = c[2] = c[3] = 0.f;
#pragma unroll
            for (int k = 0; k < 4; k++) {
                const uint32_t b0 = (k & 1) ? b[k >> 1].z : b[k >> 1].x, b1 = (k & 1) ? b[k >> 1].w : b[k >> 1].y;
                mma(c, a[2 * k].x, a[2 * k].y, a[2 * k].z, a[2 * k].w, b0, b1);
                mma(e, a[2 * k + 1].x, a[2 * k + 1].y, a[2 * k + 1].z, a[2 * k + 1].w, b0, b1);
            }
            const float mine = ((t & 1) ? ((t & 2) ? e[2] : e[0]) : ((t & 2) ? c[2] : c[0])) * 0.12751743f;
            const float other = shx(mine, 4);
            if (!(g & 1)) st2_x1(gs + (B_QA + rk * 8 + ((j >> 1) & 1) * 4 + (j >> 5)) * 4096 + w8 * 128 + ((j >> 2) & 7) * 16 + (g >> 1) * 4 + t, enc(pack2(mine, other)));
            if (u8 == 0) TRACE(15);
        }
        const uint32_t cls = ldcls();
        __nanosleep(QA_DELAY);
        {
            uint4 qb[8];
            const uint32_t* pq = gs + near_off(B_QA + rk * 8 + wq4, cls) + lane * 4;
            const uint32_t* pq2 = gs + near_off(B_QA + rk * 8 + 4 + wq4, cls) + lane * 4;
            if (lane == 0) {
                mbar_expect(BAR(QT), 4096);
                asm volatile("cp.async.bulk.shared::cluster.global.mbarrier::complete_tx::bytes [%0], [%1], 4096, [%2];"
                             :: "r"(sb + SM_U + 5 * 32768 + w8 * 4096), "l"(gs + near_off(B_QA + rk * 8 + w8, cls)), "r"(BAR(QT)) : "memory");
            }
            const uint32_t qs = sb + SM_U + 5 * 32768 + wq4 * 4096 + lane * 16;
            mbar_wait(BAR(QT), 0);
#pragma unroll
            for (int i = 0; i < 8; i++) { a[i] = lds128(qs + i * 512); qb[i] = lds128(qs + 16384 + i * 512); }
            poll<512, QA_SLEEP, true>(a, pq);
            poll<512, QA_SLEEP, true>(qb, pq2);
            if (lane == 0) mbar_arrive(BAR(EB_WUK));
            auto add2 = [](uint32_t x, uint32_t y) { uint32_t r; asm("add.rn.bf16x2 %0, %1, %2;" : "=r"(r) : "r"(x), "r"(y)); return r; };
#pragma unroll
            for (int i = 0; i < 8; i++) a[i] = make_uint4(add2(a[i].x, qb[i].x), add2(a[i].y, qb[i].y), add2(a[i].z, qb[i].z), add2(a[i].w, qb[i].w));
        }
        if (u8 == 0) TRACE(8);
        {
            float m = -INFINITY, l = 0.f;
            uint32_t xl = sb + SM_XB + w8 * 2048 + lane * 16, xr = peer_addr(xl, rk ^ 1), bsr = peer_addr(BAR(SF0 + v), rk ^ 1);
            uint32_t pa = sb + SM_XA + v * 2048 + wq4 * 512 + lane * 16, ma = sb + SM_MX + v * 128 + (wq4 * 8 + g) * 4;
            uint32_t fb = BAR(IT_CKV + v * 2), sf = BAR(SF0 + v);
            uint32_t dlo = __reduce_or_sync(0xffffffffu, (((sb + SM_U + v * 16384) & 0x3FFFFu) >> 4) | 0x10000u);
            uint32_t ck[9] = {0, 0, 0, 0, 0, 0, 0, 0, 0};
            if (STAG && v) __nanosleep(STAG);
#pragma unroll 1
            for (int n = 0; n < NUNITS; n++) {
                CLK(ck[0], n == TU); CLK(ck[8], n == TU + 1);
                float d[2][16], sc[8];
#pragma unroll
                for (int i = 0; i < 2; i++) {
                    mbar_wait(fb + i * 8, 0);
                    if (i == 0) CLK(ck[1], n == TU);
                    wg_fence();
#pragma unroll
                    for (int s = 0; s < 8; s++) wgmma_rs_n32(d[i], a[s], (0x40000080ull << 32) | (dlo + i * 512 + (s >> 2) * 64 + (s & 3) * 2), s);
                    wg_commit();
                }
                CLK(ck[2], n == TU);
#pragma unroll
                for (int i = 0; i < 2; i++) {
                    if (i) wg_wait0(); else wg_wait1();
#pragma unroll
                    for (int k = 0; k < 16; k++) asm volatile("" : "+f"(d[i][k]) :: "memory");
                    sc[4 * i] = d[i][0] + d[i][6]; sc[4 * i + 1] = d[i][1] + d[i][7]; sc[4 * i + 2] = d[i][8] + d[i][14]; sc[4 * i + 3] = d[i][9] + d[i][15];
                    asm volatile("st.async.weak.shared::cluster.mbarrier::complete_tx::bytes.v4.f32 [%0], {%1, %2, %3, %4}, [%5];"
                                 :: "r"(xr + i * 1024), "f"(sc[4 * i]), "f"(sc[4 * i + 1]), "f"(sc[4 * i + 2]), "f"(sc[4 * i + 3]), "r"(bsr) : "memory");
                }
                CLK(ck[3], n == TU);
                if (u8 == 128) TRACE_Q(56 + (n < 6 ? n : -40));
                if (n >= 3) mbar_wait(BAR(EB_UNIT0 + n - 3), 0);
                dlo += n == 5 ? -5 * 2048 : 2048;
                fb += 32; xr ^= 512; bsr += 16;
                pin(fb); pin(xr); pin(bsr);
                CLK(ck[4], n == TU);
                mbar_wait(sf, 0);
                CLK(ck[5], n == TU);
                const float4 x = ldsf4(xl), y = ldsf4(xl + 1024);
                sc[0] += x.x; sc[1] += x.y; sc[2] += x.z; sc[3] += x.w; sc[4] += y.x; sc[5] += y.y; sc[6] += y.z; sc[7] += y.w;
                float pr[8];
#pragma unroll
                for (int i = 0; i < 8; i++) pr[i] = ex2(sc[i] - m);
                float mx = fmaxf(fmaxf(fmaxf(sc[0], sc[1]), fmaxf(sc[2], sc[3])), fmaxf(fmaxf(sc[4], sc[5]), fmaxf(sc[6], sc[7])));
                if (__builtin_expect(__any_sync(0xffffffffu, mx > m), 0)) {
                    mx = fmaxf(mx, shx(mx, 1));
                    mx = fmaxf(mx, shx(mx, 2));
                    const float mn = fmaxf(m, ceilf(mx * 0.0625f) * 16.f);
                    l *= ex2(m - mn);
                    m = mn;
#pragma unroll
                    for (int i = 0; i < 8; i++) pr[i] = ex2(sc[i] - m);
                }
                CLK(ck[6], n == TU);
                stsf(ma, m);
                asm volatile("st.shared.v4.u32 [%0], {%1, %2, %3, %4};" :: "r"(pa), "r"(pack2(pr[0], pr[1])), "r"(pack2(pr[2], pr[3])),
                             "r"(pack2(pr[4], pr[5])), "r"(pack2(pr[6], pr[7])) : "memory");
                __syncwarp();
                if (lane == 0) mbar_arrive(sf + (PF0 - SF0) * 8);
                CLK(ck[7], n == TU);
                l += ((pr[0] + pr[1]) + (pr[2] + pr[3])) + ((pr[4] + pr[5]) + (pr[6] + pr[7]));
                xl ^= 512; sf += 16; ma += 256; pa += (n == 2 || n == 5) ? -8192 : 4096;
            }
            l += shx(l, 1);
            l += shx(l, 2);
            float2* mlx = (float2*)(sm + SM_MX + 2048) + wq4 * 8 + g;
            if (v == 0) { *mlx = make_float2(m, l); bar_arrive(11, 256); }
            else {
                mbar_wait(BAR(JD), 0);
                bar_sync(11, 256);
                const float2 o = *mlx;
                const float mn = fmaxf(m, o.x);
                l = l * ex2(m - mn) + o.y * ex2(o.x - mn);
                if ((wq4 >> 1) == rk) st_x4(gs + (B_ML + wq4 * 8 + g) * 4096 + (t >> 1) * 1024 + (j >> 1) * 8 + (t & 1) * 4, encf(mn), encf(l), 1u, 1u);
            }
        }
        const int pi = j < NFF ? rk * 128 + w8 * 16 + (lane & 15) : ((j - J_RED) & 15) * 16 + v * 8 + lb4 * 4 + wq4;
        const uint32_t xw = *(const uint32_t*)(xin + 2 * pi);
        {
            const uint32_t ab = sb + SM_U + B_WUV * 32768 + v * 4096 + a128;
            uint32_t pa = sb + SM_PB + wq4 * 320 + frag_off(64 * v + 32 * (g >> 2) + 16 * (t & 1) + 8 * (t >> 1) + 2 * (g & 3));
            uint32_t fa = sb + SM_PB + g * 320 + t * 16;
            const uint32_t* pe = gs + G_E1 + j * 8192 + (w8 >> 1) * 2048 + ((((cls >> 1) ^ (w8 >> 1)) & 1) << 10) + (((w8 & 1) * 16 + t) * 8 + g) * 4;
            uint32_t* p2 = gs + (B_E2 + (j >> 4)) * 4096 + (t >> 1) * 1024 + (j & 12) * 64 + w8 * 32 + (j & 3) * 8 + (g & 6) + (t & 1);
            pin(pa); pin(fa); pin(pe); pin(p2);
            const uint32_t mk = (g & 1) ? 0xffff0000u : 0x0000ffffu, m0 = (g & 2) ? 0u : mk, m1 = (g & 2) ? mk : 0u;
            uint4 pv[4];
            bool hv = false;
            bar_sync(3, 416);
            TK(0);
            uint4 wa = lds128(sb + SM_W + (wq4 * 4 + t) * 16);
            uint32_t wb[8] = {wa.x & m0, wa.x & m1, wa.y & m0, wa.y & m1, wa.z & m0, wa.z & m1, wa.w & m0, wa.w & m1};
            pv[0] = pv[1] = pv[2] = pv[3] = make_uint4(0u, 0u, 0u, 0u);
            if ((WHATIF & 1) && g < 4) pv[0] = pv[1] = pv[2] = pv[3] = make_uint4(1u, 1u, 1u, 1u);
            poll<512, E1_SLEEP, true>(pv, pe, [&]() {
                if (!hv) {
                    hv = __all_sync(0xffffffffu, mbar_test(BAR(IT_WUV + t), 0));
                    if (hv) load8<true>(a, [&](int s) { return ab + (s >> 1) * 8192 + (s & 1) * 2048; });
                }
            });
            if (lane == 0) TRACE_Q(48 + w8);
            if (u8 == 0) TRACE_Q(18);
            TK(1);
            float lo, hi2;
            float2 inv;
#pragma unroll 1
            for (int pass = 0;; pass++) {
                float e[4][4];
#pragma unroll
                for (int i = 0; i < 4; i++) {
                    e[i][0] = e[i][1] = e[i][2] = e[i][3] = 0.f;
                    mma(e[i], pv[i].x, pv[i].y, pv[i].z, pv[i].w, wb[2 * i], wb[2 * i + 1]);
                }
                const float r0 = (t & 2) ? (e[0][2] + e[1][2]) + (e[2][2] + e[3][2]) : (e[0][0] + e[1][0]) + (e[2][0] + e[3][0]);
                const float r1 = (t & 2) ? (e[0][3] + e[1][3]) + (e[2][3] + e[3][3]) : (e[0][1] + e[1][1]) + (e[2][1] + e[3][1]);
                const uint32_t hi = pack2(r0, r1);
                sts32(pa, hi); sts32(pa + 1280, pack2(r0 - bflo(hi), r1 - bfhi(hi)));
                if (!hv) {
#pragma unroll 1
                    for (int i = 0; i < 4; i++) mbar_wait(BAR(IT_WUV + i), 0);
                    load8<true>(a, [&](int s) { return ab + (s >> 1) * 8192 + (s & 1) * 2048; });
                    hv = true;
                }
                TK(2);
                bar_sync(1, 256);
                TK(3);
                if (u8 == 0) TRACE(19);
                ldfrag(b, fa);
                mma8(c, a, b);
                TK(4);
                mbar_wait(BAR(WR), 0);
                asm volatile("ld.shared.v2.f32 {%0, %1}, [%2];" : "=f"(inv.x), "=f"(inv.y) : "r"(sb + SM_FQ) : "memory");
                TK(5);
                quad_pair(c[0] + c[1], c[2] + c[3], t, lo, hi2);
                if (__builtin_expect(__all_sync(0xffffffffu, pass || __float_as_uint(inv.y) == 0), 1)) break;
                wa = lds128(sb + SM_W2 + (wq4 * 4 + t) * 16);
                wb[0] = wa.x & m0; wb[1] = wa.x & m1; wb[2] = wa.y & m0; wb[3] = wa.y & m1; wb[4] = wa.z & m0; wb[5] = wa.z & m1; wb[6] = wa.w & m0; wb[7] = wa.w & m1;
                bar_sync(1, 256);
            }
            if (!(g & 1)) st_x1(p2, enc(pack2(lo * inv.x, hi2 * inv.x)));
            bar_arrive(4, 288);
            TK(6);
            if (u8 == 0) TRACE(20);
        }
        uint32_t mb[3] = {0u, 0u, 0u};
        const uint32_t* pm = gs + near_off(B_MB, cls) + pi;
        pin(pm);
        if (j < NFF) poll_start<1024>(mb, pm);
        uint4 a2[8];
        TK(7); TK(8); TK(9); TK(10);
        if (v == 0) {
            const uint32_t ab = sb + SM_U + B_WO * 32768 + a128;
            uint32_t* p3 = gs + (B_E3 + ((j >> 1) & 3)) * 4096 + (t >> 1) * 1024 + (rk * 2 + (wq4 >> 1)) * 256 + (j >> 3) * 16 + (wq4 & 1) * 8 + (t & 1) * 4 + (g >> 1);
            pin(p3);
            uint2 bb[8];
#pragma unroll
            for (int i = 0; i < 8; i++) bb[i] = make_uint2(0u, 0u);
            bool ho = false;
            auto ldo = [&]() { load8<true>(a, [&](int s) { return ab + s * 2048; }); load8<true>(a2, [&](int s) { return ab + 16384 + s * 2048; }); };
            TK(7);
            poll<128, E2_SLEEP, true>(bb, gs + near_off(B_E2 + (j >> 4), cls) + (((j >> 3) & 1) * 2 + lb4) * 256 + (lane & 15) * 2, [&]() {
                if (!ho) {
                    ho = __all_sync(0xffffffffu, mbar_test(BAR(IT_WO + t), 0));
                    if (ho) ldo();
                }
            });
            if (!ho) {
#pragma unroll 1
                for (int i = 0; i < 4; i++) mbar_wait(BAR(IT_WO + i), 0);
                ldo();
            }
            TK(8);
            if (u8 == 0) TRACE(21);
            float e[4][4];
#pragma unroll
            for (int s = 0; s < 16; s++) {
                const uint4& x = (s & 2) ? a2[(s >> 2) * 2 + (s & 1)] : a[(s >> 2) * 2 + (s & 1)];
                const uint2& y = bb[(s >> 2) * 2 + (s & 1)];
                if (s < 4) e[s][0] = e[s][1] = e[s][2] = e[s][3] = 0.f;
                mma(e[s & 3], x.x, x.y, x.z, x.w, y.x, y.y);
            }
            TK(9); TK(10);
            float lo, hi;
            quad_pair((t & 2) ? (e[2][0] + e[3][0]) + (e[2][1] + e[3][1]) : (e[0][0] + e[1][0]) + (e[0][1] + e[1][1]),
                      (t & 2) ? (e[2][2] + e[3][2]) + (e[2][3] + e[3][3]) : (e[0][2] + e[1][2]) + (e[0][3] + e[1][3]), t, lo, hi);
            if (!(g & 1)) st_x1(p3, enc(pack2(lo, hi)));
            bar_arrive(1, 256);
            if (u8 == 0) TRACE(22);
        } else bar_sync(1, 256);
        TK(11);
        if (j < NFF) {
            const uint32_t* p3 = gs + near_off(B_E3 + rk * 2 + v, cls) + wq4 * 256 + lane;
            uint32_t za = sb + SM_FZ + lb4 * 576 + frag_off(w8 * 32 + (lane & 15) * 2);
            uint32_t fa = sb + SM_FZ + (g & 3) * 576 + lb4 * 256 + t * 16, ya = sb + SM_Y + u8 * 4;
            poll<1024, MB_SLEEP, true>(mb, pm);
            const uint32_t kk = pack2(1.f + bflo(mb[2]), 1.f + bfhi(mb[2]));
            sts32(za + 2 * 576, lb4 ? mb[1] : kk);
            uint32_t e3[8] = {0u, 0u, 0u, 0u, 0u, 0u, 0u, 0u};
            uint32_t ra = peer_addr(sb + SM_RED + (rk * 2 + v) * 512 + ((wq4 & 1) * 16 + (t >> 1) * 8 + g) * 16 + (t & 1) * 8, wq4 >> 1), tbo = peer_addr(BAR(QB), wq4 >> 1);
            pin(za); pin(fa); pin(ya); pin(ra); pin(tbo);
            if (lane == 0) mbar_expect(BAR(QB), 256);
            TK(12);
            const uint32_t gb = BAR(IT_X + v * 2), ab = sb + SM_U + (B_X + v) * 32768 + a128;
            bool early = false, early2 = false;
            auto ldw = [&]() {
                if (!early) {
                    early = __all_sync(0xffffffffu, mbar_test(gb, 0));
                    if (early) load8<true>(a, [&](int s) { return ab + s * 2048; });
                }
                if (!early2) {
                    early2 = __all_sync(0xffffffffu, mbar_test(gb + 8, 0));
                    if (early2) load8<true>(a2, [&](int s) { return ab + 16384 + s * 2048; });
                }
            };
            poll<128, E3_SLEEP, true>(e3, p3, ldw);
            TK(13);
            if (u8 == 0) TRACE(23);
            const float s0 = sumlo(e3), s1 = sumhi(e3);
            const float y0 = fmaf(bflo(mb[0]), s0 + shx(s0, 16), bflo(xw)), y1 = fmaf(bfhi(mb[0]), s1 + shx(s1, 16), bfhi(xw));
            stsf(ya, lb4 ? y1 : y0);
            const float z0 = y0 * bflo(kk), z1 = y1 * bfhi(kk);
            const uint32_t zh = pack2(z0, z1);
            sts32(za, lb4 ? pack2(z0 - bflo(zh), z1 - bfhi(zh)) : zh);
            TK(14);
            bar_sync(7, 288);
            TK(15);
            if (u8 == 0) TRACE(24);
            ldfrag(b, fa);
            if (!early) { mbar_wait(gb, 0); load8<true>(a, [&](int s) { return ab + s * 2048; }); }
            {
                float e[4][4];
#pragma unroll
                for (int s = 0; s < 16; s++) {
                    if (s == (SPLIT4 ? 8 : 0) && !early2) { mbar_wait(gb + 8, 0); load8<true>(a2, [&](int q) { return ab + 16384 + q * 2048; }); }
                    const int z = SPLIT4 ? s : (s & 1) | (s & 2) << 2 | (s >> 2) << 1;
                    const uint4& x = z < 8 ? a[z] : a2[z & 7];
                    const uint4& y = b[(z >> 1) & 3];
                    float (&d)[4] = e[(z >> 3) * 2 + (z & 1)];
                    if (!(z & 6)) d[0] = d[1] = d[2] = d[3] = 0.f;
                    mma(d, x.x, x.y, x.z, x.w, (s & 1) ? y.z : y.x, (s & 1) ? y.w : y.y);
                }
                const bool hi = t >> 1;
                const float k0 = hi ? e[2][2] + e[3][2] : e[0][0] + e[1][0], k1 = hi ? e[2][3] + e[3][3] : e[0][1] + e[1][1];
                const float o0 = hi ? e[2][0] + e[3][0] : e[0][2] + e[1][2], o1 = hi ? e[2][1] + e[3][1] : e[0][3] + e[1][3];
                TKD(16, o0);
                st_async2(ra, k0 + shx(o0, 2), k1 + shx(o1, 2), tbo);
            }
            TK(17);
        } else if (j >= J_RED && j < J_END) {
            uint32_t ga[1], e3[1];
            poll<0, MB_SLEEP>(ga, pm);
            poll<0, 100>(e3, gs + near_off(B_E3 + (pi >> 6), cls) + (pi & 48) * 16 + (lane & 15) * 16 + (pi & 15));
            if (E5_DELAY) __nanosleep(E5_DELAY);
            float y0 = bflo(e3[0]), y1 = bfhi(e3[0]);
#pragma unroll
            for (int o = 8; o; o >>= 1) { y0 += shx(y0, o); y1 += shx(y1, o); }
            y0 = fmaf(bflo(ga[0]), y0, bflo(xw)); y1 = fmaf(bfhi(ga[0]), y1, bfhi(xw));
            bar_sync(7, 320);
            const uint32_t gb = lds32(sb + SM_FV + 256 + (pi & 15) * 4);
            uint32_t* po = (uint32_t*)out + pi;
            pin(po);
            const uint32_t nz = lane < NFF / 2 ? 0u : 0x80008000u;
            uint2 yv[2] = {make_uint2(nz, nz), make_uint2(nz, nz)};
            poll<NFF * 32, E5_SLEEP, true>(yv, gs + near_off(B_E5 + j - J_RED, cls) + lane * 16 + w8 * 2);
            if (u8 == 0) TRACE(26);
            const float l0 = bflo(yv[0].x) + bflo(yv[1].x), h0 = bfhi(yv[0].x) + bfhi(yv[1].x);
            const float l1 = bflo(yv[0].y) + bflo(yv[1].y), h1 = bfhi(yv[0].y) + bfhi(yv[1].y);
            float s0 = (lb4 ? h0 : l0) + shx(lb4 ? l0 : h0, 16), s1 = (lb4 ? h1 : l1) + shx(lb4 ? l1 : h1, 16);
#pragma unroll
            for (int o = 8; o; o >>= 1) { s0 += shx(s0, o); s1 += shx(s1, o); }
            if (!(lane & 15)) *po = pack2(fmaf(bflo(gb), s0, y0), fmaf(bfhi(gb), s1, y1));
            if (u8 == 0) TRACE(27);
        }
    }
}

typedef CUresult (*EncFn)(CUtensorMap*, CUtensorMapDataType, cuuint32_t, void*, const cuuint64_t*, const cuuint64_t*,
                          const cuuint32_t*, const cuuint32_t*, CUtensorMapInterleave, CUtensorMapSwizzle,
                          CUtensorMapL2promotion, CUtensorMapFloatOOBfill);

void make_map(EncFn enc_fn, CUtensorMap* m, const void* p, cuuint64_t d0, cuuint64_t d1, cuuint64_t d2, cuuint64_t d3,
              cuuint64_t s1, cuuint64_t s2, cuuint64_t s3, cuuint32_t b0, cuuint32_t b1, cuuint32_t b2, cuuint32_t b3, CUtensorMapSwizzle sw) {
    const cuuint64_t dims[4] = {d0, d1, d2, d3}, strides[3] = {s1, s2, s3};
    const cuuint32_t box[4] = {b0, b1, b2, b3}, es[4] = {1, 1, 1, 1};
    enc_fn(m, CU_TENSOR_MAP_DATA_TYPE_BFLOAT16, 4, (void*)p, dims, strides, box, es,
           CU_TENSOR_MAP_INTERLEAVE_NONE, sw, CU_TENSOR_MAP_L2_PROMOTION_L2_64B, CU_TENSOR_MAP_FLOAT_OOB_FILL_NONE);
}

uint32_t* scratch = nullptr;

struct Tune { const char* win; const char* late; int tau, t_off; const char* tail[3][4]; };
Tune tune = {"66666666655555555555555555555555544444444",
             "00000000000000000999999999999999999999999", 320, -240,
             {{"VVVVOOOOguguDD", "zzzzzzzzzzzzzz", "88888888999988", "2fffdbbbl444td"},
              {"VMVMVVOOOO", "zzzzzzzzzz", "9999998888", "2999998ddd"},
              {"VVVVOOOOMM", "zzzzzzzzzz", "8888888888", "eaaa9hhhes"}}};
bool ready = false;

}

extern "C" void kernel_launch(void* const* d_in, const int* in_sizes, int n_in, void* d_out, int out_size) {
    (void)in_sizes; (void)n_in; (void)out_size;
    static Maps maps;
    static const void* cached[12] = {};
    bool same = ready;
    for (int i = 0; i < 12 && same; i++) same = cached[i] == d_in[i];
    if (!same) {
        void* fn = nullptr;
        cudaDriverEntryPointQueryResult qr;
        cudaGetDriverEntryPoint("cuTensorMapEncodeTiled", &fn, cudaEnableDefault, &qr);
        EncFn e = (EncFn)fn;
        const CUtensorMapSwizzle S128 = CU_TENSOR_MAP_SWIZZLE_128B;
        make_map(e, &maps.m[MP_WQ], d_in[2], 64, 512, 64, 1, 8192, 128, 8192, 64, 64, 1, 1, S128);
        make_map(e, &maps.m[MP_WUK], d_in[3], 64, 512, 64, 1, 8192, 128, 8192, 64, 64, 1, 1, S128);
        make_map(e, &maps.m[MP_CKV], d_in[1], 64, 8, 8, 4096, 1024, 128, 8192, 64, 8, 4, 2, S128);
        make_map(e, &maps.m[MP_MODB], d_in[11], 3072, 512, 1, 1, 6144, 6144, 6144, 64, 128, 1, 1, S128);
        make_map(e, &maps.m[MP_WUV], d_in[4], 64, 512, 64, 1, 8192, 128, 8192, 64, 32, 2, 1, S128);
        make_map(e, &maps.m[MP_WO], d_in[5], 512, 4096, 1, 1, 1024, 1024, 1024, 64, 64, 1, 1, S128);
        make_map(e, &maps.m[MP_GATE], d_in[7], 1792, 512, 1, 1, 3584, 3584, 3584, 64, 128, 1, 1, S128);
        make_map(e, &maps.m[MP_UP], d_in[8], 1792, 512, 1, 1, 3584, 3584, 3584, 64, 128, 1, 1, S128);
        make_map(e, &maps.m[MP_DOWN], d_in[9], 64, 1792, 8, 1, 1024, 128, 1024, 64, 32, 4, 1, S128);
        for (int r = 0; r < 3; r++) {
            int ids[56], cnt[128] = {}, tn = tune.t_off - (W0 - 1) * tune.tau;
            uint2* sc = maps.sched[r];
            auto dig = [](char ch) { return ch >= 'a' ? ch - 'a' + 10 : ch - '0'; };
            for (int i = 0; i < 56; i++) sc[i] = make_uint2(0u, 0u);
            for (int i = 0;; i++) {
                int id = i, buf, dep, w, wl;
                if (i < IT_WUV) {
                    const int u = (i - IT_CKV) >> 2;
                    buf = i < IT_CKV ? 4 + ((i - 1) >> 2) : u % 6;
                    dep = i < IT_CKV || u < 4 ? -1 : u < 6 ? EB_WQ + u - 4 : EB_UNIT0 + u - 6;
                    w = dig(tune.win[i]); wl = dig(tune.late[i]);
                    if (i) tn += tune.tau;
                } else {
                    const char ch = tune.tail[r][0][i - IT_WUV];
                    if (!ch) break;
                    buf = ch == 'V' ? B_WUV : ch == 'O' ? B_WO : ch == 'D' ? B_DN : ch == 'u' ? B_X + 1 : B_X;
                    id = (ch == 'V' ? IT_WUV : ch == 'O' ? IT_WO : ch == 'D' ? IT_DOWN : ch == 'u' ? IT_X + 2 : IT_X) + cnt[(int)ch]++;
                    dep = EB_UNIT0 + (buf < 2 ? buf + 6 : buf);
                    w = dig(tune.tail[r][1][i - IT_WUV]); wl = dig(tune.tail[r][2][i - IT_WUV]);
                    tn += 32 * dig(tune.tail[r][3][i - IT_WUV]);
                }
                if (id < IT_X ? (id - 1) & 3 : (id - IT_X) & 1) dep = -1;
                ids[i] = id;
                auto back = [&](int d) { return i < d ? 0 : (ids[i - d] && ids[i - d] <= NCP ? 1 : ids[i - d]) + 1; };
                sc[i].x = id | (buf * 4 + (id < IT_X ? (id - 1) & 3 : ((id - IT_X) & 1) * 2)) << 6 | (dep + 1) << 11 | (w > 32 ? NEVER + 1 : back(w)) << 18 | (wl ? back(wl) : 0) << 25;
                sc[i].y = tn;
            }
        }
        cudaGetSymbolAddress((void**)&scratch, g_scratch);
        scratch = (uint32_t*)(((uintptr_t)scratch + (2u << 20) - 1) & ~(uintptr_t)((2u << 20) - 1));
        cudaFuncSetAttribute(fused_kernel, cudaFuncAttributeMaxDynamicSharedMemorySize, SM_TOTAL);
        for (int i = 0; i < 12; i++) cached[i] = d_in[i];
        ready = true;
    }
    const First f = {{(const uint8_t*)d_in[2], (const uint8_t*)d_in[11]}, {(const __nv_bfloat16*)d_in[0], (const __nv_bfloat16*)d_in[10]}};
    fused_kernel<<<NCTA, NTHREADS, SM_TOTAL>>>(f, (__nv_bfloat16*)d_out, scratch, maps);
}
```

```cpp
#include <cuda_runtime.h>
#include <cuda_bf16.h>
#include <cuda.h>
#include <stdint.h>
#include <limits.h>

namespace {

constexpr int NCTA = 128;
constexpr int NTHREADS = 512;
constexpr int NUNITS = 8;
constexpr int NFF = 56, J_RED = 104, J_END = 120;
constexpr uint32_t SPIN_LIMIT = 1u << 22;

#define E1_EARLY 50
#define STAG 300
#define NUMA 1
#define NPROBE 3
#define NCP 2
#define W0 4
#define RD_ITEM 15
#define JAN_SLEEP 100
#define RD_SLEEP 400
#define HA_DELAY 200
#define H_SLEEP 100
#define QA_DELAY 600
#define QA_SLEEP 200
#define ML_DELAY 300
#define E1_SLEEP 50
#define MB_SLEEP 100
constexpr int B_WUV = 2, B_WO = 3, B_X = 4  , B_DN = 0;

constexpr int SM_U = 0;
constexpr int SM_XA = 6 * 32768;
constexpr int SM_XB = SM_XA + 12288;
constexpr int SM_MX = SM_XB + 16384;
constexpr int SM_FZ = SM_XB + 8192;
constexpr int SM_PB = SM_XB;
constexpr int SM_Y = SM_XB + 12288;
constexpr int SM_RED = SM_XB + 4096;
constexpr int SM_FS = SM_XB + 20480;
constexpr int SM_FV = SM_FS + 1024;
constexpr int SM_QX = SM_XA + 8192;
constexpr int SM_FQ = SM_FV + 512;
constexpr int SM_CLS = SM_FQ + 128;
constexpr int SM_W = SM_FQ + 256;
constexpr int SM_W2 = SM_MX + 2304;
constexpr int SM_SCR = SM_XA + 9216;
constexpr int SM_TR = SM_XB + 19456;
constexpr int SM_BAR = SM_W + 256;
constexpr int SM_TOTAL = SM_BAR + 1024;
static_assert(SM_TOTAL <= 232448, "smem");

enum { IT_MODA = 0, IT_WQ = 1, IT_WUK = 5, IT_CKV = 9, IT_WUV = 41, IT_WO = 45, IT_X = 49  , IT_DOWN = 53, NITEMS = 55,
       NEVER = 63,
       SF0 = 64,
       PF0 = 80,
       EB_UNIT0 = 96, MBB = 103,
       EB_WQ = 104, EB_WUK, QT, QB, JD, WR };

enum { MP_WQ = 0, MP_WUK, MP_CKV, MP_MODB, MP_WUV, MP_WO, MP_GATE, MP_UP, MP_DOWN, NMAPS };
struct First { const uint8_t* w[2]; const __nv_bfloat16* v[2]; };
struct Maps { CUtensorMap m[NMAPS]; uint2 sched[3][56]; };

enum { B_HA = 0,
       B_MB = 6,
       B_RD = 7,
       B_E2 = 8,
       B_QA = 16,
       B_ML = 32,
       B_E5 = 64,
       B_E3 = 80,
       B_PR = 96,
       B_TR = 100 };
constexpr int G_E1 = 1 << 19;
constexpr int G_TR = B_TR * 4096;
__device__ __align__(1024) uint32_t g_scratch[(8 << 20) / 4];

#define TRACE(slot) do {} while (0)
#define TRACE_Q(slot) do {} while (0)
#define TRACE_GT(slot) do {} while (0)

__device__ __forceinline__ uint32_t s2u(const void* p) { return (uint32_t)__cvta_generic_to_shared(p); }
__device__ __forceinline__ void mbar_init(uint32_t b, int c) { asm volatile("mbarrier.init.shared::cta.b64 [%0], %1;" :: "r"(b), "r"(c) : "memory"); }
__device__ __forceinline__ void mbar_expect(uint32_t b, uint32_t bytes) { asm volatile("mbarrier.arrive.expect_tx.shared::cta.b64 _, [%0], %1;" :: "r"(b), "r"(bytes) : "memory"); }
__device__ __forceinline__ void mbar_arrive(uint32_t b) { asm volatile("mbarrier.arrive.shared::cta.b64 _, [%0];" :: "r"(b) : "memory"); }
__device__ __forceinline__ void mbar_wait(uint32_t b, uint32_t ph) {
    asm volatile("{\n.reg .pred p;\nW: mbarrier.try_wait.parity.shared::cta.b64 p, [%0], %1;\n@!p bra W;\n}" :: "r"(b), "r"(ph) : "memory");
}
__device__ __forceinline__ void mbar_waitb(uint32_t b, uint32_t ph) {
    asm volatile("{\n.reg .pred p;\n.reg .u32 n;\nmov.u32 n, 0;\n"
                 "W: mbarrier.try_wait.parity.shared::cta.b64 p, [%0], %1;\n@p bra D;\n"
                 "add.u32 n, n, 1;\nsetp.lt.u32 p, n, 0x100000;\n@p bra W;\ntrap;\nD:\n}" :: "r"(b), "r"(ph) : "memory");
}
__device__ __forceinline__ uint32_t mbar_test(uint32_t b, uint32_t ph) {
    uint32_t ok;
    asm volatile("{\n.reg .pred p;\nmbarrier.test_wait.parity.shared::cta.b64 p, [%1], %2;\nselp.u32 %0, 1, 0, p;\n}" : "=r"(ok) : "r"(b), "r"(ph) : "memory");
    return ok;
}
__device__ __forceinline__ void bar_sync(int id, int n) { asm volatile("bar.sync %0, %1;" :: "r"(id), "r"(n) : "memory"); }
__device__ __forceinline__ void bar_arrive(int id, int n) { asm volatile("bar.arrive %0, %1;" :: "r"(id), "r"(n) : "memory"); }
__device__ __forceinline__ uint32_t peer_addr(uint32_t a, uint32_t rank) { uint32_t r; asm("mapa.shared::cluster.u32 %0, %1, %2;" : "=r"(r) : "r"(a), "r"(rank)); return r; }
__device__ __forceinline__ void st_async1(uint32_t a, float x, uint32_t bar) {
    asm volatile("st.async.weak.shared::cluster.mbarrier::complete_tx::bytes.f32 [%0], %1, [%2];" :: "r"(a), "f"(x), "r"(bar) : "memory");
}
__device__ __forceinline__ void st_async2(uint32_t a, float x, float y, uint32_t bar) {
    asm volatile("st.async.weak.shared::cluster.mbarrier::complete_tx::bytes.v2.f32 [%0], {%1, %2}, [%3];" :: "r"(a), "f"(x), "f"(y), "r"(bar) : "memory");
}
__device__ __forceinline__ uint32_t gtime() { uint32_t t; asm volatile("mov.u32 %0, %%globaltimer_lo;" : "=r"(t)); return t; }
__device__ __forceinline__ void fence_gpu() { asm volatile("fence.acq_rel.gpu;" ::: "memory"); }

__device__ __forceinline__ uint32_t enc(uint32_t b) { uint32_t r; asm("max.u32 %0, %1, 1;" : "=r"(r) : "r"(b)); return r; }
__device__ __forceinline__ uint32_t encf(float f) { return enc(__float_as_uint(f)); }
__device__ __forceinline__ void st_x1(uint32_t* p, uint32_t v) { asm volatile("st.relaxed.gpu.global.u32 [%0], %1;" :: "l"(p), "r"(v) : "memory"); }
__device__ __forceinline__ void st_x4(void* p, uint32_t a, uint32_t b, uint32_t c, uint32_t d) {
    asm volatile("st.relaxed.gpu.global.v4.u32 [%0], {%1, %2, %3, %4};" :: "l"(p), "r"(a), "r"(b), "r"(c), "r"(d) : "memory");
}
__device__ __forceinline__ void st2_x1(uint32_t* p, uint32_t v) { st_x1(p, v); st_x1(p + 1024, v); }
__device__ __forceinline__ void st2_x4(uint32_t* p, uint32_t a, uint32_t b, uint32_t c, uint32_t d) { st_x4(p, a, b, c, d); st_x4(p + 1024, a, b, c, d); }
__device__ __forceinline__ int near_off(int b, uint32_t cls) { return b * 4096 + (((__popc(b & 0x2C) ^ cls) & 1) << 10); }
__device__ __forceinline__ void ld_x(uint32_t& v, const void* p) { asm volatile("ld.relaxed.gpu.global.u32 %0, [%1];" : "=r"(v) : "l"(p) : "memory"); }
__device__ __forceinline__ void ld_x(uint4& v, const void* p) {
    asm volatile("ld.relaxed.gpu.global.v4.u32 {%0, %1, %2, %3}, [%4];" : "=r"(v.x), "=r"(v.y), "=r"(v.z), "=r"(v.w) : "l"(p) : "memory");
}
__device__ __forceinline__ void ld_x(uint2& v, const void* p) { asm volatile("ld.relaxed.gpu.global.v2.u32 {%0, %1}, [%2];" : "=r"(v.x), "=r"(v.y) : "l"(p) : "memory"); }
__device__ __forceinline__ uint32_t minw(uint32_t v) { return v; }
__device__ __forceinline__ uint32_t minw(const uint2& v) { return min(v.x, v.y); }
__device__ __forceinline__ uint32_t minw(const uint4& v) { return min(__vimin3_u32(v.x, v.y, v.z), v.w); }
template <int N> __device__ __forceinline__ uint32_t mint(const uint32_t* m) {
    if constexpr (N == 1) return m[0];
    else if constexpr (N == 2) return min(m[0], m[1]);
    else return __vimin3_u32(mint<(N + 2) / 3>(m), mint<(N + 1) / 3>(m + (N + 2) / 3), mint<N / 3>(m + (N + 2) / 3 + (N + 1) / 3));
}

template <int STRIDE, int S4 = 4 * STRIDE, typename T, int N>
__device__ __forceinline__ void poll_start(T (&v)[N], const void* base) {
#pragma unroll
    for (int i = 0; i < N; i++) ld_x(v[i], (const uint8_t*)base + (i & 3) * STRIDE + (i >> 2) * S4);
}
struct Nop { __device__ void operator()() const {} };
template <int STRIDE, int SLEEP, bool STARTED = false, int S4 = 4 * STRIDE, typename T, int N, typename F = Nop>
__device__ __forceinline__ void poll(T (&v)[N], const void* base, F idle = F()) {
    if (!STARTED) { poll_start<STRIDE, S4>(v, base); idle(); }
#pragma unroll 1
    for (uint32_t it = 0;; it++) {
        uint32_t m[N];
#pragma unroll
        for (int i = 0; i < N; i++) m[i] = minw(v[i]);
        if (__all_sync(0xffffffffu, mint<N>(m) != 0)) break;
        if (SLEEP && it > 0) __nanosleep(SLEEP);
#pragma unroll
        for (int i = 0; i < N; i++) if (!m[i]) ld_x(v[i], (const uint8_t*)base + (i & 3) * STRIDE + (i >> 2) * S4);
        idle();
        if (it > SPIN_LIMIT) __trap();
    }
}

__device__ __forceinline__ float bflo(uint32_t w) { return __uint_as_float(w << 16); }
__device__ __forceinline__ float bfhi(uint32_t w) { return __uint_as_float(w & 0xffff0000u); }
__device__ __forceinline__ uint32_t pack2(float lo, float hi) {
    uint32_t r; asm("cvt.rn.bf16x2.f32 %0, %1, %2;" : "=r"(r) : "f"(hi), "f"(lo)); return r;
}
__device__ __forceinline__ float rbf(float x) { return __uint_as_float(pack2(0.f, x)); }
__device__ __forceinline__ float sumlo(const uint32_t (&v)[8]) { return ((bflo(v[0]) + bflo(v[1])) + (bflo(v[2]) + bflo(v[3]))) + ((bflo(v[4]) + bflo(v[5])) + (bflo(v[6]) + bflo(v[7]))); }
__device__ __forceinline__ float sumhi(const uint32_t (&v)[8]) { return ((bfhi(v[0]) + bfhi(v[1])) + (bfhi(v[2]) + bfhi(v[3]))) + ((bfhi(v[4]) + bfhi(v[5])) + (bfhi(v[6]) + bfhi(v[7]))); }
__device__ __forceinline__ float ex2(float x) { float r; asm("ex2.approx.ftz.f32 %0, %1;" : "=f"(r) : "f"(x)); return r; }
__device__ __forceinline__ float shx(float v, int m) { return __shfl_xor_sync(0xffffffffu, v, m); }
__device__ __forceinline__ uint4 lds128(uint32_t a) { uint4 v; asm volatile("ld.shared.v4.u32 {%0, %1, %2, %3}, [%4];" : "=r"(v.x), "=r"(v.y), "=r"(v.z), "=r"(v.w) : "r"(a) : "memory"); return v; }
__device__ __forceinline__ uint32_t lds32(uint32_t a) { uint32_t v; asm volatile("ld.shared.u32 %0, [%1];" : "=r"(v) : "r"(a) : "memory"); return v; }
__device__ __forceinline__ void sts32(uint32_t a, uint32_t v) { asm volatile("st.shared.u32 [%0], %1;" :: "r"(a), "r"(v) : "memory"); }
__device__ __forceinline__ void sts16(uint32_t a, uint32_t v) { asm volatile("st.shared.u16 [%0], %1;" :: "r"(a), "h"((uint16_t)v) : "memory"); }
__device__ __forceinline__ int frag_off(int k) { return (k >> 5) * 64 + ((k >> 1) & 3) * 16 + ((k >> 4) & 1) * 8 + ((k >> 3) & 1) * 4 + (k & 1) * 2; }

template <bool TRANS>
__device__ __forceinline__ uint4 ldsm(uint32_t a) {
    uint4 r;
    if (TRANS) asm volatile("ldmatrix.sync.aligned.m8n8.x4.trans.shared.b16 {%0, %1, %2, %3}, [%4];" : "=r"(r.x), "=r"(r.y), "=r"(r.z), "=r"(r.w) : "r"(a) : "memory");
    else asm volatile("ldmatrix.sync.aligned.m8n8.x4.shared.b16 {%0, %1, %2, %3}, [%4];" : "=r"(r.x), "=r"(r.y), "=r"(r.z), "=r"(r.w) : "r"(a) : "memory");
    return r;
}
__device__ __forceinline__ void mma(float (&c)[4], uint32_t a0, uint32_t a1, uint32_t a2, uint32_t a3, uint32_t b0, uint32_t b1) {
    asm volatile("mma.sync.aligned.m16n8k16.row.col.f32.bf16.bf16.f32 {%0,%1,%2,%3}, {%4,%5,%6,%7}, {%8,%9}, {%0,%1,%2,%3};"
                 : "+f"(c[0]), "+f"(c[1]), "+f"(c[2]), "+f"(c[3]) : "r"(a0), "r"(a1), "r"(a2), "r"(a3), "r"(b0), "r"(b1));
}
template <bool TRANS, typename F>
__device__ __forceinline__ void load8(uint4 (&a)[8], F addr) {
    __syncwarp();
#pragma unroll
    for (int s = 0; s < 8; s++) a[s] = ldsm<TRANS>(addr(s));
}
__device__ __forceinline__ void mma8(float (&c)[4], const uint4 (&a)[8], const uint4 (&b)[4]) {
    float e[4][4];
#pragma unroll
    for (int s = 0; s < 8; s++) {
        if (s < 4) e[s][0] = e[s][1] = e[s][2] = e[s][3] = 0.f;
        mma(e[s & 3], a[s].x, a[s].y, a[s].z, a[s].w, (s & 1) ? b[s >> 1].z : b[s >> 1].x, (s & 1) ? b[s >> 1].w : b[s >> 1].y);
    }
#pragma unroll
    for (int i = 0; i < 4; i++) c[i] = (e[0][i] + e[1][i]) + (e[2][i] + e[3][i]);
}
__device__ __forceinline__ void ldfrag(uint4 (&b)[4], uint32_t a) {
    asm volatile("ld.shared.v4.u32 {%0,%1,%2,%3}, [%16];\nld.shared.v4.u32 {%4,%5,%6,%7}, [%16+64];\n"
                 "ld.shared.v4.u32 {%8,%9,%10,%11}, [%16+128];\nld.shared.v4.u32 {%12,%13,%14,%15}, [%16+192];\n"
                 : "=r"(b[0].x), "=r"(b[0].y), "=r"(b[0].z), "=r"(b[0].w), "=r"(b[1].x), "=r"(b[1].y), "=r"(b[1].z), "=r"(b[1].w),
                   "=r"(b[2].x), "=r"(b[2].y), "=r"(b[2].z), "=r"(b[2].w), "=r"(b[3].x), "=r"(b[3].y), "=r"(b[3].z), "=r"(b[3].w) : "r"(a) : "memory");
}
__device__ __forceinline__ void quad_pair(float x, float y, int t, float& lo, float& hi) {
    const float k = ((t & 1) ? y : x) + shx((t & 1) ? x : y, 1);
    lo = k + shx(k, 2); hi = shx(k, 4) + shx(k, 6);
}
__device__ __forceinline__ void pin(uint32_t& x) { asm volatile("" : "+r"(x)); }
template <typename T> __device__ __forceinline__ void pin(T*& x) { asm volatile("" : "+l"(x)); }
__device__ __forceinline__ float4 ldsf4(uint32_t a) { const uint4 v = lds128(a); return make_float4(__uint_as_float(v.x), __uint_as_float(v.y), __uint_as_float(v.z), __uint_as_float(v.w)); }
__device__ __forceinline__ float sum4(const float4& f) { return (f.x + f.y) + (f.z + f.w); }
__device__ __forceinline__ void stsf(uint32_t a, float v) { sts32(a, __float_as_uint(v)); }

__device__ __forceinline__ void wg_fence() { asm volatile("wgmma.fence.sync.aligned;" ::: "memory"); }
__device__ __forceinline__ void wg_commit() { asm volatile("wgmma.commit_group.sync.aligned;" ::: "memory"); }
__device__ __forceinline__ void wg_wait1() { asm volatile("wgmma.wait_group.sync.aligned 1;" ::: "memory"); }
__device__ __forceinline__ void wg_wait0() { asm volatile("wgmma.wait_group.sync.aligned 0;" ::: "memory"); }
#define R8(o) "+f"(d[o]), "+f"(d[o + 1]), "+f"(d[o + 2]), "+f"(d[o + 3]), "+f"(d[o + 4]), "+f"(d[o + 5]), "+f"(d[o + 6]), "+f"(d[o + 7])
__device__ __forceinline__ void wgmma_rs_n32(float (&d)[16], const uint4& a, uint64_t db, int acc) {
    asm volatile("{\n.reg .pred p;\nsetp.ne.b32 p, %21, 0;\n"
        "wgmma.mma_async.sync.aligned.m64n32k16.f32.bf16.bf16 "
        "{%0,%1,%2,%3,%4,%5,%6,%7,%8,%9,%10,%11,%12,%13,%14,%15}, {%16,%17,%18,%19}, %20, p, 1, 1, 0;\n}"
        : R8(0), R8(8) : "r"(a.x), "r"(a.y), "r"(a.z), "r"(a.w), "l"(db), "r"(acc));
}
#define PV_LO "{%0,%1,%2,%3,%4,%5,%6,%7,%8,%9,%10,%11,%12,%13,%14,%15,%16,%17,%18,%19,%20,%21,%22,%23,%24,%25,%26,%27,%28,%29,%30,%31,%32,%33,%34,%35,%36,%37,%38,%39,%40,%41,%42,%43,%44,%45,%46,%47,%48,%49,%50,%51,%52,%53,%54,%55,%56,%57,%58,%59,%60,%61,%62,%63}, "
#define PV_HI "{%64,%65,%66,%67,%68,%69,%70,%71,%72,%73,%74,%75,%76,%77,%78,%79,%80,%81,%82,%83,%84,%85,%86,%87,%88,%89,%90,%91,%92,%93,%94,%95,%96,%97,%98,%99,%100,%101,%102,%103,%104,%105,%106,%107,%108,%109,%110,%111,%112,%113,%114,%115,%116,%117,%118,%119,%120,%121,%122,%123,%124,%125,%126,%127}, "
__device__ __forceinline__ void wgmma_pv(float (&d)[128], const uint4& a, uint32_t blo, int acc) {
    asm volatile("{\n.reg .pred p;\n.reg .b32 u0, u1, u2, u3, t;\n.reg .b64 d0, d1, d2, d3;\nsetp.ne.b32 p, %133, 0;\n"
        "mov.b64 d0, {%132, 0x40000100};\nadd.u32 t, %132, 512;\nmov.b64 d1, {t, 0x40000100};\n"
        "add.u32 t, %132, 128;\nmov.b64 d2, {t, 0x40000100};\nadd.u32 t, %132, 640;\nmov.b64 d3, {t, 0x40000100};\n"
        "wgmma.fence.sync.aligned;\n"
        "wgmma.mma_async.sync.aligned.m64n128k16.f32.bf16.bf16 " PV_LO "{%128, u0, %129, u1}, d0, p, 1, 1, 1;\n"
        "wgmma.mma_async.sync.aligned.m64n128k16.f32.bf16.bf16 " PV_LO "{%130, u2, %131, u3}, d1, 1, 1, 1, 1;\n"
        "wgmma.commit_group.sync.aligned;\n"
        "wgmma.mma_async.sync.aligned.m64n128k16.f32.bf16.bf16 " PV_HI "{%128, u0, %129, u1}, d2, p, 1, 1, 1;\n"
        "wgmma.mma_async.sync.aligned.m64n128k16.f32.bf16.bf16 " PV_HI "{%130, u2, %131, u3}, d3, 1, 1, 1, 1;\n"
        "wgmma.commit_group.sync.aligned;\n}"
        : R8(0), R8(8), R8(16), R8(24), R8(32), R8(40), R8(48), R8(56), R8(64), R8(72), R8(80), R8(88), R8(96), R8(104), R8(112), R8(120)
        : "r"(a.x), "r"(a.y), "r"(a.z), "r"(a.w), "r"(blo), "r"(acc) : "memory");
}

template <int NW>
__device__ __forceinline__ void ln_stats(float s, float q, float sh, float* scr, int w, int lane, int bar, float& mean_b, float& sd_b) {
#pragma unroll
    for (int o = 16; o; o >>= 1) { s += shx(s, o); q += shx(q, o); }
    constexpr float n = 512.f / NW;
    if (lane == 0) { scr[w] = sh + s * (1.f / n); scr[NW + w] = q - s * s * (1.f / n); }
    bar_sync(bar, NW * 32);
    float mu = 0.f, m2 = 0.f;
#pragma unroll
    for (int i = 0; i < NW; i++) { mu += scr[i]; m2 += scr[NW + i]; }
    mu *= 1.f / NW;
#pragma unroll
    for (int i = 0; i < NW; i++) { const float d = scr[i] - mu; m2 = fmaf(n * d, d, m2); }
    mean_b = rbf(mu);
    sd_b = rbf(sqrtf(rbf(rbf(fmaxf(m2, 0.f) * (1.f / 512.f)) + 1e-5f)));
}
__device__ __forceinline__ float ln_mod(float x, float mean_b, float sd_b, float c, float s) {
    return rbf(rbf(__fdividef(rbf(x - mean_b), sd_b)) * rbf(1.f + c)) + s;
}

__global__ void __cluster_dims__(2, 1, 1) __launch_bounds__(NTHREADS, 1)
fused_kernel(const __grid_constant__ First F, __nv_bfloat16* __restrict__ out, uint32_t* __restrict__ gs, const __grid_constant__ Maps M) {
    extern __shared__ __align__(1024) uint8_t sm[];
    const uint32_t sb = s2u(sm);
    const int tid = threadIdx.x, lane = tid & 31;
    const int j = blockIdx.x, rk = j & 1;
    const int g = lane >> 2, t = lane & 3;
    const int r8 = lane & 7, lb3 = (lane >> 3) & 1, lb4 = lane >> 4;
    uint64_t pol;
    asm("createpolicy.fractional.L2::evict_first.b64 %0, 1.0;" : "=l"(pol));
    {
        auto cpa = [&](uint32_t d, const uint8_t* s) {
            asm volatile("cp.async.cg.shared.global.L2::cache_hint.L2::128B [%0], [%1], 16, %2;" :: "r"(d), "l"(s), "l"(pol) : "memory");
        };
        const uint32_t ut = threadIdx.x, uj = blockIdx.x;
        const uint8_t* w = F.w[ut >= 128];
        if (ut < 128) {
            const uint32_t dq = (sb + ut * 16) ^ ((ut * 2) & 0x70);
            const uint8_t* sq = w + (uint32_t)(((uj & 1) * 256 + (ut >> 3)) * 8192 + (uj >> 1) * 128 + (ut & 7) * 16);
#pragma unroll
            for (int i = 0; i < 4 * NCP; i++) cpa(dq + 4 * 32768 + i * 2048, sq + i * 131072);
        } else if (ut < 384) {
            const uint32_t dm = (sb + ut * 16) ^ ((ut * 2) & 0x10);
            const uint8_t* sa = w + (uint32_t)(((uj >> 5) * 128 + (ut >> 1) - 64) * 6144 + (uj & 31) * 32 + (ut & 1) * 16);
            cpa(dm + SM_XA - 2048, sa); cpa(dm + SM_XA + 2048, sa + 1024);
        }
        else if (ut == 480 && uj < 64) asm volatile("prefetch.global.L2 [%0];" :: "l"(F.v[(uj >> 3) & 1] + (uj & 7) * 64));
    }
    const int warp = __shfl_sync(0xffffffffu, tid >> 5, 0);
    const __nv_bfloat16* const xin = F.v[0];
    uint32_t* const pl = gs + (warp < 2 ? (B_PR + (j >> 5)) * 4096 + (j & 31) * 32 : G_E1 + j * 8192) + (warp & 1) * 1024 + lane;
    if (warp < 4) st_x1(pl, 1u);
    auto BAR = [&](int i) -> uint32_t { return sb + SM_BAR + i * 8; };
    const uint32_t a16 = (r8 + 8 * lb4) * 32 + ((lb3 ^ (r8 >> 2)) * 16);
    const uint32_t a128 = (r8 + 8 * lb4) * 128 + ((((warp & 3) * 2 + lb3) ^ r8) * 16);
    auto ldcls = [&]() -> uint32_t { return *(const volatile uint32_t*)(sm + SM_CLS); };
    auto clear_head = [&]() {
        st2_x1(gs + (B_HA + ((j >> 4) & 1) * 2 + lb4) * 4096 + (j >> 5) * 256 + (j & 15) * 16 + (lane & 15), 0u);
        st2_x4(gs + (B_QA + rk * 8 + ((j >> 1) & 1) * 4 + (j >> 5)) * 4096 + g * 128 + ((j >> 2) & 7) * 16 + t * 4, 0u, 0u, 0u, 0u);
        if (lane < 8) st2_x1(gs + B_RD * 4096 + j * 8 + lane, 0u);
    };
    auto tma = [&](uint32_t dst, int mp, uint32_t bar, int c0, int c1, int c2, int c3) {
        asm volatile("{\n.reg .pred p;\nelect.sync _|p, 0xffffffff;\n"
                     "@p cp.async.bulk.tensor.4d.shared::cluster.global.mbarrier::complete_tx::bytes.L2::cache_hint [%0], [%1, {%3, %4, %5, %6}], [%2], %7;\n}"
                     :: "r"(dst), "l"(&M.m[mp]), "r"(bar), "r"(c0), "r"(c1), "r"(c2), "r"(c3), "l"(pol) : "memory");
    };
    if (warp <= 12 || warp == 15) {
        const int grp = warp == 12 ? 0 : warp == 15 ? 13 : warp + 1;
        const uint32_t cnt = grp < 10 ? 1 : grp < 13 ? 4 : 8;
        if (lane == 0) {
#pragma unroll
            for (int i = 0; i < 8; i++) mbar_init(BAR(grp * 8 + i), (i < 2 && grp == 0) ? (i ? 128 : 256) : cnt);
        }
        __syncwarp();
        if (grp < 10 && lane < 8 && (grp || lane > NCP)) mbar_expect(BAR(grp * 8 + lane), grp >= 8 ? 4096 : grp * 8 + lane < IT_X ? 8192 : 16384);
        asm volatile("fence.mbarrier_init.release.cluster;" ::: "memory");
        __syncwarp();
        if (warp == 12) {
#pragma unroll
            for (int i = NCP + 1; i < W0; i++) tma(sb + (15 + i) * 8192, MP_WQ, BAR(i), 0, rk * 256 + (i - 1) * 64, j >> 1, 0);
        }
    } else if (warp == 13) {
        if (lane < NMAPS) asm volatile("prefetch.tensormap [%0];" :: "l"(&M.m[lane]) : "memory");
    } else if (warp == 14) {
        clear_head();
    }
    __syncthreads();
    uint32_t in1 = 0, in2 = 0;
    if (warp < 4) { in1 = *(const uint32_t*)(xin + 2 * tid); in2 = *(const uint32_t*)(xin + 256 + 2 * tid); }
    else if (warp < 12) in1 = *(const uint32_t*)(F.v[1] + 2 * (tid - 128));
    if (warp < 12) asm volatile("cp.async.mbarrier.arrive.noinc.shared::cta.b64 [%0];" :: "r"(BAR(warp < 4)) : "memory");
    asm volatile("barrier.cluster.arrive.relaxed.aligned;" ::: "memory");

    if (warp >= 12) {
    asm volatile("setmaxnreg.dec.sync.aligned.u32 64;");
    if (warp == 12) {
        static_assert(W0 > NCP && W0 <= 5 && NCP >= 1 && NCP <= 4, "W0");
        const uint2* sched = M.sched[j < NFF ? 0 : j < J_RED ? 1 : 2];
        uint2 en = sched[W0];
        const uint32_t t0 = gtime();
#pragma unroll 1
        for (int i = W0; en.x; i++) {
            const uint32_t e = en.x, tn = t0 + en.y;
            en = sched[i + 1];
            const int id = e & 63, w0 = (e >> 11) & 127, w1 = (e >> 18) & 127;
            int mp, c0 = 0, c1 = 0, c2 = 0, c3 = 0;
            if (id < IT_CKV) { const int k = id - IT_WQ; mp = MP_WQ + (k >> 2); c1 = rk * 256 + (k & 3) * 64; c2 = j >> 1; }
            else if (id < IT_WUV) { const int k = id - IT_CKV; mp = MP_CKV; c2 = rk * 4; c3 = (k * 64 + (j >> 1)) * 2; }
            else if (id < IT_WO) { mp = MP_WUV; c1 = (j & 3) * 32 + (id - IT_WUV) * 128; c2 = (j >> 2) * 2; }
            else if (id < IT_X) { mp = MP_WO; c0 = (j & 7) * 64; c1 = (j >> 3) * 256 + (id - IT_WO) * 64; }
            else if (id < IT_DOWN) {
                if (j >= J_END) break;
                const int k = id - IT_X;
                mp = j < NFF ? MP_GATE + (k >> 1) : MP_MODB; c0 = (j >> 1) * 64 + (j < NFF ? 0 : 1024 - NFF * 32); c1 = rk * 256 + (k & 1) * 128;
            } else { mp = MP_DOWN; c1 = j * 32; c2 = (id - IT_DOWN) * 4; }
            if (w0) mbar_wait(BAR(w0 - 1), 0);
            const int w2 = e >> 25;
            if (w2) {
                mbar_wait(BAR(w2 - 1), 0);
                while (!__any_sync(0xffffffffu, mbar_test(BAR(w1 - 1), 0) | ((int)(gtime() - tn) > 0))) {}
            } else if (w1) mbar_wait(BAR(w1 - 1), 0);
            tma(sb + ((e >> 6) & 31) * 8192, mp, BAR(id), c0, c1, c2, c3);
        }
    } else if (warp == 13) {
#pragma unroll
        for (int i = 0; i < 2; i++) st_x4(gs + (B_ML + rk * 16 + i * 8 + g) * 4096 + (t >> 1) * 1024 + (j >> 1) * 8 + (t & 1) * 4, 0u, 0u, 0u, 0u);
        if (lane < 16) st2_x4(gs + (B_E2 + (j >> 4)) * 4096 + (j & 15) * 64 + lane * 4, 0u, 0u, 0u, 0u);
        st2_x1(gs + (B_E3 + (j >> 5)) * 4096 + (j & 31) * 32 + lane, 0u);
        if (lane < 8) st2_x1(gs + B_MB * 4096 + j * 8 + lane, 0u);
        if (j < NFF) {
#pragma unroll
            for (int i = 0; i < 2; i++) st2_x4(gs + (B_E5 + i * 8 + g) * 4096 + j * 16 + t * 4, 0u, 0u, 0u, 0u);
        }
        bar_sync(9, 64);
        const uint32_t cs = ldcls();
#pragma unroll 1
        for (int i = 0; i < 32; i++) {
            st_x4(gs + G_E1 + j * 8192 + (i >> 3) * 2048 + ((((cs >> 1) ^ (i >> 3)) & 1) << 10) + (i & 7) * 128 + lane * 4, 0u, 0u, 0u, 0u);
            __nanosleep(JAN_SLEEP);
        }
        fence_gpu();
        if (lane < 8) st2_x1(gs + B_RD * 4096 + j * 8 + lane, 1u + (cs >> 1));
        if (lane == 0) TRACE(41);
        uint32_t rd[4];
        mbar_wait(BAR(IT_CKV + RD_ITEM), 0);
        poll<1024, RD_SLEEP>(rd, gs + near_off(B_RD, cs) + lane * 8);
#pragma unroll
        for (int i = 0; i < 4; i++) {
            const uint32_t m = __ballot_sync(0xffffffffu, rd[i] == 2u);
            if (lane == 0) sts32(sb + SM_CLS + 16 + i * 4, m);
        }
        __syncwarp();
        if (lane < 8) mbar_arrive(BAR(JD));
        if (lane == 0) TRACE(42);
    } else if (warp == 14) {
        uint2 ml[2];
        mbar_waitb(BAR(JD), 0);
        const uint32_t cls = ldcls();
        mbar_waitb(BAR(PF0 + 2 * NUNITS - 1), 0);
        __nanosleep(ML_DELAY);
        const uint32_t* pl2 = gs + near_off(B_ML + (j >> 2), cls) + lane * 8;
        const uint32_t wa = sb + SM_W + lb4 * 64 + t * 16 + (g & 3) * 4;
        poll_start<1024>(ml, pl2);
        uint32_t w0 = 0, w1 = 0, redo = 0;
        bool first = true;
#pragma unroll 1
        for (uint32_t it = 0;; it++) {
            const bool p0 = minw(ml[0]) != 0, p1 = minw(ml[1]) != 0;
            const int n = __popc(__ballot_sync(0xffffffffu, p0)) + __popc(__ballot_sync(0xffffffffu, p1));
            const uint32_t x0 = ml[0].x, x1 = ml[1].x;
            if (n < 64) {
                if (!p0) ld_x(ml[0], pl2);
                if (!p1) ld_x(ml[1], pl2 + 256);
            }
            if (n == 64 || (first && n >= E1_EARLY)) {
                auto ord = [](int x) { return x ^ ((x >> 31) & 0x7fffffff); };
                const int o0 = ord(x0), o1 = ord(x1);
                const float mm = __int_as_float(ord(__reduce_max_sync(0xffffffffu, max(p0 ? o0 : INT_MIN, p1 ? o1 : INT_MIN))));
                const float lo = __int_as_float(ord(__reduce_min_sync(0xffffffffu, min(p0 ? o0 : INT_MAX, p1 ? o1 : INT_MAX))));
                const uint32_t v0 = pack2(ex2((p0 ? __uint_as_float(x0) : lo) - mm), 0.f), v1 = pack2(ex2((p1 ? __uint_as_float(x1) : lo) - mm), 0.f);
                redo = !first && __any_sync(0xffffffffu, v0 != w0 || v1 != w1);
                w0 = v0; w1 = v1;
                sts32(wa - redo * (SM_W - SM_W2), w0 * 0x10001u); sts32(wa - redo * (SM_W - SM_W2) + 128, w1 * 0x10001u);
                if (first) bar_arrive(3, 416);
                first = false;
                if (n == 64) break;
            }
            if (it > SPIN_LIMIT) __trap();
        }
        if (lane == 0) TRACE_Q(37);
        float L = bflo(w0) * __uint_as_float(ml[0].y) + bflo(w1) * __uint_as_float(ml[1].y);
#pragma unroll
        for (int o = 16; o; o >>= 1) L += shx(L, o);
        if (lane == 0) *(float2*)(sm + SM_FQ) = make_float2(__frcp_rn(L), __uint_as_float(redo));
        __syncwarp();
        if (lane < 8) mbar_arrive(BAR(WR));
        if (lane == 0) TRACE(10);
        bar_sync(4, 288);
        clear_head();
        if (j < NFF) {
            uint32_t ya = sb + SM_Y + lane * 16, sa = peer_addr(sb + SM_RED + 2048 + rk * 8, lane & 1), tb = peer_addr(BAR(MBB), lane & 1);
            pin(ya); pin(sa); pin(tb);
            bar_sync(7, 288);
            const float4 y0 = ldsf4(ya), y1 = ldsf4(ya + 512);
            float s = sum4(y0) + sum4(y1);
            float q = (fmaf(y0.x, y0.x, y0.y * y0.y) + fmaf(y0.z, y0.z, y0.w * y0.w)) + (fmaf(y1.x, y1.x, y1.y * y1.y) + fmaf(y1.z, y1.z, y1.w * y1.w));
#pragma unroll
            for (int o = 16; o; o >>= 1) { s += shx(s, o); q += shx(q, o); }
            if (lane < 2) st_async2(sa, s, q, tb);
        }
    } else if (warp == 15) {
        mbar_waitb(BAR(IT_X - 1), 0);
        if (j < J_END) mbar_waitb(BAR(j < NFF ? NITEMS - 1 : MBB), 0);
    }
    } else if (warp < 4) {
        float* scr = (float*)(sm + SM_SCR);
        uint32_t cls;
        {
            uint2 ha[8];
            {
                uint32_t best = 0xffffffffu;
#pragma unroll
                for (int i = 0; i < NPROBE; i++) {
                    uint32_t t0, t1, o;
                    asm volatile("mov.u32 %0, %%clock;" : "=r"(t0));
                    asm volatile("atom.relaxed.gpu.global.exch.b32 %0, [%1], %2;" : "=r"(o) : "l"(pl), "r"(2u + i) : "memory");
                    asm volatile("{\n.reg .pred p;\nsetp.ne.u32 p, %1, 0x1234567;\nmov.u32 %0, 0;\n@p mov.u32 %0, %%clock;\n}" : "=r"(t1) : "r"(o));
                    best = min(best, t1 - t0);
                }
                if (lane == 0) scr[16 + warp] = __uint_as_float(best);
            }
            const float sh = __shfl_sync(0xffffffffu, bflo(in1), 0);
            const float v0 = bflo(in1) - sh, v1 = bfhi(in1) - sh, v2 = bflo(in2) - sh, v3 = bfhi(in2) - sh;
            float mb, sd;
            ln_stats<4>((v0 + v1) + (v2 + v3), (v0 * v0 + v1 * v1) + (v2 * v2 + v3 * v3), sh, scr, warp, lane, 2, mb, sd);
            if (!rk) in2 = in1;
            const uint4 lt = *(const uint4*)(scr + 16);
            cls = NUMA ? ((lt.y < lt.x) ^ (__popc((B_PR + (j >> 5)) & 0x2C) & 1)) | (lt.w < lt.z) << 1 : 0;
            if (warp == 0) { if (lane == 0) sts32(sb + SM_CLS, cls); bar_arrive(9, 64); }
            if (tid == 0) TRACE(38);
            asm volatile("barrier.cluster.wait.aligned;" ::: "memory");
            mbar_wait(BAR(IT_MODA), 0);
            __nanosleep(HA_DELAY);
            poll<1024, H_SLEEP, false, 16384>(ha, gs + near_off(B_HA + rk * 2, cls) + 2 * tid);
            auto rsum = [](uint32_t a, uint32_t b, uint32_t c, uint32_t d) { return rbf((__uint_as_float(a) + __uint_as_float(b)) + (__uint_as_float(c) + __uint_as_float(d))); };
            sts32(sb + SM_FV + frag_off(2 * tid),
                  pack2(ln_mod(bflo(in2), mb, sd, rsum(ha[4].x, ha[5].x, ha[6].x, ha[7].x), rsum(ha[0].x, ha[1].x, ha[2].x, ha[3].x)),
                        ln_mod(bfhi(in2), mb, sd, rsum(ha[4].y, ha[5].y, ha[6].y, ha[7].y), rsum(ha[0].y, ha[1].y, ha[2].y, ha[3].y))));
            bar_arrive(5, 384);
            mbar_wait(BAR(QB), 0);
            if (tid < 64) {
                const float* qx = (const float*)(sm + SM_QX) + tid;
                sts16(sb + SM_FQ + frag_off(tid), pack2((qx[0] + qx[64]) + (qx[128] + qx[192]), 0.f));
            }
            bar_arrive(6, 384);
        }
        asm volatile("setmaxnreg.inc.sync.aligned.u32 192;");
        float acc[128];
        float M = 0.f;
        uint32_t pa = sb + SM_XA + warp * 512 + lane * 16, ma = sb + SM_MX + (warp * 8 + g) * 4, pf = BAR(PF0);
        uint32_t blo = __reduce_or_sync(0xffffffffu, (((sb + SM_U) & 0x3FFFFu) >> 4) | 0x400000u);
        uint32_t* e1[4];
#pragma unroll
        for (int i = 0; i < 4; i++) e1[i] = gs + G_E1 + (warp * 8 + g) * 4 * 8192 + (rk * 2 + (j >> 6)) * 2048 + ((j >> 1) & 31) * 32 + t * 4;
#pragma unroll 1
        for (int h = 0; h < 2 * NUNITS; h++) {
            mbar_wait(pf, 0);
            const float m = __uint_as_float(lds32(ma));
            const uint4 pn = lds128(pa);
            wg_wait0();
#pragma unroll
            for (int i = 0; i < 128; i++) asm volatile("" : "+f"(acc[i]) :: "memory");
            if (h == 0) M = m;
            uint32_t b2 = 0x3f803f80u;
            if (__builtin_expect(__any_sync(0xffffffffu, m != M), 0)) {
                const float Mn = fmaxf(M, m), alpha = ex2(M - Mn), beta = ex2(m - Mn);
                M = Mn;
                b2 = pack2(beta, beta);
#pragma unroll
                for (int jj = 0; jj < 32; jj++) { acc[4 * jj] *= alpha; acc[4 * jj + 1] *= alpha; }
            }
            auto mul2 = [](uint32_t x, uint32_t y) { uint32_t r; asm("mul.rn.bf16x2 %0, %1, %2;" : "=r"(r) : "r"(x), "r"(y)); return r; };
            const uint4 p = make_uint4(mul2(pn.x, b2), mul2(pn.y, b2), mul2(pn.z, b2), mul2(pn.w, b2));
            if (tid == 0 && (h & 1)) TRACE_Q(48 + (h >> 1));
            wgmma_pv(acc, p, blo, h);
            if (lane == 0 && h > 0 && !(h & 1)) mbar_arrive(BAR(EB_UNIT0 + (h >> 1) - 1));
            blo += h == 11 ? -11 * 1024 : 1024;
            pa += (h == 5 || h == 11) ? -5 * 2048 : 2048;
            ma += 128; pf += 8;
            if (h == 2 * NUNITS - 3) {
                mbar_wait(BAR(JD), 0);
                const uint32_t hm = (*(const uint32_t*)(sm + SM_CLS + 16 + warp * 4) >> (g * 4)) ^ ((j >> 6) ? 15u : 0u);
#pragma unroll
                for (int i = 0; i < 4; i++) e1[i] += ((hm >> i) & 1) << 10;
            }
        }
#pragma unroll
        for (int vv = 0; vv < 2; vv++) {
            if (vv && M == 1.f) __trap();
            if (vv) wg_wait0(); else wg_wait1();
#pragma unroll
            for (int i = 0; i < 64; i++) asm volatile("" : "+f"(acc[vv * 64 + i]) :: "memory");
            if (tid == 0 && !vv) TRACE_Q(63);
#pragma unroll
            for (int i = 0; i < 4; i++) {
                const float* a = &acc[vv * 64 + i * 16];
                st_x4(e1[i] + i * 8192 + vv * 16, enc(pack2(a[0], a[1])), enc(pack2(a[4], a[5])), enc(pack2(a[8], a[9])), enc(pack2(a[12], a[13])));
            }
        }
        bar_arrive(3, 416);
        if (tid == 0) TRACE_Q(17);
        if (j < NFF) {
            uint4 a[16];
            const uint32_t ad = sb + SM_U + B_DN * 32768 + warp * 8192 + (r8 + 8 * lb4) * 128 + (lb3 ^ r8) * 16;
            uint32_t rl = sb + SM_RED + lane * 16;
            uint32_t* p5 = gs + (B_E5 + warp * 4 + (t >> 1)) * 4096 + j * 16 + (t & 1) * 8 + g;
            pin(rl); pin(p5);
            if (lane == 0) mbar_expect(BAR(MBB), 4);
            auto ldd = [&]() {
#pragma unroll
                for (int s = 0; s < 16; s++) a[s] = ldsm<true>((ad ^ ((s & 3) * 32)) + (s >> 2) * 2048);
            };
            const uint32_t db = BAR(IT_DOWN + (warp >> 1));
            mbar_wait(BAR(MBB), 0);
            const float4 st = ldsf4(sb + SM_RED + 2048);
            const bool hd = __all_sync(0xffffffffu, mbar_test(db, 0));
            if (hd) ldd();
            const float mu = (st.x + st.z) * (1.f / 512.f);
            float rstd;
            asm volatile("rsqrt.approx.ftz.f32 %0, %1;" : "=f"(rstd) : "f"(fmaxf(fmaf(-mu, mu, (st.y + st.w) * (1.f / 512.f)), 0.f) + 1e-5f));
            mbar_wait(BAR(QB), 1);
            if (tid == 0) TRACE(25);
            const float4 f0 = ldsf4(rl), f2 = ldsf4(rl + 1024), f1 = ldsf4(rl + 512), f3 = ldsf4(rl + 1536);
            const float gg = fmaf(rstd, fmaf(-mu, f0.z + f2.z, (f0.x + f0.y) + (f2.x + f2.y)), f0.w + f2.w);
            const float uu = fmaf(rstd, fmaf(-mu, f1.z + f3.z, (f1.x + f1.y) + (f3.x + f3.y)), f1.w + f3.w);
            const float hh = __fdividef(gg * uu, 1.f + ex2(-gg * fmaf(gg * gg, 0.10294324f, 2.3022082f)));
            uint32_t hb[4];
#pragma unroll
            for (int i = 0; i < 4; i++) hb[i] = pack2(__shfl_sync(0xffffffffu, hh, 2 * t + 8 * i), __shfl_sync(0xffffffffu, hh, 2 * t + 8 * i + 1));
            if (!hd) { mbar_wait(db, 0); ldd(); }
#pragma unroll
            for (int i = 0; i < 2; i++) {
                uint32_t res = 0;
#pragma unroll
                for (int k = 0; k < 4; k++) {
                    float c[4] = {0.f, 0.f, 0.f, 0.f};
                    const uint4 &x = a[i * 8 + k], &y = a[i * 8 + k + 4];
                    mma(c, x.x, x.y, x.z, x.w, hb[0], hb[1]);
                    mma(c, y.x, y.y, y.z, y.w, hb[2], hb[3]);
                    if (t == k) res = pack2(c[0], c[2]);
                }
                st2_x1(p5 + i * 8192, enc(res));
            }
            if (tid == 0) { TRACE(27); TRACE_GT(47); }
        } else if (j < J_END) {
            uint4 a[8], b[4];
            float c[4], e[4];
            const bool own = (warp >> 1) == rk;
            const uint32_t xa = sb + SM_FV + (warp & 1) * 64 + g * 8;
            if (lane == 0) mbar_expect(BAR(MBB), own ? 64 : 0);
#pragma unroll
            for (int i = 0; i < 2; i++) {
                ldfrag(b, sb + SM_FS + rk * 512 + i * 256 + t * 16);
                mbar_wait(BAR(IT_X + i), 0);
                const uint32_t ab = sb + SM_U + B_X * 32768 + i * 16384 + a128;
                load8<true>(a, [&](int s) { return ab + s * 2048; });
                mma8(i ? e : c, a, b);
            }
            c[0] += e[0]; c[2] += e[2];
            if (!own) {
                if (t == 0) st_async2(peer_addr(xa, rk ^ 1), c[0], c[2], peer_addr(BAR(MBB), rk ^ 1));
            } else {
                mbar_wait(BAR(MBB), 0);
                const float2 pp = *(const float2*)(sm + (xa - sb));
                const float mine = t ? c[2] + pp.y : c[0] + pp.x, other = shx(mine, 4);
                const uint32_t w = (warp & 1) * 8 + t * 4 + (g >> 1), val = enc(pack2(mine, other));
                if (t < 2 && !(g & 1)) {
                    if (j < J_RED) st2_x1(gs + B_MB * 4096 + (j - NFF) * 16 + w, val);
                    else sts32(sb + SM_FV + 256 + w * 4, val);
                }
                if (j >= J_RED) bar_arrive(7, 320);
                if (lane == 0) TRACE(11);
            }
        }
    } else {
        const int u8 = tid - 128, w8 = warp - 4;
        const int v = w8 >> 2, wq4 = w8 & 3;
        {
            const float c0 = bflo(in1), c1 = bfhi(in1);
            sts32(sb + SM_FS + frag_off(2 * u8), pack2(__fdividef(c0, 1.f + __expf(-c0)), __fdividef(c1, 1.f + __expf(-c1))));
        }
        bar_sync(1, 256);
        asm volatile("barrier.cluster.wait.aligned;" ::: "memory");
        uint4 a[8], b[4]; float c[4];
        if (w8 < 2) {
            ldfrag(b, sb + SM_FS + (j >> 5) * 256 + t * 16);
            mbar_wait(BAR(IT_MODA), 0);
            if (u8 == 0) TRACE(12);
            const uint32_t ab = sb + SM_XA + w8 * 4096 + a16;
            load8<true>(a, [&](int s) { return ab + s * 512; });
            mma8(c, a, b);
            if (t < 2) st2_x1(gs + (B_HA + ((j >> 4) & 1) * 2 + w8) * 4096 + (j >> 5) * 256 + (j & 15) * 16 + t * 8 + g, encf(t ? c[2] : c[0]));
        }
        {
            mbar_wait(BAR(IT_WQ + 2 * v <= NCP ? 1 : IT_WQ + 2 * v), 0); mbar_wait(BAR(IT_WQ + 2 * v + 1 <= NCP ? 1 : IT_WQ + 2 * v + 1), 0);
            const uint32_t ab = sb + SM_U + 4 * 32768 + v * 16384 + a128;
            load8<true>(a, [&](int s) { return ab + s * 2048; });
            if (lane == 0) mbar_arrive(BAR(EB_WQ));
            bar_sync(5, 384);
            if (u8 == 0) TRACE(13);
            ldfrag(b, sb + SM_FV + v * 256 + t * 16);
            mma8(c, a, b);
            if (t < 2) {
                const float qv = t ? c[2] : c[0];
                const uint32_t qa_ = sb + SM_QX + ((rk * 2 + v) * 64 + wq4 * 16 + t * 8 + g) * 4;
                asm volatile("st.async.weak.shared::cluster.mbarrier::complete_tx::bytes.f32 [%0], %1, [%2];"
                             :: "r"(peer_addr(qa_, rk ^ 1)), "f"(qv), "r"(peer_addr(BAR(QB), rk ^ 1)) : "memory");
                sts32(qa_, __float_as_uint(qv));
            }
            __syncwarp();
            if (lane == 0) mbar_expect(BAR(QB), 64);
        }
        {
            mbar_wait(BAR(IT_WUK + v), 0); mbar_wait(BAR(IT_WUK + v + 2), 0);
            const uint32_t ab = sb + SM_U + 5 * 32768 + (w8 * 16 + r8 + 8 * lb3) * 128;
            const uint32_t x16 = (lb4 ^ r8) * 16;
            load8<false>(a, [&](int s) { return ab + (s & 1) * 16384 + (x16 ^ ((s >> 1) * 32)); });
            bar_sync(6, 384);
            if (u8 == 0) TRACE(14);
            b[0] = lds128(sb + SM_FQ + t * 16); b[1] = lds128(sb + SM_FQ + 64 + t * 16);
            float e[4] = {0.f, 0.f, 0.f, 0.f};
            c[0] = c[1] = c[2] = c[3] = 0.f;
#pragma unroll
            for (int k = 0; k < 4; k++) {
                const uint32_t b0 = (k & 1) ? b[k >> 1].z : b[k >> 1].x, b1 = (k & 1) ? b[k >> 1].w : b[k >> 1].y;
                mma(c, a[2 * k].x, a[2 * k].y, a[2 * k].z, a[2 * k].w, b0, b1);
                mma(e, a[2 * k + 1].x, a[2 * k + 1].y, a[2 * k + 1].z, a[2 * k + 1].w, b0, b1);
            }
            const float mine = ((t & 1) ? ((t & 2) ? e[2] : e[0]) : ((t & 2) ? c[2] : c[0])) * 0.12751743f;
            const float other = shx(mine, 4);
            if (!(g & 1)) st2_x1(gs + (B_QA + rk * 8 + ((j >> 1) & 1) * 4 + (j >> 5)) * 4096 + w8 * 128 + ((j >> 2) & 7) * 16 + (g >> 1) * 4 + t, enc(pack2(mine, other)));
            if (u8 == 0) TRACE(15);
        }
        const uint32_t cls = ldcls();
        __nanosleep(QA_DELAY);
        {
            uint4 qb[8];
            const uint32_t* pq = gs + near_off(B_QA + rk * 8 + wq4, cls) + lane * 4;
            const uint32_t* pq2 = gs + near_off(B_QA + rk * 8 + 4 + wq4, cls) + lane * 4;
            if (lane == 0) {
                mbar_expect(BAR(QT), 4096);
                asm volatile("cp.async.bulk.shared::cluster.global.mbarrier::complete_tx::bytes [%0], [%1], 4096, [%2];"
                             :: "r"(sb + SM_U + 5 * 32768 + w8 * 4096), "l"(gs + near_off(B_QA + rk * 8 + w8, cls)), "r"(BAR(QT)) : "memory");
            }
            const uint32_t qs = sb + SM_U + 5 * 32768 + wq4 * 4096 + lane * 16;
            mbar_wait(BAR(QT), 0);
#pragma unroll
            for (int i = 0; i < 8; i++) { a[i] = lds128(qs + i * 512); qb[i] = lds128(qs + 16384 + i * 512); }
            poll<512, QA_SLEEP, true>(a, pq);
            poll<512, QA_SLEEP, true>(qb, pq2);
            if (lane == 0) mbar_arrive(BAR(EB_WUK));
            auto add2 = [](uint32_t x, uint32_t y) { uint32_t r; asm("add.rn.bf16x2 %0, %1, %2;" : "=r"(r) : "r"(x), "r"(y)); return r; };
#pragma unroll
            for (int i = 0; i < 8; i++) a[i] = make_uint4(add2(a[i].x, qb[i].x), add2(a[i].y, qb[i].y), add2(a[i].z, qb[i].z), add2(a[i].w, qb[i].w));
        }
        if (u8 == 0) TRACE(8);
        {
            float m = -INFINITY, l = 0.f;
            uint32_t xl = sb + SM_XB + w8 * 2048 + lane * 16, xr = peer_addr(xl, rk ^ 1), bsr = peer_addr(BAR(SF0 + v), rk ^ 1);
            uint32_t pa = sb + SM_XA + v * 2048 + wq4 * 512 + lane * 16, ma = sb + SM_MX + v * 128 + (wq4 * 8 + g) * 4;
            uint32_t fb = BAR(IT_CKV + v * 2), sf = BAR(SF0 + v);
            uint32_t dlo = __reduce_or_sync(0xffffffffu, (((sb + SM_U + v * 16384) & 0x3FFFFu) >> 4) | 0x10000u);
            if (STAG && v) __nanosleep(STAG);
#pragma unroll 1
            for (int n = 0; n < NUNITS; n++) {
                float d[2][16], sc[8];
#pragma unroll
                for (int i = 0; i < 2; i++) {
                    mbar_wait(fb + i * 8, 0);
                    wg_fence();
#pragma unroll
                    for (int s = 0; s < 8; s++) wgmma_rs_n32(d[i], a[s], (0x40000080ull << 32) | (dlo + i * 512 + (s >> 2) * 64 + (s & 3) * 2), s);
                    wg_commit();
                }
#pragma unroll
                for (int i = 0; i < 2; i++) {
                    if (i) wg_wait0(); else wg_wait1();
#pragma unroll
                    for (int k = 0; k < 16; k++) asm volatile("" : "+f"(d[i][k]) :: "memory");
                    sc[4 * i] = d[i][0] + d[i][6]; sc[4 * i + 1] = d[i][1] + d[i][7]; sc[4 * i + 2] = d[i][8] + d[i][14]; sc[4 * i + 3] = d[i][9] + d[i][15];
                    asm volatile("st.async.weak.shared::cluster.mbarrier::complete_tx::bytes.v4.f32 [%0], {%1, %2, %3, %4}, [%5];"
                                 :: "r"(xr + i * 1024), "f"(sc[4 * i]), "f"(sc[4 * i + 1]), "f"(sc[4 * i + 2]), "f"(sc[4 * i + 3]), "r"(bsr) : "memory");
                }
                if (u8 == 128) TRACE_Q(56 + (n < 6 ? n : -40));
                if (n >= 3) mbar_wait(BAR(EB_UNIT0 + n - 3), 0);
                dlo += n == 5 ? -5 * 2048 : 2048;
                fb += 32; xr ^= 512; bsr += 16;
                pin(fb); pin(xr); pin(bsr);
                mbar_wait(sf, 0);
                const float4 x = ldsf4(xl), y = ldsf4(xl + 1024);
                sc[0] += x.x; sc[1] += x.y; sc[2] += x.z; sc[3] += x.w; sc[4] += y.x; sc[5] += y.y; sc[6] += y.z; sc[7] += y.w;
                float pr[8];
#pragma unroll
                for (int i = 0; i < 8; i++) pr[i] = ex2(sc[i] - m);
                float mx = fmaxf(fmaxf(fmaxf(sc[0], sc[1]), fmaxf(sc[2], sc[3])), fmaxf(fmaxf(sc[4], sc[5]), fmaxf(sc[6], sc[7])));
                if (__builtin_expect(__any_sync(0xffffffffu, mx > m), 0)) {
                    mx = fmaxf(mx, shx(mx, 1));
                    mx = fmaxf(mx, shx(mx, 2));
                    const float mn = fmaxf(m, ceilf(mx * 0.0625f) * 16.f);
                    l *= ex2(m - mn);
                    m = mn;
#pragma unroll
                    for (int i = 0; i < 8; i++) pr[i] = ex2(sc[i] - m);
                }
                stsf(ma, m);
                asm volatile("st.shared.v4.u32 [%0], {%1, %2, %3, %4};" :: "r"(pa), "r"(pack2(pr[0], pr[1])), "r"(pack2(pr[2], pr[3])),
                             "r"(pack2(pr[4], pr[5])), "r"(pack2(pr[6], pr[7])) : "memory");
                __syncwarp();
                if (lane == 0) mbar_arrive(sf + (PF0 - SF0) * 8);
                l += ((pr[0] + pr[1]) + (pr[2] + pr[3])) + ((pr[4] + pr[5]) + (pr[6] + pr[7]));
                xl ^= 512; sf += 16; ma += 256; pa += (n == 2 || n == 5) ? -8192 : 4096;
            }
            l += shx(l, 1);
            l += shx(l, 2);
            float2* mlx = (float2*)(sm + SM_MX + 2048) + wq4 * 8 + g;
            if (v == 0) { *mlx = make_float2(m, l); bar_arrive(11, 256); }
            else {
                mbar_wait(BAR(JD), 0);
                bar_sync(11, 256);
                const float2 o = *mlx;
                const float mn = fmaxf(m, o.x);
                l = l * ex2(m - mn) + o.y * ex2(o.x - mn);
                if ((wq4 >> 1) == rk) st_x4(gs + (B_ML + wq4 * 8 + g) * 4096 + (t >> 1) * 1024 + (j >> 1) * 8 + (t & 1) * 4, encf(mn), encf(l), 1u, 1u);
            }
        }
        const int pi = j < NFF ? rk * 128 + w8 * 16 + (lane & 15) : ((j - J_RED) & 15) * 16 + v * 8 + lb4 * 4 + wq4;
        const uint32_t xw = *(const uint32_t*)(xin + 2 * pi);
        const uint32_t* pm = gs + near_off(B_MB, cls) + pi;
        const uint32_t* pb = gs + near_off(B_E2 + (j >> 4), cls) + (((j >> 3) & 1) * 2 + lb4) * 256 + (lane & 15) * 2;
        pin(pm); pin(pb);
        {
            const uint32_t ab = sb + SM_U + B_WUV * 32768 + v * 4096 + a128;
            uint32_t pa = sb + SM_PB + wq4 * 320 + frag_off(64 * v + 32 * (g >> 2) + 16 * (t & 1) + 8 * (t >> 1) + 2 * (g & 3));
            uint32_t fa = sb + SM_PB + g * 320 + t * 16;
            const uint32_t* pe = gs + G_E1 + j * 8192 + (w8 >> 1) * 2048 + ((((cls >> 1) ^ (w8 >> 1)) & 1) << 10) + (((w8 & 1) * 16 + t) * 8 + g) * 4;
            uint32_t* p2 = gs + (B_E2 + (j >> 4)) * 4096 + (t >> 1) * 1024 + (j & 12) * 64 + w8 * 32 + (j & 3) * 8 + (g & 6) + (t & 1);
            pin(pa); pin(fa); pin(pe); pin(p2);
            const uint32_t mk = (g & 1) ? 0xffff0000u : 0x0000ffffu, m0 = (g & 2) ? 0u : mk, m1 = (g & 2) ? mk : 0u;
            uint4 pv[4];
            bool hv = false;
            bar_sync(3, 416);
            uint4 wa = lds128(sb + SM_W + (wq4 * 4 + t) * 16);
            uint32_t wb[8] = {wa.x & m0, wa.x & m1, wa.y & m0, wa.y & m1, wa.z & m0, wa.z & m1, wa.w & m0, wa.w & m1};
            pv[0] = pv[1] = pv[2] = pv[3] = make_uint4(0u, 0u, 0u, 0u);
            poll<512, E1_SLEEP, true>(pv, pe, [&]() {
                if (!hv) {
                    hv = __all_sync(0xffffffffu, mbar_test(BAR(IT_WUV + t), 0));
                    if (hv) load8<true>(a, [&](int s) { return ab + (s >> 1) * 8192 + (s & 1) * 2048; });
                }
            });
            if (lane == 0) TRACE_Q(48 + w8);
            if (u8 == 0) TRACE_Q(18);
            float lo, hi2;
            float2 inv;
#pragma unroll 1
            for (int pass = 0;; pass++) {
                float e[4][4];
#pragma unroll
                for (int i = 0; i < 4; i++) {
                    e[i][0] = e[i][1] = e[i][2] = e[i][3] = 0.f;
                    mma(e[i], pv[i].x, pv[i].y, pv[i].z, pv[i].w, wb[2 * i], wb[2 * i + 1]);
                }
                const float r0 = (t & 2) ? (e[0][2] + e[1][2]) + (e[2][2] + e[3][2]) : (e[0][0] + e[1][0]) + (e[2][0] + e[3][0]);
                const float r1 = (t & 2) ? (e[0][3] + e[1][3]) + (e[2][3] + e[3][3]) : (e[0][1] + e[1][1]) + (e[2][1] + e[3][1]);
                const uint32_t hi = pack2(r0, r1);
                sts32(pa, hi); sts32(pa + 1280, pack2(r0 - bflo(hi), r1 - bfhi(hi)));
                if (!hv) {
#pragma unroll 1
                    for (int i = 0; i < 4; i++) mbar_wait(BAR(IT_WUV + i), 0);
                    load8<true>(a, [&](int s) { return ab + (s >> 1) * 8192 + (s & 1) * 2048; });
                    hv = true;
                }
                bar_sync(1, 256);
                if (u8 == 0) TRACE(19);
                ldfrag(b, fa);
                mma8(c, a, b);
                mbar_wait(BAR(WR), 0);
                asm volatile("ld.shared.v2.f32 {%0, %1}, [%2];" : "=f"(inv.x), "=f"(inv.y) : "r"(sb + SM_FQ) : "memory");
                quad_pair(c[0] + c[1], c[2] + c[3], t, lo, hi2);
                if (__builtin_expect(__all_sync(0xffffffffu, pass || __float_as_uint(inv.y) == 0), 1)) break;
                wa = lds128(sb + SM_W2 + (wq4 * 4 + t) * 16);
                wb[0] = wa.x & m0; wb[1] = wa.x & m1; wb[2] = wa.y & m0; wb[3] = wa.y & m1; wb[4] = wa.z & m0; wb[5] = wa.z & m1; wb[6] = wa.w & m0; wb[7] = wa.w & m1;
                bar_sync(1, 256);
            }
            if (!(g & 1)) st_x1(p2, enc(pack2(lo * inv.x, hi2 * inv.x)));
            bar_arrive(4, 288);
            if (u8 == 0) TRACE(20);
        }
        uint32_t mb[3] = {0u, 0u, 0u};
        if (j < NFF) poll_start<1024>(mb, pm);
        uint4 a2[8];
        if (v == 0) {
            const uint32_t ab = sb + SM_U + B_WO * 32768 + a128;
            uint32_t* p3 = gs + (B_E3 + ((j >> 1) & 3)) * 4096 + (t >> 1) * 1024 + (rk * 2 + (wq4 >> 1)) * 256 + (j >> 3) * 16 + (wq4 & 1) * 8 + (t & 1) * 4 + (g >> 1);
            pin(p3);
            uint2 bb[8];
#pragma unroll
            for (int i = 0; i < 8; i++) bb[i] = make_uint2(0u, 0u);
            bool ho = false;
            auto ldo = [&]() { load8<true>(a, [&](int s) { return ab + s * 2048; }); load8<true>(a2, [&](int s) { return ab + 16384 + s * 2048; }); };
            auto idle = [&]() {
                if (!ho) {
                    ho = __all_sync(0xffffffffu, mbar_test(BAR(IT_WO + t), 0));
                    if (ho) ldo();
                }
            };
            poll<128, 0, true>(bb, pb, idle);
            if (!ho) {
#pragma unroll 1
                for (int i = 0; i < 4; i++) mbar_wait(BAR(IT_WO + i), 0);
                ldo();
            }
            if (u8 == 0) TRACE(21);
            float e[4][4];
#pragma unroll
            for (int s = 0; s < 16; s++) {
                const uint4& x = (s & 2) ? a2[(s >> 2) * 2 + (s & 1)] : a[(s >> 2) * 2 + (s & 1)];
                const uint2& y = bb[(s >> 2) * 2 + (s & 1)];
                if (s < 4) e[s][0] = e[s][1] = e[s][2] = e[s][3] = 0.f;
                mma(e[s & 3], x.x, x.y, x.z, x.w, y.x, y.y);
            }
            float lo, hi;
            quad_pair((t & 2) ? (e[2][0] + e[3][0]) + (e[2][1] + e[3][1]) : (e[0][0] + e[1][0]) + (e[0][1] + e[1][1]),
                      (t & 2) ? (e[2][2] + e[3][2]) + (e[2][3] + e[3][3]) : (e[0][2] + e[1][2]) + (e[0][3] + e[1][3]), t, lo, hi);
            if (!(g & 1)) st_x1(p3, enc(pack2(lo, hi)));
            bar_arrive(1, 256);
            if (u8 == 0) TRACE(22);
        } else bar_sync(1, 256);
        if (j < NFF) {
            const uint32_t* p3 = gs + near_off(B_E3 + rk * 2 + v, cls) + wq4 * 256 + lane;
            uint32_t za = sb + SM_FZ + lb4 * 576 + frag_off(w8 * 32 + (lane & 15) * 2);
            uint32_t fa = sb + SM_FZ + (g & 3) * 576 + lb4 * 256 + t * 16, ya = sb + SM_Y + u8 * 4;
            poll<1024, MB_SLEEP, true>(mb, pm);
            const uint32_t kk = pack2(1.f + bflo(mb[2]), 1.f + bfhi(mb[2]));
            sts32(za + 2 * 576, lb4 ? mb[1] : kk);
            uint32_t e3[8] = {0u, 0u, 0u, 0u, 0u, 0u, 0u, 0u};
            uint32_t ra = peer_addr(sb + SM_RED + (rk * 2 + v) * 512 + ((wq4 & 1) * 16 + (t >> 1) * 8 + g) * 16 + (t & 1) * 8, wq4 >> 1), tbo = peer_addr(BAR(QB), wq4 >> 1);
            pin(za); pin(fa); pin(ya); pin(ra); pin(tbo);
            if (lane == 0) mbar_expect(BAR(QB), 256);
            const uint32_t gb = BAR(IT_X + v * 2), ab = sb + SM_U + (B_X + v) * 32768 + a128;
            bool early = false, early2 = false;
            auto ldw = [&]() {
                if (!early) {
                    early = __all_sync(0xffffffffu, mbar_test(gb, 0));
                    if (early) load8<true>(a, [&](int s) { return ab + s * 2048; });
                }
                if (!early2) {
                    early2 = __all_sync(0xffffffffu, mbar_test(gb + 8, 0));
                    if (early2) load8<true>(a2, [&](int s) { return ab + 16384 + s * 2048; });
                }
            };
            poll<128, 0, true>(e3, p3, ldw);
            if (u8 == 0) TRACE(23);
            const float s0 = sumlo(e3), s1 = sumhi(e3);
            const float y0 = fmaf(bflo(mb[0]), s0 + shx(s0, 16), bflo(xw)), y1 = fmaf(bfhi(mb[0]), s1 + shx(s1, 16), bfhi(xw));
            stsf(ya, lb4 ? y1 : y0);
            const float z0 = y0 * bflo(kk), z1 = y1 * bfhi(kk);
            const uint32_t zh = pack2(z0, z1);
            sts32(za, lb4 ? pack2(z0 - bflo(zh), z1 - bfhi(zh)) : zh);
            bar_sync(7, 288);
            if (u8 == 0) TRACE(24);
            ldfrag(b, fa);
            if (!early) { mbar_wait(gb, 0); load8<true>(a, [&](int s) { return ab + s * 2048; }); }
            {
                float e[4][4];
#pragma unroll
                for (int s = 0; s < 16; s++) {
                    if (s == 8 && !early2) { mbar_wait(gb + 8, 0); load8<true>(a2, [&](int q) { return ab + 16384 + q * 2048; }); }
                    const uint4& x = s < 8 ? a[s] : a2[s & 7];
                    const uint4& y = b[(s >> 1) & 3];
                    float (&d)[4] = e[(s >> 3) * 2 + (s & 1)];
                    if (!(s & 6)) d[0] = d[1] = d[2] = d[3] = 0.f;
                    mma(d, x.x, x.y, x.z, x.w, (s & 1) ? y.z : y.x, (s & 1) ? y.w : y.y);
                }
                const bool hi = t >> 1;
                const float k0 = hi ? e[2][2] + e[3][2] : e[0][0] + e[1][0], k1 = hi ? e[2][3] + e[3][3] : e[0][1] + e[1][1];
                const float o0 = hi ? e[2][0] + e[3][0] : e[0][2] + e[1][2], o1 = hi ? e[2][1] + e[3][1] : e[0][3] + e[1][3];
                st_async2(ra, k0 + shx(o0, 2), k1 + shx(o1, 2), tbo);
            }
        } else if (j >= J_RED && j < J_END) {
            uint32_t ga[1], e3[1];
            poll<0, MB_SLEEP>(ga, pm);
            poll<0, 100>(e3, gs + near_off(B_E3 + (pi >> 6), cls) + (pi & 48) * 16 + (lane & 15) * 16 + (pi & 15));
            float y0 = bflo(e3[0]), y1 = bfhi(e3[0]);
#pragma unroll
            for (int o = 8; o; o >>= 1) { y0 += shx(y0, o); y1 += shx(y1, o); }
            y0 = fmaf(bflo(ga[0]), y0, bflo(xw)); y1 = fmaf(bfhi(ga[0]), y1, bfhi(xw));
            bar_sync(7, 320);
            const uint32_t gb = lds32(sb + SM_FV + 256 + (pi & 15) * 4);
            uint32_t* po = (uint32_t*)out + pi;
            pin(po);
            const uint32_t nz = lane < NFF / 2 ? 0u : 0x80008000u;
            uint2 yv[2] = {make_uint2(nz, nz), make_uint2(nz, nz)};
            poll<NFF * 32, 0, true>(yv, gs + near_off(B_E5 + j - J_RED, cls) + lane * 16 + w8 * 2);
            if (u8 == 0) TRACE(26);
            const float l0 = bflo(yv[0].x) + bflo(yv[1].x), h0 = bfhi(yv[0].x) + bfhi(yv[1].x);
            const float l1 = bflo(yv[0].y) + bflo(yv[1].y), h1 = bfhi(yv[0].y) + bfhi(yv[1].y);
            float s0 = (lb4 ? h0 : l0) + shx(lb4 ? l0 : h0, 16), s1 = (lb4 ? h1 : l1) + shx(lb4 ? l1 : h1, 16);
#pragma unroll
            for (int o = 8; o; o >>= 1) { s0 += shx(s0, o); s1 += shx(s1, o); }
            if (!(lane & 15)) *po = pack2(fmaf(bflo(gb), s0, y0), fmaf(bfhi(gb), s1, y1));
            if (u8 == 0) TRACE(27);
        }
    }
}

typedef CUresult (*EncFn)(CUtensorMap*, CUtensorMapDataType, cuuint32_t, void*, const cuuint64_t*, const cuuint64_t*,
                          const cuuint32_t*, const cuuint32_t*, CUtensorMapInterleave, CUtensorMapSwizzle,
                          CUtensorMapL2promotion, CUtensorMapFloatOOBfill);

void make_map(EncFn enc_fn, CUtensorMap* m, const void* p, cuuint64_t d0, cuuint64_t d1, cuuint64_t d2, cuuint64_t d3,
              cuuint64_t s1, cuuint64_t s2, cuuint64_t s3, cuuint32_t b0, cuuint32_t b1, cuuint32_t b2, cuuint32_t b3, CUtensorMapSwizzle sw) {
    const cuuint64_t dims[4] = {d0, d1, d2, d3}, strides[3] = {s1, s2, s3};
    const cuuint32_t box[4] = {b0, b1, b2, b3}, es[4] = {1, 1, 1, 1};
    enc_fn(m, CU_TENSOR_MAP_DATA_TYPE_BFLOAT16, 4, (void*)p, dims, strides, box, es,
           CU_TENSOR_MAP_INTERLEAVE_NONE, sw, CU_TENSOR_MAP_L2_PROMOTION_L2_64B, CU_TENSOR_MAP_FLOAT_OOB_FILL_NONE);
}

uint32_t* scratch = nullptr;

struct Tune { const char* win; const char* late; int tau, t_off; const char* tail[3][4]; };
Tune tune = {"66666666655555555555555555555555544444444",
             "00000000000000000999999999999999999999999", 320, -240,
             {{"VVVVOOOOguguDD", "zzzzzzzzzzzzzz", "88888888999988", "2fffdbbbl444td"},
              {"VMVMVVOOOO", "zzzzzzzzzz", "9999998888", "2999998ddd"},
              {"VVVVOOOOMM", "zzzzzzzzzz", "8888888888", "eaaa9hhhes"}}};
bool ready = false;

}

extern "C" void kernel_launch(void* const* d_in, const int* in_sizes, int n_in, void* d_out, int out_size) {
    (void)in_sizes; (void)n_in; (void)out_size;
    static Maps maps;
    static const void* cached[12] = {};
    bool same = ready;
    for (int i = 0; i < 12 && same; i++) same = cached[i] == d_in[i];
    if (!same) {
        void* fn = nullptr;
        cudaDriverEntryPointQueryResult qr;
        cudaGetDriverEntryPoint("cuTensorMapEncodeTiled", &fn, cudaEnableDefault, &qr);
        EncFn e = (EncFn)fn;
        const CUtensorMapSwizzle S128 = CU_TENSOR_MAP_SWIZZLE_128B;
        make_map(e, &maps.m[MP_WQ], d_in[2], 64, 512, 64, 1, 8192, 128, 8192, 64, 64, 1, 1, S128);
        make_map(e, &maps.m[MP_WUK], d_in[3], 64, 512, 64, 1, 8192, 128, 8192, 64, 64, 1, 1, S128);
        make_map(e, &maps.m[MP_CKV], d_in[1], 64, 8, 8, 4096, 1024, 128, 8192, 64, 8, 4, 2, S128);
        make_map(e, &maps.m[MP_MODB], d_in[11], 3072, 512, 1, 1, 6144, 6144, 6144, 64, 128, 1, 1, S128);
        make_map(e, &maps.m[MP_WUV], d_in[4], 64, 512, 64, 1, 8192, 128, 8192, 64, 32, 2, 1, S128);
        make_map(e, &maps.m[MP_WO], d_in[5], 512, 4096, 1, 1, 1024, 1024, 1024, 64, 64, 1, 1, S128);
        make_map(e, &maps.m[MP_GATE], d_in[7], 1792, 512, 1, 1, 3584, 3584, 3584, 64, 128, 1, 1, S128);
        make_map(e, &maps.m[MP_UP], d_in[8], 1792, 512, 1, 1, 3584, 3584, 3584, 64, 128, 1, 1, S128);
        make_map(e, &maps.m[MP_DOWN], d_in[9], 64, 1792, 8, 1, 1024, 128, 1024, 64, 32, 4, 1, S128);
        for (int r = 0; r < 3; r++) {
            int ids[56], cnt[128] = {}, tn = tune.t_off - (W0 - 1) * tune.tau;
            uint2* sc = maps.sched[r];
            auto dig = [](char ch) { return ch >= 'a' ? ch - 'a' + 10 : ch - '0'; };
            for (int i = 0; i < 56; i++) sc[i] = make_uint2(0u, 0u);
            for (int i = 0;; i++) {
                int id = i, buf, dep, w, wl;
                if (i < IT_WUV) {
                    const int u = (i - IT_CKV) >> 2;
                    buf = i < IT_CKV ? 4 + ((i - 1) >> 2) : u % 6;
                    dep = i < IT_CKV || u < 4 ? -1 : u < 6 ? EB_WQ + u - 4 : EB_UNIT0 + u - 6;
                    w = dig(tune.win[i]); wl = dig(tune.late[i]);
                    if (i) tn += tune.tau;
                } else {
                    const char ch = tune.tail[r][0][i - IT_WUV];
                    if (!ch) break;
                    buf = ch == 'V' ? B_WUV : ch == 'O' ? B_WO : ch == 'D' ? B_DN : ch == 'u' ? B_X + 1 : B_X;
                    id = (ch == 'V' ? IT_WUV : ch == 'O' ? IT_WO : ch == 'D' ? IT_DOWN : ch == 'u' ? IT_X + 2 : IT_X) + cnt[(int)ch]++;
                    dep = EB_UNIT0 + (buf < 2 ? buf + 6 : buf);
                    w = dig(tune.tail[r][1][i - IT_WUV]); wl = dig(tune.tail[r][2][i - IT_WUV]);
                    tn += 32 * dig(tune.tail[r][3][i - IT_WUV]);
                }
                if (id < IT_X ? (id - 1) & 3 : (id - IT_X) & 1) dep = -1;
                ids[i] = id;
                auto back = [&](int d) { return i < d ? 0 : (ids[i - d] && ids[i - d] <= NCP ? 1 : ids[i - d]) + 1; };
                sc[i].x = id | (buf * 4 + (id < IT_X ? (id - 1) & 3 : ((id - IT_X) & 1) * 2)) << 6 | (dep + 1) << 11 | (w > 32 ? NEVER + 1 : back(w)) << 18 | (wl ? back(wl) : 0) << 25;
                sc[i].y = tn;
            }
        }
        cudaGetSymbolAddress((void**)&scratch, g_scratch);
        scratch = (uint32_t*)(((uintptr_t)scratch + (2u << 20) - 1) & ~(uintptr_t)((2u << 20) - 1));
        cudaFuncSetAttribute(fused_kernel, cudaFuncAttributeMaxDynamicSharedMemorySize, SM_TOTAL);
        for (int i = 0; i < 12; i++) cached[i] = d_in[i];
        ready = true;
    }
    const First f = {{(const uint8_t*)d_in[2], (const uint8_t*)d_in[11]}, {(const __nv_bfloat16*)d_in[0], (const __nv_bfloat16*)d_in[10]}};
    fused_kernel<<<NCTA, NTHREADS, SM_TOTAL>>>(f, (__nv_bfloat16*)d_out, scratch, maps);
}
```

```cpp
#include <cuda_runtime.h>
#include <cuda_bf16.h>
#include <cuda.h>
#include <stdint.h>
#include <limits.h>

namespace {

constexpr int NCTA = 128;
constexpr int NTHREADS = 512;
constexpr int NUNITS = 8;
constexpr int NFF = 56, J_RED = 104, J_END = 120;
constexpr uint32_t SPIN_LIMIT = 1u << 22;

#define E1_EARLY 50
#define STAG 300
#define NUMA 1
#define NPROBE 3
#define NCP 2
#define W0 4
#define RD_ITEM 15
#define JAN_SLEEP 100
#define RD_SLEEP 400
#define HA_DELAY 200
#define H_SLEEP 100
#define QA_DELAY 600
#define QA_SLEEP 200
#define ML_DELAY 300
#define E1_SLEEP 50
#define MB_SLEEP 100
constexpr int B_WUV = 2, B_WO = 3, B_X = 4  , B_DN = 0;

constexpr int SM_U = 0;
constexpr int SM_XA = 6 * 32768;
constexpr int SM_XB = SM_XA + 12288;
constexpr int SM_MX = SM_XB + 16384;
constexpr int SM_FZ = SM_XB + 8192;
constexpr int SM_PB = SM_XB;
constexpr int SM_Y = SM_XB + 12288;
constexpr int SM_RED = SM_XB + 4096;
constexpr int SM_FS = SM_XB + 20480;
constexpr int SM_FV = SM_FS + 1024;
constexpr int SM_QX = SM_XA + 8192;
constexpr int SM_FQ = SM_FV + 512;
constexpr int SM_CLS = SM_FQ + 128;
constexpr int SM_W = SM_FQ + 256;
constexpr int SM_W2 = SM_MX + 2304;
constexpr int SM_SCR = SM_XA + 9216;
constexpr int SM_TR = SM_XB + 19456;
constexpr int SM_BAR = SM_W + 256;
constexpr int SM_TOTAL = SM_BAR + 1024;
static_assert(SM_TOTAL <= 232448, "smem");

enum { IT_MODA = 0, IT_WQ = 1, IT_WUK = 5, IT_CKV = 9, IT_WUV = 41, IT_WO = 45, IT_X = 49  , IT_DOWN = 53, NITEMS = 55,
       NEVER = 63,
       SF0 = 64,
       PF0 = 80,
       EB_UNIT0 = 96, MBB = 103,
       EB_WQ = 104, EB_WUK, QT, QB, JD, WR };

enum { MP_WQ = 0, MP_WUK, MP_CKV, MP_WUV, MP_DOWN, MP_WO, MP_GATE, MP_UP, MP_MODB, NMAPS };
struct First { const uint8_t* w[2]; const __nv_bfloat16* v[2]; };
struct Maps { CUtensorMap m[NMAPS]; uint2 sched[3][56]; };

enum { B_HA = 0,
       B_MB = 6,
       B_RD = 7,
       B_E2 = 8,
       B_QA = 16,
       B_ML = 32,
       B_E5 = 64,
       B_E3 = 80,
       B_PR = 96,
       B_TR = 100 };
constexpr int G_E1 = 1 << 19;
constexpr int G_TR = B_TR * 4096;
__device__ __align__(1024) uint32_t g_scratch[(8 << 20) / 4];

#define TRACE(slot) do {} while (0)
#define TRACE_Q(slot) do {} while (0)
#define TRACE_GT(slot) do {} while (0)

__device__ __forceinline__ uint32_t s2u(const void* p) { return (uint32_t)__cvta_generic_to_shared(p); }
__device__ __forceinline__ void mbar_init(uint32_t b, int c) { asm volatile("mbarrier.init.shared::cta.b64 [%0], %1;" :: "r"(b), "r"(c) : "memory"); }
__device__ __forceinline__ void mbar_expect(uint32_t b, uint32_t bytes) { asm volatile("mbarrier.arrive.expect_tx.shared::cta.b64 _, [%0], %1;" :: "r"(b), "r"(bytes) : "memory"); }
__device__ __forceinline__ void mbar_arrive(uint32_t b) { asm volatile("mbarrier.arrive.shared::cta.b64 _, [%0];" :: "r"(b) : "memory"); }
__device__ __forceinline__ void mbar_wait(uint32_t b, uint32_t ph) {
    asm volatile("{\n.reg .pred p;\nW: mbarrier.try_wait.parity.shared::cta.b64 p, [%0], %1;\n@!p bra W;\n}" :: "r"(b), "r"(ph) : "memory");
}
__device__ __forceinline__ void mbar_waitb(uint32_t b, uint32_t ph) {
    asm volatile("{\n.reg .pred p;\n.reg .u32 n;\nmov.u32 n, 0;\n"
                 "W: mbarrier.try_wait.parity.shared::cta.b64 p, [%0], %1;\n@p bra D;\n"
                 "add.u32 n, n, 1;\nsetp.lt.u32 p, n, 0x100000;\n@p bra W;\ntrap;\nD:\n}" :: "r"(b), "r"(ph) : "memory");
}
__device__ __forceinline__ uint32_t mbar_test(uint32_t b, uint32_t ph) {
    uint32_t ok;
    asm volatile("{\n.reg .pred p;\nmbarrier.test_wait.parity.shared::cta.b64 p, [%1], %2;\nselp.u32 %0, 1, 0, p;\n}" : "=r"(ok) : "r"(b), "r"(ph) : "memory");
    return ok;
}
__device__ __forceinline__ void bar_sync(int id, int n) { asm volatile("bar.sync %0, %1;" :: "r"(id), "r"(n) : "memory"); }
__device__ __forceinline__ void bar_arrive(int id, int n) { asm volatile("bar.arrive %0, %1;" :: "r"(id), "r"(n) : "memory"); }
__device__ __forceinline__ uint32_t peer_addr(uint32_t a, uint32_t rank) { uint32_t r; asm("mapa.shared::cluster.u32 %0, %1, %2;" : "=r"(r) : "r"(a), "r"(rank)); return r; }
__device__ __forceinline__ void st_async1(uint32_t a, float x, uint32_t bar) {
    asm volatile("st.async.weak.shared::cluster.mbarrier::complete_tx::bytes.f32 [%0], %1, [%2];" :: "r"(a), "f"(x), "r"(bar) : "memory");
}
__device__ __forceinline__ void st_async2(uint32_t a, float x, float y, uint32_t bar) {
    asm volatile("st.async.weak.shared::cluster.mbarrier::complete_tx::bytes.v2.f32 [%0], {%1, %2}, [%3];" :: "r"(a), "f"(x), "f"(y), "r"(bar) : "memory");
}
__device__ __forceinline__ uint32_t gtime() { uint32_t t; asm volatile("mov.u32 %0, %%globaltimer_lo;" : "=r"(t)); return t; }
__device__ __forceinline__ void fence_gpu() { asm volatile("fence.acq_rel.gpu;" ::: "memory"); }

__device__ __forceinline__ uint32_t enc(uint32_t b) { uint32_t r; asm("max.u32 %0, %1, 1;" : "=r"(r) : "r"(b)); return r; }
__device__ __forceinline__ uint32_t encf(float f) { return enc(__float_as_uint(f)); }
__device__ __forceinline__ void st_x1(uint32_t* p, uint32_t v) { asm volatile("st.relaxed.gpu.global.u32 [%0], %1;" :: "l"(p), "r"(v) : "memory"); }
__device__ __forceinline__ void st_x4(void* p, uint32_t a, uint32_t b, uint32_t c, uint32_t d) {
    asm volatile("st.relaxed.gpu.global.v4.u32 [%0], {%1, %2, %3, %4};" :: "l"(p), "r"(a), "r"(b), "r"(c), "r"(d) : "memory");
}
__device__ __forceinline__ void st2_x1(uint32_t* p, uint32_t v) { st_x1(p, v); st_x1(p + 1024, v); }
__device__ __forceinline__ void st2_x4(uint32_t* p, uint32_t a, uint32_t b, uint32_t c, uint32_t d) { st_x4(p, a, b, c, d); st_x4(p + 1024, a, b, c, d); }
__device__ __forceinline__ int near_off(int b, uint32_t cls) { return b * 4096 + (((__popc(b & 0x2C) ^ cls) & 1) << 10); }
__device__ __forceinline__ void ld_x(uint32_t& v, const void* p) { asm volatile("ld.relaxed.gpu.global.u32 %0, [%1];" : "=r"(v) : "l"(p) : "memory"); }
__device__ __forceinline__ void ld_x(uint4& v, const void* p) {
    asm volatile("ld.relaxed.gpu.global.v4.u32 {%0, %1, %2, %3}, [%4];" : "=r"(v.x), "=r"(v.y), "=r"(v.z), "=r"(v.w) : "l"(p) : "memory");
}
__device__ __forceinline__ void ld_x(uint2& v, const void* p) { asm volatile("ld.relaxed.gpu.global.v2.u32 {%0, %1}, [%2];" : "=r"(v.x), "=r"(v.y) : "l"(p) : "memory"); }
__device__ __forceinline__ uint32_t minw(uint32_t v) { return v; }
__device__ __forceinline__ uint32_t minw(const uint2& v) { return min(v.x, v.y); }
__device__ __forceinline__ uint32_t minw(const uint4& v) { return min(__vimin3_u32(v.x, v.y, v.z), v.w); }
template <int N> __device__ __forceinline__ uint32_t mint(const uint32_t* m) {
    if constexpr (N == 1) return m[0];
    else if constexpr (N == 2) return min(m[0], m[1]);
    else return __vimin3_u32(mint<(N + 2) / 3>(m), mint<(N + 1) / 3>(m + (N + 2) / 3), mint<N / 3>(m + (N + 2) / 3 + (N + 1) / 3));
}

template <int STRIDE, int S4 = 4 * STRIDE, typename T, int N>
__device__ __forceinline__ void poll_start(T (&v)[N], const void* base) {
#pragma unroll
    for (int i = 0; i < N; i++) ld_x(v[i], (const uint8_t*)base + (i & 3) * STRIDE + (i >> 2) * S4);
}
struct Nop { __device__ void operator()() const {} };
template <int STRIDE, int SLEEP, bool STARTED = false, int S4 = 4 * STRIDE, typename T, int N, typename F = Nop>
__device__ __forceinline__ void poll(T (&v)[N], const void* base, F idle = F()) {
    if (!STARTED) { poll_start<STRIDE, S4>(v, base); idle(); }
#pragma unroll 1
    for (uint32_t it = 0;; it++) {
        uint32_t m[N];
#pragma unroll
        for (int i = 0; i < N; i++) m[i] = minw(v[i]);
        if (__all_sync(0xffffffffu, mint<N>(m) != 0)) break;
        if (SLEEP && it > 0) __nanosleep(SLEEP);
#pragma unroll
        for (int i = 0; i < N; i++) if (!m[i]) ld_x(v[i], (const uint8_t*)base + (i & 3) * STRIDE + (i >> 2) * S4);
        idle();
        if (it > SPIN_LIMIT) __trap();
    }
}

__device__ __forceinline__ float bflo(uint32_t w) { return __uint_as_float(w << 16); }
__device__ __forceinline__ float bfhi(uint32_t w) { return __uint_as_float(w & 0xffff0000u); }
__device__ __forceinline__ uint32_t pack2(float lo, float hi) {
    uint32_t r; asm("cvt.rn.bf16x2.f32 %0, %1, %2;" : "=r"(r) : "f"(hi), "f"(lo)); return r;
}
__device__ __forceinline__ float rbf(float x) { return __uint_as_float(pack2(0.f, x)); }
__device__ __forceinline__ float sumlo(const uint32_t (&v)[8]) { return ((bflo(v[0]) + bflo(v[1])) + (bflo(v[2]) + bflo(v[3]))) + ((bflo(v[4]) + bflo(v[5])) + (bflo(v[6]) + bflo(v[7]))); }
__device__ __forceinline__ float sumhi(const uint32_t (&v)[8]) { return ((bfhi(v[0]) + bfhi(v[1])) + (bfhi(v[2]) + bfhi(v[3]))) + ((bfhi(v[4]) + bfhi(v[5])) + (bfhi(v[6]) + bfhi(v[7]))); }
__device__ __forceinline__ float ex2(float x) { float r; asm("ex2.approx.ftz.f32 %0, %1;" : "=f"(r) : "f"(x)); return r; }
__device__ __forceinline__ float shx(float v, int m) { return __shfl_xor_sync(0xffffffffu, v, m); }
__device__ __forceinline__ uint4 lds128(uint32_t a) { uint4 v; asm volatile("ld.shared.v4.u32 {%0, %1, %2, %3}, [%4];" : "=r"(v.x), "=r"(v.y), "=r"(v.z), "=r"(v.w) : "r"(a) : "memory"); return v; }
__device__ __forceinline__ uint32_t lds32(uint32_t a) { uint32_t v; asm volatile("ld.shared.u32 %0, [%1];" : "=r"(v) : "r"(a) : "memory"); return v; }
__device__ __forceinline__ void sts32(uint32_t a, uint32_t v) { asm volatile("st.shared.u32 [%0], %1;" :: "r"(a), "r"(v) : "memory"); }
__device__ __forceinline__ void sts16(uint32_t a, uint32_t v) { asm volatile("st.shared.u16 [%0], %1;" :: "r"(a), "h"((uint16_t)v) : "memory"); }
__device__ __forceinline__ int frag_off(int k) { return (k >> 5) * 64 + ((k >> 1) & 3) * 16 + ((k >> 4) & 1) * 8 + ((k >> 3) & 1) * 4 + (k & 1) * 2; }

template <bool TRANS>
__device__ __forceinline__ uint4 ldsm(uint32_t a) {
    uint4 r;
    if (TRANS) asm volatile("ldmatrix.sync.aligned.m8n8.x4.trans.shared.b16 {%0, %1, %2, %3}, [%4];" : "=r"(r.x), "=r"(r.y), "=r"(r.z), "=r"(r.w) : "r"(a) : "memory");
    else asm volatile("ldmatrix.sync.aligned.m8n8.x4.shared.b16 {%0, %1, %2, %3}, [%4];" : "=r"(r.x), "=r"(r.y), "=r"(r.z), "=r"(r.w) : "r"(a) : "memory");
    return r;
}
__device__ __forceinline__ void mma(float (&c)[4], uint32_t a0, uint32_t a1, uint32_t a2, uint32_t a3, uint32_t b0, uint32_t b1) {
    asm volatile("mma.sync.aligned.m16n8k16.row.col.f32.bf16.bf16.f32 {%0,%1,%2,%3}, {%4,%5,%6,%7}, {%8,%9}, {%0,%1,%2,%3};"
                 : "+f"(c[0]), "+f"(c[1]), "+f"(c[2]), "+f"(c[3]) : "r"(a0), "r"(a1), "r"(a2), "r"(a3), "r"(b0), "r"(b1));
}
template <bool TRANS, typename F>
__device__ __forceinline__ void load8(uint4 (&a)[8], F addr) {
    __syncwarp();
#pragma unroll
    for (int s = 0; s < 8; s++) a[s] = ldsm<TRANS>(addr(s));
}
__device__ __forceinline__ void mma8(float (&c)[4], const uint4 (&a)[8], const uint4 (&b)[4]) {
    float e[4][4];
#pragma unroll
    for (int s = 0; s < 8; s++) {
        if (s < 4) e[s][0] = e[s][1] = e[s][2] = e[s][3] = 0.f;
        mma(e[s & 3], a[s].x, a[s].y, a[s].z, a[s].w, (s & 1) ? b[s >> 1].z : b[s >> 1].x, (s & 1) ? b[s >> 1].w : b[s >> 1].y);
    }
#pragma unroll
    for (int i = 0; i < 4; i++) c[i] = (e[0][i] + e[1][i]) + (e[2][i] + e[3][i]);
}
__device__ __forceinline__ void ldfrag(uint4 (&b)[4], uint32_t a) {
    asm volatile("ld.shared.v4.u32 {%0,%1,%2,%3}, [%16];\nld.shared.v4.u32 {%4,%5,%6,%7}, [%16+64];\n"
                 "ld.shared.v4.u32 {%8,%9,%10,%11}, [%16+128];\nld.shared.v4.u32 {%12,%13,%14,%15}, [%16+192];\n"
                 : "=r"(b[0].x), "=r"(b[0].y), "=r"(b[0].z), "=r"(b[0].w), "=r"(b[1].x), "=r"(b[1].y), "=r"(b[1].z), "=r"(b[1].w),
                   "=r"(b[2].x), "=r"(b[2].y), "=r"(b[2].z), "=r"(b[2].w), "=r"(b[3].x), "=r"(b[3].y), "=r"(b[3].z), "=r"(b[3].w) : "r"(a) : "memory");
}
__device__ __forceinline__ void quad_pair(float x, float y, int t, float& lo, float& hi) {
    const float k = ((t & 1) ? y : x) + shx((t & 1) ? x : y, 1);
    lo = k + shx(k, 2); hi = shx(k, 4) + shx(k, 6);
}
__device__ __forceinline__ void pin(uint32_t& x) { asm volatile("" : "+r"(x)); }
template <typename T> __device__ __forceinline__ void pin(T*& x) { asm volatile("" : "+l"(x)); }
__device__ __forceinline__ float4 ldsf4(uint32_t a) { const uint4 v = lds128(a); return make_float4(__uint_as_float(v.x), __uint_as_float(v.y), __uint_as_float(v.z), __uint_as_float(v.w)); }
__device__ __forceinline__ float sum4(const float4& f) { return (f.x + f.y) + (f.z + f.w); }
__device__ __forceinline__ void stsf(uint32_t a, float v) { sts32(a, __float_as_uint(v)); }

__device__ __forceinline__ void wg_fence() { asm volatile("wgmma.fence.sync.aligned;" ::: "memory"); }
__device__ __forceinline__ void wg_commit() { asm volatile("wgmma.commit_group.sync.aligned;" ::: "memory"); }
__device__ __forceinline__ void wg_wait1() { asm volatile("wgmma.wait_group.sync.aligned 1;" ::: "memory"); }
__device__ __forceinline__ void wg_wait0() { asm volatile("wgmma.wait_group.sync.aligned 0;" ::: "memory"); }
#define R8(o) "+f"(d[o]), "+f"(d[o + 1]), "+f"(d[o + 2]), "+f"(d[o + 3]), "+f"(d[o + 4]), "+f"(d[o + 5]), "+f"(d[o + 6]), "+f"(d[o + 7])
__device__ __forceinline__ void wgmma_rs_n32(float (&d)[16], const uint4& a, uint64_t db, int acc) {
    asm volatile("{\n.reg .pred p;\nsetp.ne.b32 p, %21, 0;\n"
        "wgmma.mma_async.sync.aligned.m64n32k16.f32.bf16.bf16 "
        "{%0,%1,%2,%3,%4,%5,%6,%7,%8,%9,%10,%11,%12,%13,%14,%15}, {%16,%17,%18,%19}, %20, p, 1, 1, 0;\n}"
        : R8(0), R8(8) : "r"(a.x), "r"(a.y), "r"(a.z), "r"(a.w), "l"(db), "r"(acc));
}
#define PV_LO "{%0,%1,%2,%3,%4,%5,%6,%7,%8,%9,%10,%11,%12,%13,%14,%15,%16,%17,%18,%19,%20,%21,%22,%23,%24,%25,%26,%27,%28,%29,%30,%31,%32,%33,%34,%35,%36,%37,%38,%39,%40,%41,%42,%43,%44,%45,%46,%47,%48,%49,%50,%51,%52,%53,%54,%55,%56,%57,%58,%59,%60,%61,%62,%63}, "
#define PV_HI "{%64,%65,%66,%67,%68,%69,%70,%71,%72,%73,%74,%75,%76,%77,%78,%79,%80,%81,%82,%83,%84,%85,%86,%87,%88,%89,%90,%91,%92,%93,%94,%95,%96,%97,%98,%99,%100,%101,%102,%103,%104,%105,%106,%107,%108,%109,%110,%111,%112,%113,%114,%115,%116,%117,%118,%119,%120,%121,%122,%123,%124,%125,%126,%127}, "
__device__ __forceinline__ void wgmma_pv(float (&d)[128], const uint4& a, uint32_t blo, int acc) {
    asm volatile("{\n.reg .pred p;\n.reg .b32 u0, u1, u2, u3, t;\n.reg .b64 d0, d1, d2, d3;\nsetp.ne.b32 p, %133, 0;\n"
        "mov.b64 d0, {%132, 0x40000100};\nadd.u32 t, %132, 512;\nmov.b64 d1, {t, 0x40000100};\n"
        "add.u32 t, %132, 128;\nmov.b64 d2, {t, 0x40000100};\nadd.u32 t, %132, 640;\nmov.b64 d3, {t, 0x40000100};\n"
        "wgmma.fence.sync.aligned;\n"
        "wgmma.mma_async.sync.aligned.m64n128k16.f32.bf16.bf16 " PV_LO "{%128, u0, %129, u1}, d0, p, 1, 1, 1;\n"
        "wgmma.mma_async.sync.aligned.m64n128k16.f32.bf16.bf16 " PV_LO "{%130, u2, %131, u3}, d1, 1, 1, 1, 1;\n"
        "wgmma.commit_group.sync.aligned;\n"
        "wgmma.mma_async.sync.aligned.m64n128k16.f32.bf16.bf16 " PV_HI "{%128, u0, %129, u1}, d2, p, 1, 1, 1;\n"
        "wgmma.mma_async.sync.aligned.m64n128k16.f32.bf16.bf16 " PV_HI "{%130, u2, %131, u3}, d3, 1, 1, 1, 1;\n"
        "wgmma.commit_group.sync.aligned;\n}"
        : R8(0), R8(8), R8(16), R8(24), R8(32), R8(40), R8(48), R8(56), R8(64), R8(72), R8(80), R8(88), R8(96), R8(104), R8(112), R8(120)
        : "r"(a.x), "r"(a.y), "r"(a.z), "r"(a.w), "r"(blo), "r"(acc) : "memory");
}

template <int NW>
__device__ __forceinline__ void ln_stats(float s, float q, float sh, float* scr, int w, int lane, int bar, float& mean_b, float& sd_b) {
#pragma unroll
    for (int o = 16; o; o >>= 1) { s += shx(s, o); q += shx(q, o); }
    constexpr float n = 512.f / NW;
    if (lane == 0) { scr[w] = sh + s * (1.f / n); scr[NW + w] = q - s * s * (1.f / n); }
    bar_sync(bar, NW * 32);
    float mu = 0.f, m2 = 0.f;
#pragma unroll
    for (int i = 0; i < NW; i++) { mu += scr[i]; m2 += scr[NW + i]; }
    mu *= 1.f / NW;
#pragma unroll
    for (int i = 0; i < NW; i++) { const float d = scr[i] - mu; m2 = fmaf(n * d, d, m2); }
    mean_b = rbf(mu);
    sd_b = rbf(sqrtf(rbf(rbf(fmaxf(m2, 0.f) * (1.f / 512.f)) + 1e-5f)));
}
__device__ __forceinline__ float ln_mod(float x, float mean_b, float sd_b, float c, float s) {
    return rbf(rbf(__fdividef(rbf(x - mean_b), sd_b)) * rbf(1.f + c)) + s;
}

__global__ void __cluster_dims__(2, 1, 1) __launch_bounds__(NTHREADS, 1)
fused_kernel(const __grid_constant__ First F, __nv_bfloat16* __restrict__ out, uint32_t* __restrict__ gs, const __grid_constant__ Maps M) {
    extern __shared__ __align__(1024) uint8_t sm[];
    const uint32_t sb = s2u(sm);
    const int tid = threadIdx.x, lane = tid & 31;
    const int j = blockIdx.x, rk = j & 1;
    const int g = lane >> 2, t = lane & 3;
    const int r8 = lane & 7, lb3 = (lane >> 3) & 1, lb4 = lane >> 4;
    uint64_t pol;
    asm("createpolicy.fractional.L2::evict_first.b64 %0, 1.0;" : "=l"(pol));
    {
        auto cpa = [&](uint32_t d, const uint8_t* s) {
            asm volatile("cp.async.cg.shared.global.L2::cache_hint.L2::128B [%0], [%1], 16, %2;" :: "r"(d), "l"(s), "l"(pol) : "memory");
        };
        const uint32_t ut = threadIdx.x, uj = blockIdx.x;
        const uint8_t* w = F.w[ut >= 128];
        if (ut < 128) {
            const uint32_t dq = (sb + ut * 16) ^ ((ut * 2) & 0x70);
            const uint8_t* sq = w + (uint32_t)(((uj & 1) * 256 + (ut >> 3)) * 8192 + (uj >> 1) * 128 + (ut & 7) * 16);
#pragma unroll
            for (int i = 0; i < 4 * NCP; i++) cpa(dq + 4 * 32768 + i * 2048, sq + i * 131072);
        } else if (ut < 384) {
            const uint32_t dm = (sb + ut * 16) ^ ((ut * 2) & 0x10);
            const uint8_t* sa = w + (uint32_t)(((uj >> 5) * 128 + (ut >> 1) - 64) * 6144 + (uj & 31) * 32 + (ut & 1) * 16);
            cpa(dm + SM_XA - 2048, sa); cpa(dm + SM_XA + 2048, sa + 1024);
        }
        else if (ut == 480 && uj < 64) asm volatile("prefetch.global.L2 [%0];" :: "l"(F.v[(uj >> 3) & 1] + (uj & 7) * 64));
    }
    const int warp = __shfl_sync(0xffffffffu, tid >> 5, 0);
    const __nv_bfloat16* const xin = F.v[0];
    uint32_t* const pl = gs + (warp < 2 ? (B_PR + (j >> 5)) * 4096 + (j & 31) * 32 : G_E1 + j * 8192) + (warp & 1) * 1024 + lane;
    if (warp < 4) st_x1(pl, 1u);
    auto BAR = [&](int i) -> uint32_t { return sb + SM_BAR + i * 8; };
    const uint32_t a16 = (r8 + 8 * lb4) * 32 + ((lb3 ^ (r8 >> 2)) * 16);
    const uint32_t a128 = (r8 + 8 * lb4) * 128 + ((((warp & 3) * 2 + lb3) ^ r8) * 16);
    auto ldcls = [&]() -> uint32_t { return *(const volatile uint32_t*)(sm + SM_CLS); };
    auto clear_head = [&]() {
        st2_x1(gs + (B_HA + ((j >> 4) & 1) * 2 + lb4) * 4096 + (j >> 5) * 256 + (j & 15) * 16 + (lane & 15), 0u);
        st2_x4(gs + (B_QA + rk * 8 + ((j >> 1) & 1) * 4 + (j >> 5)) * 4096 + g * 128 + ((j >> 2) & 7) * 16 + t * 4, 0u, 0u, 0u, 0u);
        if (lane < 8) st2_x1(gs + B_RD * 4096 + j * 8 + lane, 0u);
    };
    auto tma = [&](uint32_t dst, const CUtensorMap* mp, uint32_t bar, int c0, int c1, int c2, int c3) {
        asm volatile("{\n.reg .pred p;\nelect.sync _|p, 0xffffffff;\n"
                     "@p cp.async.bulk.tensor.4d.shared::cluster.global.mbarrier::complete_tx::bytes.L2::cache_hint [%0], [%1, {%3, %4, %5, %6}], [%2], %7;\n}"
                     :: "r"(dst), "l"(mp), "r"(bar), "r"(c0), "r"(c1), "r"(c2), "r"(c3), "l"(pol) : "memory");
    };
    if (warp <= 12 || warp == 15) {
        const int grp = warp == 12 ? 0 : warp == 15 ? 13 : warp + 1;
        const uint32_t cnt = grp < 10 ? 1 : grp < 13 ? 4 : 8;
        if (lane == 0) {
#pragma unroll
            for (int i = 0; i < 8; i++) mbar_init(BAR(grp * 8 + i), (i < 2 && grp == 0) ? (i ? 128 : 256) : cnt);
        }
        __syncwarp();
        if (grp < 10 && lane < 8 && (grp || lane > NCP)) mbar_expect(BAR(grp * 8 + lane), grp >= 8 ? 4096 : grp * 8 + lane < IT_X ? 8192 : 16384);
        asm volatile("fence.mbarrier_init.release.cluster;" ::: "memory");
        __syncwarp();
        if (warp == 12) {
#pragma unroll
            for (int i = NCP + 1; i < W0; i++) tma(sb + (15 + i) * 8192, &M.m[MP_WQ], BAR(i), 0, rk * 256 + (i - 1) * 64, j >> 1, 0);
        }
    } else if (warp == 13) {
        if (lane < NMAPS) asm volatile("prefetch.tensormap [%0];" :: "l"(&M.m[lane]) : "memory");
    } else if (warp == 14) {
        clear_head();
    }
    __syncthreads();
    uint32_t in1 = 0, in2 = 0;
    if (warp < 4) { in1 = *(const uint32_t*)(xin + 2 * tid); in2 = *(const uint32_t*)(xin + 256 + 2 * tid); }
    else if (warp < 12) in1 = *(const uint32_t*)(F.v[1] + 2 * (tid - 128));
    if (warp < 12) asm volatile("cp.async.mbarrier.arrive.noinc.shared::cta.b64 [%0];" :: "r"(BAR(warp < 4)) : "memory");
    asm volatile("barrier.cluster.arrive.relaxed.aligned;" ::: "memory");

    if (warp >= 12) {
    asm volatile("setmaxnreg.dec.sync.aligned.u32 64;");
    if (warp == 12) {
        static_assert(W0 > NCP && W0 <= 5 && NCP >= 1 && NCP <= 4, "W0");
        const uint2* sched = M.sched[j < NFF ? 0 : j < J_RED ? 1 : 2];
        uint2 en = sched[W0];
        const uint32_t t0 = gtime();
        const uint32_t sp = __reduce_or_sync(0xffffffffu, sb);
        const int cx = (j >> 1) * 64 + (j < NFF ? 0 : 1024 - NFF * 32);
#pragma unroll 1
        for (int i = W0; en.x; i++) {
            const uint32_t e = en.x, tn = t0 + (int16_t)en.y, mp = (en.y >> 16) & 15, st = (en.y >> 20) * 64;
            en = sched[i + 1];
            if (mp == MP_MODB && j >= J_END) break;
            uint32_t c0 = mp == MP_WO ? (j & 7) * 64 : mp > MP_WO ? cx : 0;
            uint32_t c1 = mp == MP_CKV ? 0 : mp == MP_DOWN ? j * 32 : st + (mp == MP_WUV ? (j & 3) * 32 : mp == MP_WO ? (j >> 3) * 256 : rk * 256);
            uint32_t c2 = mp < MP_CKV ? j >> 1 : mp == MP_CKV ? rk * 4 : mp == MP_WUV ? (j >> 2) * 2 : mp == MP_DOWN ? st >> 4 : 0;
            uint32_t c3 = mp == MP_CKV ? st * 2 + (j & ~1) : 0;
            uint32_t dst = sp + ((e << 7) & 0x3e000), bar = sp + SM_BAR + (e & 63) * 8;
            const uint32_t w0 = (e >> 8) & 0x3f8, w1 = (e >> 15) & 0x3f8, w2 = (e >> 22) & 0x3f8, bb = sp + SM_BAR - 8;
            const CUtensorMap* pm = &M.m[mp];
            pin(dst); pin(bar); pin(c0); pin(c1); pin(c2); pin(c3); pin(pm);
            if (w0) mbar_wait(bb + w0, 0);
            if (w2) {
                mbar_wait(bb + w2, 0);
                while (!__any_sync(0xffffffffu, mbar_test(bb + w1, 0) | ((int)(gtime() - tn) > 0))) {}
            } else if (w1) mbar_wait(bb + w1, 0);
            tma(dst, pm, bar, c0, c1, c2, c3);
        }
    } else if (warp == 13) {
#pragma unroll
        for (int i = 0; i < 2; i++) st_x4(gs + (B_ML + rk * 16 + i * 8 + g) * 4096 + (t >> 1) * 1024 + (j >> 1) * 8 + (t & 1) * 4, 0u, 0u, 0u, 0u);
        if (lane < 16) st2_x4(gs + (B_E2 + (j >> 4)) * 4096 + (j & 15) * 64 + lane * 4, 0u, 0u, 0u, 0u);
        st2_x1(gs + (B_E3 + (j >> 5)) * 4096 + (j & 31) * 32 + lane, 0u);
        if (lane < 8) st2_x1(gs + B_MB * 4096 + j * 8 + lane, 0u);
        if (j < NFF) {
#pragma unroll
            for (int i = 0; i < 2; i++) st2_x4(gs + (B_E5 + i * 8 + g) * 4096 + j * 16 + t * 4, 0u, 0u, 0u, 0u);
        }
        bar_sync(9, 64);
        const uint32_t cs = ldcls();
#pragma unroll 1
        for (int i = 0; i < 32; i++) {
            st_x4(gs + G_E1 + j * 8192 + (i >> 3) * 2048 + ((((cs >> 1) ^ (i >> 3)) & 1) << 10) + (i & 7) * 128 + lane * 4, 0u, 0u, 0u, 0u);
            __nanosleep(JAN_SLEEP);
        }
        fence_gpu();
        if (lane < 8) st2_x1(gs + B_RD * 4096 + j * 8 + lane, 1u + (cs >> 1));
        if (lane == 0) TRACE(41);
        uint32_t rd[4];
        mbar_wait(BAR(IT_CKV + RD_ITEM), 0);
        poll<1024, RD_SLEEP>(rd, gs + near_off(B_RD, cs) + lane * 8);
#pragma unroll
        for (int i = 0; i < 4; i++) {
            const uint32_t m = __ballot_sync(0xffffffffu, rd[i] == 2u);
            if (lane == 0) sts32(sb + SM_CLS + 16 + i * 4, m);
        }
        __syncwarp();
        if (lane < 8) mbar_arrive(BAR(JD));
        if (lane == 0) TRACE(42);
    } else if (warp == 14) {
        uint2 ml[2];
        mbar_waitb(BAR(JD), 0);
        const uint32_t cls = ldcls();
        mbar_waitb(BAR(PF0 + 2 * NUNITS - 1), 0);
        __nanosleep(ML_DELAY);
        const uint32_t* pl2 = gs + near_off(B_ML + (j >> 2), cls) + lane * 8;
        const uint32_t wa = sb + SM_W + lb4 * 64 + t * 16 + (g & 3) * 4;
        poll_start<1024>(ml, pl2);
        uint32_t w0 = 0, w1 = 0, redo = 0;
        bool first = true;
#pragma unroll 1
        for (uint32_t it = 0;; it++) {
            const bool p0 = minw(ml[0]) != 0, p1 = minw(ml[1]) != 0;
            const int n = __popc(__ballot_sync(0xffffffffu, p0)) + __popc(__ballot_sync(0xffffffffu, p1));
            const uint32_t x0 = ml[0].x, x1 = ml[1].x;
            if (n < 64) {
                if (!p0) ld_x(ml[0], pl2);
                if (!p1) ld_x(ml[1], pl2 + 256);
            }
            if (n == 64 || (first && n >= E1_EARLY)) {
                auto ord = [](int x) { return x ^ ((x >> 31) & 0x7fffffff); };
                const int o0 = ord(x0), o1 = ord(x1);
                const float mm = __int_as_float(ord(__reduce_max_sync(0xffffffffu, max(p0 ? o0 : INT_MIN, p1 ? o1 : INT_MIN))));
                const float lo = __int_as_float(ord(__reduce_min_sync(0xffffffffu, min(p0 ? o0 : INT_MAX, p1 ? o1 : INT_MAX))));
                const uint32_t v0 = pack2(ex2((p0 ? __uint_as_float(x0) : lo) - mm), 0.f), v1 = pack2(ex2((p1 ? __uint_as_float(x1) : lo) - mm), 0.f);
                redo = !first && __any_sync(0xffffffffu, v0 != w0 || v1 != w1);
                w0 = v0; w1 = v1;
                sts32(wa - redo * (SM_W - SM_W2), w0 * 0x10001u); sts32(wa - redo * (SM_W - SM_W2) + 128, w1 * 0x10001u);
                if (first) bar_arrive(3, 416);
                first = false;
                if (n == 64) break;
            }
            if (it > SPIN_LIMIT) __trap();
        }
        if (lane == 0) TRACE_Q(37);
        float L = bflo(w0) * __uint_as_float(ml[0].y) + bflo(w1) * __uint_as_float(ml[1].y);
#pragma unroll
        for (int o = 16; o; o >>= 1) L += shx(L, o);
        if (lane == 0) *(float2*)(sm + SM_FQ) = make_float2(__frcp_rn(L), __uint_as_float(redo));
        __syncwarp();
        if (lane < 8) mbar_arrive(BAR(WR));
        if (lane == 0) TRACE(10);
        bar_sync(4, 288);
        clear_head();
        if (j < NFF) {
            uint32_t ya = sb + SM_Y + lane * 16, sa = peer_addr(sb + SM_RED + 2048 + rk * 8, lane & 1), tb = peer_addr(BAR(MBB), lane & 1);
            pin(ya); pin(sa); pin(tb);
            bar_sync(7, 288);
            const float4 y0 = ldsf4(ya), y1 = ldsf4(ya + 512);
            float s = sum4(y0) + sum4(y1);
            float q = (fmaf(y0.x, y0.x, y0.y * y0.y) + fmaf(y0.z, y0.z, y0.w * y0.w)) + (fmaf(y1.x, y1.x, y1.y * y1.y) + fmaf(y1.z, y1.z, y1.w * y1.w));
#pragma unroll
            for (int o = 16; o; o >>= 1) { s += shx(s, o); q += shx(q, o); }
            if (lane < 2) st_async2(sa, s, q, tb);
        }
    } else if (warp == 15) {
        mbar_waitb(BAR(IT_X - 1), 0);
        if (j < J_END) mbar_waitb(BAR(j < NFF ? NITEMS - 1 : MBB), 0);
    }
    } else if (warp < 4) {
        float* scr = (float*)(sm + SM_SCR);
        uint32_t cls;
        {
            uint2 ha[8];
            {
                uint32_t best = 0xffffffffu;
#pragma unroll
                for (int i = 0; i < NPROBE; i++) {
                    uint32_t t0, t1, o;
                    asm volatile("mov.u32 %0, %%clock;" : "=r"(t0));
                    asm volatile("atom.relaxed.gpu.global.exch.b32 %0, [%1], %2;" : "=r"(o) : "l"(pl), "r"(2u + i) : "memory");
                    asm volatile("{\n.reg .pred p;\nsetp.ne.u32 p, %1, 0x1234567;\nmov.u32 %0, 0;\n@p mov.u32 %0, %%clock;\n}" : "=r"(t1) : "r"(o));
                    best = min(best, t1 - t0);
                }
                if (lane == 0) scr[16 + warp] = __uint_as_float(best);
            }
            const float sh = __shfl_sync(0xffffffffu, bflo(in1), 0);
            const float v0 = bflo(in1) - sh, v1 = bfhi(in1) - sh, v2 = bflo(in2) - sh, v3 = bfhi(in2) - sh;
            float mb, sd;
            ln_stats<4>((v0 + v1) + (v2 + v3), (v0 * v0 + v1 * v1) + (v2 * v2 + v3 * v3), sh, scr, warp, lane, 2, mb, sd);
            if (!rk) in2 = in1;
            const uint4 lt = *(const uint4*)(scr + 16);
            cls = NUMA ? ((lt.y < lt.x) ^ (__popc((B_PR + (j >> 5)) & 0x2C) & 1)) | (lt.w < lt.z) << 1 : 0;
            if (warp == 0) { if (lane == 0) sts32(sb + SM_CLS, cls); bar_arrive(9, 64); }
            if (tid == 0) TRACE(38);
            asm volatile("barrier.cluster.wait.aligned;" ::: "memory");
            mbar_wait(BAR(IT_MODA), 0);
            __nanosleep(HA_DELAY);
            poll<1024, H_SLEEP, false, 16384>(ha, gs + near_off(B_HA + rk * 2, cls) + 2 * tid);
            auto rsum = [](uint32_t a, uint32_t b, uint32_t c, uint32_t d) { return rbf((__uint_as_float(a) + __uint_as_float(b)) + (__uint_as_float(c) + __uint_as_float(d))); };
            sts32(sb + SM_FV + frag_off(2 * tid),
                  pack2(ln_mod(bflo(in2), mb, sd, rsum(ha[4].x, ha[5].x, ha[6].x, ha[7].x), rsum(ha[0].x, ha[1].x, ha[2].x, ha[3].x)),
                        ln_mod(bfhi(in2), mb, sd, rsum(ha[4].y, ha[5].y, ha[6].y, ha[7].y), rsum(ha[0].y, ha[1].y, ha[2].y, ha[3].y))));
            bar_arrive(5, 384);
            mbar_wait(BAR(QB), 0);
            if (tid < 64) {
                const float* qx = (const float*)(sm + SM_QX) + tid;
                sts16(sb + SM_FQ + frag_off(tid), pack2((qx[0] + qx[64]) + (qx[128] + qx[192]), 0.f));
            }
            bar_arrive(6, 384);
        }
        asm volatile("setmaxnreg.inc.sync.aligned.u32 192;");
        float acc[128];
        float M = 0.f;
        uint32_t pa = sb + SM_XA + warp * 512 + lane * 16, ma = sb + SM_MX + (warp * 8 + g) * 4, pf = BAR(PF0);
        uint32_t blo = __reduce_or_sync(0xffffffffu, (((sb + SM_U) & 0x3FFFFu) >> 4) | 0x400000u);
        uint32_t* e1[4];
#pragma unroll
        for (int i = 0; i < 4; i++) e1[i] = gs + G_E1 + (warp * 8 + g) * 4 * 8192 + (rk * 2 + (j >> 6)) * 2048 + ((j >> 1) & 31) * 32 + t * 4;
#pragma unroll 1
        for (int h = 0; h < 2 * NUNITS; h++) {
            mbar_wait(pf, 0);
            const float m = __uint_as_float(lds32(ma));
            const uint4 pn = lds128(pa);
            wg_wait0();
#pragma unroll
            for (int i = 0; i < 128; i++) asm volatile("" : "+f"(acc[i]) :: "memory");
            if (h == 0) M = m;
            uint32_t b2 = 0x3f803f80u;
            if (__builtin_expect(__any_sync(0xffffffffu, m != M), 0)) {
                const float Mn = fmaxf(M, m), alpha = ex2(M - Mn), beta = ex2(m - Mn);
                M = Mn;
                b2 = pack2(beta, beta);
#pragma unroll
                for (int jj = 0; jj < 32; jj++) { acc[4 * jj] *= alpha; acc[4 * jj + 1] *= alpha; }
            }
            auto mul2 = [](uint32_t x, uint32_t y) { uint32_t r; asm("mul.rn.bf16x2 %0, %1, %2;" : "=r"(r) : "r"(x), "r"(y)); return r; };
            const uint4 p = make_uint4(mul2(pn.x, b2), mul2(pn.y, b2), mul2(pn.z, b2), mul2(pn.w, b2));
            if (tid == 0 && (h & 1)) TRACE_Q(48 + (h >> 1));
            wgmma_pv(acc, p, blo, h);
            if (lane == 0 && h > 0 && !(h & 1)) mbar_arrive(BAR(EB_UNIT0 + (h >> 1) - 1));
            blo += h == 11 ? -11 * 1024 : 1024;
            pa += (h == 5 || h == 11) ? -5 * 2048 : 2048;
            ma += 128; pf += 8;
            if (h == 2 * NUNITS - 3) {
                mbar_wait(BAR(JD), 0);
                const uint32_t hm = (*(const uint32_t*)(sm + SM_CLS + 16 + warp * 4) >> (g * 4)) ^ ((j >> 6) ? 15u : 0u);
#pragma unroll
                for (int i = 0; i < 4; i++) e1[i] += ((hm >> i) & 1) << 10;
            }
        }
#pragma unroll
        for (int vv = 0; vv < 2; vv++) {
            if (vv && M == 1.f) __trap();
            if (vv) wg_wait0(); else wg_wait1();
#pragma unroll
            for (int i = 0; i < 64; i++) asm volatile("" : "+f"(acc[vv * 64 + i]) :: "memory");
            if (tid == 0 && !vv) TRACE_Q(63);
#pragma unroll
            for (int i = 0; i < 4; i++) {
                const float* a = &acc[vv * 64 + i * 16];
                st_x4(e1[i] + i * 8192 + vv * 16, enc(pack2(a[0], a[1])), enc(pack2(a[4], a[5])), enc(pack2(a[8], a[9])), enc(pack2(a[12], a[13])));
            }
        }
        bar_arrive(3, 416);
        if (tid == 0) TRACE_Q(17);
        if (j < NFF) {
            uint4 a[16];
            const uint32_t ad = sb + SM_U + B_DN * 32768 + warp * 8192 + (r8 + 8 * lb4) * 128 + (lb3 ^ r8) * 16;
            uint32_t rl = sb + SM_RED + lane * 16;
            uint32_t* p5 = gs + (B_E5 + warp * 4 + (t >> 1)) * 4096 + j * 16 + (t & 1) * 8 + g;
            pin(rl); pin(p5);
            if (lane == 0) mbar_expect(BAR(MBB), 4);
            auto ldd = [&]() {
#pragma unroll
                for (int s = 0; s < 16; s++) a[s] = ldsm<true>((ad ^ ((s & 3) * 32)) + (s >> 2) * 2048);
            };
            const uint32_t db = BAR(IT_DOWN + (warp >> 1));
            mbar_wait(BAR(MBB), 0);
            const float4 st = ldsf4(sb + SM_RED + 2048);
            const bool hd = __all_sync(0xffffffffu, mbar_test(db, 0));
            if (hd) ldd();
            const float mu = (st.x + st.z) * (1.f / 512.f);
            float rstd;
            asm volatile("rsqrt.approx.ftz.f32 %0, %1;" : "=f"(rstd) : "f"(fmaxf(fmaf(-mu, mu, (st.y + st.w) * (1.f / 512.f)), 0.f) + 1e-5f));
            mbar_wait(BAR(QB), 1);
            if (tid == 0) TRACE(25);
            const float4 f0 = ldsf4(rl), f2 = ldsf4(rl + 1024), f1 = ldsf4(rl + 512), f3 = ldsf4(rl + 1536);
            const float gg = fmaf(rstd, fmaf(-mu, f0.z + f2.z, (f0.x + f0.y) + (f2.x + f2.y)), f0.w + f2.w);
            const float uu = fmaf(rstd, fmaf(-mu, f1.z + f3.z, (f1.x + f1.y) + (f3.x + f3.y)), f1.w + f3.w);
            const float hh = __fdividef(gg * uu, 1.f + ex2(-gg * fmaf(gg * gg, 0.10294324f, 2.3022082f)));
            uint32_t hb[4];
#pragma unroll
            for (int i = 0; i < 4; i++) hb[i] = pack2(__shfl_sync(0xffffffffu, hh, 2 * t + 8 * i), __shfl_sync(0xffffffffu, hh, 2 * t + 8 * i + 1));
            if (!hd) { mbar_wait(db, 0); ldd(); }
#pragma unroll
            for (int i = 0; i < 2; i++) {
                uint32_t res = 0;
#pragma unroll
                for (int k = 0; k < 4; k++) {
                    float c[4] = {0.f, 0.f, 0.f, 0.f};
                    const uint4 &x = a[i * 8 + k], &y = a[i * 8 + k + 4];
                    mma(c, x.x, x.y, x.z, x.w, hb[0], hb[1]);
                    mma(c, y.x, y.y, y.z, y.w, hb[2], hb[3]);
                    if (t == k) res = pack2(c[0], c[2]);
                }
                st2_x1(p5 + i * 8192, enc(res));
            }
            if (tid == 0) { TRACE(27); TRACE_GT(47); }
        } else if (j < J_END) {
            uint4 a[8], b[4];
            float c[4], e[4];
            const bool own = (warp >> 1) == rk;
            const uint32_t xa = sb + SM_FV + (warp & 1) * 64 + g * 8;
            if (lane == 0) mbar_expect(BAR(MBB), own ? 64 : 0);
#pragma unroll
            for (int i = 0; i < 2; i++) {
                ldfrag(b, sb + SM_FS + rk * 512 + i * 256 + t * 16);
                mbar_wait(BAR(IT_X + i), 0);
                const uint32_t ab = sb + SM_U + B_X * 32768 + i * 16384 + a128;
                load8<true>(a, [&](int s) { return ab + s * 2048; });
                mma8(i ? e : c, a, b);
            }
            c[0] += e[0]; c[2] += e[2];
            if (!own) {
                if (t == 0) st_async2(peer_addr(xa, rk ^ 1), c[0], c[2], peer_addr(BAR(MBB), rk ^ 1));
            } else {
                mbar_wait(BAR(MBB), 0);
                const float2 pp = *(const float2*)(sm + (xa - sb));
                const float mine = t ? c[2] + pp.y : c[0] + pp.x, other = shx(mine, 4);
                const uint32_t w = (warp & 1) * 8 + t * 4 + (g >> 1), val = enc(pack2(mine, other));
                if (t < 2 && !(g & 1)) {
                    if (j < J_RED) st2_x1(gs + B_MB * 4096 + (j - NFF) * 16 + w, val);
                    else sts32(sb + SM_FV + 256 + w * 4, val);
                }
                if (j >= J_RED) bar_arrive(7, 320);
                if (lane == 0) TRACE(11);
            }
        }
    } else {
        const int u8 = tid - 128, w8 = warp - 4;
        const int v = w8 >> 2, wq4 = w8 & 3;
        {
            const float c0 = bflo(in1), c1 = bfhi(in1);
            sts32(sb + SM_FS + frag_off(2 * u8), pack2(__fdividef(c0, 1.f + __expf(-c0)), __fdividef(c1, 1.f + __expf(-c1))));
        }
        bar_sync(1, 256);
        asm volatile("barrier.cluster.wait.aligned;" ::: "memory");
        uint4 a[8], b[4]; float c[4];
        if (w8 < 2) {
            ldfrag(b, sb + SM_FS + (j >> 5) * 256 + t * 16);
            mbar_wait(BAR(IT_MODA), 0);
            if (u8 == 0) TRACE(12);
            const uint32_t ab = sb + SM_XA + w8 * 4096 + a16;
            load8<true>(a, [&](int s) { return ab + s * 512; });
            mma8(c, a, b);
            if (t < 2) st2_x1(gs + (B_HA + ((j >> 4) & 1) * 2 + w8) * 4096 + (j >> 5) * 256 + (j & 15) * 16 + t * 8 + g, encf(t ? c[2] : c[0]));
        }
        {
            mbar_wait(BAR(IT_WQ + 2 * v <= NCP ? 1 : IT_WQ + 2 * v), 0); mbar_wait(BAR(IT_WQ + 2 * v + 1 <= NCP ? 1 : IT_WQ + 2 * v + 1), 0);
            const uint32_t ab = sb + SM_U + 4 * 32768 + v * 16384 + a128;
            load8<true>(a, [&](int s) { return ab + s * 2048; });
            if (lane == 0) mbar_arrive(BAR(EB_WQ));
            bar_sync(5, 384);
            if (u8 == 0) TRACE(13);
            ldfrag(b, sb + SM_FV + v * 256 + t * 16);
            mma8(c, a, b);
            if (t < 2) {
                const float qv = t ? c[2] : c[0];
                const uint32_t qa_ = sb + SM_QX + ((rk * 2 + v) * 64 + wq4 * 16 + t * 8 + g) * 4;
                asm volatile("st.async.weak.shared::cluster.mbarrier::complete_tx::bytes.f32 [%0], %1, [%2];"
                             :: "r"(peer_addr(qa_, rk ^ 1)), "f"(qv), "r"(peer_addr(BAR(QB), rk ^ 1)) : "memory");
                sts32(qa_, __float_as_uint(qv));
            }
            __syncwarp();
            if (lane == 0) mbar_expect(BAR(QB), 64);
        }
        {
            mbar_wait(BAR(IT_WUK + v), 0); mbar_wait(BAR(IT_WUK + v + 2), 0);
            const uint32_t ab = sb + SM_U + 5 * 32768 + (w8 * 16 + r8 + 8 * lb3) * 128;
            const uint32_t x16 = (lb4 ^ r8) * 16;
            load8<false>(a, [&](int s) { return ab + (s & 1) * 16384 + (x16 ^ ((s >> 1) * 32)); });
            bar_sync(6, 384);
            if (u8 == 0) TRACE(14);
            b[0] = lds128(sb + SM_FQ + t * 16); b[1] = lds128(sb + SM_FQ + 64 + t * 16);
            float e[4] = {0.f, 0.f, 0.f, 0.f};
            c[0] = c[1] = c[2] = c[3] = 0.f;
#pragma unroll
            for (int k = 0; k < 4; k++) {
                const uint32_t b0 = (k & 1) ? b[k >> 1].z : b[k >> 1].x, b1 = (k & 1) ? b[k >> 1].w : b[k >> 1].y;
                mma(c, a[2 * k].x, a[2 * k].y, a[2 * k].z, a[2 * k].w, b0, b1);
                mma(e, a[2 * k + 1].x, a[2 * k + 1].y, a[2 * k + 1].z, a[2 * k + 1].w, b0, b1);
            }
            const float mine = ((t & 1) ? ((t & 2) ? e[2] : e[0]) : ((t & 2) ? c[2] : c[0])) * 0.12751743f;
            const float other = shx(mine, 4);
            if (!(g & 1)) st2_x1(gs + (B_QA + rk * 8 + ((j >> 1) & 1) * 4 + (j >> 5)) * 4096 + w8 * 128 + ((j >> 2) & 7) * 16 + (g >> 1) * 4 + t, enc(pack2(mine, other)));
            if (u8 == 0) TRACE(15);
        }
        const uint32_t cls = ldcls();
        __nanosleep(QA_DELAY);
        {
            uint4 qb[8];
            const uint32_t* pq = gs + near_off(B_QA + rk * 8 + wq4, cls) + lane * 4;
            const uint32_t* pq2 = gs + near_off(B_QA + rk * 8 + 4 + wq4, cls) + lane * 4;
            if (lane == 0) {
                mbar_expect(BAR(QT), 4096);
                asm volatile("cp.async.bulk.shared::cluster.global.mbarrier::complete_tx::bytes [%0], [%1], 4096, [%2];"
                             :: "r"(sb + SM_U + 5 * 32768 + w8 * 4096), "l"(gs + near_off(B_QA + rk * 8 + w8, cls)), "r"(BAR(QT)) : "memory");
            }
            const uint32_t qs = sb + SM_U + 5 * 32768 + wq4 * 4096 + lane * 16;
            mbar_wait(BAR(QT), 0);
#pragma unroll
            for (int i = 0; i < 8; i++) { a[i] = lds128(qs + i * 512); qb[i] = lds128(qs + 16384 + i * 512); }
            poll<512, QA_SLEEP, true>(a, pq);
            poll<512, QA_SLEEP, true>(qb, pq2);
            if (lane == 0) mbar_arrive(BAR(EB_WUK));
            auto add2 = [](uint32_t x, uint32_t y) { uint32_t r; asm("add.rn.bf16x2 %0, %1, %2;" : "=r"(r) : "r"(x), "r"(y)); return r; };
#pragma unroll
            for (int i = 0; i < 8; i++) a[i] = make_uint4(add2(a[i].x, qb[i].x), add2(a[i].y, qb[i].y), add2(a[i].z, qb[i].z), add2(a[i].w, qb[i].w));
        }
        if (u8 == 0) TRACE(8);
        {
            float m = -INFINITY, l = 0.f;
            uint32_t xl = sb + SM_XB + w8 * 2048 + lane * 16, xr = peer_addr(xl, rk ^ 1), bsr = peer_addr(BAR(SF0 + v), rk ^ 1);
            uint32_t pa = sb + SM_XA + v * 2048 + wq4 * 512 + lane * 16, ma = sb + SM_MX + v * 128 + (wq4 * 8 + g) * 4;
            uint32_t fb = BAR(IT_CKV + v * 2), sf = BAR(SF0 + v);
            uint32_t dlo = __reduce_or_sync(0xffffffffu, (((sb + SM_U + v * 16384) & 0x3FFFFu) >> 4) | 0x10000u);
            if (STAG && v) __nanosleep(STAG);
#pragma unroll 1
            for (int n = 0; n < NUNITS; n++) {
                float d[2][16], sc[8];
#pragma unroll
                for (int i = 0; i < 2; i++) {
                    mbar_wait(fb + i * 8, 0);
                    wg_fence();
#pragma unroll
                    for (int s = 0; s < 8; s++) wgmma_rs_n32(d[i], a[s], (0x40000080ull << 32) | (dlo + i * 512 + (s >> 2) * 64 + (s & 3) * 2), s);
                    wg_commit();
                }
#pragma unroll
                for (int i = 0; i < 2; i++) {
                    if (i) wg_wait0(); else wg_wait1();
#pragma unroll
                    for (int k = 0; k < 16; k++) asm volatile("" : "+f"(d[i][k]) :: "memory");
                    sc[4 * i] = d[i][0] + d[i][6]; sc[4 * i + 1] = d[i][1] + d[i][7]; sc[4 * i + 2] = d[i][8] + d[i][14]; sc[4 * i + 3] = d[i][9] + d[i][15];
                    asm volatile("st.async.weak.shared::cluster.mbarrier::complete_tx::bytes.v4.f32 [%0], {%1, %2, %3, %4}, [%5];"
                                 :: "r"(xr + i * 1024), "f"(sc[4 * i]), "f"(sc[4 * i + 1]), "f"(sc[4 * i + 2]), "f"(sc[4 * i + 3]), "r"(bsr) : "memory");
                }
                if (u8 == 128) TRACE_Q(56 + (n < 6 ? n : -40));
                if (n >= 3) mbar_wait(BAR(EB_UNIT0 + n - 3), 0);
                dlo += n == 5 ? -5 * 2048 : 2048;
                fb += 32; xr ^= 512; bsr += 16;
                pin(fb); pin(xr); pin(bsr);
                mbar_wait(sf, 0);
                const float4 x = ldsf4(xl), y = ldsf4(xl + 1024);
                sc[0] += x.x; sc[1] += x.y; sc[2] += x.z; sc[3] += x.w; sc[4] += y.x; sc[5] += y.y; sc[6] += y.z; sc[7] += y.w;
                float pr[8];
#pragma unroll
                for (int i = 0; i < 8; i++) pr[i] = ex2(sc[i] - m);
                float mx = fmaxf(fmaxf(fmaxf(sc[0], sc[1]), fmaxf(sc[2], sc[3])), fmaxf(fmaxf(sc[4], sc[5]), fmaxf(sc[6], sc[7])));
                if (__builtin_expect(__any_sync(0xffffffffu, mx > m), 0)) {
                    mx = fmaxf(mx, shx(mx, 1));
                    mx = fmaxf(mx, shx(mx, 2));
                    const float mn = fmaxf(m, ceilf(mx * 0.0625f) * 16.f);
                    l *= ex2(m - mn);
                    m = mn;
#pragma unroll
                    for (int i = 0; i < 8; i++) pr[i] = ex2(sc[i] - m);
                }
                stsf(ma, m);
                asm volatile("st.shared.v4.u32 [%0], {%1, %2, %3, %4};" :: "r"(pa), "r"(pack2(pr[0], pr[1])), "r"(pack2(pr[2], pr[3])),
                             "r"(pack2(pr[4], pr[5])), "r"(pack2(pr[6], pr[7])) : "memory");
                __syncwarp();
                if (lane == 0) mbar_arrive(sf + (PF0 - SF0) * 8);
                l += ((pr[0] + pr[1]) + (pr[2] + pr[3])) + ((pr[4] + pr[5]) + (pr[6] + pr[7]));
                xl ^= 512; sf += 16; ma += 256; pa += (n == 2 || n == 5) ? -8192 : 4096;
            }
            l += shx(l, 1);
            l += shx(l, 2);
            float2* mlx = (float2*)(sm + SM_MX + 2048) + wq4 * 8 + g;
            if (v == 0) { *mlx = make_float2(m, l); bar_arrive(11, 256); }
            else {
                mbar_wait(BAR(JD), 0);
                bar_sync(11, 256);
                const float2 o = *mlx;
                const float mn = fmaxf(m, o.x);
                l = l * ex2(m - mn) + o.y * ex2(o.x - mn);
                if ((wq4 >> 1) == rk) st_x4(gs + (B_ML + wq4 * 8 + g) * 4096 + (t >> 1) * 1024 + (j >> 1) * 8 + (t & 1) * 4, encf(mn), encf(l), 1u, 1u);
            }
        }
        const int pi = j < NFF ? rk * 128 + w8 * 16 + (lane & 15) : ((j - J_RED) & 15) * 16 + v * 8 + lb4 * 4 + wq4;
        const uint32_t xw = *(const uint32_t*)(xin + 2 * pi);
        const uint32_t* pm = gs + near_off(B_MB, cls) + pi;
        const uint32_t* pb = gs + near_off(B_E2 + (j >> 4), cls) + (((j >> 3) & 1) * 2 + lb4) * 256 + (lane & 15) * 2;
        pin(pm); pin(pb);
        {
            const uint32_t ab = sb + SM_U + B_WUV * 32768 + v * 4096 + a128;
            uint32_t pa = sb + SM_PB + wq4 * 320 + frag_off(64 * v + 32 * (g >> 2) + 16 * (t & 1) + 8 * (t >> 1) + 2 * (g & 3));
            uint32_t fa = sb + SM_PB + g * 320 + t * 16;
            const uint32_t* pe = gs + G_E1 + j * 8192 + (w8 >> 1) * 2048 + ((((cls >> 1) ^ (w8 >> 1)) & 1) << 10) + (((w8 & 1) * 16 + t) * 8 + g) * 4;
            uint32_t* p2 = gs + (B_E2 + (j >> 4)) * 4096 + (t >> 1) * 1024 + (j & 12) * 64 + w8 * 32 + (j & 3) * 8 + (g & 6) + (t & 1);
            pin(pa); pin(fa); pin(pe); pin(p2);
            const uint32_t mk = (g & 1) ? 0xffff0000u : 0x0000ffffu, m0 = (g & 2) ? 0u : mk, m1 = (g & 2) ? mk : 0u;
            uint4 pv[4];
            bool hv = false;
            bar_sync(3, 416);
            uint4 wa = lds128(sb + SM_W + (wq4 * 4 + t) * 16);
            uint32_t wb[8] = {wa.x & m0, wa.x & m1, wa.y & m0, wa.y & m1, wa.z & m0, wa.z & m1, wa.w & m0, wa.w & m1};
            pv[0] = pv[1] = pv[2] = pv[3] = make_uint4(0u, 0u, 0u, 0u);
            poll<512, E1_SLEEP, true>(pv, pe, [&]() {
                if (!hv) {
                    hv = __all_sync(0xffffffffu, mbar_test(BAR(IT_WUV + t), 0));
                    if (hv) load8<true>(a, [&](int s) { return ab + (s >> 1) * 8192 + (s & 1) * 2048; });
                }
            });
            if (lane == 0) TRACE_Q(48 + w8);
            if (u8 == 0) TRACE_Q(18);
            float lo, hi2;
            float2 inv;
#pragma unroll 1
            for (int pass = 0;; pass++) {
                float e[4][4];
#pragma unroll
                for (int i = 0; i < 4; i++) {
                    e[i][0] = e[i][1] = e[i][2] = e[i][3] = 0.f;
                    mma(e[i], pv[i].x, pv[i].y, pv[i].z, pv[i].w, wb[2 * i], wb[2 * i + 1]);
                }
                const float r0 = (t & 2) ? (e[0][2] + e[1][2]) + (e[2][2] + e[3][2]) : (e[0][0] + e[1][0]) + (e[2][0] + e[3][0]);
                const float r1 = (t & 2) ? (e[0][3] + e[1][3]) + (e[2][3] + e[3][3]) : (e[0][1] + e[1][1]) + (e[2][1] + e[3][1]);
                const uint32_t hi = pack2(r0, r1);
                sts32(pa, hi); sts32(pa + 1280, pack2(r0 - bflo(hi), r1 - bfhi(hi)));
                if (!hv) {
#pragma unroll 1
                    for (int i = 0; i < 4; i++) mbar_wait(BAR(IT_WUV + i), 0);
                    load8<true>(a, [&](int s) { return ab + (s >> 1) * 8192 + (s & 1) * 2048; });
                    hv = true;
                }
                bar_sync(1, 256);
                if (u8 == 0) TRACE(19);
                ldfrag(b, fa);
                mma8(c, a, b);
                mbar_wait(BAR(WR), 0);
                asm volatile("ld.shared.v2.f32 {%0, %1}, [%2];" : "=f"(inv.x), "=f"(inv.y) : "r"(sb + SM_FQ) : "memory");
                quad_pair(c[0] + c[1], c[2] + c[3], t, lo, hi2);
                if (__builtin_expect(__all_sync(0xffffffffu, pass || __float_as_uint(inv.y) == 0), 1)) break;
                wa = lds128(sb + SM_W2 + (wq4 * 4 + t) * 16);
                wb[0] = wa.x & m0; wb[1] = wa.x & m1; wb[2] = wa.y & m0; wb[3] = wa.y & m1; wb[4] = wa.z & m0; wb[5] = wa.z & m1; wb[6] = wa.w & m0; wb[7] = wa.w & m1;
                bar_sync(1, 256);
            }
            if (!(g & 1)) st_x1(p2, enc(pack2(lo * inv.x, hi2 * inv.x)));
            bar_arrive(4, 288);
            if (u8 == 0) TRACE(20);
        }
        uint32_t mb[3] = {0u, 0u, 0u};
        if (j < NFF) poll_start<1024>(mb, pm);
        uint4 a2[8];
        if (v == 0) {
            const uint32_t ab = sb + SM_U + B_WO * 32768 + a128;
            uint32_t* p3 = gs + (B_E3 + ((j >> 1) & 3)) * 4096 + (t >> 1) * 1024 + (rk * 2 + (wq4 >> 1)) * 256 + (j >> 3) * 16 + (wq4 & 1) * 8 + (t & 1) * 4 + (g >> 1);
            pin(p3);
            uint2 bb[8];
#pragma unroll
            for (int i = 0; i < 8; i++) bb[i] = make_uint2(0u, 0u);
            bool ho = false;
            auto ldo = [&]() { load8<true>(a, [&](int s) { return ab + s * 2048; }); load8<true>(a2, [&](int s) { return ab + 16384 + s * 2048; }); };
            auto idle = [&]() {
                if (!ho) {
                    ho = __all_sync(0xffffffffu, mbar_test(BAR(IT_WO + t), 0));
                    if (ho) ldo();
                }
            };
            poll<128, 0, true>(bb, pb, idle);
            if (!ho) {
#pragma unroll 1
                for (int i = 0; i < 4; i++) mbar_wait(BAR(IT_WO + i), 0);
                ldo();
            }
            if (u8 == 0) TRACE(21);
            float e[4][4];
#pragma unroll
            for (int s = 0; s < 16; s++) {
                const uint4& x = (s & 2) ? a2[(s >> 2) * 2 + (s & 1)] : a[(s >> 2) * 2 + (s & 1)];
                const uint2& y = bb[(s >> 2) * 2 + (s & 1)];
                if (s < 4) e[s][0] = e[s][1] = e[s][2] = e[s][3] = 0.f;
                mma(e[s & 3], x.x, x.y, x.z, x.w, y.x, y.y);
            }
            float lo, hi;
            quad_pair((t & 2) ? (e[2][0] + e[3][0]) + (e[2][1] + e[3][1]) : (e[0][0] + e[1][0]) + (e[0][1] + e[1][1]),
                      (t & 2) ? (e[2][2] + e[3][2]) + (e[2][3] + e[3][3]) : (e[0][2] + e[1][2]) + (e[0][3] + e[1][3]), t, lo, hi);
            if (!(g & 1)) st_x1(p3, enc(pack2(lo, hi)));
            bar_arrive(1, 256);
            if (u8 == 0) TRACE(22);
        } else bar_sync(1, 256);
        if (j < NFF) {
            const uint32_t* p3 = gs + near_off(B_E3 + rk * 2 + v, cls) + wq4 * 256 + lane;
            uint32_t za = sb + SM_FZ + lb4 * 576 + frag_off(w8 * 32 + (lane & 15) * 2);
            uint32_t fa = sb + SM_FZ + (g & 3) * 576 + lb4 * 256 + t * 16, ya = sb + SM_Y + u8 * 4;
            poll<1024, MB_SLEEP, true>(mb, pm);
            const uint32_t kk = pack2(1.f + bflo(mb[2]), 1.f + bfhi(mb[2]));
            sts32(za + 2 * 576, lb4 ? mb[1] : kk);
            uint32_t e3[8] = {0u, 0u, 0u, 0u, 0u, 0u, 0u, 0u};
            uint32_t ra = peer_addr(sb + SM_RED + (rk * 2 + v) * 512 + ((wq4 & 1) * 16 + (t >> 1) * 8 + g) * 16 + (t & 1) * 8, wq4 >> 1), tbo = peer_addr(BAR(QB), wq4 >> 1);
            pin(za); pin(fa); pin(ya); pin(ra); pin(tbo);
            if (lane == 0) mbar_expect(BAR(QB), 256);
            const uint32_t gb = BAR(IT_X + v * 2), ab = sb + SM_U + (B_X + v) * 32768 + a128;
            bool early = false, early2 = false;
            auto ldw = [&]() {
                if (!early) {
                    early = __all_sync(0xffffffffu, mbar_test(gb, 0));
                    if (early) load8<true>(a, [&](int s) { return ab + s * 2048; });
                }
                if (!early2) {
                    early2 = __all_sync(0xffffffffu, mbar_test(gb + 8, 0));
                    if (early2) load8<true>(a2, [&](int s) { return ab + 16384 + s * 2048; });
                }
            };
            poll<128, 0, true>(e3, p3, ldw);
            if (u8 == 0) TRACE(23);
            const float s0 = sumlo(e3), s1 = sumhi(e3);
            const float y0 = fmaf(bflo(mb[0]), s0 + shx(s0, 16), bflo(xw)), y1 = fmaf(bfhi(mb[0]), s1 + shx(s1, 16), bfhi(xw));
            stsf(ya, lb4 ? y1 : y0);
            const float z0 = y0 * bflo(kk), z1 = y1 * bfhi(kk);
            const uint32_t zh = pack2(z0, z1);
            sts32(za, lb4 ? pack2(z0 - bflo(zh), z1 - bfhi(zh)) : zh);
            bar_sync(7, 288);
            if (u8 == 0) TRACE(24);
            ldfrag(b, fa);
            if (!early) { mbar_wait(gb, 0); load8<true>(a, [&](int s) { return ab + s * 2048; }); }
            {
                float e[4][4];
#pragma unroll
                for (int s = 0; s < 16; s++) {
                    if (s == 8 && !early2) { mbar_wait(gb + 8, 0); load8<true>(a2, [&](int q) { return ab + 16384 + q * 2048; }); }
                    const uint4& x = s < 8 ? a[s] : a2[s & 7];
                    const uint4& y = b[(s >> 1) & 3];
                    float (&d)[4] = e[(s >> 3) * 2 + (s & 1)];
                    if (!(s & 6)) d[0] = d[1] = d[2] = d[3] = 0.f;
                    mma(d, x.x, x.y, x.z, x.w, (s & 1) ? y.z : y.x, (s & 1) ? y.w : y.y);
                }
                const bool hi = t >> 1;
                const float k0 = hi ? e[2][2] + e[3][2] : e[0][0] + e[1][0], k1 = hi ? e[2][3] + e[3][3] : e[0][1] + e[1][1];
                const float o0 = hi ? e[2][0] + e[3][0] : e[0][2] + e[1][2], o1 = hi ? e[2][1] + e[3][1] : e[0][3] + e[1][3];
                st_async2(ra, k0 + shx(o0, 2), k1 + shx(o1, 2), tbo);
            }
        } else if (j >= J_RED && j < J_END) {
            uint32_t ga[1], e3[1];
            poll<0, MB_SLEEP>(ga, pm);
            poll<0, 100>(e3, gs + near_off(B_E3 + (pi >> 6), cls) + (pi & 48) * 16 + (lane & 15) * 16 + (pi & 15));
            float y0 = bflo(e3[0]), y1 = bfhi(e3[0]);
#pragma unroll
            for (int o = 8; o; o >>= 1) { y0 += shx(y0, o); y1 += shx(y1, o); }
            y0 = fmaf(bflo(ga[0]), y0, bflo(xw)); y1 = fmaf(bfhi(ga[0]), y1, bfhi(xw));
            bar_sync(7, 320);
            const uint32_t gb = lds32(sb + SM_FV + 256 + (pi & 15) * 4);
            uint32_t* po = (uint32_t*)out + pi;
            pin(po);
            const uint32_t nz = lane < NFF / 2 ? 0u : 0x80008000u;
            uint2 yv[2] = {make_uint2(nz, nz), make_uint2(nz, nz)};
            poll<NFF * 32, 0, true>(yv, gs + near_off(B_E5 + j - J_RED, cls) + lane * 16 + w8 * 2);
            if (u8 == 0) TRACE(26);
            const float l0 = bflo(yv[0].x) + bflo(yv[1].x), h0 = bfhi(yv[0].x) + bfhi(yv[1].x);
            const float l1 = bflo(yv[0].y) + bflo(yv[1].y), h1 = bfhi(yv[0].y) + bfhi(yv[1].y);
            float s0 = (lb4 ? h0 : l0) + shx(lb4 ? l0 : h0, 16), s1 = (lb4 ? h1 : l1) + shx(lb4 ? l1 : h1, 16);
#pragma unroll
            for (int o = 8; o; o >>= 1) { s0 += shx(s0, o); s1 += shx(s1, o); }
            if (!(lane & 15)) *po = pack2(fmaf(bflo(gb), s0, y0), fmaf(bfhi(gb), s1, y1));
            if (u8 == 0) TRACE(27);
        }
    }
}

typedef CUresult (*EncFn)(CUtensorMap*, CUtensorMapDataType, cuuint32_t, void*, const cuuint64_t*, const cuuint64_t*,
                          const cuuint32_t*, const cuuint32_t*, CUtensorMapInterleave, CUtensorMapSwizzle,
                          CUtensorMapL2promotion, CUtensorMapFloatOOBfill);

void make_map(EncFn enc_fn, CUtensorMap* m, const void* p, cuuint64_t d0, cuuint64_t d1, cuuint64_t d2, cuuint64_t d3,
              cuuint64_t s1, cuuint64_t s2, cuuint64_t s3, cuuint32_t b0, cuuint32_t b1, cuuint32_t b2, cuuint32_t b3, CUtensorMapSwizzle sw) {
    const cuuint64_t dims[4] = {d0, d1, d2, d3}, strides[3] = {s1, s2, s3};
    const cuuint32_t box[4] = {b0, b1, b2, b3}, es[4] = {1, 1, 1, 1};
    enc_fn(m, CU_TENSOR_MAP_DATA_TYPE_BFLOAT16, 4, (void*)p, dims, strides, box, es,
           CU_TENSOR_MAP_INTERLEAVE_NONE, sw, CU_TENSOR_MAP_L2_PROMOTION_L2_64B, CU_TENSOR_MAP_FLOAT_OOB_FILL_NONE);
}

uint32_t* scratch = nullptr;

struct Tune { const char* win; const char* late; int tau, t_off; const char* tail[3][4]; };
Tune tune = {"66666666655555555555555555555555544444444",
             "00000000000000000999999999999999999999999", 320, -240,
             {{"VVVVOOOOguguDD", "zzzzzzzzzzzzzz", "88888888999988", "2fffdbbbhaaafg"},
              {"VMVMVVOOOO", "zzzzzzzzzz", "9999998888", "2999998ddd"},
              {"VVVVOOOOMM", "zzzzzzzzzz", "8888888888", "eaaa9hhhkn"}}};
bool ready = false;

}

extern "C" void kernel_launch(void* const* d_in, const int* in_sizes, int n_in, void* d_out, int out_size) {
    (void)in_sizes; (void)n_in; (void)out_size;
    static Maps maps;
    static const void* cached[12] = {};
    bool same = ready;
    for (int i = 0; i < 12 && same; i++) same = cached[i] == d_in[i];
    if (!same) {
        void* fn = nullptr;
        cudaDriverEntryPointQueryResult qr;
        cudaGetDriverEntryPoint("cuTensorMapEncodeTiled", &fn, cudaEnableDefault, &qr);
        EncFn e = (EncFn)fn;
        const CUtensorMapSwizzle S128 = CU_TENSOR_MAP_SWIZZLE_128B;
        make_map(e, &maps.m[MP_WQ], d_in[2], 64, 512, 64, 1, 8192, 128, 8192, 64, 64, 1, 1, S128);
        make_map(e, &maps.m[MP_WUK], d_in[3], 64, 512, 64, 1, 8192, 128, 8192, 64, 64, 1, 1, S128);
        make_map(e, &maps.m[MP_CKV], d_in[1], 64, 8, 8, 4096, 1024, 128, 8192, 64, 8, 4, 2, S128);
        make_map(e, &maps.m[MP_MODB], d_in[11], 3072, 512, 1, 1, 6144, 6144, 6144, 64, 128, 1, 1, S128);
        make_map(e, &maps.m[MP_WUV], d_in[4], 64, 512, 64, 1, 8192, 128, 8192, 64, 32, 2, 1, S128);
        make_map(e, &maps.m[MP_WO], d_in[5], 512, 4096, 1, 1, 1024, 1024, 1024, 64, 64, 1, 1, S128);
        make_map(e, &maps.m[MP_GATE], d_in[7], 1792, 512, 1, 1, 3584, 3584, 3584, 64, 128, 1, 1, S128);
        make_map(e, &maps.m[MP_UP], d_in[8], 1792, 512, 1, 1, 3584, 3584, 3584, 64, 128, 1, 1, S128);
        make_map(e, &maps.m[MP_DOWN], d_in[9], 64, 1792, 8, 1, 1024, 128, 1024, 64, 32, 4, 1, S128);
        for (int r = 0; r < 3; r++) {
            int ids[56], cnt[128] = {}, tn = tune.t_off - (W0 - 1) * tune.tau;
            uint2* sc = maps.sched[r];
            auto dig = [](char ch) { return ch >= 'a' ? ch - 'a' + 10 : ch - '0'; };
            for (int i = 0; i < 56; i++) sc[i] = make_uint2(0u, 0u);
            for (int i = 0;; i++) {
                int id = i, buf, dep, w, wl;
                if (i < IT_WUV) {
                    const int u = (i - IT_CKV) >> 2;
                    buf = i < IT_CKV ? 4 + ((i - 1) >> 2) : u % 6;
                    dep = i < IT_CKV || u < 4 ? -1 : u < 6 ? EB_WQ + u - 4 : EB_UNIT0 + u - 6;
                    w = dig(tune.win[i]); wl = dig(tune.late[i]);
                    if (i) tn += tune.tau;
                } else {
                    const char ch = tune.tail[r][0][i - IT_WUV];
                    if (!ch) break;
                    buf = ch == 'V' ? B_WUV : ch == 'O' ? B_WO : ch == 'D' ? B_DN : ch == 'u' ? B_X + 1 : B_X;
                    id = (ch == 'V' ? IT_WUV : ch == 'O' ? IT_WO : ch == 'D' ? IT_DOWN : ch == 'u' ? IT_X + 2 : IT_X) + cnt[(int)ch]++;
                    dep = EB_UNIT0 + (buf < 2 ? buf + 6 : buf);
                    w = dig(tune.tail[r][1][i - IT_WUV]); wl = dig(tune.tail[r][2][i - IT_WUV]);
                    tn += 32 * dig(tune.tail[r][3][i - IT_WUV]);
                }
                if (id < IT_X ? (id - 1) & 3 : (id - IT_X) & 1) dep = -1;
                ids[i] = id;
                auto back = [&](int d) { return i < d ? 0 : (ids[i - d] && ids[i - d] <= NCP ? 1 : ids[i - d]) + 1; };
                sc[i].x = id | (buf * 4 + (id < IT_X ? (id - 1) & 3 : ((id - IT_X) & 1) * 2)) << 6 | (dep + 1) << 11 | (w > 32 ? NEVER + 1 : back(w)) << 18 | (wl ? back(wl) : 0) << 25;
                const int mp = id < IT_CKV ? MP_WQ + ((id - 1) >> 2) : id < IT_WUV ? MP_CKV : id < IT_WO ? MP_WUV : id < IT_X ? MP_WO
                             : id >= IT_DOWN ? MP_DOWN : r ? MP_MODB : MP_GATE + ((id - IT_X) >> 1);
                const int step = mp == MP_CKV ? id - IT_CKV : mp == MP_WUV ? (id - IT_WUV) * 2 : mp == MP_DOWN ? id - IT_DOWN : id < IT_X ? (id - 1) & 3 : ((id - IT_X) & 1) * 2;
                sc[i].y = (tn & 0xffff) | (mp & 15) << 16 | step << 20;
            }
        }
        cudaGetSymbolAddress((void**)&scratch, g_scratch);
        scratch = (uint32_t*)(((uintptr_t)scratch + (2u << 20) - 1) & ~(uintptr_t)((2u << 20) - 1));
        cudaFuncSetAttribute(fused_kernel, cudaFuncAttributeMaxDynamicSharedMemorySize, SM_TOTAL);
        for (int i = 0; i < 12; i++) cached[i] = d_in[i];
        ready = true;
    }
    const First f = {{(const uint8_t*)d_in[2], (const uint8_t*)d_in[11]}, {(const __nv_bfloat16*)d_in[0], (const __nv_bfloat16*)d_in[10]}};
    fused_kernel<<<NCTA, NTHREADS, SM_TOTAL>>>(f, (__nv_bfloat16*)d_out, scratch, maps);
}
```

```cpp
#include <cuda_runtime.h>
#include <cuda_bf16.h>
#include <cuda.h>
#include <stdint.h>
#include <limits.h>

namespace {

constexpr int NCTA = 128;
constexpr int NTHREADS = 512;
constexpr int NUNITS = 8;
constexpr int NFF = 56, J_RED = 104, J_END = 120;
constexpr uint32_t SPIN_LIMIT = 1u << 22;

#define E1_EARLY 50
#define STAG 300
#define NUMA 1
#define NPROBE 3
#define NCP 2
#define W0 4
#define RD_ITEM 15
#define JAN_SLEEP 100
#define RD_SLEEP 400
#define HA_DELAY 200
#define H_SLEEP 100
#define QA_DELAY 600
#define QA_SLEEP 200
#define ML_DELAY 300
#define E1_SLEEP 50
#define MB_SLEEP 100
constexpr int B_WUV = 2, B_WO = 3, B_X = 4  , B_DN = 0;

constexpr int SM_U = 0;
constexpr int SM_XA = 6 * 32768;
constexpr int SM_XB = SM_XA + 12288;
constexpr int SM_MX = SM_XB + 16384;
constexpr int SM_FZ = SM_XB + 8192;
constexpr int SM_PB = SM_XB;
constexpr int SM_Y = SM_XB + 12288;
constexpr int SM_RED = SM_XB + 4096;
constexpr int SM_FS = SM_XB + 20480;
constexpr int SM_FV = SM_FS + 1024;
constexpr int SM_QX = SM_XA + 8192;
constexpr int SM_FQ = SM_FV + 512;
constexpr int SM_CLS = SM_FQ + 128;
constexpr int SM_W = SM_FQ + 256;
constexpr int SM_W2 = SM_MX + 2304;
constexpr int SM_SCR = SM_XA + 9216;
constexpr int SM_TR = SM_XB + 19456;
constexpr int SM_BAR = SM_W + 256;
constexpr int SM_TOTAL = SM_BAR + 1024;
static_assert(SM_TOTAL <= 232448, "smem");

enum { IT_MODA = 0, IT_WQ = 1, IT_WUK = 5, IT_CKV = 9, IT_WUV = 41, IT_WO = 45, IT_X = 49  , IT_DOWN = 53, NITEMS = 55,
       NEVER = 63,
       SF0 = 64,
       PF0 = 80,
       EB_UNIT0 = 96, MBB = 103,
       EB_WQ = 104, EB_WUK, QT, QB, JD, WR };

enum { MP_WQ = 0, MP_WUK, MP_CKV, MP_WUV, MP_DOWN, MP_WO, MP_GATE, MP_UP, MP_MODB, NMAPS };
struct First { const uint8_t* w[2]; const __nv_bfloat16* v[2]; };
struct Maps { CUtensorMap m[NMAPS]; uint2 sched[3][56]; };

enum { B_HA = 0,
       B_MB = 6,
       B_RD = 7,
       B_E2 = 8,
       B_QA = 16,
       B_ML = 32,
       B_E5 = 64,
       B_E3 = 80,
       B_PR = 96,
       B_TR = 100 };
constexpr int G_E1 = 1 << 19;
constexpr int G_TR = B_TR * 4096;
__device__ __align__(1024) uint32_t g_scratch[(8 << 20) / 4];

#define TRACE(slot) do {} while (0)
#define TRACE_Q(slot) do {} while (0)
#define TRACE_GT(slot) do {} while (0)

__device__ __forceinline__ uint32_t s2u(const void* p) { return (uint32_t)__cvta_generic_to_shared(p); }
__device__ __forceinline__ void mbar_init(uint32_t b, int c) { asm volatile("mbarrier.init.shared::cta.b64 [%0], %1;" :: "r"(b), "r"(c) : "memory"); }
__device__ __forceinline__ void mbar_expect(uint32_t b, uint32_t bytes) { asm volatile("mbarrier.arrive.expect_tx.shared::cta.b64 _, [%0], %1;" :: "r"(b), "r"(bytes) : "memory"); }
__device__ __forceinline__ void mbar_arrive(uint32_t b) { asm volatile("mbarrier.arrive.shared::cta.b64 _, [%0];" :: "r"(b) : "memory"); }
__device__ __forceinline__ void mbar_wait(uint32_t b, uint32_t ph) {
    asm volatile("{\n.reg .pred p;\nW: mbarrier.try_wait.parity.shared::cta.b64 p, [%0], %1;\n@!p bra W;\n}" :: "r"(b), "r"(ph) : "memory");
}
__device__ __forceinline__ void mbar_waitb(uint32_t b, uint32_t ph) {
    asm volatile("{\n.reg .pred p;\n.reg .u32 n;\nmov.u32 n, 0;\n"
                 "W: mbarrier.try_wait.parity.shared::cta.b64 p, [%0], %1;\n@p bra D;\n"
                 "add.u32 n, n, 1;\nsetp.lt.u32 p, n, 0x100000;\n@p bra W;\ntrap;\nD:\n}" :: "r"(b), "r"(ph) : "memory");
}
__device__ __forceinline__ uint32_t mbar_test(uint32_t b, uint32_t ph) {
    uint32_t ok;
    asm volatile("{\n.reg .pred p;\nmbarrier.test_wait.parity.shared::cta.b64 p, [%1], %2;\nselp.u32 %0, 1, 0, p;\n}" : "=r"(ok) : "r"(b), "r"(ph) : "memory");
    return ok;
}
__device__ __forceinline__ void bar_sync(int id, int n) { asm volatile("bar.sync %0, %1;" :: "r"(id), "r"(n) : "memory"); }
__device__ __forceinline__ void bar_arrive(int id, int n) { asm volatile("bar.arrive %0, %1;" :: "r"(id), "r"(n) : "memory"); }
__device__ __forceinline__ uint32_t peer_addr(uint32_t a, uint32_t rank) { uint32_t r; asm("mapa.shared::cluster.u32 %0, %1, %2;" : "=r"(r) : "r"(a), "r"(rank)); return r; }
__device__ __forceinline__ void st_async1(uint32_t a, float x, uint32_t bar) {
    asm volatile("st.async.weak.shared::cluster.mbarrier::complete_tx::bytes.f32 [%0], %1, [%2];" :: "r"(a), "f"(x), "r"(bar) : "memory");
}
__device__ __forceinline__ void st_async2(uint32_t a, float x, float y, uint32_t bar) {
    asm volatile("st.async.weak.shared::cluster.mbarrier::complete_tx::bytes.v2.f32 [%0], {%1, %2}, [%3];" :: "r"(a), "f"(x), "f"(y), "r"(bar) : "memory");
}
__device__ __forceinline__ uint32_t gtime() { uint32_t t; asm volatile("mov.u32 %0, %%globaltimer_lo;" : "=r"(t)); return t; }
__device__ __forceinline__ void fence_gpu() { asm volatile("fence.acq_rel.gpu;" ::: "memory"); }

__device__ __forceinline__ uint32_t enc(uint32_t b) { uint32_t r; asm("max.u32 %0, %1, 1;" : "=r"(r) : "r"(b)); return r; }
__device__ __forceinline__ uint32_t encf(float f) { return enc(__float_as_uint(f)); }
__device__ __forceinline__ void st_x1(uint32_t* p, uint32_t v) { asm volatile("st.relaxed.gpu.global.u32 [%0], %1;" :: "l"(p), "r"(v) : "memory"); }
__device__ __forceinline__ void st_x4(void* p, uint32_t a, uint32_t b, uint32_t c, uint32_t d) {
    asm volatile("st.relaxed.gpu.global.v4.u32 [%0], {%1, %2, %3, %4};" :: "l"(p), "r"(a), "r"(b), "r"(c), "r"(d) : "memory");
}
__device__ __forceinline__ void st2_x1(uint32_t* p, uint32_t v) { st_x1(p, v); st_x1(p + 1024, v); }
__device__ __forceinline__ void st2_x4(uint32_t* p, uint32_t a, uint32_t b, uint32_t c, uint32_t d) { st_x4(p, a, b, c, d); st_x4(p + 1024, a, b, c, d); }
__device__ __forceinline__ int near_off(int b, uint32_t cls) { return b * 4096 + (((__popc(b & 0x2C) ^ cls) & 1) << 10); }
__device__ __forceinline__ void ld_x(uint32_t& v, const void* p) { asm volatile("ld.relaxed.gpu.global.u32 %0, [%1];" : "=r"(v) : "l"(p) : "memory"); }
__device__ __forceinline__ void ld_x(uint4& v, const void* p) {
    asm volatile("ld.relaxed.gpu.global.v4.u32 {%0, %1, %2, %3}, [%4];" : "=r"(v.x), "=r"(v.y), "=r"(v.z), "=r"(v.w) : "l"(p) : "memory");
}
__device__ __forceinline__ void ld_x(uint2& v, const void* p) { asm volatile("ld.relaxed.gpu.global.v2.u32 {%0, %1}, [%2];" : "=r"(v.x), "=r"(v.y) : "l"(p) : "memory"); }
__device__ __forceinline__ uint32_t minw(uint32_t v) { return v; }
__device__ __forceinline__ uint32_t minw(const uint2& v) { return min(v.x, v.y); }
__device__ __forceinline__ uint32_t minw(const uint4& v) { return min(__vimin3_u32(v.x, v.y, v.z), v.w); }
template <int N> __device__ __forceinline__ uint32_t mint(const uint32_t* m) {
    if constexpr (N == 1) return m[0];
    else if constexpr (N == 2) return min(m[0], m[1]);
    else return __vimin3_u32(mint<(N + 2) / 3>(m), mint<(N + 1) / 3>(m + (N + 2) / 3), mint<N / 3>(m + (N + 2) / 3 + (N + 1) / 3));
}

template <int STRIDE, int S4 = 4 * STRIDE, typename T, int N>
__device__ __forceinline__ void poll_start(T (&v)[N], const void* base) {
#pragma unroll
    for (int i = 0; i < N; i++) ld_x(v[i], (const uint8_t*)base + (i & 3) * STRIDE + (i >> 2) * S4);
}
struct Nop { __device__ void operator()() const {} };
template <int STRIDE, int SLEEP, bool STARTED = false, int S4 = 4 * STRIDE, typename T, int N, typename F = Nop>
__device__ __forceinline__ void poll(T (&v)[N], const void* base, F idle = F()) {
    if (!STARTED) { poll_start<STRIDE, S4>(v, base); idle(); }
#pragma unroll 1
    for (uint32_t it = 0;; it++) {
        uint32_t m[N];
#pragma unroll
        for (int i = 0; i < N; i++) m[i] = minw(v[i]);
        if (__all_sync(0xffffffffu, mint<N>(m) != 0)) break;
        if (SLEEP && it > 0) __nanosleep(SLEEP);
#pragma unroll
        for (int i = 0; i < N; i++) if (!m[i]) ld_x(v[i], (const uint8_t*)base + (i & 3) * STRIDE + (i >> 2) * S4);
        idle();
        if (it > SPIN_LIMIT) __trap();
    }
}

__device__ __forceinline__ float bflo(uint32_t w) { return __uint_as_float(w << 16); }
__device__ __forceinline__ float bfhi(uint32_t w) { return __uint_as_float(w & 0xffff0000u); }
__device__ __forceinline__ uint32_t pack2(float lo, float hi) {
    uint32_t r; asm("cvt.rn.bf16x2.f32 %0, %1, %2;" : "=r"(r) : "f"(hi), "f"(lo)); return r;
}
__device__ __forceinline__ float rbf(float x) { return __uint_as_float(pack2(0.f, x)); }
__device__ __forceinline__ float sumlo(const uint32_t (&v)[8]) { return ((bflo(v[0]) + bflo(v[1])) + (bflo(v[2]) + bflo(v[3]))) + ((bflo(v[4]) + bflo(v[5])) + (bflo(v[6]) + bflo(v[7]))); }
__device__ __forceinline__ float sumhi(const uint32_t (&v)[8]) { return ((bfhi(v[0]) + bfhi(v[1])) + (bfhi(v[2]) + bfhi(v[3]))) + ((bfhi(v[4]) + bfhi(v[5])) + (bfhi(v[6]) + bfhi(v[7]))); }
__device__ __forceinline__ float ex2(float x) { float r; asm("ex2.approx.ftz.f32 %0, %1;" : "=f"(r) : "f"(x)); return r; }
__device__ __forceinline__ float shx(float v, int m) { return __shfl_xor_sync(0xffffffffu, v, m); }
__device__ __forceinline__ uint4 lds128(uint32_t a) { uint4 v; asm volatile("ld.shared.v4.u32 {%0, %1, %2, %3}, [%4];" : "=r"(v.x), "=r"(v.y), "=r"(v.z), "=r"(v.w) : "r"(a) : "memory"); return v; }
__device__ __forceinline__ uint32_t lds32(uint32_t a) { uint32_t v; asm volatile("ld.shared.u32 %0, [%1];" : "=r"(v) : "r"(a) : "memory"); return v; }
__device__ __forceinline__ void sts32(uint32_t a, uint32_t v) { asm volatile("st.shared.u32 [%0], %1;" :: "r"(a), "r"(v) : "memory"); }
__device__ __forceinline__ void sts16(uint32_t a, uint32_t v) { asm volatile("st.shared.u16 [%0], %1;" :: "r"(a), "h"((uint16_t)v) : "memory"); }
__device__ __forceinline__ int frag_off(int k) { return (k >> 5) * 64 + ((k >> 1) & 3) * 16 + ((k >> 4) & 1) * 8 + ((k >> 3) & 1) * 4 + (k & 1) * 2; }

template <bool TRANS>
__device__ __forceinline__ uint4 ldsm(uint32_t a) {
    uint4 r;
    if (TRANS) asm volatile("ldmatrix.sync.aligned.m8n8.x4.trans.shared.b16 {%0, %1, %2, %3}, [%4];" : "=r"(r.x), "=r"(r.y), "=r"(r.z), "=r"(r.w) : "r"(a) : "memory");
    else asm volatile("ldmatrix.sync.aligned.m8n8.x4.shared.b16 {%0, %1, %2, %3}, [%4];" : "=r"(r.x), "=r"(r.y), "=r"(r.z), "=r"(r.w) : "r"(a) : "memory");
    return r;
}
__device__ __forceinline__ void mma(float (&c)[4], uint32_t a0, uint32_t a1, uint32_t a2, uint32_t a3, uint32_t b0, uint32_t b1) {
    asm volatile("mma.sync.aligned.m16n8k16.row.col.f32.bf16.bf16.f32 {%0,%1,%2,%3}, {%4,%5,%6,%7}, {%8,%9}, {%0,%1,%2,%3};"
                 : "+f"(c[0]), "+f"(c[1]), "+f"(c[2]), "+f"(c[3]) : "r"(a0), "r"(a1), "r"(a2), "r"(a3), "r"(b0), "r"(b1));
}
template <bool TRANS, typename F>
__device__ __forceinline__ void load8(uint4 (&a)[8], F addr) {
    __syncwarp();
#pragma unroll
    for (int s = 0; s < 8; s++) a[s] = ldsm<TRANS>(addr(s));
}
__device__ __forceinline__ void mma8(float (&c)[4], const uint4 (&a)[8], const uint4 (&b)[4]) {
    float e[4][4];
#pragma unroll
    for (int s = 0; s < 8; s++) {
        if (s < 4) e[s][0] = e[s][1] = e[s][2] = e[s][3] = 0.f;
        mma(e[s & 3], a[s].x, a[s].y, a[s].z, a[s].w, (s & 1) ? b[s >> 1].z : b[s >> 1].x, (s & 1) ? b[s >> 1].w : b[s >> 1].y);
    }
#pragma unroll
    for (int i = 0; i < 4; i++) c[i] = (e[0][i] + e[1][i]) + (e[2][i] + e[3][i]);
}
__device__ __forceinline__ void ldfrag(uint4 (&b)[4], uint32_t a) {
    asm volatile("ld.shared.v4.u32 {%0,%1,%2,%3}, [%16];\nld.shared.v4.u32 {%4,%5,%6,%7}, [%16+64];\n"
                 "ld.shared.v4.u32 {%8,%9,%10,%11}, [%16+128];\nld.shared.v4.u32 {%12,%13,%14,%15}, [%16+192];\n"
                 : "=r"(b[0].x), "=r"(b[0].y), "=r"(b[0].z), "=r"(b[0].w), "=r"(b[1].x), "=r"(b[1].y), "=r"(b[1].z), "=r"(b[1].w),
                   "=r"(b[2].x), "=r"(b[2].y), "=r"(b[2].z), "=r"(b[2].w), "=r"(b[3].x), "=r"(b[3].y), "=r"(b[3].z), "=r"(b[3].w) : "r"(a) : "memory");
}
__device__ __forceinline__ void quad_pair(float x, float y, int t, float& lo, float& hi) {
    const float k = ((t & 1) ? y : x) + shx((t & 1) ? x : y, 1);
    lo = k + shx(k, 2); hi = shx(k, 4) + shx(k, 6);
}
__device__ __forceinline__ void pin(uint32_t& x) { asm volatile("" : "+r"(x)); }
template <typename T> __device__ __forceinline__ void pin(T*& x) { asm volatile("" : "+l"(x)); }
__device__ __forceinline__ float4 ldsf4(uint32_t a) { const uint4 v = lds128(a); return make_float4(__uint_as_float(v.x), __uint_as_float(v.y), __uint_as_float(v.z), __uint_as_float(v.w)); }
__device__ __forceinline__ float sum4(const float4& f) { return (f.x + f.y) + (f.z + f.w); }
__device__ __forceinline__ void stsf(uint32_t a, float v) { sts32(a, __float_as_uint(v)); }

__device__ __forceinline__ void wg_fence() { asm volatile("wgmma.fence.sync.aligned;" ::: "memory"); }
__device__ __forceinline__ void wg_commit() { asm volatile("wgmma.commit_group.sync.aligned;" ::: "memory"); }
__device__ __forceinline__ void wg_wait1() { asm volatile("wgmma.wait_group.sync.aligned 1;" ::: "memory"); }
__device__ __forceinline__ void wg_wait0() { asm volatile("wgmma.wait_group.sync.aligned 0;" ::: "memory"); }
#define R8(o) "+f"(d[o]), "+f"(d[o + 1]), "+f"(d[o + 2]), "+f"(d[o + 3]), "+f"(d[o + 4]), "+f"(d[o + 5]), "+f"(d[o + 6]), "+f"(d[o + 7])
__device__ __forceinline__ void wgmma_rs_n32(float (&d)[16], const uint4& a, uint64_t db, int acc) {
    asm volatile("{\n.reg .pred p;\nsetp.ne.b32 p, %21, 0;\n"
        "wgmma.mma_async.sync.aligned.m64n32k16.f32.bf16.bf16 "
        "{%0,%1,%2,%3,%4,%5,%6,%7,%8,%9,%10,%11,%12,%13,%14,%15}, {%16,%17,%18,%19}, %20, p, 1, 1, 0;\n}"
        : R8(0), R8(8) : "r"(a.x), "r"(a.y), "r"(a.z), "r"(a.w), "l"(db), "r"(acc));
}
#define PV_LO "{%0,%1,%2,%3,%4,%5,%6,%7,%8,%9,%10,%11,%12,%13,%14,%15,%16,%17,%18,%19,%20,%21,%22,%23,%24,%25,%26,%27,%28,%29,%30,%31,%32,%33,%34,%35,%36,%37,%38,%39,%40,%41,%42,%43,%44,%45,%46,%47,%48,%49,%50,%51,%52,%53,%54,%55,%56,%57,%58,%59,%60,%61,%62,%63}, "
#define PV_HI "{%64,%65,%66,%67,%68,%69,%70,%71,%72,%73,%74,%75,%76,%77,%78,%79,%80,%81,%82,%83,%84,%85,%86,%87,%88,%89,%90,%91,%92,%93,%94,%95,%96,%97,%98,%99,%100,%101,%102,%103,%104,%105,%106,%107,%108,%109,%110,%111,%112,%113,%114,%115,%116,%117,%118,%119,%120,%121,%122,%123,%124,%125,%126,%127}, "
__device__ __forceinline__ void wgmma_pv(float (&d)[128], const uint4& a, uint32_t blo, int acc) {
    asm volatile("{\n.reg .pred p;\n.reg .b32 u0, u1, u2, u3, t;\n.reg .b64 d0, d1, d2, d3;\nsetp.ne.b32 p, %133, 0;\n"
        "mov.b64 d0, {%132, 0x40000100};\nadd.u32 t, %132, 512;\nmov.b64 d1, {t, 0x40000100};\n"
        "add.u32 t, %132, 128;\nmov.b64 d2, {t, 0x40000100};\nadd.u32 t, %132, 640;\nmov.b64 d3, {t, 0x40000100};\n"
        "wgmma.fence.sync.aligned;\n"
        "wgmma.mma_async.sync.aligned.m64n128k16.f32.bf16.bf16 " PV_LO "{%128, u0, %129, u1}, d0, p, 1, 1, 1;\n"
        "wgmma.mma_async.sync.aligned.m64n128k16.f32.bf16.bf16 " PV_LO "{%130, u2, %131, u3}, d1, 1, 1, 1, 1;\n"
        "wgmma.commit_group.sync.aligned;\n"
        "wgmma.mma_async.sync.aligned.m64n128k16.f32.bf16.bf16 " PV_HI "{%128, u0, %129, u1}, d2, p, 1, 1, 1;\n"
        "wgmma.mma_async.sync.aligned.m64n128k16.f32.bf16.bf16 " PV_HI "{%130, u2, %131, u3}, d3, 1, 1, 1, 1;\n"
        "wgmma.commit_group.sync.aligned;\n}"
        : R8(0), R8(8), R8(16), R8(24), R8(32), R8(40), R8(48), R8(56), R8(64), R8(72), R8(80), R8(88), R8(96), R8(104), R8(112), R8(120)
        : "r"(a.x), "r"(a.y), "r"(a.z), "r"(a.w), "r"(blo), "r"(acc) : "memory");
}

template <int NW>
__device__ __forceinline__ void ln_stats(float s, float q, float sh, float* scr, int w, int lane, int bar, float& mean_b, float& sd_b) {
#pragma unroll
    for (int o = 16; o; o >>= 1) { s += shx(s, o); q += shx(q, o); }
    constexpr float n = 512.f / NW;
    if (lane == 0) { scr[w] = sh + s * (1.f / n); scr[NW + w] = q - s * s * (1.f / n); }
    bar_sync(bar, NW * 32);
    float mu = 0.f, m2 = 0.f;
#pragma unroll
    for (int i = 0; i < NW; i++) { mu += scr[i]; m2 += scr[NW + i]; }
    mu *= 1.f / NW;
#pragma unroll
    for (int i = 0; i < NW; i++) { const float d = scr[i] - mu; m2 = fmaf(n * d, d, m2); }
    mean_b = rbf(mu);
    sd_b = rbf(sqrtf(rbf(rbf(fmaxf(m2, 0.f) * (1.f / 512.f)) + 1e-5f)));
}
__device__ __forceinline__ float ln_mod(float x, float mean_b, float sd_b, float c, float s) {
    return rbf(rbf(__fdividef(rbf(x - mean_b), sd_b)) * rbf(1.f + c)) + s;
}

__global__ void __cluster_dims__(2, 1, 1) __launch_bounds__(NTHREADS, 1)
fused_kernel(const __grid_constant__ First F, __nv_bfloat16* __restrict__ out, uint32_t* __restrict__ gs, const __grid_constant__ Maps M) {
    extern __shared__ __align__(1024) uint8_t sm[];
    const uint32_t sb = s2u(sm);
    const int tid = threadIdx.x, lane = tid & 31;
    const int j = blockIdx.x, rk = j & 1;
    const int g = lane >> 2, t = lane & 3;
    const int r8 = lane & 7, lb3 = (lane >> 3) & 1, lb4 = lane >> 4;
    uint64_t pol;
    asm("createpolicy.fractional.L2::evict_first.b64 %0, 1.0;" : "=l"(pol));
    {
        auto cpa = [&](uint32_t d, const uint8_t* s) {
            asm volatile("cp.async.cg.shared.global.L2::cache_hint.L2::128B [%0], [%1], 16, %2;" :: "r"(d), "l"(s), "l"(pol) : "memory");
        };
        const uint32_t ut = threadIdx.x, uj = blockIdx.x;
        const uint8_t* w = F.w[ut >= 128];
        if (ut < 128) {
            const uint32_t dq = (sb + ut * 16) ^ ((ut * 2) & 0x70);
            const uint8_t* sq = w + (uint32_t)(((uj & 1) * 256 + (ut >> 3)) * 8192 + (uj >> 1) * 128 + (ut & 7) * 16);
#pragma unroll
            for (int i = 0; i < 4 * NCP; i++) cpa(dq + 4 * 32768 + i * 2048, sq + i * 131072);
        } else if (ut < 384) {
            const uint32_t dm = (sb + ut * 16) ^ ((ut * 2) & 0x10);
            const uint8_t* sa = w + (uint32_t)(((uj >> 5) * 128 + (ut >> 1) - 64) * 6144 + (uj & 31) * 32 + (ut & 1) * 16);
            cpa(dm + SM_XA - 2048, sa); cpa(dm + SM_XA + 2048, sa + 1024);
        }
        else if (ut == 480 && uj < 64) asm volatile("prefetch.global.L2 [%0];" :: "l"(F.v[(uj >> 3) & 1] + (uj & 7) * 64));
    }
    const int warp = __shfl_sync(0xffffffffu, tid >> 5, 0);
    const __nv_bfloat16* const xin = F.v[0];
    uint32_t* const pl = gs + (warp < 2 ? (B_PR + (j >> 5)) * 4096 + (j & 31) * 32 : G_E1 + j * 8192) + (warp & 1) * 1024 + lane;
    if (warp < 4) st_x1(pl, 1u);
    auto BAR = [&](int i) -> uint32_t { return sb + SM_BAR + i * 8; };
    const uint32_t a16 = (r8 + 8 * lb4) * 32 + ((lb3 ^ (r8 >> 2)) * 16);
    const uint32_t a128 = (r8 + 8 * lb4) * 128 + ((((warp & 3) * 2 + lb3) ^ r8) * 16);
    auto ldcls = [&]() -> uint32_t { return *(const volatile uint32_t*)(sm + SM_CLS); };
    auto clear_head = [&]() {
        st2_x1(gs + (B_HA + ((j >> 4) & 1) * 2 + lb4) * 4096 + (j >> 5) * 256 + (j & 15) * 16 + (lane & 15), 0u);
        st2_x4(gs + (B_QA + rk * 8 + ((j >> 1) & 1) * 4 + (j >> 5)) * 4096 + g * 128 + ((j >> 2) & 7) * 16 + t * 4, 0u, 0u, 0u, 0u);
        if (lane < 8) st2_x1(gs + B_RD * 4096 + j * 8 + lane, 0u);
    };
    auto tma = [&](uint32_t dst, const CUtensorMap* mp, uint32_t bar, int c0, int c1, int c2, int c3) {
        asm volatile("{\n.reg .pred p;\nelect.sync _|p, 0xffffffff;\n"
                     "@p cp.async.bulk.tensor.4d.shared::cluster.global.mbarrier::complete_tx::bytes.L2::cache_hint [%0], [%1, {%3, %4, %5, %6}], [%2], %7;\n}"
                     :: "r"(dst), "l"(mp), "r"(bar), "r"(c0), "r"(c1), "r"(c2), "r"(c3), "l"(pol) : "memory");
    };
    if (warp <= 12 || warp == 15) {
        const int grp = warp == 12 ? 0 : warp == 15 ? 13 : warp + 1;
        const uint32_t cnt = grp < 10 ? 1 : grp < 13 ? 4 : 8;
        if (lane == 0) {
#pragma unroll
            for (int i = 0; i < 8; i++) mbar_init(BAR(grp * 8 + i), (i < 2 && grp == 0) ? (i ? 128 : 256) : cnt);
        }
        __syncwarp();
        if (grp < 10 && lane < 8 && (grp || lane > NCP)) mbar_expect(BAR(grp * 8 + lane), grp >= 8 ? 4096 : grp * 8 + lane < IT_X ? 8192 : 16384);
        asm volatile("fence.mbarrier_init.release.cluster;" ::: "memory");
        __syncwarp();
        if (warp == 12) {
#pragma unroll
            for (int i = NCP + 1; i < W0; i++) tma(sb + (15 + i) * 8192, &M.m[MP_WQ], BAR(i), 0, rk * 256 + (i - 1) * 64, j >> 1, 0);
        }
    } else if (warp == 13) {
        if (lane < NMAPS) asm volatile("prefetch.tensormap [%0];" :: "l"(&M.m[lane]) : "memory");
    } else if (warp == 14) {
        clear_head();
    }
    __syncthreads();
    uint32_t in1 = 0, in2 = 0;
    if (warp < 4) { in1 = *(const uint32_t*)(xin + 2 * tid); in2 = *(const uint32_t*)(xin + 256 + 2 * tid); }
    else if (warp < 12) in1 = *(const uint32_t*)(F.v[1] + 2 * (tid - 128));
    if (warp < 12) asm volatile("cp.async.mbarrier.arrive.noinc.shared::cta.b64 [%0];" :: "r"(BAR(warp < 4)) : "memory");
    asm volatile("barrier.cluster.arrive.relaxed.aligned;" ::: "memory");

    if (warp >= 12) {
    asm volatile("setmaxnreg.dec.sync.aligned.u32 64;");
    if (warp == 12) {
        static_assert(W0 > NCP && W0 <= 5 && NCP >= 1 && NCP <= 4, "W0");
        const uint2* sched = M.sched[j < NFF ? 0 : j < J_RED ? 1 : 2];
        uint2 en = sched[W0];
        const uint32_t t0 = gtime();
        const uint32_t sp = __reduce_or_sync(0xffffffffu, sb);
        const int cx = (j >> 1) * 64 + (j < NFF ? 0 : 1024 - NFF * 32);
#pragma unroll 1
        for (int i = W0; en.x; i++) {
            const uint32_t e = en.x, tn = t0 + (int16_t)en.y, mp = (en.y >> 16) & 15, st = (en.y >> 20) * 64;
            en = sched[i + 1];
            if (mp == MP_MODB && j >= J_END) break;
            uint32_t c0 = mp == MP_WO ? (j & 7) * 64 : mp > MP_WO ? cx : 0;
            uint32_t c1 = mp == MP_CKV ? 0 : mp == MP_DOWN ? j * 32 : st + (mp == MP_WUV ? (j & 3) * 32 : mp == MP_WO ? (j >> 3) * 256 : rk * 256);
            uint32_t c2 = mp < MP_CKV ? j >> 1 : mp == MP_CKV ? rk * 4 : mp == MP_WUV ? (j >> 2) * 2 : mp == MP_DOWN ? st >> 4 : 0;
            uint32_t c3 = mp == MP_CKV ? st * 2 + (j & ~1) : 0;
            uint32_t dst = sp + ((e << 7) & 0x3e000), bar = sp + SM_BAR + (e & 63) * 8;
            const uint32_t w0 = (e >> 8) & 0x3f8, w1 = (e >> 15) & 0x3f8, w2 = (e >> 22) & 0x3f8, bb = sp + SM_BAR - 8;
            const CUtensorMap* pm = &M.m[mp];
            pin(dst); pin(bar); pin(c0); pin(c1); pin(c2); pin(c3); pin(pm);
            if (w0) mbar_wait(bb + w0, 0);
            if (w2) {
                mbar_wait(bb + w2, 0);
                while (!__any_sync(0xffffffffu, mbar_test(bb + w1, 0) | ((int)(gtime() - tn) > 0))) {}
            } else if (w1) mbar_wait(bb + w1, 0);
            tma(dst, pm, bar, c0, c1, c2, c3);
        }
    } else if (warp == 13) {
#pragma unroll
        for (int i = 0; i < 2; i++) st_x4(gs + (B_ML + rk * 16 + i * 8 + g) * 4096 + (t >> 1) * 1024 + (j >> 1) * 8 + (t & 1) * 4, 0u, 0u, 0u, 0u);
        if (lane < 16) st2_x4(gs + (B_E2 + (j >> 4)) * 4096 + (j & 15) * 64 + lane * 4, 0u, 0u, 0u, 0u);
        st2_x1(gs + (B_E3 + (j >> 5)) * 4096 + (j & 31) * 32 + lane, 0u);
        if (lane < 8) st2_x1(gs + B_MB * 4096 + j * 8 + lane, 0u);
        if (j < NFF) {
#pragma unroll
            for (int i = 0; i < 2; i++) st2_x4(gs + (B_E5 + i * 8 + g) * 4096 + j * 16 + t * 4, 0u, 0u, 0u, 0u);
        }
        bar_sync(9, 64);
        const uint32_t cs = ldcls();
#pragma unroll 1
        for (int i = 0; i < 32; i++) {
            st_x4(gs + G_E1 + j * 8192 + (i >> 3) * 2048 + ((((cs >> 1) ^ (i >> 3)) & 1) << 10) + (i & 7) * 128 + lane * 4, 0u, 0u, 0u, 0u);
            __nanosleep(JAN_SLEEP);
        }
        fence_gpu();
        if (lane < 8) st2_x1(gs + B_RD * 4096 + j * 8 + lane, 1u + (cs >> 1));
        if (lane == 0) TRACE(41);
        uint32_t rd[4];
        mbar_wait(BAR(IT_CKV + RD_ITEM), 0);
        poll<1024, RD_SLEEP>(rd, gs + near_off(B_RD, cs) + lane * 8);
#pragma unroll
        for (int i = 0; i < 4; i++) {
            const uint32_t m = __ballot_sync(0xffffffffu, rd[i] == 2u);
            if (lane == 0) sts32(sb + SM_CLS + 16 + i * 4, m);
        }
        __syncwarp();
        if (lane < 8) mbar_arrive(BAR(JD));
        if (lane == 0) TRACE(42);
    } else if (warp == 14) {
        uint2 ml[2];
        mbar_waitb(BAR(JD), 0);
        const uint32_t cls = ldcls();
        mbar_waitb(BAR(PF0 + 2 * NUNITS - 1), 0);
        __nanosleep(ML_DELAY);
        const uint32_t* pl2 = gs + near_off(B_ML + (j >> 2), cls) + lane * 8;
        const uint32_t wa = sb + SM_W + lb4 * 64 + t * 16 + (g & 3) * 4;
        poll_start<1024>(ml, pl2);
        uint32_t w0 = 0, w1 = 0, redo = 0;
        bool first = true;
#pragma unroll 1
        for (uint32_t it = 0;; it++) {
            const bool p0 = minw(ml[0]) != 0, p1 = minw(ml[1]) != 0;
            const int n = __popc(__ballot_sync(0xffffffffu, p0)) + __popc(__ballot_sync(0xffffffffu, p1));
            const uint32_t x0 = ml[0].x, x1 = ml[1].x;
            if (n < 64) {
                if (!p0) ld_x(ml[0], pl2);
                if (!p1) ld_x(ml[1], pl2 + 256);
            }
            if (n == 64 || (first && n >= E1_EARLY)) {
                auto ord = [](int x) { return x ^ ((x >> 31) & 0x7fffffff); };
                const int o0 = ord(x0), o1 = ord(x1);
                const float mm = __int_as_float(ord(__reduce_max_sync(0xffffffffu, max(p0 ? o0 : INT_MIN, p1 ? o1 : INT_MIN))));
                const float lo = __int_as_float(ord(__reduce_min_sync(0xffffffffu, min(p0 ? o0 : INT_MAX, p1 ? o1 : INT_MAX))));
                const uint32_t v0 = pack2(ex2((p0 ? __uint_as_float(x0) : lo) - mm), 0.f), v1 = pack2(ex2((p1 ? __uint_as_float(x1) : lo) - mm), 0.f);
                redo = !first && __any_sync(0xffffffffu, v0 != w0 || v1 != w1);
                w0 = v0; w1 = v1;
                sts32(wa - redo * (SM_W - SM_W2), w0 * 0x10001u); sts32(wa - redo * (SM_W - SM_W2) + 128, w1 * 0x10001u);
                if (first) bar_arrive(3, 416);
                first = false;
                if (n == 64) break;
            }
            if (it > SPIN_LIMIT) __trap();
        }
        if (lane == 0) TRACE_Q(37);
        float L = bflo(w0) * __uint_as_float(ml[0].y) + bflo(w1) * __uint_as_float(ml[1].y);
#pragma unroll
        for (int o = 16; o; o >>= 1) L += shx(L, o);
        if (lane == 0) *(float2*)(sm + SM_FQ) = make_float2(__frcp_rn(L), __uint_as_float(redo));
        __syncwarp();
        if (lane < 8) mbar_arrive(BAR(WR));
        if (lane == 0) TRACE(10);
        bar_sync(4, 288);
        clear_head();
        if (j < NFF) {
            uint32_t ya = sb + SM_Y + lane * 16, sa = peer_addr(sb + SM_RED + 2048 + rk * 8, lane & 1), tb = peer_addr(BAR(MBB), lane & 1);
            pin(ya); pin(sa); pin(tb);
            bar_sync(7, 288);
            const float4 y0 = ldsf4(ya), y1 = ldsf4(ya + 512);
            float s = sum4(y0) + sum4(y1);
            float q = (fmaf(y0.x, y0.x, y0.y * y0.y) + fmaf(y0.z, y0.z, y0.w * y0.w)) + (fmaf(y1.x, y1.x, y1.y * y1.y) + fmaf(y1.z, y1.z, y1.w * y1.w));
#pragma unroll
            for (int o = 16; o; o >>= 1) { s += shx(s, o); q += shx(q, o); }
            if (lane < 2) st_async2(sa, s, q, tb);
        }
    } else if (warp == 15) {
        mbar_waitb(BAR(IT_X - 1), 0);
        if (j < J_END) mbar_waitb(BAR(j < NFF ? NITEMS - 1 : MBB), 0);
    }
    } else if (warp < 4) {
        float* scr = (float*)(sm + SM_SCR);
        uint32_t cls;
        {
            uint2 ha[8];
            {
                uint32_t best = 0xffffffffu;
#pragma unroll
                for (int i = 0; i < NPROBE; i++) {
                    uint32_t t0, t1, o;
                    asm volatile("mov.u32 %0, %%clock;" : "=r"(t0));
                    asm volatile("atom.relaxed.gpu.global.exch.b32 %0, [%1], %2;" : "=r"(o) : "l"(pl), "r"(2u + i) : "memory");
                    asm volatile("{\n.reg .pred p;\nsetp.ne.u32 p, %1, 0x1234567;\nmov.u32 %0, 0;\n@p mov.u32 %0, %%clock;\n}" : "=r"(t1) : "r"(o));
                    best = min(best, t1 - t0);
                }
                if (lane == 0) scr[16 + warp] = __uint_as_float(best);
            }
            const float sh = __shfl_sync(0xffffffffu, bflo(in1), 0);
            const float v0 = bflo(in1) - sh, v1 = bfhi(in1) - sh, v2 = bflo(in2) - sh, v3 = bfhi(in2) - sh;
            float mb, sd;
            ln_stats<4>((v0 + v1) + (v2 + v3), (v0 * v0 + v1 * v1) + (v2 * v2 + v3 * v3), sh, scr, warp, lane, 2, mb, sd);
            if (!rk) in2 = in1;
            const uint4 lt = *(const uint4*)(scr + 16);
            cls = NUMA ? ((lt.y < lt.x) ^ (__popc((B_PR + (j >> 5)) & 0x2C) & 1)) | (lt.w < lt.z) << 1 : 0;
            if (warp == 0) { if (lane == 0) sts32(sb + SM_CLS, cls); bar_arrive(9, 64); }
            if (tid == 0) TRACE(38);
            asm volatile("barrier.cluster.wait.aligned;" ::: "memory");
            mbar_wait(BAR(IT_MODA), 0);
            __nanosleep(HA_DELAY);
            poll<1024, H_SLEEP, false, 16384>(ha, gs + near_off(B_HA + rk * 2, cls) + 2 * tid);
            auto rsum = [](uint32_t a, uint32_t b, uint32_t c, uint32_t d) { return rbf((__uint_as_float(a) + __uint_as_float(b)) + (__uint_as_float(c) + __uint_as_float(d))); };
            sts32(sb + SM_FV + frag_off(2 * tid),
                  pack2(ln_mod(bflo(in2), mb, sd, rsum(ha[4].x, ha[5].x, ha[6].x, ha[7].x), rsum(ha[0].x, ha[1].x, ha[2].x, ha[3].x)),
                        ln_mod(bfhi(in2), mb, sd, rsum(ha[4].y, ha[5].y, ha[6].y, ha[7].y), rsum(ha[0].y, ha[1].y, ha[2].y, ha[3].y))));
            bar_arrive(5, 384);
            mbar_wait(BAR(QB), 0);
            if (tid < 64) {
                const float* qx = (const float*)(sm + SM_QX) + tid;
                sts16(sb + SM_FQ + frag_off(tid), pack2((qx[0] + qx[64]) + (qx[128] + qx[192]), 0.f));
            }
            bar_arrive(6, 384);
        }
        asm volatile("setmaxnreg.inc.sync.aligned.u32 192;");
        float acc[128];
        float M = 0.f;
        uint32_t pa = sb + SM_XA + warp * 512 + lane * 16, ma = sb + SM_MX + (warp * 8 + g) * 4, pf = BAR(PF0);
        uint32_t blo = __reduce_or_sync(0xffffffffu, (((sb + SM_U) & 0x3FFFFu) >> 4) | 0x400000u);
        uint32_t* e1[4];
#pragma unroll
        for (int i = 0; i < 4; i++) e1[i] = gs + G_E1 + (warp * 8 + g) * 4 * 8192 + (rk * 2 + (j >> 6)) * 2048 + ((j >> 1) & 31) * 32 + t * 4;
#pragma unroll 1
        for (int h = 0; h < 2 * NUNITS; h++) {
            mbar_wait(pf, 0);
            const float m = __uint_as_float(lds32(ma));
            const uint4 pn = lds128(pa);
            wg_wait0();
#pragma unroll
            for (int i = 0; i < 128; i++) asm volatile("" : "+f"(acc[i]) :: "memory");
            if (h == 0) M = m;
            uint32_t b2 = 0x3f803f80u;
            if (__builtin_expect(__any_sync(0xffffffffu, m != M), 0)) {
                const float Mn = fmaxf(M, m), alpha = ex2(M - Mn), beta = ex2(m - Mn);
                M = Mn;
                b2 = pack2(beta, beta);
#pragma unroll
                for (int jj = 0; jj < 32; jj++) { acc[4 * jj] *= alpha; acc[4 * jj + 1] *= alpha; }
            }
            auto mul2 = [](uint32_t x, uint32_t y) { uint32_t r; asm("mul.rn.bf16x2 %0, %1, %2;" : "=r"(r) : "r"(x), "r"(y)); return r; };
            const uint4 p = make_uint4(mul2(pn.x, b2), mul2(pn.y, b2), mul2(pn.z, b2), mul2(pn.w, b2));
            if (tid == 0 && (h & 1)) TRACE_Q(48 + (h >> 1));
            wgmma_pv(acc, p, blo, h);
            if (lane == 0 && h > 0 && !(h & 1)) mbar_arrive(BAR(EB_UNIT0 + (h >> 1) - 1));
            blo += h == 11 ? -11 * 1024 : 1024;
            pa += (h == 5 || h == 11) ? -5 * 2048 : 2048;
            ma += 128; pf += 8;
            if (h == 2 * NUNITS - 3) {
                mbar_wait(BAR(JD), 0);
                const uint32_t hm = (*(const uint32_t*)(sm + SM_CLS + 16 + warp * 4) >> (g * 4)) ^ ((j >> 6) ? 15u : 0u);
#pragma unroll
                for (int i = 0; i < 4; i++) e1[i] += ((hm >> i) & 1) << 10;
            }
        }
#pragma unroll
        for (int vv = 0; vv < 2; vv++) {
            if (vv && M == 1.f) __trap();
            if (vv) wg_wait0(); else wg_wait1();
#pragma unroll
            for (int i = 0; i < 64; i++) asm volatile("" : "+f"(acc[vv * 64 + i]) :: "memory");
            if (tid == 0 && !vv) TRACE_Q(63);
#pragma unroll
            for (int i = 0; i < 4; i++) {
                const float* a = &acc[vv * 64 + i * 16];
                st_x4(e1[i] + i * 8192 + vv * 16, enc(pack2(a[0], a[1])), enc(pack2(a[4], a[5])), enc(pack2(a[8], a[9])), enc(pack2(a[12], a[13])));
            }
        }
        bar_arrive(3, 416);
        if (tid == 0) TRACE_Q(17);
        if (j < NFF) {
            uint4 a[16];
            const uint32_t ad = sb + SM_U + B_DN * 32768 + warp * 8192 + (r8 + 8 * lb4) * 128 + (lb3 ^ r8) * 16;
            uint32_t rl = sb + SM_RED + lane * 16;
            uint32_t* p5 = gs + (B_E5 + warp * 4 + (t >> 1)) * 4096 + j * 16 + (t & 1) * 8 + g;
            pin(rl); pin(p5);
            if (lane == 0) mbar_expect(BAR(MBB), 4);
            auto ldd = [&]() {
#pragma unroll
                for (int s = 0; s < 16; s++) a[s] = ldsm<true>((ad ^ ((s & 3) * 32)) + (s >> 2) * 2048);
            };
            const uint32_t db = BAR(IT_DOWN + (warp >> 1));
            mbar_wait(BAR(MBB), 0);
            const float4 st = ldsf4(sb + SM_RED + 2048);
            const bool hd = __all_sync(0xffffffffu, mbar_test(db, 0));
            if (hd) ldd();
            const float mu = (st.x + st.z) * (1.f / 512.f);
            float rstd;
            asm volatile("rsqrt.approx.ftz.f32 %0, %1;" : "=f"(rstd) : "f"(fmaxf(fmaf(-mu, mu, (st.y + st.w) * (1.f / 512.f)), 0.f) + 1e-5f));
            mbar_wait(BAR(QB), 1);
            if (tid == 0) TRACE(25);
            const float4 f0 = ldsf4(rl), f2 = ldsf4(rl + 1024), f1 = ldsf4(rl + 512), f3 = ldsf4(rl + 1536);
            const float gg = fmaf(rstd, fmaf(-mu, f0.z + f2.z, (f0.x + f0.y) + (f2.x + f2.y)), f0.w + f2.w);
            const float uu = fmaf(rstd, fmaf(-mu, f1.z + f3.z, (f1.x + f1.y) + (f3.x + f3.y)), f1.w + f3.w);
            const float hh = __fdividef(gg * uu, 1.f + ex2(-gg * fmaf(gg * gg, 0.10294324f, 2.3022082f)));
            uint32_t hb[4];
#pragma unroll
            for (int i = 0; i < 4; i++) hb[i] = pack2(__shfl_sync(0xffffffffu, hh, 2 * t + 8 * i), __shfl_sync(0xffffffffu, hh, 2 * t + 8 * i + 1));
            if (!hd) { mbar_wait(db, 0); ldd(); }
#pragma unroll
            for (int i = 0; i < 2; i++) {
                uint32_t res = 0;
#pragma unroll
                for (int k = 0; k < 4; k++) {
                    float c[4] = {0.f, 0.f, 0.f, 0.f};
                    const uint4 &x = a[i * 8 + k], &y = a[i * 8 + k + 4];
                    mma(c, x.x, x.y, x.z, x.w, hb[0], hb[1]);
                    mma(c, y.x, y.y, y.z, y.w, hb[2], hb[3]);
                    if (t == k) res = pack2(c[0], c[2]);
                }
                st2_x1(p5 + i * 8192, enc(res));
            }
            if (tid == 0) { TRACE(27); TRACE_GT(47); }
        } else if (j < J_END) {
            uint4 a[8], b[4];
            float c[4], e[4];
            const bool own = (warp >> 1) == rk;
            const uint32_t xa = sb + SM_FV + (warp & 1) * 64 + g * 8;
            if (lane == 0) mbar_expect(BAR(MBB), own ? 64 : 0);
#pragma unroll
            for (int i = 0; i < 2; i++) {
                ldfrag(b, sb + SM_FS + rk * 512 + i * 256 + t * 16);
                mbar_wait(BAR(IT_X + i), 0);
                const uint32_t ab = sb + SM_U + B_X * 32768 + i * 16384 + a128;
                load8<true>(a, [&](int s) { return ab + s * 2048; });
                mma8(i ? e : c, a, b);
            }
            c[0] += e[0]; c[2] += e[2];
            if (!own) {
                if (t == 0) st_async2(peer_addr(xa, rk ^ 1), c[0], c[2], peer_addr(BAR(MBB), rk ^ 1));
            } else {
                mbar_wait(BAR(MBB), 0);
                const float2 pp = *(const float2*)(sm + (xa - sb));
                const float mine = t ? c[2] + pp.y : c[0] + pp.x, other = shx(mine, 4);
                const uint32_t w = (warp & 1) * 8 + t * 4 + (g >> 1), val = enc(pack2(mine, other));
                if (t < 2 && !(g & 1)) {
                    if (j < J_RED) st2_x1(gs + B_MB * 4096 + (j - NFF) * 16 + w, val);
                    else sts32(sb + SM_FV + 256 + w * 4, val);
                }
                __syncwarp();
                if (j >= J_RED && lane < 4) mbar_arrive(BAR(QB));
                if (lane == 0) TRACE(11);
            }
        }
    } else {
        const int u8 = tid - 128, w8 = warp - 4;
        const int v = w8 >> 2, wq4 = w8 & 3;
        {
            const float c0 = bflo(in1), c1 = bfhi(in1);
            sts32(sb + SM_FS + frag_off(2 * u8), pack2(__fdividef(c0, 1.f + __expf(-c0)), __fdividef(c1, 1.f + __expf(-c1))));
        }
        bar_sync(1, 256);
        asm volatile("barrier.cluster.wait.aligned;" ::: "memory");
        uint4 a[8], b[4]; float c[4];
        if (w8 < 2) {
            ldfrag(b, sb + SM_FS + (j >> 5) * 256 + t * 16);
            mbar_wait(BAR(IT_MODA), 0);
            if (u8 == 0) TRACE(12);
            const uint32_t ab = sb + SM_XA + w8 * 4096 + a16;
            load8<true>(a, [&](int s) { return ab + s * 512; });
            mma8(c, a, b);
            if (t < 2) st2_x1(gs + (B_HA + ((j >> 4) & 1) * 2 + w8) * 4096 + (j >> 5) * 256 + (j & 15) * 16 + t * 8 + g, encf(t ? c[2] : c[0]));
        }
        {
            mbar_wait(BAR(IT_WQ + 2 * v <= NCP ? 1 : IT_WQ + 2 * v), 0); mbar_wait(BAR(IT_WQ + 2 * v + 1 <= NCP ? 1 : IT_WQ + 2 * v + 1), 0);
            const uint32_t ab = sb + SM_U + 4 * 32768 + v * 16384 + a128;
            load8<true>(a, [&](int s) { return ab + s * 2048; });
            if (lane == 0) mbar_arrive(BAR(EB_WQ));
            bar_sync(5, 384);
            if (u8 == 0) TRACE(13);
            ldfrag(b, sb + SM_FV + v * 256 + t * 16);
            mma8(c, a, b);
            if (t < 2) {
                const float qv = t ? c[2] : c[0];
                const uint32_t qa_ = sb + SM_QX + ((rk * 2 + v) * 64 + wq4 * 16 + t * 8 + g) * 4;
                asm volatile("st.async.weak.shared::cluster.mbarrier::complete_tx::bytes.f32 [%0], %1, [%2];"
                             :: "r"(peer_addr(qa_, rk ^ 1)), "f"(qv), "r"(peer_addr(BAR(QB), rk ^ 1)) : "memory");
                sts32(qa_, __float_as_uint(qv));
            }
            __syncwarp();
            if (lane == 0) mbar_expect(BAR(QB), 64);
        }
        {
            mbar_wait(BAR(IT_WUK + v), 0); mbar_wait(BAR(IT_WUK + v + 2), 0);
            const uint32_t ab = sb + SM_U + 5 * 32768 + (w8 * 16 + r8 + 8 * lb3) * 128;
            const uint32_t x16 = (lb4 ^ r8) * 16;
            load8<false>(a, [&](int s) { return ab + (s & 1) * 16384 + (x16 ^ ((s >> 1) * 32)); });
            bar_sync(6, 384);
            if (u8 == 0) TRACE(14);
            b[0] = lds128(sb + SM_FQ + t * 16); b[1] = lds128(sb + SM_FQ + 64 + t * 16);
            float e[4] = {0.f, 0.f, 0.f, 0.f};
            c[0] = c[1] = c[2] = c[3] = 0.f;
#pragma unroll
            for (int k = 0; k < 4; k++) {
                const uint32_t b0 = (k & 1) ? b[k >> 1].z : b[k >> 1].x, b1 = (k & 1) ? b[k >> 1].w : b[k >> 1].y;
                mma(c, a[2 * k].x, a[2 * k].y, a[2 * k].z, a[2 * k].w, b0, b1);
                mma(e, a[2 * k + 1].x, a[2 * k + 1].y, a[2 * k + 1].z, a[2 * k + 1].w, b0, b1);
            }
            const float mine = ((t & 1) ? ((t & 2) ? e[2] : e[0]) : ((t & 2) ? c[2] : c[0])) * 0.12751743f;
            const float other = shx(mine, 4);
            if (!(g & 1)) st2_x1(gs + (B_QA + rk * 8 + ((j >> 1) & 1) * 4 + (j >> 5)) * 4096 + w8 * 128 + ((j >> 2) & 7) * 16 + (g >> 1) * 4 + t, enc(pack2(mine, other)));
            if (u8 == 0) TRACE(15);
        }
        const uint32_t cls = ldcls();
        __nanosleep(QA_DELAY);
        {
            uint4 qb[8];
            const uint32_t* pq = gs + near_off(B_QA + rk * 8 + wq4, cls) + lane * 4;
            const uint32_t* pq2 = gs + near_off(B_QA + rk * 8 + 4 + wq4, cls) + lane * 4;
            if (lane == 0) {
                mbar_expect(BAR(QT), 4096);
                asm volatile("cp.async.bulk.shared::cluster.global.mbarrier::complete_tx::bytes [%0], [%1], 4096, [%2];"
                             :: "r"(sb + SM_U + 5 * 32768 + w8 * 4096), "l"(gs + near_off(B_QA + rk * 8 + w8, cls)), "r"(BAR(QT)) : "memory");
            }
            const uint32_t qs = sb + SM_U + 5 * 32768 + wq4 * 4096 + lane * 16;
            mbar_wait(BAR(QT), 0);
#pragma unroll
            for (int i = 0; i < 8; i++) { a[i] = lds128(qs + i * 512); qb[i] = lds128(qs + 16384 + i * 512); }
            poll<512, QA_SLEEP, true>(a, pq);
            poll<512, QA_SLEEP, true>(qb, pq2);
            if (lane == 0) mbar_arrive(BAR(EB_WUK));
            auto add2 = [](uint32_t x, uint32_t y) { uint32_t r; asm("add.rn.bf16x2 %0, %1, %2;" : "=r"(r) : "r"(x), "r"(y)); return r; };
#pragma unroll
            for (int i = 0; i < 8; i++) a[i] = make_uint4(add2(a[i].x, qb[i].x), add2(a[i].y, qb[i].y), add2(a[i].z, qb[i].z), add2(a[i].w, qb[i].w));
        }
        if (u8 == 0) TRACE(8);
        {
            float m = -INFINITY, l = 0.f;
            uint32_t xl = sb + SM_XB + w8 * 2048 + lane * 16, xr = peer_addr(xl, rk ^ 1), bsr = peer_addr(BAR(SF0 + v), rk ^ 1);
            uint32_t pa = sb + SM_XA + v * 2048 + wq4 * 512 + lane * 16, ma = sb + SM_MX + v * 128 + (wq4 * 8 + g) * 4;
            uint32_t fb = BAR(IT_CKV + v * 2), sf = BAR(SF0 + v);
            uint32_t dlo = __reduce_or_sync(0xffffffffu, (((sb + SM_U + v * 16384) & 0x3FFFFu) >> 4) | 0x10000u);
            if (STAG && v) __nanosleep(STAG);
#pragma unroll 1
            for (int n = 0; n < NUNITS; n++) {
                float d[2][16], sc[8];
#pragma unroll
                for (int i = 0; i < 2; i++) {
                    mbar_wait(fb + i * 8, 0);
                    wg_fence();
#pragma unroll
                    for (int s = 0; s < 8; s++) wgmma_rs_n32(d[i], a[s], (0x40000080ull << 32) | (dlo + i * 512 + (s >> 2) * 64 + (s & 3) * 2), s);
                    wg_commit();
                }
#pragma unroll
                for (int i = 0; i < 2; i++) {
                    if (i) wg_wait0(); else wg_wait1();
#pragma unroll
                    for (int k = 0; k < 16; k++) asm volatile("" : "+f"(d[i][k]) :: "memory");
                    sc[4 * i] = d[i][0] + d[i][6]; sc[4 * i + 1] = d[i][1] + d[i][7]; sc[4 * i + 2] = d[i][8] + d[i][14]; sc[4 * i + 3] = d[i][9] + d[i][15];
                    asm volatile("st.async.weak.shared::cluster.mbarrier::complete_tx::bytes.v4.f32 [%0], {%1, %2, %3, %4}, [%5];"
                                 :: "r"(xr + i * 1024), "f"(sc[4 * i]), "f"(sc[4 * i + 1]), "f"(sc[4 * i + 2]), "f"(sc[4 * i + 3]), "r"(bsr) : "memory");
                }
                if (u8 == 128) TRACE_Q(56 + (n < 6 ? n : -40));
                if (n >= 3) mbar_wait(BAR(EB_UNIT0 + n - 3), 0);
                dlo += n == 5 ? -5 * 2048 : 2048;
                fb += 32; xr ^= 512; bsr += 16;
                pin(fb); pin(xr); pin(bsr);
                mbar_wait(sf, 0);
                const float4 x = ldsf4(xl), y = ldsf4(xl + 1024);
                sc[0] += x.x; sc[1] += x.y; sc[2] += x.z; sc[3] += x.w; sc[4] += y.x; sc[5] += y.y; sc[6] += y.z; sc[7] += y.w;
                float pr[8];
#pragma unroll
                for (int i = 0; i < 8; i++) pr[i] = ex2(sc[i] - m);
                float mx = fmaxf(fmaxf(fmaxf(sc[0], sc[1]), fmaxf(sc[2], sc[3])), fmaxf(fmaxf(sc[4], sc[5]), fmaxf(sc[6], sc[7])));
                if (__builtin_expect(__any_sync(0xffffffffu, mx > m), 0)) {
                    mx = fmaxf(mx, shx(mx, 1));
                    mx = fmaxf(mx, shx(mx, 2));
                    const float mn = fmaxf(m, ceilf(mx * 0.0625f) * 16.f);
                    l *= ex2(m - mn);
                    m = mn;
#pragma unroll
                    for (int i = 0; i < 8; i++) pr[i] = ex2(sc[i] - m);
                }
                stsf(ma, m);
                asm volatile("st.shared.v4.u32 [%0], {%1, %2, %3, %4};" :: "r"(pa), "r"(pack2(pr[0], pr[1])), "r"(pack2(pr[2], pr[3])),
                             "r"(pack2(pr[4], pr[5])), "r"(pack2(pr[6], pr[7])) : "memory");
                __syncwarp();
                if (lane == 0) mbar_arrive(sf + (PF0 - SF0) * 8);
                l += ((pr[0] + pr[1]) + (pr[2] + pr[3])) + ((pr[4] + pr[5]) + (pr[6] + pr[7]));
                xl ^= 512; sf += 16; ma += 256; pa += (n == 2 || n == 5) ? -8192 : 4096;
            }
            l += shx(l, 1);
            l += shx(l, 2);
            float2* mlx = (float2*)(sm + SM_MX + 2048) + wq4 * 8 + g;
            if (v == 0) { *mlx = make_float2(m, l); bar_arrive(11, 256); }
            else {
                mbar_wait(BAR(JD), 0);
                bar_sync(11, 256);
                const float2 o = *mlx;
                const float mn = fmaxf(m, o.x);
                l = l * ex2(m - mn) + o.y * ex2(o.x - mn);
                if ((wq4 >> 1) == rk) st_x4(gs + (B_ML + wq4 * 8 + g) * 4096 + (t >> 1) * 1024 + (j >> 1) * 8 + (t & 1) * 4, encf(mn), encf(l), 1u, 1u);
            }
        }
        const int pi = j < NFF ? rk * 128 + w8 * 16 + (lane & 15) : ((j - J_RED) & 15) * 16 + v * 8 + lb4 * 4 + wq4;
        const uint32_t xw = *(const uint32_t*)(xin + 2 * pi);
        const uint32_t* pm = gs + near_off(B_MB, cls) + pi;
        const uint32_t* pb = gs + near_off(B_E2 + (j >> 4), cls) + (((j >> 3) & 1) * 2 + lb4) * 256 + (lane & 15) * 2;
        pin(pm); pin(pb);
        {
            const uint32_t ab = sb + SM_U + B_WUV * 32768 + v * 4096 + a128;
            uint32_t pa = sb + SM_PB + wq4 * 320 + frag_off(64 * v + 32 * (g >> 2) + 16 * (t & 1) + 8 * (t >> 1) + 2 * (g & 3));
            uint32_t fa = sb + SM_PB + g * 320 + t * 16;
            const uint32_t* pe = gs + G_E1 + j * 8192 + (w8 >> 1) * 2048 + ((((cls >> 1) ^ (w8 >> 1)) & 1) << 10) + (((w8 & 1) * 16 + t) * 8 + g) * 4;
            uint32_t* p2 = gs + (B_E2 + (j >> 4)) * 4096 + (t >> 1) * 1024 + (j & 12) * 64 + w8 * 32 + (j & 3) * 8 + (g & 6) + (t & 1);
            pin(pa); pin(fa); pin(pe); pin(p2);
            const uint32_t mk = (g & 1) ? 0xffff0000u : 0x0000ffffu, m0 = (g & 2) ? 0u : mk, m1 = (g & 2) ? mk : 0u;
            uint4 pv[4];
            bool hv = false;
            bar_sync(3, 416);
            uint4 wa = lds128(sb + SM_W + (wq4 * 4 + t) * 16);
            uint32_t wb[8] = {wa.x & m0, wa.x & m1, wa.y & m0, wa.y & m1, wa.z & m0, wa.z & m1, wa.w & m0, wa.w & m1};
            pv[0] = pv[1] = pv[2] = pv[3] = make_uint4(0u, 0u, 0u, 0u);
            poll<512, E1_SLEEP, true>(pv, pe, [&]() {
                if (!hv) {
                    hv = __all_sync(0xffffffffu, mbar_test(BAR(IT_WUV + t), 0));
                    if (hv) load8<true>(a, [&](int s) { return ab + (s >> 1) * 8192 + (s & 1) * 2048; });
                }
            });
            if (lane == 0) TRACE_Q(48 + w8);
            if (u8 == 0) TRACE_Q(18);
            float lo, hi2;
            float2 inv;
#pragma unroll 1
            for (int pass = 0;; pass++) {
                float e[4][4];
#pragma unroll
                for (int i = 0; i < 4; i++) {
                    e[i][0] = e[i][1] = e[i][2] = e[i][3] = 0.f;
                    mma(e[i], pv[i].x, pv[i].y, pv[i].z, pv[i].w, wb[2 * i], wb[2 * i + 1]);
                }
                const float r0 = (t & 2) ? (e[0][2] + e[1][2]) + (e[2][2] + e[3][2]) : (e[0][0] + e[1][0]) + (e[2][0] + e[3][0]);
                const float r1 = (t & 2) ? (e[0][3] + e[1][3]) + (e[2][3] + e[3][3]) : (e[0][1] + e[1][1]) + (e[2][1] + e[3][1]);
                const uint32_t hi = pack2(r0, r1);
                sts32(pa, hi); sts32(pa + 1280, pack2(r0 - bflo(hi), r1 - bfhi(hi)));
                if (!hv) {
#pragma unroll 1
                    for (int i = 0; i < 4; i++) mbar_wait(BAR(IT_WUV + i), 0);
                    load8<true>(a, [&](int s) { return ab + (s >> 1) * 8192 + (s & 1) * 2048; });
                    hv = true;
                }
                bar_sync(1, 256);
                if (u8 == 0) TRACE(19);
                ldfrag(b, fa);
                mma8(c, a, b);
                mbar_wait(BAR(WR), 0);
                asm volatile("ld.shared.v2.f32 {%0, %1}, [%2];" : "=f"(inv.x), "=f"(inv.y) : "r"(sb + SM_FQ) : "memory");
                quad_pair(c[0] + c[1], c[2] + c[3], t, lo, hi2);
                if (__builtin_expect(__all_sync(0xffffffffu, pass || __float_as_uint(inv.y) == 0), 1)) break;
                wa = lds128(sb + SM_W2 + (wq4 * 4 + t) * 16);
                wb[0] = wa.x & m0; wb[1] = wa.x & m1; wb[2] = wa.y & m0; wb[3] = wa.y & m1; wb[4] = wa.z & m0; wb[5] = wa.z & m1; wb[6] = wa.w & m0; wb[7] = wa.w & m1;
                bar_sync(1, 256);
            }
            if (!(g & 1)) st_x1(p2, enc(pack2(lo * inv.x, hi2 * inv.x)));
            bar_arrive(4, 288);
            if (u8 == 0) TRACE(20);
        }
        uint32_t mb[3] = {0u, 0u, 0u};
        if (j < NFF) poll_start<1024>(mb, pm);
        uint4 a2[8];
        if (v == 0) {
            const uint32_t ab = sb + SM_U + B_WO * 32768 + a128;
            uint32_t* p3 = gs + (B_E3 + ((j >> 1) & 3)) * 4096 + (t >> 1) * 1024 + (rk * 2 + (wq4 >> 1)) * 256 + (j >> 3) * 16 + (wq4 & 1) * 8 + (t & 1) * 4 + (g >> 1);
            pin(p3);
            uint2 bb[8];
#pragma unroll
            for (int i = 0; i < 8; i++) bb[i] = make_uint2(0u, 0u);
            bool ho = false;
            auto ldo = [&]() { load8<true>(a, [&](int s) { return ab + s * 2048; }); load8<true>(a2, [&](int s) { return ab + 16384 + s * 2048; }); };
            auto idle = [&]() {
                if (!ho) {
                    ho = __all_sync(0xffffffffu, mbar_test(BAR(IT_WO + t), 0));
                    if (ho) ldo();
                }
            };
            poll<128, 0, true>(bb, pb, idle);
            if (!ho) {
#pragma unroll 1
                for (int i = 0; i < 4; i++) mbar_wait(BAR(IT_WO + i), 0);
                ldo();
            }
            if (u8 == 0) TRACE(21);
            float e[4][4];
#pragma unroll
            for (int s = 0; s < 16; s++) {
                const uint4& x = (s & 2) ? a2[(s >> 2) * 2 + (s & 1)] : a[(s >> 2) * 2 + (s & 1)];
                const uint2& y = bb[(s >> 2) * 2 + (s & 1)];
                if (s < 4) e[s][0] = e[s][1] = e[s][2] = e[s][3] = 0.f;
                mma(e[s & 3], x.x, x.y, x.z, x.w, y.x, y.y);
            }
            float lo, hi;
            quad_pair((t & 2) ? (e[2][0] + e[3][0]) + (e[2][1] + e[3][1]) : (e[0][0] + e[1][0]) + (e[0][1] + e[1][1]),
                      (t & 2) ? (e[2][2] + e[3][2]) + (e[2][3] + e[3][3]) : (e[0][2] + e[1][2]) + (e[0][3] + e[1][3]), t, lo, hi);
            if (!(g & 1)) st_x1(p3, enc(pack2(lo, hi)));
            bar_arrive(1, 256);
            if (u8 == 0) TRACE(22);
        } else bar_sync(1, 256);
        if (j < NFF) {
            const uint32_t* p3 = gs + near_off(B_E3 + rk * 2 + v, cls) + wq4 * 256 + lane;
            uint32_t za = sb + SM_FZ + lb4 * 576 + frag_off(w8 * 32 + (lane & 15) * 2);
            uint32_t fa = sb + SM_FZ + (g & 3) * 576 + lb4 * 256 + t * 16, ya = sb + SM_Y + u8 * 4;
            poll<1024, MB_SLEEP, true>(mb, pm);
            const uint32_t kk = pack2(1.f + bflo(mb[2]), 1.f + bfhi(mb[2]));
            sts32(za + 2 * 576, lb4 ? mb[1] : kk);
            uint32_t e3[8] = {0u, 0u, 0u, 0u, 0u, 0u, 0u, 0u};
            uint32_t ra = peer_addr(sb + SM_RED + (rk * 2 + v) * 512 + ((wq4 & 1) * 16 + (t >> 1) * 8 + g) * 16 + (t & 1) * 8, wq4 >> 1), tbo = peer_addr(BAR(QB), wq4 >> 1);
            pin(za); pin(fa); pin(ya); pin(ra); pin(tbo);
            if (lane == 0) mbar_expect(BAR(QB), 256);
            const uint32_t gb = BAR(IT_X + v * 2), ab = sb + SM_U + (B_X + v) * 32768 + a128;
            bool early = false, early2 = false;
            auto ldw = [&]() {
                if (!early) {
                    early = __all_sync(0xffffffffu, mbar_test(gb, 0));
                    if (early) load8<true>(a, [&](int s) { return ab + s * 2048; });
                }
                if (!early2) {
                    early2 = __all_sync(0xffffffffu, mbar_test(gb + 8, 0));
                    if (early2) load8<true>(a2, [&](int s) { return ab + 16384 + s * 2048; });
                }
            };
            poll<128, 0, true>(e3, p3, ldw);
            if (u8 == 0) TRACE(23);
            const float s0 = sumlo(e3), s1 = sumhi(e3);
            const float y0 = fmaf(bflo(mb[0]), s0 + shx(s0, 16), bflo(xw)), y1 = fmaf(bfhi(mb[0]), s1 + shx(s1, 16), bfhi(xw));
            stsf(ya, lb4 ? y1 : y0);
            const float z0 = y0 * bflo(kk), z1 = y1 * bfhi(kk);
            const uint32_t zh = pack2(z0, z1);
            sts32(za, lb4 ? pack2(z0 - bflo(zh), z1 - bfhi(zh)) : zh);
            bar_sync(7, 288);
            if (u8 == 0) TRACE(24);
            ldfrag(b, fa);
            if (!early) { mbar_wait(gb, 0); load8<true>(a, [&](int s) { return ab + s * 2048; }); }
            {
                float e[4][4];
#pragma unroll
                for (int s = 0; s < 16; s++) {
                    if (s == 8 && !early2) { mbar_wait(gb + 8, 0); load8<true>(a2, [&](int q) { return ab + 16384 + q * 2048; }); }
                    const uint4& x = s < 8 ? a[s] : a2[s & 7];
                    const uint4& y = b[(s >> 1) & 3];
                    float (&d)[4] = e[(s >> 3) * 2 + (s & 1)];
                    if (!(s & 6)) d[0] = d[1] = d[2] = d[3] = 0.f;
                    mma(d, x.x, x.y, x.z, x.w, (s & 1) ? y.z : y.x, (s & 1) ? y.w : y.y);
                }
                const bool hi = t >> 1;
                const float k0 = hi ? e[2][2] + e[3][2] : e[0][0] + e[1][0], k1 = hi ? e[2][3] + e[3][3] : e[0][1] + e[1][1];
                const float o0 = hi ? e[2][0] + e[3][0] : e[0][2] + e[1][2], o1 = hi ? e[2][1] + e[3][1] : e[0][3] + e[1][3];
                st_async2(ra, k0 + shx(o0, 2), k1 + shx(o1, 2), tbo);
            }
        } else if (j >= J_RED && j < J_END) {
            uint32_t ga[1], e3[1];
            poll<0, MB_SLEEP>(ga, pm);
            poll<0, 100>(e3, gs + near_off(B_E3 + (pi >> 6), cls) + (pi & 48) * 16 + (lane & 15) * 16 + (pi & 15));
            float y0 = bflo(e3[0]), y1 = bfhi(e3[0]);
#pragma unroll
            for (int o = 8; o; o >>= 1) { y0 += shx(y0, o); y1 += shx(y1, o); }
            y0 = fmaf(bflo(ga[0]), y0, bflo(xw)); y1 = fmaf(bfhi(ga[0]), y1, bfhi(xw));
            uint32_t gb = 0;
            auto ldg = [&]() { if (__all_sync(0xffffffffu, mbar_test(BAR(QB), 1))) gb = lds32(sb + SM_FV + 256 + (pi & 15) * 4); };
            uint32_t* po = (uint32_t*)out + pi;
            pin(po);
            const uint32_t nz = lane < NFF / 2 ? 0u : 0x80008000u;
            uint2 yv[2] = {make_uint2(nz, nz), make_uint2(nz, nz)};
            poll<NFF * 32, 0, true>(yv, gs + near_off(B_E5 + j - J_RED, cls) + lane * 16 + w8 * 2, ldg);
            if (u8 == 0) TRACE(26);
            const float l0 = bflo(yv[0].x) + bflo(yv[1].x), h0 = bfhi(yv[0].x) + bfhi(yv[1].x);
            const float l1 = bflo(yv[0].y) + bflo(yv[1].y), h1 = bfhi(yv[0].y) + bfhi(yv[1].y);
            float s0 = (lb4 ? h0 : l0) + shx(lb4 ? l0 : h0, 16), s1 = (lb4 ? h1 : l1) + shx(lb4 ? l1 : h1, 16);
#pragma unroll
            for (int o = 8; o; o >>= 1) { s0 += shx(s0, o); s1 += shx(s1, o); }
            if (__any_sync(0xffffffffu, !gb)) { mbar_wait(BAR(QB), 1); ldg(); }
            if (!(lane & 15)) *po = pack2(fmaf(bflo(gb), s0, y0), fmaf(bfhi(gb), s1, y1));
            if (u8 == 0) TRACE(27);
        }
    }
}

typedef CUresult (*EncFn)(CUtensorMap*, CUtensorMapDataType, cuuint32_t, void*, const cuuint64_t*, const cuuint64_t*,
                          const cuuint32_t*, const cuuint32_t*, CUtensorMapInterleave, CUtensorMapSwizzle,
                          CUtensorMapL2promotion, CUtensorMapFloatOOBfill);

void make_map(EncFn enc_fn, CUtensorMap* m, const void* p, cuuint64_t d0, cuuint64_t d1, cuuint64_t d2, cuuint64_t d3,
              cuuint64_t s1, cuuint64_t s2, cuuint64_t s3, cuuint32_t b0, cuuint32_t b1, cuuint32_t b2, cuuint32_t b3, CUtensorMapSwizzle sw) {
    const cuuint64_t dims[4] = {d0, d1, d2, d3}, strides[3] = {s1, s2, s3};
    const cuuint32_t box[4] = {b0, b1, b2, b3}, es[4] = {1, 1, 1, 1};
    enc_fn(m, CU_TENSOR_MAP_DATA_TYPE_BFLOAT16, 4, (void*)p, dims, strides, box, es,
           CU_TENSOR_MAP_INTERLEAVE_NONE, sw, CU_TENSOR_MAP_L2_PROMOTION_L2_64B, CU_TENSOR_MAP_FLOAT_OOB_FILL_NONE);
}

uint32_t* scratch = nullptr;

struct Tune { const char* win; const char* late; int tau, t_off; const char* tail[3][4]; };
Tune tune = {"66666666655555555555555555555555544444444",
             "00000000000000000999999999999999999999999", 320, -240,
             {{"VVVVOOOOguguDD", "zzzzzzzzzzzzzz", "88888888999988", "2fffdbbbl444td"},
              {"VMVMVVOOOO", "zzzzzzzzzz", "9999998888", "2999998ddd"},
              {"VVVVOOOOMM", "zzzzzzzzzz", "8888888888", "eaaa9hhhes"}}};
bool ready = false;

}

extern "C" void kernel_launch(void* const* d_in, const int* in_sizes, int n_in, void* d_out, int out_size) {
    (void)in_sizes; (void)n_in; (void)out_size;
    static Maps maps;
    static const void* cached[12] = {};
    bool same = ready;
    for (int i = 0; i < 12 && same; i++) same = cached[i] == d_in[i];
    if (!same) {
        void* fn = nullptr;
        cudaDriverEntryPointQueryResult qr;
        cudaGetDriverEntryPoint("cuTensorMapEncodeTiled", &fn, cudaEnableDefault, &qr);
        EncFn e = (EncFn)fn;
        const CUtensorMapSwizzle S128 = CU_TENSOR_MAP_SWIZZLE_128B;
        make_map(e, &maps.m[MP_WQ], d_in[2], 64, 512, 64, 1, 8192, 128, 8192, 64, 64, 1, 1, S128);
        make_map(e, &maps.m[MP_WUK], d_in[3], 64, 512, 64, 1, 8192, 128, 8192, 64, 64, 1, 1, S128);
        make_map(e, &maps.m[MP_CKV], d_in[1], 64, 8, 8, 4096, 1024, 128, 8192, 64, 8, 4, 2, S128);
        make_map(e, &maps.m[MP_MODB], d_in[11], 3072, 512, 1, 1, 6144, 6144, 6144, 64, 128, 1, 1, S128);
        make_map(e, &maps.m[MP_WUV], d_in[4], 64, 512, 64, 1, 8192, 128, 8192, 64, 32, 2, 1, S128);
        make_map(e, &maps.m[MP_WO], d_in[5], 512, 4096, 1, 1, 1024, 1024, 1024, 64, 64, 1, 1, S128);
        make_map(e, &maps.m[MP_GATE], d_in[7], 1792, 512, 1, 1, 3584, 3584, 3584, 64, 128, 1, 1, S128);
        make_map(e, &maps.m[MP_UP], d_in[8], 1792, 512, 1, 1, 3584, 3584, 3584, 64, 128, 1, 1, S128);
        make_map(e, &maps.m[MP_DOWN], d_in[9], 64, 1792, 8, 1, 1024, 128, 1024, 64, 32, 4, 1, S128);
        for (int r = 0; r < 3; r++) {
            int ids[56], cnt[128] = {}, tn = tune.t_off - (W0 - 1) * tune.tau;
            uint2* sc = maps.sched[r];
            auto dig = [](char ch) { return ch >= 'a' ? ch - 'a' + 10 : ch >= 'A' ? ch - 'A' + 36 : ch - '0'; };
            for (int i = 0; i < 56; i++) sc[i] = make_uint2(0u, 0u);
            for (int i = 0;; i++) {
                int id = i, buf, dep, w, wl;
                if (i < IT_WUV) {
                    const int u = (i - IT_CKV) >> 2;
                    buf = i < IT_CKV ? 4 + ((i - 1) >> 2) : u % 6;
                    dep = i < IT_CKV || u < 4 ? -1 : u < 6 ? EB_WQ + u - 4 : EB_UNIT0 + u - 6;
                    w = dig(tune.win[i]); wl = dig(tune.late[i]);
                    if (i) tn += tune.tau;
                } else {
                    const char ch = tune.tail[r][0][i - IT_WUV];
                    if (!ch) break;
                    buf = ch == 'V' ? B_WUV : ch == 'O' ? B_WO : ch == 'D' ? B_DN : ch == 'u' ? B_X + 1 : B_X;
                    id = (ch == 'V' ? IT_WUV : ch == 'O' ? IT_WO : ch == 'D' ? IT_DOWN : ch == 'u' ? IT_X + 2 : IT_X) + cnt[(int)ch]++;
                    dep = EB_UNIT0 + (buf < 2 ? buf + 6 : buf);
                    w = dig(tune.tail[r][1][i - IT_WUV]); wl = dig(tune.tail[r][2][i - IT_WUV]);
                    tn += 32 * dig(tune.tail[r][3][i - IT_WUV]);
                }
                if (id < IT_X ? (id - 1) & 3 : (id - IT_X) & 1) dep = -1;
                ids[i] = id;
                auto back = [&](int d) { return i < d ? 0 : (ids[i - d] && ids[i - d] <= NCP ? 1 : ids[i - d]) + 1; };
                sc[i].x = id | (buf * 4 + (id < IT_X ? (id - 1) & 3 : ((id - IT_X) & 1) * 2)) << 6 | (dep + 1) << 11 | (w > 32 ? NEVER + 1 : back(w)) << 18 | (wl ? back(wl) : 0) << 25;
                const int mp = id < IT_CKV ? MP_WQ + ((id - 1) >> 2) : id < IT_WUV ? MP_CKV : id < IT_WO ? MP_WUV : id < IT_X ? MP_WO
                             : id >= IT_DOWN ? MP_DOWN : r ? MP_MODB : MP_GATE + ((id - IT_X) >> 1);
                const int step = mp == MP_CKV ? id - IT_CKV : mp == MP_WUV ? (id - IT_WUV) * 2 : mp == MP_DOWN ? id - IT_DOWN : id < IT_X ? (id - 1) & 3 : ((id - IT_X) & 1) * 2;
                sc[i].y = (tn & 0xffff) | (mp & 15) << 16 | step << 20;
            }
        }
        cudaGetSymbolAddress((void**)&scratch, g_scratch);
        scratch = (uint32_t*)(((uintptr_t)scratch + (2u << 20) - 1) & ~(uintptr_t)((2u << 20) - 1));
        cudaFuncSetAttribute(fused_kernel, cudaFuncAttributeMaxDynamicSharedMemorySize, SM_TOTAL);
        for (int i = 0; i < 12; i++) cached[i] = d_in[i];
        ready = true;
    }
    const First f = {{(const uint8_t*)d_in[2], (const uint8_t*)d_in[11]}, {(const __nv_bfloat16*)d_in[0], (const __nv_bfloat16*)d_in[10]}};
    fused_kernel<<<NCTA, NTHREADS, SM_TOTAL>>>(f, (__nv_bfloat16*)d_out, scratch, maps);
}
```

```cpp
#include <cuda_runtime.h>
#include <cuda_bf16.h>
#include <cuda.h>
#include <stdint.h>
#include <limits.h>

namespace {

constexpr int NCTA = 128;
constexpr int NTHREADS = 512;
constexpr int NUNITS = 8;
constexpr int NFF = 56, J_RED = 104, J_END = 120;
constexpr uint32_t SPIN_LIMIT = 1u << 22;

#define E1_EARLY 50
#define STAG 300
#define NUMA 1
#define NPROBE 3
#define NCP 2
#define W0 4
#define RD_ITEM 15
#define JAN_SLEEP 100
#define RD_SLEEP 400
#define HA_DELAY 200
#define H_SLEEP 100
#define QA_DELAY 600
#define QA_SLEEP 200
#define ML_DELAY 300
#define E1_SLEEP 50
#define MB_SLEEP 100
constexpr int B_WUV = 2, B_WO = 3, B_X = 4  , B_DN = 0;

constexpr int SM_U = 0;
constexpr int SM_XA = 6 * 32768;
constexpr int SM_XB = SM_XA + 12288;
constexpr int SM_MX = SM_XB + 16384;
constexpr int SM_FZ = SM_XB + 8192;
constexpr int SM_PB = SM_XB;
constexpr int SM_Y = SM_XB + 12288;
constexpr int SM_RED = SM_XB + 4096;
constexpr int SM_FS = SM_XB + 20480;
constexpr int SM_FV = SM_FS + 1024;
constexpr int SM_QX = SM_XA + 8192;
constexpr int SM_FQ = SM_FV + 512;
constexpr int SM_CLS = SM_FQ + 128;
constexpr int SM_W = SM_FQ + 256;
constexpr int SM_W2 = SM_MX + 2304;
constexpr int SM_SCR = SM_XA + 9216;
constexpr int SM_TR = SM_XB + 19456;
constexpr int SM_BAR = SM_W + 256;
constexpr int SM_TOTAL = SM_BAR + 1024;
static_assert(SM_TOTAL <= 232448, "smem");

enum { IT_MODA = 0, IT_WQ = 1, IT_WUK = 5, IT_CKV = 9, IT_WUV = 41, IT_WO = 45, IT_X = 49  , IT_DOWN = 53, NITEMS = 55,
       NEVER = 63,
       SF0 = 64,
       PF0 = 80,
       EB_UNIT0 = 96, MBB = 103,
       EB_WQ = 104, EB_WUK, QT, QB, JD, WR };

enum { MP_WQ = 0, MP_WUK, MP_CKV, MP_WUV, MP_DOWN, MP_WO, MP_GATE, MP_UP, MP_MODB, NMAPS };
struct First { const uint8_t* w[2]; const __nv_bfloat16* v[2]; };
struct Maps { CUtensorMap m[NMAPS]; uint2 sched[3][56]; };

enum { B_HA = 0,
       B_MB = 6,
       B_RD = 7,
       B_E2 = 8,
       B_QA = 16,
       B_ML = 32,
       B_E5 = 64,
       B_E3 = 80,
       B_PR = 96,
       B_TR = 100 };
constexpr int G_E1 = 1 << 19;
constexpr int G_TR = B_TR * 4096;
__device__ __align__(1024) uint32_t g_scratch[(8 << 20) / 4];

#define TRACE(slot) do {} while (0)
#define TRACE_Q(slot) do {} while (0)
#define TRACE_GT(slot) do {} while (0)

__device__ __forceinline__ uint32_t s2u(const void* p) { return (uint32_t)__cvta_generic_to_shared(p); }
__device__ __forceinline__ void mbar_init(uint32_t b, int c) { asm volatile("mbarrier.init.shared::cta.b64 [%0], %1;" :: "r"(b), "r"(c) : "memory"); }
__device__ __forceinline__ void mbar_expect(uint32_t b, uint32_t bytes) { asm volatile("mbarrier.arrive.expect_tx.shared::cta.b64 _, [%0], %1;" :: "r"(b), "r"(bytes) : "memory"); }
__device__ __forceinline__ void mbar_arrive(uint32_t b) { asm volatile("mbarrier.arrive.shared::cta.b64 _, [%0];" :: "r"(b) : "memory"); }
__device__ __forceinline__ void mbar_wait(uint32_t b, uint32_t ph) {
    asm volatile("{\n.reg .pred p;\nW: mbarrier.try_wait.parity.shared::cta.b64 p, [%0], %1;\n@!p bra W;\n}" :: "r"(b), "r"(ph) : "memory");
}
__device__ __forceinline__ void mbar_waitb(uint32_t b, uint32_t ph) {
    asm volatile("{\n.reg .pred p;\n.reg .u32 n;\nmov.u32 n, 0;\n"
                 "W: mbarrier.try_wait.parity.shared::cta.b64 p, [%0], %1;\n@p bra D;\n"
                 "add.u32 n, n, 1;\nsetp.lt.u32 p, n, 0x100000;\n@p bra W;\ntrap;\nD:\n}" :: "r"(b), "r"(ph) : "memory");
}
__device__ __forceinline__ uint32_t mbar_test(uint32_t b, uint32_t ph) {
    uint32_t ok;
    asm volatile("{\n.reg .pred p;\nmbarrier.test_wait.parity.shared::cta.b64 p, [%1], %2;\nselp.u32 %0, 1, 0, p;\n}" : "=r"(ok) : "r"(b), "r"(ph) : "memory");
    return ok;
}
__device__ __forceinline__ void bar_sync(int id, int n) { asm volatile("bar.sync %0, %1;" :: "r"(id), "r"(n) : "memory"); }
__device__ __forceinline__ void bar_arrive(int id, int n) { asm volatile("bar.arrive %0, %1;" :: "r"(id), "r"(n) : "memory"); }
__device__ __forceinline__ uint32_t peer_addr(uint32_t a, uint32_t rank) { uint32_t r; asm("mapa.shared::cluster.u32 %0, %1, %2;" : "=r"(r) : "r"(a), "r"(rank)); return r; }
__device__ __forceinline__ void st_async1(uint32_t a, float x, uint32_t bar) {
    asm volatile("st.async.weak.shared::cluster.mbarrier::complete_tx::bytes.f32 [%0], %1, [%2];" :: "r"(a), "f"(x), "r"(bar) : "memory");
}
__device__ __forceinline__ void st_async2(uint32_t a, float x, float y, uint32_t bar) {
    asm volatile("st.async.weak.shared::cluster.mbarrier::complete_tx::bytes.v2.f32 [%0], {%1, %2}, [%3];" :: "r"(a), "f"(x), "f"(y), "r"(bar) : "memory");
}
__device__ __forceinline__ uint32_t gtime() { uint32_t t; asm volatile("mov.u32 %0, %%globaltimer_lo;" : "=r"(t)); return t; }
__device__ __forceinline__ void fence_gpu() { asm volatile("fence.acq_rel.gpu;" ::: "memory"); }

__device__ __forceinline__ uint32_t enc(uint32_t b) { uint32_t r; asm("max.u32 %0, %1, 1;" : "=r"(r) : "r"(b)); return r; }
__device__ __forceinline__ uint32_t encf(float f) { return enc(__float_as_uint(f)); }
__device__ __forceinline__ void st_x1(uint32_t* p, uint32_t v) { asm volatile("st.relaxed.gpu.global.u32 [%0], %1;" :: "l"(p), "r"(v) : "memory"); }
__device__ __forceinline__ void st_x4(void* p, uint32_t a, uint32_t b, uint32_t c, uint32_t d) {
    asm volatile("st.relaxed.gpu.global.v4.u32 [%0], {%1, %2, %3, %4};" :: "l"(p), "r"(a), "r"(b), "r"(c), "r"(d) : "memory");
}
__device__ __forceinline__ void st2_x1(uint32_t* p, uint32_t v) { st_x1(p, v); st_x1(p + 1024, v); }
__device__ __forceinline__ void st2_x4(uint32_t* p, uint32_t a, uint32_t b, uint32_t c, uint32_t d) { st_x4(p, a, b, c, d); st_x4(p + 1024, a, b, c, d); }
__device__ __forceinline__ int near_off(int b, uint32_t cls) { return b * 4096 + (((__popc(b & 0x2C) ^ cls) & 1) << 10); }
__device__ __forceinline__ void ld_x(uint32_t& v, const void* p) { asm volatile("ld.relaxed.gpu.global.u32 %0, [%1];" : "=r"(v) : "l"(p) : "memory"); }
__device__ __forceinline__ void ld_x(uint4& v, const void* p) {
    asm volatile("ld.relaxed.gpu.global.v4.u32 {%0, %1, %2, %3}, [%4];" : "=r"(v.x), "=r"(v.y), "=r"(v.z), "=r"(v.w) : "l"(p) : "memory");
}
__device__ __forceinline__ void ld_x(uint2& v, const void* p) { asm volatile("ld.relaxed.gpu.global.v2.u32 {%0, %1}, [%2];" : "=r"(v.x), "=r"(v.y) : "l"(p) : "memory"); }
__device__ __forceinline__ uint32_t minw(uint32_t v) { return v; }
__device__ __forceinline__ uint32_t minw(const uint2& v) { return min(v.x, v.y); }
__device__ __forceinline__ uint32_t minw(const uint4& v) { return min(__vimin3_u32(v.x, v.y, v.z), v.w); }
template <int N> __device__ __forceinline__ uint32_t mint(const uint32_t* m) {
    if constexpr (N == 1) return m[0];
    else if constexpr (N == 2) return min(m[0], m[1]);
    else return __vimin3_u32(mint<(N + 2) / 3>(m), mint<(N + 1) / 3>(m + (N + 2) / 3), mint<N / 3>(m + (N + 2) / 3 + (N + 1) / 3));
}

template <int STRIDE, int S4 = 4 * STRIDE, typename T, int N>
__device__ __forceinline__ void poll_start(T (&v)[N], const void* base) {
#pragma unroll
    for (int i = 0; i < N; i++) ld_x(v[i], (const uint8_t*)base + (i & 3) * STRIDE + (i >> 2) * S4);
}
struct Nop { __device__ void operator()() const {} };
template <int STRIDE, int SLEEP, bool STARTED = false, int S4 = 4 * STRIDE, typename T, int N, typename F = Nop>
__device__ __forceinline__ void poll(T (&v)[N], const void* base, F idle = F()) {
    if (!STARTED) { poll_start<STRIDE, S4>(v, base); idle(); }
#pragma unroll 1
    for (uint32_t it = 0;; it++) {
        uint32_t m[N];
#pragma unroll
        for (int i = 0; i < N; i++) m[i] = minw(v[i]);
        if (__all_sync(0xffffffffu, mint<N>(m) != 0)) break;
        if (SLEEP && it > 0) __nanosleep(SLEEP);
#pragma unroll
        for (int i = 0; i < N; i++) if (!m[i]) ld_x(v[i], (const uint8_t*)base + (i & 3) * STRIDE + (i >> 2) * S4);
        idle();
        if (it > SPIN_LIMIT) __trap();
    }
}

__device__ __forceinline__ float bflo(uint32_t w) { return __uint_as_float(w << 16); }
__device__ __forceinline__ float bfhi(uint32_t w) { return __uint_as_float(w & 0xffff0000u); }
__device__ __forceinline__ uint32_t pack2(float lo, float hi) {
    uint32_t r; asm("cvt.rn.bf16x2.f32 %0, %1, %2;" : "=r"(r) : "f"(hi), "f"(lo)); return r;
}
__device__ __forceinline__ float rbf(float x) { return __uint_as_float(pack2(0.f, x)); }
__device__ __forceinline__ float sumlo(const uint32_t (&v)[8]) { return ((bflo(v[0]) + bflo(v[1])) + (bflo(v[2]) + bflo(v[3]))) + ((bflo(v[4]) + bflo(v[5])) + (bflo(v[6]) + bflo(v[7]))); }
__device__ __forceinline__ float sumhi(const uint32_t (&v)[8]) { return ((bfhi(v[0]) + bfhi(v[1])) + (bfhi(v[2]) + bfhi(v[3]))) + ((bfhi(v[4]) + bfhi(v[5])) + (bfhi(v[6]) + bfhi(v[7]))); }
__device__ __forceinline__ float ex2(float x) { float r; asm("ex2.approx.ftz.f32 %0, %1;" : "=f"(r) : "f"(x)); return r; }
__device__ __forceinline__ float shx(float v, int m) { return __shfl_xor_sync(0xffffffffu, v, m); }
__device__ __forceinline__ uint4 lds128(uint32_t a) { uint4 v; asm volatile("ld.shared.v4.u32 {%0, %1, %2, %3}, [%4];" : "=r"(v.x), "=r"(v.y), "=r"(v.z), "=r"(v.w) : "r"(a) : "memory"); return v; }
__device__ __forceinline__ uint32_t lds32(uint32_t a) { uint32_t v; asm volatile("ld.shared.u32 %0, [%1];" : "=r"(v) : "r"(a) : "memory"); return v; }
__device__ __forceinline__ void sts32(uint32_t a, uint32_t v) { asm volatile("st.shared.u32 [%0], %1;" :: "r"(a), "r"(v) : "memory"); }
__device__ __forceinline__ void sts16(uint32_t a, uint32_t v) { asm volatile("st.shared.u16 [%0], %1;" :: "r"(a), "h"((uint16_t)v) : "memory"); }
__device__ __forceinline__ int frag_off(int k) { return (k >> 5) * 64 + ((k >> 1) & 3) * 16 + ((k >> 4) & 1) * 8 + ((k >> 3) & 1) * 4 + (k & 1) * 2; }

template <bool TRANS>
__device__ __forceinline__ uint4 ldsm(uint32_t a) {
    uint4 r;
    if (TRANS) asm volatile("ldmatrix.sync.aligned.m8n8.x4.trans.shared.b16 {%0, %1, %2, %3}, [%4];" : "=r"(r.x), "=r"(r.y), "=r"(r.z), "=r"(r.w) : "r"(a) : "memory");
    else asm volatile("ldmatrix.sync.aligned.m8n8.x4.shared.b16 {%0, %1, %2, %3}, [%4];" : "=r"(r.x), "=r"(r.y), "=r"(r.z), "=r"(r.w) : "r"(a) : "memory");
    return r;
}
__device__ __forceinline__ void mma(float (&c)[4], uint32_t a0, uint32_t a1, uint32_t a2, uint32_t a3, uint32_t b0, uint32_t b1) {
    asm volatile("mma.sync.aligned.m16n8k16.row.col.f32.bf16.bf16.f32 {%0,%1,%2,%3}, {%4,%5,%6,%7}, {%8,%9}, {%0,%1,%2,%3};"
                 : "+f"(c[0]), "+f"(c[1]), "+f"(c[2]), "+f"(c[3]) : "r"(a0), "r"(a1), "r"(a2), "r"(a3), "r"(b0), "r"(b1));
}
template <bool TRANS, typename F>
__device__ __forceinline__ void load8(uint4 (&a)[8], F addr) {
    __syncwarp();
#pragma unroll
    for (int s = 0; s < 8; s++) a[s] = ldsm<TRANS>(addr(s));
}
__device__ __forceinline__ void mma8(float (&c)[4], const uint4 (&a)[8], const uint4 (&b)[4]) {
    float e[4][4];
#pragma unroll
    for (int s = 0; s < 8; s++) {
        if (s < 4) e[s][0] = e[s][1] = e[s][2] = e[s][3] = 0.f;
        mma(e[s & 3], a[s].x, a[s].y, a[s].z, a[s].w, (s & 1) ? b[s >> 1].z : b[s >> 1].x, (s & 1) ? b[s >> 1].w : b[s >> 1].y);
    }
#pragma unroll
    for (int i = 0; i < 4; i++) c[i] = (e[0][i] + e[1][i]) + (e[2][i] + e[3][i]);
}
__device__ __forceinline__ void ldfrag(uint4 (&b)[4], uint32_t a) {
    asm volatile("ld.shared.v4.u32 {%0,%1,%2,%3}, [%16];\nld.shared.v4.u32 {%4,%5,%6,%7}, [%16+64];\n"
                 "ld.shared.v4.u32 {%8,%9,%10,%11}, [%16+128];\nld.shared.v4.u32 {%12,%13,%14,%15}, [%16+192];\n"
                 : "=r"(b[0].x), "=r"(b[0].y), "=r"(b[0].z), "=r"(b[0].w), "=r"(b[1].x), "=r"(b[1].y), "=r"(b[1].z), "=r"(b[1].w),
                   "=r"(b[2].x), "=r"(b[2].y), "=r"(b[2].z), "=r"(b[2].w), "=r"(b[3].x), "=r"(b[3].y), "=r"(b[3].z), "=r"(b[3].w) : "r"(a) : "memory");
}
__device__ __forceinline__ void quad_pair(float x, float y, int t, float& lo, float& hi) {
    const float k = ((t & 1) ? y : x) + shx((t & 1) ? x : y, 1);
    lo = k + shx(k, 2); hi = shx(k, 4) + shx(k, 6);
}
__device__ __forceinline__ void pin(uint32_t& x) { asm volatile("" : "+r"(x)); }
template <typename T> __device__ __forceinline__ void pin(T*& x) { asm volatile("" : "+l"(x)); }
__device__ __forceinline__ float4 ldsf4(uint32_t a) { const uint4 v = lds128(a); return make_float4(__uint_as_float(v.x), __uint_as_float(v.y), __uint_as_float(v.z), __uint_as_float(v.w)); }
__device__ __forceinline__ float sum4(const float4& f) { return (f.x + f.y) + (f.z + f.w); }
__device__ __forceinline__ void stsf(uint32_t a, float v) { sts32(a, __float_as_uint(v)); }

__device__ __forceinline__ void wg_fence() { asm volatile("wgmma.fence.sync.aligned;" ::: "memory"); }
__device__ __forceinline__ void wg_commit() { asm volatile("wgmma.commit_group.sync.aligned;" ::: "memory"); }
__device__ __forceinline__ void wg_wait1() { asm volatile("wgmma.wait_group.sync.aligned 1;" ::: "memory"); }
__device__ __forceinline__ void wg_wait0() { asm volatile("wgmma.wait_group.sync.aligned 0;" ::: "memory"); }
#define R8(o) "+f"(d[o]), "+f"(d[o + 1]), "+f"(d[o + 2]), "+f"(d[o + 3]), "+f"(d[o + 4]), "+f"(d[o + 5]), "+f"(d[o + 6]), "+f"(d[o + 7])
__device__ __forceinline__ void wgmma_rs_n32(float (&d)[16], const uint4& a, uint64_t db, int acc) {
    asm volatile("{\n.reg .pred p;\nsetp.ne.b32 p, %21, 0;\n"
        "wgmma.mma_async.sync.aligned.m64n32k16.f32.bf16.bf16 "
        "{%0,%1,%2,%3,%4,%5,%6,%7,%8,%9,%10,%11,%12,%13,%14,%15}, {%16,%17,%18,%19}, %20, p, 1, 1, 0;\n}"
        : R8(0), R8(8) : "r"(a.x), "r"(a.y), "r"(a.z), "r"(a.w), "l"(db), "r"(acc));
}
#define PV_LO "{%0,%1,%2,%3,%4,%5,%6,%7,%8,%9,%10,%11,%12,%13,%14,%15,%16,%17,%18,%19,%20,%21,%22,%23,%24,%25,%26,%27,%28,%29,%30,%31,%32,%33,%34,%35,%36,%37,%38,%39,%40,%41,%42,%43,%44,%45,%46,%47,%48,%49,%50,%51,%52,%53,%54,%55,%56,%57,%58,%59,%60,%61,%62,%63}, "
#define PV_HI "{%64,%65,%66,%67,%68,%69,%70,%71,%72,%73,%74,%75,%76,%77,%78,%79,%80,%81,%82,%83,%84,%85,%86,%87,%88,%89,%90,%91,%92,%93,%94,%95,%96,%97,%98,%99,%100,%101,%102,%103,%104,%105,%106,%107,%108,%109,%110,%111,%112,%113,%114,%115,%116,%117,%118,%119,%120,%121,%122,%123,%124,%125,%126,%127}, "
__device__ __forceinline__ void wgmma_pv(float (&d)[128], const uint4& a, uint32_t blo, int acc) {
    asm volatile("{\n.reg .pred p;\n.reg .b32 u0, u1, u2, u3, t;\n.reg .b64 d0, d1, d2, d3;\nsetp.ne.b32 p, %133, 0;\n"
        "mov.b64 d0, {%132, 0x40000100};\nadd.u32 t, %132, 512;\nmov.b64 d1, {t, 0x40000100};\n"
        "add.u32 t, %132, 128;\nmov.b64 d2, {t, 0x40000100};\nadd.u32 t, %132, 640;\nmov.b64 d3, {t, 0x40000100};\n"
        "wgmma.fence.sync.aligned;\n"
        "wgmma.mma_async.sync.aligned.m64n128k16.f32.bf16.bf16 " PV_LO "{%128, u0, %129, u1}, d0, p, 1, 1, 1;\n"
        "wgmma.mma_async.sync.aligned.m64n128k16.f32.bf16.bf16 " PV_LO "{%130, u2, %131, u3}, d1, 1, 1, 1, 1;\n"
        "wgmma.commit_group.sync.aligned;\n"
        "wgmma.mma_async.sync.aligned.m64n128k16.f32.bf16.bf16 " PV_HI "{%128, u0, %129, u1}, d2, p, 1, 1, 1;\n"
        "wgmma.mma_async.sync.aligned.m64n128k16.f32.bf16.bf16 " PV_HI "{%130, u2, %131, u3}, d3, 1, 1, 1, 1;\n"
        "wgmma.commit_group.sync.aligned;\n}"
        : R8(0), R8(8), R8(16), R8(24), R8(32), R8(40), R8(48), R8(56), R8(64), R8(72), R8(80), R8(88), R8(96), R8(104), R8(112), R8(120)
        : "r"(a.x), "r"(a.y), "r"(a.z), "r"(a.w), "r"(blo), "r"(acc) : "memory");
}

template <int NW>
__device__ __forceinline__ void ln_stats(float s, float q, float sh, float* scr, int w, int lane, int bar, float& mean_b, float& sd_b) {
#pragma unroll
    for (int o = 16; o; o >>= 1) { s += shx(s, o); q += shx(q, o); }
    constexpr float n = 512.f / NW;
    if (lane == 0) { scr[w] = sh + s * (1.f / n); scr[NW + w] = q - s * s * (1.f / n); }
    bar_sync(bar, NW * 32);
    float mu = 0.f, m2 = 0.f;
#pragma unroll
    for (int i = 0; i < NW; i++) { mu += scr[i]; m2 += scr[NW + i]; }
    mu *= 1.f / NW;
#pragma unroll
    for (int i = 0; i < NW; i++) { const float d = scr[i] - mu; m2 = fmaf(n * d, d, m2); }
    mean_b = rbf(mu);
    sd_b = rbf(sqrtf(rbf(rbf(fmaxf(m2, 0.f) * (1.f / 512.f)) + 1e-5f)));
}
__device__ __forceinline__ float ln_mod(float x, float mean_b, float sd_b, float c, float s) {
    return rbf(rbf(__fdividef(rbf(x - mean_b), sd_b)) * rbf(1.f + c)) + s;
}

__global__ void __cluster_dims__(2, 1, 1) __launch_bounds__(NTHREADS, 1)
fused_kernel(const __grid_constant__ First F, __nv_bfloat16* __restrict__ out, uint32_t* __restrict__ gs, const __grid_constant__ Maps M) {
    extern __shared__ __align__(1024) uint8_t sm[];
    const uint32_t sb = s2u(sm);
    const int tid = threadIdx.x, lane = tid & 31;
    const int j = blockIdx.x, rk = j & 1;
    const int g = lane >> 2, t = lane & 3;
    const int r8 = lane & 7, lb3 = (lane >> 3) & 1, lb4 = lane >> 4;
    uint64_t pol;
    asm("createpolicy.fractional.L2::evict_first.b64 %0, 1.0;" : "=l"(pol));
    {
        auto cpa = [&](uint32_t d, const uint8_t* s) {
            asm volatile("cp.async.cg.shared.global.L2::cache_hint.L2::128B [%0], [%1], 16, %2;" :: "r"(d), "l"(s), "l"(pol) : "memory");
        };
        const uint32_t ut = threadIdx.x, uj = blockIdx.x;
        const uint8_t* w = F.w[ut >= 128];
        if (ut < 128) {
            const uint32_t dq = (sb + ut * 16) ^ ((ut * 2) & 0x70);
            const uint8_t* sq = w + (uint32_t)(((uj & 1) * 256 + (ut >> 3)) * 8192 + (uj >> 1) * 128 + (ut & 7) * 16);
#pragma unroll
            for (int i = 0; i < 4 * NCP; i++) cpa(dq + 4 * 32768 + i * 2048, sq + i * 131072);
        } else if (ut < 384) {
            const uint32_t dm = (sb + ut * 16) ^ ((ut * 2) & 0x10);
            const uint8_t* sa = w + (uint32_t)(((uj >> 5) * 128 + (ut >> 1) - 64) * 6144 + (uj & 31) * 32 + (ut & 1) * 16);
            cpa(dm + SM_XA - 2048, sa); cpa(dm + SM_XA + 2048, sa + 1024);
        }
        else if (ut == 480 && uj < 64) asm volatile("prefetch.global.L2 [%0];" :: "l"(F.v[(uj >> 3) & 1] + (uj & 7) * 64));
    }
    const int warp = __shfl_sync(0xffffffffu, tid >> 5, 0);
    const __nv_bfloat16* const xin = F.v[0];
    uint32_t* const pl = gs + (warp < 2 ? (B_PR + (j >> 5)) * 4096 + (j & 31) * 32 : G_E1 + j * 8192) + (warp & 1) * 1024 + lane;
    if (warp < 4) st_x1(pl, 1u);
    auto BAR = [&](int i) -> uint32_t { return sb + SM_BAR + i * 8; };
    const uint32_t a16 = (r8 + 8 * lb4) * 32 + ((lb3 ^ (r8 >> 2)) * 16);
    const uint32_t a128 = (r8 + 8 * lb4) * 128 + ((((warp & 3) * 2 + lb3) ^ r8) * 16);
    auto ldcls = [&]() -> uint32_t { return *(const volatile uint32_t*)(sm + SM_CLS); };
    auto clear_head = [&]() {
        st2_x1(gs + (B_HA + ((j >> 4) & 1) * 2 + lb4) * 4096 + (j >> 5) * 256 + (j & 15) * 16 + (lane & 15), 0u);
        st2_x4(gs + (B_QA + rk * 8 + ((j >> 1) & 1) * 4 + (j >> 5)) * 4096 + g * 128 + ((j >> 2) & 7) * 16 + t * 4, 0u, 0u, 0u, 0u);
        if (lane < 8) st2_x1(gs + B_RD * 4096 + j * 8 + lane, 0u);
    };
    auto tma = [&](uint32_t dst, const CUtensorMap* mp, uint32_t bar, int c0, int c1, int c2, int c3) {
        asm volatile("{\n.reg .pred p;\nelect.sync _|p, 0xffffffff;\n"
                     "@p cp.async.bulk.tensor.4d.shared::cluster.global.mbarrier::complete_tx::bytes.L2::cache_hint [%0], [%1, {%3, %4, %5, %6}], [%2], %7;\n}"
                     :: "r"(dst), "l"(mp), "r"(bar), "r"(c0), "r"(c1), "r"(c2), "r"(c3), "l"(pol) : "memory");
    };
    if (warp <= 12 || warp == 15) {
        const int grp = warp == 12 ? 0 : warp == 15 ? 13 : warp + 1;
        const uint32_t cnt = grp < 10 ? 1 : grp < 13 ? 4 : 8;
        if (lane == 0) {
#pragma unroll
            for (int i = 0; i < 8; i++) mbar_init(BAR(grp * 8 + i), (i < 2 && grp == 0) ? (i ? 128 : 256) : cnt);
        }
        __syncwarp();
        if (grp < 10 && lane < 8 && (grp || lane > NCP)) mbar_expect(BAR(grp * 8 + lane), grp >= 8 ? 4096 : grp * 8 + lane < IT_X ? 8192 : 16384);
        asm volatile("fence.mbarrier_init.release.cluster;" ::: "memory");
        __syncwarp();
        if (warp == 12) {
#pragma unroll
            for (int i = NCP + 1; i < W0; i++) tma(sb + (15 + i) * 8192, &M.m[MP_WQ], BAR(i), 0, rk * 256 + (i - 1) * 64, j >> 1, 0);
        }
    } else if (warp == 13) {
        if (lane < NMAPS) asm volatile("prefetch.tensormap [%0];" :: "l"(&M.m[lane]) : "memory");
    } else if (warp == 14) {
        clear_head();
    }
    __syncthreads();
    uint32_t in1 = 0, in2 = 0;
    if (warp < 4) { in1 = *(const uint32_t*)(xin + 2 * tid); in2 = *(const uint32_t*)(xin + 256 + 2 * tid); }
    else if (warp < 12) in1 = *(const uint32_t*)(F.v[1] + 2 * (tid - 128));
    if (warp < 12) asm volatile("cp.async.mbarrier.arrive.noinc.shared::cta.b64 [%0];" :: "r"(BAR(warp < 4)) : "memory");
    asm volatile("barrier.cluster.arrive.relaxed.aligned;" ::: "memory");

    if (warp >= 12) {
    asm volatile("setmaxnreg.dec.sync.aligned.u32 64;");
    if (warp == 12) {
        static_assert(W0 > NCP && W0 <= 5 && NCP >= 1 && NCP <= 4, "W0");
        const uint2* sched = M.sched[j < NFF ? 0 : j < J_RED ? 1 : 2];
        uint2 en = sched[W0];
        const uint32_t t0 = gtime();
        const uint32_t sp = __reduce_or_sync(0xffffffffu, sb);
        const int cx = (j >> 1) * 64 + (j < NFF ? 0 : 1024 - NFF * 32);
#pragma unroll 1
        for (int i = W0; en.x; i++) {
            const uint32_t e = en.x, tn = t0 + (int16_t)en.y, mp = (en.y >> 16) & 15, st = (en.y >> 20) * 64;
            en = sched[i + 1];
            if (mp == MP_MODB && j >= J_END) break;
            uint32_t c0 = mp == MP_WO ? (j & 7) * 64 : mp > MP_WO ? cx : 0;
            uint32_t c1 = mp == MP_CKV ? 0 : mp == MP_DOWN ? j * 32 : st + (mp == MP_WUV ? (j & 3) * 32 : mp == MP_WO ? (j >> 3) * 256 : rk * 256);
            uint32_t c2 = mp < MP_CKV ? j >> 1 : mp == MP_CKV ? rk * 4 : mp == MP_WUV ? (j >> 2) * 2 : mp == MP_DOWN ? st >> 4 : 0;
            uint32_t c3 = mp == MP_CKV ? st * 2 + (j & ~1) : 0;
            uint32_t dst = sp + ((e << 7) & 0x3e000), bar = sp + SM_BAR + (e & 63) * 8;
            const uint32_t w0 = (e >> 8) & 0x3f8, w1 = (e >> 15) & 0x3f8, w2 = (e >> 22) & 0x3f8, bb = sp + SM_BAR - 8;
            const CUtensorMap* pm = &M.m[mp];
            pin(dst); pin(bar); pin(c0); pin(c1); pin(c2); pin(c3); pin(pm);
            if (w0) mbar_wait(bb + w0, 0);
            if (w2) {
                mbar_wait(bb + w2, 0);
                while (!__any_sync(0xffffffffu, mbar_test(bb + w1, 0) | ((int)(gtime() - tn) > 0))) {}
            } else if (w1) mbar_wait(bb + w1, 0);
            tma(dst, pm, bar, c0, c1, c2, c3);
        }
    } else if (warp == 13) {
#pragma unroll
        for (int i = 0; i < 2; i++) st_x4(gs + (B_ML + rk * 16 + i * 8 + g) * 4096 + (t >> 1) * 1024 + (j >> 1) * 8 + (t & 1) * 4, 0u, 0u, 0u, 0u);
        if (lane < 16) st2_x4(gs + (B_E2 + (j >> 4)) * 4096 + (j & 15) * 64 + lane * 4, 0u, 0u, 0u, 0u);
        st2_x1(gs + (B_E3 + (j >> 5)) * 4096 + (j & 31) * 32 + lane, 0u);
        if (lane < 8) st2_x1(gs + B_MB * 4096 + j * 8 + lane, 0u);
        if (j < NFF) {
#pragma unroll
            for (int i = 0; i < 2; i++) st2_x4(gs + (B_E5 + i * 8 + g) * 4096 + j * 16 + t * 4, 0u, 0u, 0u, 0u);
        }
        bar_sync(9, 64);
        const uint32_t cs = ldcls();
#pragma unroll 1
        for (int i = 0; i < 32; i++) {
            st_x4(gs + G_E1 + j * 8192 + (i >> 3) * 2048 + ((((cs >> 1) ^ (i >> 3)) & 1) << 10) + (i & 7) * 128 + lane * 4, 0u, 0u, 0u, 0u);
            __nanosleep(JAN_SLEEP);
        }
        fence_gpu();
        if (lane < 8) st2_x1(gs + B_RD * 4096 + j * 8 + lane, 1u + (cs >> 1));
        if (lane == 0) TRACE(41);
        uint32_t rd[4];
        mbar_wait(BAR(IT_CKV + RD_ITEM), 0);
        poll<1024, RD_SLEEP>(rd, gs + near_off(B_RD, cs) + lane * 8);
#pragma unroll
        for (int i = 0; i < 4; i++) {
            const uint32_t m = __ballot_sync(0xffffffffu, rd[i] == 2u);
            if (lane == 0) sts32(sb + SM_CLS + 16 + i * 4, m);
        }
        __syncwarp();
        if (lane < 8) mbar_arrive(BAR(JD));
        if (lane == 0) TRACE(42);
    } else if (warp == 14) {
        uint2 ml[2];
        mbar_waitb(BAR(JD), 0);
        const uint32_t cls = ldcls();
        mbar_waitb(BAR(PF0 + 2 * NUNITS - 1), 0);
        __nanosleep(ML_DELAY);
        const uint32_t* pl2 = gs + near_off(B_ML + (j >> 2), cls) + lane * 8;
        const uint32_t wa = sb + SM_W + lb4 * 64 + t * 16 + (g & 3) * 4;
        poll_start<1024>(ml, pl2);
        uint32_t w0 = 0, w1 = 0, redo = 0;
        bool first = true;
#pragma unroll 1
        for (uint32_t it = 0;; it++) {
            const bool p0 = minw(ml[0]) != 0, p1 = minw(ml[1]) != 0;
            const int n = __popc(__ballot_sync(0xffffffffu, p0)) + __popc(__ballot_sync(0xffffffffu, p1));
            const uint32_t x0 = ml[0].x, x1 = ml[1].x;
            if (n < 64) {
                if (!p0) ld_x(ml[0], pl2);
                if (!p1) ld_x(ml[1], pl2 + 256);
            }
            if (n == 64 || (first && n >= E1_EARLY)) {
                auto ord = [](int x) { return x ^ ((x >> 31) & 0x7fffffff); };
                const int o0 = ord(x0), o1 = ord(x1);
                const float mm = __int_as_float(ord(__reduce_max_sync(0xffffffffu, max(p0 ? o0 : INT_MIN, p1 ? o1 : INT_MIN))));
                const float lo = __int_as_float(ord(__reduce_min_sync(0xffffffffu, min(p0 ? o0 : INT_MAX, p1 ? o1 : INT_MAX))));
                const uint32_t v0 = pack2(ex2((p0 ? __uint_as_float(x0) : lo) - mm), 0.f), v1 = pack2(ex2((p1 ? __uint_as_float(x1) : lo) - mm), 0.f);
                redo = !first && __any_sync(0xffffffffu, v0 != w0 || v1 != w1);
                w0 = v0; w1 = v1;
                sts32(wa - redo * (SM_W - SM_W2), w0 * 0x10001u); sts32(wa - redo * (SM_W - SM_W2) + 128, w1 * 0x10001u);
                if (first) bar_arrive(3, 416);
                first = false;
                if (n == 64) break;
            }
            if (it > SPIN_LIMIT) __trap();
        }
        if (lane == 0) TRACE_Q(37);
        float L = bflo(w0) * __uint_as_float(ml[0].y) + bflo(w1) * __uint_as_float(ml[1].y);
#pragma unroll
        for (int o = 16; o; o >>= 1) L += shx(L, o);
        if (lane == 0) *(float2*)(sm + SM_FQ) = make_float2(__frcp_rn(L), __uint_as_float(redo));
        __syncwarp();
        if (lane < 8) mbar_arrive(BAR(WR));
        if (lane == 0) TRACE(10);
        bar_sync(4, 288);
        clear_head();
        if (j < NFF) {
            uint32_t ya = sb + SM_Y + lane * 16, sa = peer_addr(sb + SM_RED + 2048 + rk * 8, lane & 1), tb = peer_addr(BAR(MBB), lane & 1);
            pin(ya); pin(sa); pin(tb);
            bar_sync(7, 288);
            const float4 y0 = ldsf4(ya), y1 = ldsf4(ya + 512);
            float s = sum4(y0) + sum4(y1);
            float q = (fmaf(y0.x, y0.x, y0.y * y0.y) + fmaf(y0.z, y0.z, y0.w * y0.w)) + (fmaf(y1.x, y1.x, y1.y * y1.y) + fmaf(y1.z, y1.z, y1.w * y1.w));
#pragma unroll
            for (int o = 16; o; o >>= 1) { s += shx(s, o); q += shx(q, o); }
            if (lane < 2) st_async2(sa, s, q, tb);
        }
    } else if (warp == 15) {
        mbar_waitb(BAR(IT_X - 1), 0);
        if (j < J_END) mbar_waitb(BAR(j < NFF ? NITEMS - 1 : MBB), 0);
    }
    } else if (warp < 4) {
        float* scr = (float*)(sm + SM_SCR);
        uint32_t cls;
        {
            uint2 ha[8];
            {
                uint32_t best = 0xffffffffu;
#pragma unroll
                for (int i = 0; i < NPROBE; i++) {
                    uint32_t t0, t1, o;
                    asm volatile("mov.u32 %0, %%clock;" : "=r"(t0));
                    asm volatile("atom.relaxed.gpu.global.exch.b32 %0, [%1], %2;" : "=r"(o) : "l"(pl), "r"(2u + i) : "memory");
                    asm volatile("{\n.reg .pred p;\nsetp.ne.u32 p, %1, 0x1234567;\nmov.u32 %0, 0;\n@p mov.u32 %0, %%clock;\n}" : "=r"(t1) : "r"(o));
                    best = min(best, t1 - t0);
                }
                if (lane == 0) scr[16 + warp] = __uint_as_float(best);
            }
            const float sh = __shfl_sync(0xffffffffu, bflo(in1), 0);
            const float v0 = bflo(in1) - sh, v1 = bfhi(in1) - sh, v2 = bflo(in2) - sh, v3 = bfhi(in2) - sh;
            float mb, sd;
            ln_stats<4>((v0 + v1) + (v2 + v3), (v0 * v0 + v1 * v1) + (v2 * v2 + v3 * v3), sh, scr, warp, lane, 2, mb, sd);
            if (!rk) in2 = in1;
            const uint4 lt = *(const uint4*)(scr + 16);
            cls = NUMA ? ((lt.y < lt.x) ^ (__popc((B_PR + (j >> 5)) & 0x2C) & 1)) | (lt.w < lt.z) << 1 : 0;
            if (warp == 0) { if (lane == 0) sts32(sb + SM_CLS, cls); bar_arrive(9, 64); }
            if (tid == 0) TRACE(38);
            asm volatile("barrier.cluster.wait.aligned;" ::: "memory");
            mbar_wait(BAR(IT_MODA), 0);
            __nanosleep(HA_DELAY);
            poll<1024, H_SLEEP, false, 16384>(ha, gs + near_off(B_HA + rk * 2, cls) + 2 * tid);
            auto rsum = [](uint32_t a, uint32_t b, uint32_t c, uint32_t d) { return rbf((__uint_as_float(a) + __uint_as_float(b)) + (__uint_as_float(c) + __uint_as_float(d))); };
            sts32(sb + SM_FV + frag_off(2 * tid),
                  pack2(ln_mod(bflo(in2), mb, sd, rsum(ha[4].x, ha[5].x, ha[6].x, ha[7].x), rsum(ha[0].x, ha[1].x, ha[2].x, ha[3].x)),
                        ln_mod(bfhi(in2), mb, sd, rsum(ha[4].y, ha[5].y, ha[6].y, ha[7].y), rsum(ha[0].y, ha[1].y, ha[2].y, ha[3].y))));
            bar_arrive(5, 384);
            mbar_wait(BAR(QB), 0);
            if (tid < 64) {
                const float* qx = (const float*)(sm + SM_QX) + tid;
                sts16(sb + SM_FQ + frag_off(tid), pack2((qx[0] + qx[64]) + (qx[128] + qx[192]), 0.f));
            }
            bar_arrive(6, 384);
        }
        asm volatile("setmaxnreg.inc.sync.aligned.u32 192;");
        float acc[128];
        float M = 0.f;
        uint32_t pa = sb + SM_XA + warp * 512 + lane * 16, ma = sb + SM_MX + (warp * 8 + g) * 4, pf = BAR(PF0);
        uint32_t blo = __reduce_or_sync(0xffffffffu, (((sb + SM_U) & 0x3FFFFu) >> 4) | 0x400000u);
        uint32_t* e1[4];
#pragma unroll
        for (int i = 0; i < 4; i++) e1[i] = gs + G_E1 + (warp * 8 + g) * 4 * 8192 + (rk * 2 + (j >> 6)) * 2048 + ((j >> 1) & 31) * 32 + t * 4;
#pragma unroll 1
        for (int h = 0; h < 2 * NUNITS; h++) {
            mbar_wait(pf, 0);
            const float m = __uint_as_float(lds32(ma));
            const uint4 pn = lds128(pa);
            wg_wait0();
#pragma unroll
            for (int i = 0; i < 128; i++) asm volatile("" : "+f"(acc[i]) :: "memory");
            if (h == 0) M = m;
            uint32_t b2 = 0x3f803f80u;
            if (__builtin_expect(__any_sync(0xffffffffu, m != M), 0)) {
                const float Mn = fmaxf(M, m), alpha = ex2(M - Mn), beta = ex2(m - Mn);
                M = Mn;
                b2 = pack2(beta, beta);
#pragma unroll
                for (int jj = 0; jj < 32; jj++) { acc[4 * jj] *= alpha; acc[4 * jj + 1] *= alpha; }
            }
            auto mul2 = [](uint32_t x, uint32_t y) { uint32_t r; asm("mul.rn.bf16x2 %0, %1, %2;" : "=r"(r) : "r"(x), "r"(y)); return r; };
            const uint4 p = make_uint4(mul2(pn.x, b2), mul2(pn.y, b2), mul2(pn.z, b2), mul2(pn.w, b2));
            if (tid == 0 && (h & 1)) TRACE_Q(48 + (h >> 1));
            wgmma_pv(acc, p, blo, h);
            if (lane == 0 && h > 0 && !(h & 1)) mbar_arrive(BAR(EB_UNIT0 + (h >> 1) - 1));
            blo += h == 11 ? -11 * 1024 : 1024;
            pa += (h == 5 || h == 11) ? -5 * 2048 : 2048;
            ma += 128; pf += 8;
            if (h == 2 * NUNITS - 3) {
                mbar_wait(BAR(JD), 0);
                const uint32_t hm = (*(const uint32_t*)(sm + SM_CLS + 16 + warp * 4) >> (g * 4)) ^ ((j >> 6) ? 15u : 0u);
#pragma unroll
                for (int i = 0; i < 4; i++) e1[i] += ((hm >> i) & 1) << 10;
            }
        }
#pragma unroll
        for (int vv = 0; vv < 2; vv++) {
            if (vv && M == 1.f) __trap();
            if (vv) wg_wait0(); else wg_wait1();
#pragma unroll
            for (int i = 0; i < 64; i++) asm volatile("" : "+f"(acc[vv * 64 + i]) :: "memory");
            if (tid == 0 && !vv) TRACE_Q(63);
#pragma unroll
            for (int i = 0; i < 4; i++) {
                const float* a = &acc[vv * 64 + i * 16];
                st_x4(e1[i] + i * 8192 + vv * 16, enc(pack2(a[0], a[1])), enc(pack2(a[4], a[5])), enc(pack2(a[8], a[9])), enc(pack2(a[12], a[13])));
            }
        }
        bar_arrive(3, 416);
        if (tid == 0) TRACE_Q(17);
        if (j < NFF) {
            uint4 a[16];
            const uint32_t ad = sb + SM_U + B_DN * 32768 + warp * 8192 + (r8 + 8 * lb4) * 128 + (lb3 ^ r8) * 16;
            uint32_t rl = sb + SM_RED + lane * 16;
            uint32_t* p5 = gs + (B_E5 + warp * 4 + (t >> 1)) * 4096 + j * 16 + (t & 1) * 8 + g;
            pin(rl); pin(p5);
            if (lane == 0) mbar_expect(BAR(MBB), 4);
            auto ldd = [&]() {
#pragma unroll
                for (int s = 0; s < 16; s++) a[s] = ldsm<true>((ad ^ ((s & 3) * 32)) + (s >> 2) * 2048);
            };
            const uint32_t db = BAR(IT_DOWN + (warp >> 1));
            mbar_wait(BAR(MBB), 0);
            const float4 st = ldsf4(sb + SM_RED + 2048);
            const bool hd = __all_sync(0xffffffffu, mbar_test(db, 0));
            if (hd) ldd();
            const float mu = (st.x + st.z) * (1.f / 512.f);
            float rstd;
            asm volatile("rsqrt.approx.ftz.f32 %0, %1;" : "=f"(rstd) : "f"(fmaxf(fmaf(-mu, mu, (st.y + st.w) * (1.f / 512.f)), 0.f) + 1e-5f));
            mbar_wait(BAR(QB), 1);
            if (tid == 0) TRACE(25);
            const float4 f0 = ldsf4(rl), f2 = ldsf4(rl + 1024), f1 = ldsf4(rl + 512), f3 = ldsf4(rl + 1536);
            const float gg = fmaf(rstd, fmaf(-mu, f0.z + f2.z, (f0.x + f0.y) + (f2.x + f2.y)), f0.w + f2.w);
            const float uu = fmaf(rstd, fmaf(-mu, f1.z + f3.z, (f1.x + f1.y) + (f3.x + f3.y)), f1.w + f3.w);
            const float hh = __fdividef(gg * uu, 1.f + ex2(-gg * fmaf(gg * gg, 0.10294324f, 2.3022082f)));
            uint32_t hb[4];
#pragma unroll
            for (int i = 0; i < 4; i++) hb[i] = pack2(__shfl_sync(0xffffffffu, hh, 2 * t + 8 * i), __shfl_sync(0xffffffffu, hh, 2 * t + 8 * i + 1));
            if (!hd) { mbar_wait(db, 0); ldd(); }
#pragma unroll
            for (int i = 0; i < 2; i++) {
                uint32_t res = 0;
#pragma unroll
                for (int k = 0; k < 4; k++) {
                    float c[4] = {0.f, 0.f, 0.f, 0.f};
                    const uint4 &x = a[i * 8 + k], &y = a[i * 8 + k + 4];
                    mma(c, x.x, x.y, x.z, x.w, hb[0], hb[1]);
                    mma(c, y.x, y.y, y.z, y.w, hb[2], hb[3]);
                    if (t == k) res = pack2(c[0], c[2]);
                }
                st2_x1(p5 + i * 8192, enc(res));
            }
            if (tid == 0) { TRACE(27); TRACE_GT(47); }
        } else if (j < J_END) {
            uint4 a[8], b[4];
            float c[4], e[4];
            const bool own = (warp >> 1) == rk;
            const uint32_t xa = sb + SM_FV + (warp & 1) * 64 + g * 8;
            if (lane == 0) mbar_expect(BAR(MBB), own ? 64 : 0);
#pragma unroll
            for (int i = 0; i < 2; i++) {
                ldfrag(b, sb + SM_FS + rk * 512 + i * 256 + t * 16);
                mbar_wait(BAR(IT_X + i), 0);
                const uint32_t ab = sb + SM_U + B_X * 32768 + i * 16384 + a128;
                load8<true>(a, [&](int s) { return ab + s * 2048; });
                mma8(i ? e : c, a, b);
            }
            c[0] += e[0]; c[2] += e[2];
            if (!own) {
                if (t == 0) st_async2(peer_addr(xa, rk ^ 1), c[0], c[2], peer_addr(BAR(MBB), rk ^ 1));
            } else {
                mbar_wait(BAR(MBB), 0);
                const float2 pp = *(const float2*)(sm + (xa - sb));
                const float mine = t ? c[2] + pp.y : c[0] + pp.x, other = shx(mine, 4);
                const uint32_t w = (warp & 1) * 8 + t * 4 + (g >> 1), val = enc(pack2(mine, other));
                if (t < 2 && !(g & 1)) {
                    if (j < J_RED) st2_x1(gs + B_MB * 4096 + (j - NFF) * 16 + w, val);
                    else sts32(sb + SM_FV + 256 + w * 4, val);
                }
                __syncwarp();
                if (j >= J_RED && lane < 4) mbar_arrive(BAR(QB));
                if (lane == 0) TRACE(11);
            }
        }
    } else {
        const int u8 = tid - 128, w8 = warp - 4;
        const int v = w8 >> 2, wq4 = w8 & 3;
        {
            const float c0 = bflo(in1), c1 = bfhi(in1);
            sts32(sb + SM_FS + frag_off(2 * u8), pack2(__fdividef(c0, 1.f + __expf(-c0)), __fdividef(c1, 1.f + __expf(-c1))));
        }
        bar_sync(1, 256);
        asm volatile("barrier.cluster.wait.aligned;" ::: "memory");
        uint4 a[8], b[4]; float c[4];
        if (w8 < 2) {
            ldfrag(b, sb + SM_FS + (j >> 5) * 256 + t * 16);
            mbar_wait(BAR(IT_MODA), 0);
            if (u8 == 0) TRACE(12);
            const uint32_t ab = sb + SM_XA + w8 * 4096 + a16;
            load8<true>(a, [&](int s) { return ab + s * 512; });
            mma8(c, a, b);
            if (t < 2) st2_x1(gs + (B_HA + ((j >> 4) & 1) * 2 + w8) * 4096 + (j >> 5) * 256 + (j & 15) * 16 + t * 8 + g, encf(t ? c[2] : c[0]));
        }
        {
            mbar_wait(BAR(IT_WQ + 2 * v <= NCP ? 1 : IT_WQ + 2 * v), 0); mbar_wait(BAR(IT_WQ + 2 * v + 1 <= NCP ? 1 : IT_WQ + 2 * v + 1), 0);
            const uint32_t ab = sb + SM_U + 4 * 32768 + v * 16384 + a128;
            load8<true>(a, [&](int s) { return ab + s * 2048; });
            if (lane == 0) mbar_arrive(BAR(EB_WQ));
            bar_sync(5, 384);
            if (u8 == 0) TRACE(13);
            ldfrag(b, sb + SM_FV + v * 256 + t * 16);
            mma8(c, a, b);
            if (t < 2) {
                const float qv = t ? c[2] : c[0];
                const uint32_t qa_ = sb + SM_QX + ((rk * 2 + v) * 64 + wq4 * 16 + t * 8 + g) * 4;
                asm volatile("st.async.weak.shared::cluster.mbarrier::complete_tx::bytes.f32 [%0], %1, [%2];"
                             :: "r"(peer_addr(qa_, rk ^ 1)), "f"(qv), "r"(peer_addr(BAR(QB), rk ^ 1)) : "memory");
                sts32(qa_, __float_as_uint(qv));
            }
            __syncwarp();
            if (lane == 0) mbar_expect(BAR(QB), 64);
        }
        {
            mbar_wait(BAR(IT_WUK + v), 0); mbar_wait(BAR(IT_WUK + v + 2), 0);
            const uint32_t ab = sb + SM_U + 5 * 32768 + (w8 * 16 + r8 + 8 * lb3) * 128;
            const uint32_t x16 = (lb4 ^ r8) * 16;
            load8<false>(a, [&](int s) { return ab + (s & 1) * 16384 + (x16 ^ ((s >> 1) * 32)); });
            bar_sync(6, 384);
            if (u8 == 0) TRACE(14);
            b[0] = lds128(sb + SM_FQ + t * 16); b[1] = lds128(sb + SM_FQ + 64 + t * 16);
            float e[4] = {0.f, 0.f, 0.f, 0.f};
            c[0] = c[1] = c[2] = c[3] = 0.f;
#pragma unroll
            for (int k = 0; k < 4; k++) {
                const uint32_t b0 = (k & 1) ? b[k >> 1].z : b[k >> 1].x, b1 = (k & 1) ? b[k >> 1].w : b[k >> 1].y;
                mma(c, a[2 * k].x, a[2 * k].y, a[2 * k].z, a[2 * k].w, b0, b1);
                mma(e, a[2 * k + 1].x, a[2 * k + 1].y, a[2 * k + 1].z, a[2 * k + 1].w, b0, b1);
            }
            const float mine = ((t & 1) ? ((t & 2) ? e[2] : e[0]) : ((t & 2) ? c[2] : c[0])) * 0.12751743f;
            const float other = shx(mine, 4);
            if (!(g & 1)) st2_x1(gs + (B_QA + rk * 8 + ((j >> 1) & 1) * 4 + (j >> 5)) * 4096 + w8 * 128 + ((j >> 2) & 7) * 16 + (g >> 1) * 4 + t, enc(pack2(mine, other)));
            if (u8 == 0) TRACE(15);
        }
        const uint32_t cls = ldcls();
        __nanosleep(QA_DELAY);
        {
            uint4 qb[8];
            const uint32_t* pq = gs + near_off(B_QA + rk * 8 + wq4, cls) + lane * 4;
            const uint32_t* pq2 = gs + near_off(B_QA + rk * 8 + 4 + wq4, cls) + lane * 4;
            if (lane == 0) {
                mbar_expect(BAR(QT), 4096);
                asm volatile("cp.async.bulk.shared::cluster.global.mbarrier::complete_tx::bytes [%0], [%1], 4096, [%2];"
                             :: "r"(sb + SM_U + 5 * 32768 + w8 * 4096), "l"(gs + near_off(B_QA + rk * 8 + w8, cls)), "r"(BAR(QT)) : "memory");
            }
            const uint32_t qs = sb + SM_U + 5 * 32768 + wq4 * 4096 + lane * 16;
            mbar_wait(BAR(QT), 0);
#pragma unroll
            for (int i = 0; i < 8; i++) { a[i] = lds128(qs + i * 512); qb[i] = lds128(qs + 16384 + i * 512); }
            poll<512, QA_SLEEP, true>(a, pq);
            poll<512, QA_SLEEP, true>(qb, pq2);
            if (lane == 0) mbar_arrive(BAR(EB_WUK));
            auto add2 = [](uint32_t x, uint32_t y) { uint32_t r; asm("add.rn.bf16x2 %0, %1, %2;" : "=r"(r) : "r"(x), "r"(y)); return r; };
#pragma unroll
            for (int i = 0; i < 8; i++) a[i] = make_uint4(add2(a[i].x, qb[i].x), add2(a[i].y, qb[i].y), add2(a[i].z, qb[i].z), add2(a[i].w, qb[i].w));
        }
        if (u8 == 0) TRACE(8);
        {
            float m = -INFINITY, l = 0.f;
            uint32_t xl = sb + SM_XB + w8 * 2048 + lane * 16, xr = peer_addr(xl, rk ^ 1), bsr = peer_addr(BAR(SF0 + v), rk ^ 1);
            uint32_t pa = sb + SM_XA + v * 2048 + wq4 * 512 + lane * 16, ma = sb + SM_MX + v * 128 + (wq4 * 8 + g) * 4;
            uint32_t fb = BAR(IT_CKV + v * 2), sf = BAR(SF0 + v);
            uint32_t dlo = __reduce_or_sync(0xffffffffu, (((sb + SM_U + v * 16384) & 0x3FFFFu) >> 4) | 0x10000u);
            if (STAG && v) __nanosleep(STAG);
#pragma unroll 1
            for (int n = 0; n < NUNITS; n++) {
                float d[2][16], sc[8];
#pragma unroll
                for (int i = 0; i < 2; i++) {
                    mbar_wait(fb + i * 8, 0);
                    wg_fence();
#pragma unroll
                    for (int s = 0; s < 8; s++) wgmma_rs_n32(d[i], a[s], (0x40000080ull << 32) | (dlo + i * 512 + (s >> 2) * 64 + (s & 3) * 2), s);
                    wg_commit();
                }
#pragma unroll
                for (int i = 0; i < 2; i++) {
                    if (i) wg_wait0(); else wg_wait1();
#pragma unroll
                    for (int k = 0; k < 16; k++) asm volatile("" : "+f"(d[i][k]) :: "memory");
                    sc[4 * i] = d[i][0] + d[i][6]; sc[4 * i + 1] = d[i][1] + d[i][7]; sc[4 * i + 2] = d[i][8] + d[i][14]; sc[4 * i + 3] = d[i][9] + d[i][15];
                    asm volatile("st.async.weak.shared::cluster.mbarrier::complete_tx::bytes.v4.f32 [%0], {%1, %2, %3, %4}, [%5];"
                                 :: "r"(xr + i * 1024), "f"(sc[4 * i]), "f"(sc[4 * i + 1]), "f"(sc[4 * i + 2]), "f"(sc[4 * i + 3]), "r"(bsr) : "memory");
                }
                if (u8 == 128) TRACE_Q(56 + (n < 6 ? n : -40));
                if (n >= 3) mbar_wait(BAR(EB_UNIT0 + n - 3), 0);
                dlo += n == 5 ? -5 * 2048 : 2048;
                fb += 32; xr ^= 512; bsr += 16;
                pin(fb); pin(xr); pin(bsr);
                mbar_wait(sf, 0);
                const float4 x = ldsf4(xl), y = ldsf4(xl + 1024);
                sc[0] += x.x; sc[1] += x.y; sc[2] += x.z; sc[3] += x.w; sc[4] += y.x; sc[5] += y.y; sc[6] += y.z; sc[7] += y.w;
                float pr[8];
#pragma unroll
                for (int i = 0; i < 8; i++) pr[i] = ex2(sc[i] - m);
                float mx = fmaxf(fmaxf(fmaxf(sc[0], sc[1]), fmaxf(sc[2], sc[3])), fmaxf(fmaxf(sc[4], sc[5]), fmaxf(sc[6], sc[7])));
                if (__builtin_expect(__any_sync(0xffffffffu, mx > m), 0)) {
                    mx = fmaxf(mx, shx(mx, 1));
                    mx = fmaxf(mx, shx(mx, 2));
                    const float mn = fmaxf(m, ceilf(mx * 0.0625f) * 16.f);
                    l *= ex2(m - mn);
                    m = mn;
#pragma unroll
                    for (int i = 0; i < 8; i++) pr[i] = ex2(sc[i] - m);
                }
                stsf(ma, m);
                asm volatile("st.shared.v4.u32 [%0], {%1, %2, %3, %4};" :: "r"(pa), "r"(pack2(pr[0], pr[1])), "r"(pack2(pr[2], pr[3])),
                             "r"(pack2(pr[4], pr[5])), "r"(pack2(pr[6], pr[7])) : "memory");
                __syncwarp();
                if (lane == 0) mbar_arrive(sf + (PF0 - SF0) * 8);
                l += ((pr[0] + pr[1]) + (pr[2] + pr[3])) + ((pr[4] + pr[5]) + (pr[6] + pr[7]));
                xl ^= 512; sf += 16; ma += 256; pa += (n == 2 || n == 5) ? -8192 : 4096;
            }
            l += shx(l, 1);
            l += shx(l, 2);
            float2* mlx = (float2*)(sm + SM_MX + 2048) + wq4 * 8 + g;
            if (v == 0) { *mlx = make_float2(m, l); bar_arrive(11, 256); }
            else {
                mbar_wait(BAR(JD), 0);
                bar_sync(11, 256);
                const float2 o = *mlx;
                const float mn = fmaxf(m, o.x);
                l = l * ex2(m - mn) + o.y * ex2(o.x - mn);
                if ((wq4 >> 1) == rk) st_x4(gs + (B_ML + wq4 * 8 + g) * 4096 + (t >> 1) * 1024 + (j >> 1) * 8 + (t & 1) * 4, encf(mn), encf(l), 1u, 1u);
            }
        }
        const int pi = j < NFF ? rk * 128 + w8 * 16 + (lane & 15) : ((j - J_RED) & 15) * 16 + v * 8 + lb4 * 4 + wq4;
        const uint32_t xw = *(const uint32_t*)(xin + 2 * pi);
        const uint32_t* pm = gs + near_off(B_MB, cls) + pi;
        const uint32_t* pb = gs + near_off(B_E2 + (j >> 4), cls) + (((j >> 3) & 1) * 2 + lb4) * 256 + (lane & 15) * 2;
        pin(pm); pin(pb);
        {
            const uint32_t ab = sb + SM_U + B_WUV * 32768 + v * 4096 + a128;
            uint32_t pa = sb + SM_PB + wq4 * 320 + frag_off(64 * v + 32 * (g >> 2) + 16 * (t & 1) + 8 * (t >> 1) + 2 * (g & 3));
            uint32_t fa = sb + SM_PB + g * 320 + t * 16;
            const uint32_t* pe = gs + G_E1 + j * 8192 + (w8 >> 1) * 2048 + ((((cls >> 1) ^ (w8 >> 1)) & 1) << 10) + (((w8 & 1) * 16 + t) * 8 + g) * 4;
            uint32_t* p2 = gs + (B_E2 + (j >> 4)) * 4096 + (t >> 1) * 1024 + (j & 12) * 64 + w8 * 32 + (j & 3) * 8 + (g & 6) + (t & 1);
            pin(pa); pin(fa); pin(pe); pin(p2);
            const uint32_t mk = (g & 1) ? 0xffff0000u : 0x0000ffffu, m0 = (g & 2) ? 0u : mk, m1 = (g & 2) ? mk : 0u;
            uint4 pv[4];
            bool hv = false;
            bar_sync(3, 416);
            uint4 wa = lds128(sb + SM_W + (wq4 * 4 + t) * 16);
            uint32_t wb[8] = {wa.x & m0, wa.x & m1, wa.y & m0, wa.y & m1, wa.z & m0, wa.z & m1, wa.w & m0, wa.w & m1};
            pv[0] = pv[1] = pv[2] = pv[3] = make_uint4(0u, 0u, 0u, 0u);
            poll<512, E1_SLEEP, true>(pv, pe, [&]() {
                if (!hv) {
                    hv = __all_sync(0xffffffffu, mbar_test(BAR(IT_WUV + t), 0));
                    if (hv) load8<true>(a, [&](int s) { return ab + (s >> 1) * 8192 + (s & 1) * 2048; });
                }
            });
            if (lane == 0) TRACE_Q(48 + w8);
            if (u8 == 0) TRACE_Q(18);
            float lo, hi2;
            float2 inv;
#pragma unroll 1
            for (int pass = 0;; pass++) {
                float e[4][4];
#pragma unroll
                for (int i = 0; i < 4; i++) {
                    e[i][0] = e[i][1] = e[i][2] = e[i][3] = 0.f;
                    mma(e[i], pv[i].x, pv[i].y, pv[i].z, pv[i].w, wb[2 * i], wb[2 * i + 1]);
                }
                const float r0 = (t & 2) ? (e[0][2] + e[1][2]) + (e[2][2] + e[3][2]) : (e[0][0] + e[1][0]) + (e[2][0] + e[3][0]);
                const float r1 = (t & 2) ? (e[0][3] + e[1][3]) + (e[2][3] + e[3][3]) : (e[0][1] + e[1][1]) + (e[2][1] + e[3][1]);
                const uint32_t hi = pack2(r0, r1);
                sts32(pa, hi); sts32(pa + 1280, pack2(r0 - bflo(hi), r1 - bfhi(hi)));
                if (!hv) {
#pragma unroll 1
                    for (int i = 0; i < 4; i++) mbar_wait(BAR(IT_WUV + i), 0);
                    load8<true>(a, [&](int s) { return ab + (s >> 1) * 8192 + (s & 1) * 2048; });
                    hv = true;
                }
                bar_sync(1, 256);
                if (u8 == 0) TRACE(19);
                ldfrag(b, fa);
                mma8(c, a, b);
                mbar_wait(BAR(WR), 0);
                asm volatile("ld.shared.v2.f32 {%0, %1}, [%2];" : "=f"(inv.x), "=f"(inv.y) : "r"(sb + SM_FQ) : "memory");
                quad_pair(c[0] + c[1], c[2] + c[3], t, lo, hi2);
                if (__builtin_expect(__all_sync(0xffffffffu, pass || __float_as_uint(inv.y) == 0), 1)) break;
                wa = lds128(sb + SM_W2 + (wq4 * 4 + t) * 16);
                wb[0] = wa.x & m0; wb[1] = wa.x & m1; wb[2] = wa.y & m0; wb[3] = wa.y & m1; wb[4] = wa.z & m0; wb[5] = wa.z & m1; wb[6] = wa.w & m0; wb[7] = wa.w & m1;
                bar_sync(1, 256);
            }
            if (!(g & 1)) st_x1(p2, enc(pack2(lo * inv.x, hi2 * inv.x)));
            bar_arrive(4, 288);
            if (u8 == 0) TRACE(20);
        }
        uint32_t mb[3] = {0u, 0u, 0u};
        if (j < NFF) poll_start<1024>(mb, pm);
        uint4 a2[8];
        if (v == 0) {
            const uint32_t ab = sb + SM_U + B_WO * 32768 + a128;
            uint32_t* p3 = gs + (B_E3 + ((j >> 1) & 3)) * 4096 + (t >> 1) * 1024 + (rk * 2 + (wq4 >> 1)) * 256 + (j >> 3) * 16 + (wq4 & 1) * 8 + (t & 1) * 4 + (g >> 1);
            pin(p3);
            uint2 bb[8];
#pragma unroll
            for (int i = 0; i < 8; i++) bb[i] = make_uint2(0u, 0u);
            bool ho = false;
            auto ldo = [&]() { load8<true>(a, [&](int s) { return ab + s * 2048; }); load8<true>(a2, [&](int s) { return ab + 16384 + s * 2048; }); };
            auto idle = [&]() {
                if (!ho) {
                    ho = __all_sync(0xffffffffu, mbar_test(BAR(IT_WO + t), 0));
                    if (ho) ldo();
                }
            };
            poll<128, 0, true>(bb, pb, idle);
            if (!ho) {
#pragma unroll 1
                for (int i = 0; i < 4; i++) mbar_wait(BAR(IT_WO + i), 0);
                ldo();
            }
            if (u8 == 0) TRACE(21);
            float e[4][4];
#pragma unroll
            for (int s = 0; s < 16; s++) {
                const uint4& x = (s & 2) ? a2[(s >> 2) * 2 + (s & 1)] : a[(s >> 2) * 2 + (s & 1)];
                const uint2& y = bb[(s >> 2) * 2 + (s & 1)];
                if (s < 4) e[s][0] = e[s][1] = e[s][2] = e[s][3] = 0.f;
                mma(e[s & 3], x.x, x.y, x.z, x.w, y.x, y.y);
            }
            float lo, hi;
            quad_pair((t & 2) ? (e[2][0] + e[3][0]) + (e[2][1] + e[3][1]) : (e[0][0] + e[1][0]) + (e[0][1] + e[1][1]),
                      (t & 2) ? (e[2][2] + e[3][2]) + (e[2][3] + e[3][3]) : (e[0][2] + e[1][2]) + (e[0][3] + e[1][3]), t, lo, hi);
            if (!(g & 1)) st_x1(p3, enc(pack2(lo, hi)));
            bar_arrive(1, 256);
            if (u8 == 0) TRACE(22);
        } else bar_sync(1, 256);
        if (j < NFF) {
            const uint32_t* p3 = gs + near_off(B_E3 + rk * 2 + v, cls) + wq4 * 256 + lane;
            uint32_t za = sb + SM_FZ + lb4 * 576 + frag_off(w8 * 32 + (lane & 15) * 2);
            uint32_t fa = sb + SM_FZ + (g & 3) * 576 + lb4 * 256 + t * 16, ya = sb + SM_Y + u8 * 4;
            poll<1024, MB_SLEEP, true>(mb, pm);
            const uint32_t kk = pack2(1.f + bflo(mb[2]), 1.f + bfhi(mb[2]));
            sts32(za + 2 * 576, lb4 ? mb[1] : kk);
            uint32_t e3[8] = {0u, 0u, 0u, 0u, 0u, 0u, 0u, 0u};
            uint32_t ra = peer_addr(sb + SM_RED + (rk * 2 + v) * 512 + ((wq4 & 1) * 16 + (t >> 1) * 8 + g) * 16 + (t & 1) * 8, wq4 >> 1), tbo = peer_addr(BAR(QB), wq4 >> 1);
            pin(za); pin(fa); pin(ya); pin(ra); pin(tbo);
            if (lane == 0) mbar_expect(BAR(QB), 256);
            const uint32_t gb = BAR(IT_X + v * 2), ab = sb + SM_U + (B_X + v) * 32768 + a128;
            bool early = false, early2 = false;
            auto ldw = [&]() {
                if (!early) {
                    early = __all_sync(0xffffffffu, mbar_test(gb, 0));
                    if (early) load8<true>(a, [&](int s) { return ab + s * 2048; });
                }
                if (!early2) {
                    early2 = __all_sync(0xffffffffu, mbar_test(gb + 8, 0));
                    if (early2) load8<true>(a2, [&](int s) { return ab + 16384 + s * 2048; });
                }
            };
            poll<128, 0, true>(e3, p3, ldw);
            if (u8 == 0) TRACE(23);
            const float s0 = sumlo(e3), s1 = sumhi(e3);
            const float y0 = fmaf(bflo(mb[0]), s0 + shx(s0, 16), bflo(xw)), y1 = fmaf(bfhi(mb[0]), s1 + shx(s1, 16), bfhi(xw));
            stsf(ya, lb4 ? y1 : y0);
            const float z0 = y0 * bflo(kk), z1 = y1 * bfhi(kk);
            const uint32_t zh = pack2(z0, z1);
            sts32(za, lb4 ? pack2(z0 - bflo(zh), z1 - bfhi(zh)) : zh);
            bar_sync(7, 288);
            if (u8 == 0) TRACE(24);
            ldfrag(b, fa);
            if (!early) { mbar_wait(gb, 0); load8<true>(a, [&](int s) { return ab + s * 2048; }); }
            {
                float e[4][4];
#pragma unroll
                for (int s = 0; s < 16; s++) {
                    if (s == 8 && !early2) { mbar_wait(gb + 8, 0); load8<true>(a2, [&](int q) { return ab + 16384 + q * 2048; }); }
                    const uint4& x = s < 8 ? a[s] : a2[s & 7];
                    const uint4& y = b[(s >> 1) & 3];
                    float (&d)[4] = e[(s >> 3) * 2 + (s & 1)];
                    if (!(s & 6)) d[0] = d[1] = d[2] = d[3] = 0.f;
                    mma(d, x.x, x.y, x.z, x.w, (s & 1) ? y.z : y.x, (s & 1) ? y.w : y.y);
                }
                const bool hi = t >> 1;
                const float k0 = hi ? e[2][2] + e[3][2] : e[0][0] + e[1][0], k1 = hi ? e[2][3] + e[3][3] : e[0][1] + e[1][1];
                const float o0 = hi ? e[2][0] + e[3][0] : e[0][2] + e[1][2], o1 = hi ? e[2][1] + e[3][1] : e[0][3] + e[1][3];
                st_async2(ra, k0 + shx(o0, 2), k1 + shx(o1, 2), tbo);
            }
        } else if (j >= J_RED && j < J_END) {
            uint32_t ga[1], e3[1];
            poll<0, MB_SLEEP>(ga, pm);
            poll<0, 100>(e3, gs + near_off(B_E3 + (pi >> 6), cls) + (pi & 48) * 16 + (lane & 15) * 16 + (pi & 15));
            float y0 = bflo(e3[0]), y1 = bfhi(e3[0]);
#pragma unroll
            for (int o = 8; o; o >>= 1) { y0 += shx(y0, o); y1 += shx(y1, o); }
            y0 = fmaf(bflo(ga[0]), y0, bflo(xw)); y1 = fmaf(bfhi(ga[0]), y1, bfhi(xw));
            uint32_t gb = 0;
            auto ldg = [&]() { if (__all_sync(0xffffffffu, mbar_test(BAR(QB), 1))) gb = lds32(sb + SM_FV + 256 + (pi & 15) * 4); };
            uint32_t* po = (uint32_t*)out + pi;
            pin(po);
            const uint32_t nz = lane < NFF / 2 ? 0u : 0x80008000u;
            uint2 yv[2] = {make_uint2(nz, nz), make_uint2(nz, nz)};
            poll<NFF * 32, 0, true>(yv, gs + near_off(B_E5 + j - J_RED, cls) + lane * 16 + w8 * 2, ldg);
            if (u8 == 0) TRACE(26);
            const float l0 = bflo(yv[0].x) + bflo(yv[1].x), h0 = bfhi(yv[0].x) + bfhi(yv[1].x);
            const float l1 = bflo(yv[0].y) + bflo(yv[1].y), h1 = bfhi(yv[0].y) + bfhi(yv[1].y);
            float s0 = (lb4 ? h0 : l0) + shx(lb4 ? l0 : h0, 16), s1 = (lb4 ? h1 : l1) + shx(lb4 ? l1 : h1, 16);
#pragma unroll
            for (int o = 8; o; o >>= 1) { s0 += shx(s0, o); s1 += shx(s1, o); }
            if (__any_sync(0xffffffffu, !gb)) { mbar_wait(BAR(QB), 1); ldg(); }
            if (!(lane & 15)) *po = pack2(fmaf(bflo(gb), s0, y0), fmaf(bfhi(gb), s1, y1));
            if (u8 == 0) TRACE(27);
        }
    }
}

typedef CUresult (*EncFn)(CUtensorMap*, CUtensorMapDataType, cuuint32_t, void*, const cuuint64_t*, const cuuint64_t*,
                          const cuuint32_t*, const cuuint32_t*, CUtensorMapInterleave, CUtensorMapSwizzle,
                          CUtensorMapL2promotion, CUtensorMapFloatOOBfill);

void make_map(EncFn enc_fn, CUtensorMap* m, const void* p, cuuint64_t d0, cuuint64_t d1, cuuint64_t d2, cuuint64_t d3,
              cuuint64_t s1, cuuint64_t s2, cuuint64_t s3, cuuint32_t b0, cuuint32_t b1, cuuint32_t b2, cuuint32_t b3, CUtensorMapSwizzle sw) {
    const cuuint64_t dims[4] = {d0, d1, d2, d3}, strides[3] = {s1, s2, s3};
    const cuuint32_t box[4] = {b0, b1, b2, b3}, es[4] = {1, 1, 1, 1};
    enc_fn(m, CU_TENSOR_MAP_DATA_TYPE_BFLOAT16, 4, (void*)p, dims, strides, box, es,
           CU_TENSOR_MAP_INTERLEAVE_NONE, sw, CU_TENSOR_MAP_L2_PROMOTION_L2_64B, CU_TENSOR_MAP_FLOAT_OOB_FILL_NONE);
}

uint32_t* scratch = nullptr;

struct Tune { const char* win; const char* late; int tau, t_off; const char* tail[3][4]; };
Tune tune = {"66666666655555555555555555555522222222222",
             "00000000000000000888888888888888888888888", 320, -240,
             {{"VVVVOOOOguguDD", "zzzzzzzzzzzzzz", "77779999999966", "addd7dddd888na"},
              {"VMVMVVOOOO", "zzzzzzzzzz", "8888889999", "2999998bbb"},
              {"VVVVOOOOMM", "zzzzzzzzzz", "9999999988", "aeee1fffki"}}};
bool ready = false;

}

extern "C" void kernel_launch(void* const* d_in, const int* in_sizes, int n_in, void* d_out, int out_size) {
    (void)in_sizes; (void)n_in; (void)out_size;
    static Maps maps;
    static const void* cached[12] = {};
    bool same = ready;
    for (int i = 0; i < 12 && same; i++) same = cached[i] == d_in[i];
    if (!same) {
        void* fn = nullptr;
        cudaDriverEntryPointQueryResult qr;
        cudaGetDriverEntryPoint("cuTensorMapEncodeTiled", &fn, cudaEnableDefault, &qr);
        EncFn e = (EncFn)fn;
        const CUtensorMapSwizzle S128 = CU_TENSOR_MAP_SWIZZLE_128B;
        make_map(e, &maps.m[MP_WQ], d_in[2], 64, 512, 64, 1, 8192, 128, 8192, 64, 64, 1, 1, S128);
        make_map(e, &maps.m[MP_WUK], d_in[3], 64, 512, 64, 1, 8192, 128, 8192, 64, 64, 1, 1, S128);
        make_map(e, &maps.m[MP_CKV], d_in[1], 64, 8, 8, 4096, 1024, 128, 8192, 64, 8, 4, 2, S128);
        make_map(e, &maps.m[MP_MODB], d_in[11], 3072, 512, 1, 1, 6144, 6144, 6144, 64, 128, 1, 1, S128);
        make_map(e, &maps.m[MP_WUV], d_in[4], 64, 512, 64, 1, 8192, 128, 8192, 64, 32, 2, 1, S128);
        make_map(e, &maps.m[MP_WO], d_in[5], 512, 4096, 1, 1, 1024, 1024, 1024, 64, 64, 1, 1, S128);
        make_map(e, &maps.m[MP_GATE], d_in[7], 1792, 512, 1, 1, 3584, 3584, 3584, 64, 128, 1, 1, S128);
        make_map(e, &maps.m[MP_UP], d_in[8], 1792, 512, 1, 1, 3584, 3584, 3584, 64, 128, 1, 1, S128);
        make_map(e, &maps.m[MP_DOWN], d_in[9], 64, 1792, 8, 1, 1024, 128, 1024, 64, 32, 4, 1, S128);
        for (int r = 0; r < 3; r++) {
            int ids[56], cnt[128] = {}, tn = tune.t_off - (W0 - 1) * tune.tau;
            uint2* sc = maps.sched[r];
            auto dig = [](char ch) { return ch >= 'a' ? ch - 'a' + 10 : ch >= 'A' ? ch - 'A' + 36 : ch - '0'; };
            for (int i = 0; i < 56; i++) sc[i] = make_uint2(0u, 0u);
            for (int i = 0;; i++) {
                int id = i, buf, dep, w, wl;
                if (i < IT_WUV) {
                    const int u = (i - IT_CKV) >> 2;
                    buf = i < IT_CKV ? 4 + ((i - 1) >> 2) : u % 6;
                    dep = i < IT_CKV || u < 4 ? -1 : u < 6 ? EB_WQ + u - 4 : EB_UNIT0 + u - 6;
                    w = dig(tune.win[i]); wl = dig(tune.late[i]);
                    if (i) tn += tune.tau;
                } else {
                    const char ch = tune.tail[r][0][i - IT_WUV];
                    if (!ch) break;
                    buf = ch == 'V' ? B_WUV : ch == 'O' ? B_WO : ch == 'D' ? B_DN : ch == 'u' ? B_X + 1 : B_X;
                    id = (ch == 'V' ? IT_WUV : ch == 'O' ? IT_WO : ch == 'D' ? IT_DOWN : ch == 'u' ? IT_X + 2 : IT_X) + cnt[(int)ch]++;
                    dep = EB_UNIT0 + (buf < 2 ? buf + 6 : buf);
                    w = dig(tune.tail[r][1][i - IT_WUV]); wl = dig(tune.tail[r][2][i - IT_WUV]);
                    tn += 32 * dig(tune.tail[r][3][i - IT_WUV]);
                }
                if (id < IT_X ? (id - 1) & 3 : (id - IT_X) & 1) dep = -1;
                ids[i] = id;
                auto back = [&](int d) { return i < d ? 0 : (ids[i - d] && ids[i - d] <= NCP ? 1 : ids[i - d]) + 1; };
                sc[i].x = id | (buf * 4 + (id < IT_X ? (id - 1) & 3 : ((id - IT_X) & 1) * 2)) << 6 | (dep + 1) << 11 | (w > 32 ? NEVER + 1 : back(w)) << 18 | (wl ? back(wl) : 0) << 25;
                const int mp = id < IT_CKV ? MP_WQ + ((id - 1) >> 2) : id < IT_WUV ? MP_CKV : id < IT_WO ? MP_WUV : id < IT_X ? MP_WO
                             : id >= IT_DOWN ? MP_DOWN : r ? MP_MODB : MP_GATE + ((id - IT_X) >> 1);
                const int step = mp == MP_CKV ? id - IT_CKV : mp == MP_WUV ? (id - IT_WUV) * 2 : mp == MP_DOWN ? id - IT_DOWN : id < IT_X ? (id - 1) & 3 : ((id - IT_X) & 1) * 2;
                sc[i].y = (tn & 0xffff) | (mp & 15) << 16 | step << 20;
            }
        }
        cudaGetSymbolAddress((void**)&scratch, g_scratch);
        scratch = (uint32_t*)(((uintptr_t)scratch + (2u << 20) - 1) & ~(uintptr_t)((2u << 20) - 1));
        cudaFuncSetAttribute(fused_kernel, cudaFuncAttributeMaxDynamicSharedMemorySize, SM_TOTAL);
        for (int i = 0; i < 12; i++) cached[i] = d_in[i];
        ready = true;
    }
    const First f = {{(const uint8_t*)d_in[2], (const uint8_t*)d_in[11]}, {(const __nv_bfloat16*)d_in[0], (const __nv_bfloat16*)d_in[10]}};
    fused_kernel<<<NCTA, NTHREADS, SM_TOTAL>>>(f, (__nv_bfloat16*)d_out, scratch, maps);
}
```

```cpp
#include <cuda_runtime.h>
#include <cuda_bf16.h>
#include <cuda.h>
#include <stdint.h>
#include <limits.h>

namespace {

constexpr int NCTA = 128;
constexpr int NTHREADS = 512;
constexpr int NUNITS = 8;
constexpr int NFF = 56, J_RED = 104, J_END = 120;
constexpr uint32_t SPIN_LIMIT = 1u << 22;

#define NEAR_CLK 390
#define E1_EARLY 50
#define STAG 300
#define NUMA 1
#define NPROBE 5
#define NCP 2
#define W0 4
#define RD_ITEM 15
#define JAN_SLEEP 100
#define RD_SLEEP 400
#define HA_DELAY 200
#define H_SLEEP 100
#define QA_DELAY 600
#define QA_SLEEP 200
#define ML_DELAY 300
#define E1_SLEEP 50
#define MB_SLEEP 100
constexpr int B_WUV = 2, B_WO = 3, B_X = 4  , B_DN = 0;

constexpr int SM_U = 0;
constexpr int SM_XA = 6 * 32768;
constexpr int SM_XB = SM_XA + 12288;
constexpr int SM_MX = SM_XB + 16384;
constexpr int SM_FZ = SM_XB + 8192;
constexpr int SM_PB = SM_XB;
constexpr int SM_Y = SM_XB + 12288;
constexpr int SM_RED = SM_XB + 4096;
constexpr int SM_FS = SM_XB + 20480;
constexpr int SM_FV = SM_FS + 1024;
constexpr int SM_QX = SM_XA + 8192;
constexpr int SM_FQ = SM_FV + 512;
constexpr int SM_CLS = SM_FQ + 128;
constexpr int SM_W = SM_FQ + 256;
constexpr int SM_W2 = SM_MX + 2304;
constexpr int SM_SCR = SM_XA + 9216;
constexpr int SM_TR = SM_XB + 19456;
constexpr int SM_BAR = SM_W + 256;
constexpr int SM_TOTAL = SM_BAR + 1024;
static_assert(SM_TOTAL <= 232448, "smem");

enum { IT_MODA = 0, IT_WQ = 1, IT_WUK = 5, IT_CKV = 9, IT_WUV = 41, IT_WO = 45, IT_X = 49  , IT_DOWN = 53, NITEMS = 55,
       NEVER = 63,
       SF0 = 64,
       PF0 = 80,
       EB_UNIT0 = 96, MBB = 103,
       EB_WQ = 104, EB_WUK, QT, QB, JD, WR };

enum { MP_WQ = 0, MP_WUK, MP_CKV, MP_WUV, MP_DOWN, MP_WO, MP_GATE, MP_UP, MP_MODB, NMAPS };
struct First { const uint8_t* w[2]; const __nv_bfloat16* v[2]; };
struct Maps { CUtensorMap m[NMAPS]; uint2 sched[3][56]; };

enum { B_HA = 0,
       B_MB = 6,
       B_RD = 7,
       B_E2 = 8,
       B_QA = 16,
       B_ML = 32,
       B_E5 = 64,
       B_E3 = 80,
       B_PR = 96,
       B_TR = 100 };
constexpr int G_E1 = 1 << 19;
constexpr int G_TR = B_TR * 4096;
__device__ __align__(1024) uint32_t g_scratch[(8 << 20) / 4];

#define TRACE(slot) do {} while (0)
#define TRACE_Q(slot) do {} while (0)
#define TRACE_GT(slot) do {} while (0)

__device__ __forceinline__ uint32_t s2u(const void* p) { return (uint32_t)__cvta_generic_to_shared(p); }
__device__ __forceinline__ void mbar_init(uint32_t b, int c) { asm volatile("mbarrier.init.shared::cta.b64 [%0], %1;" :: "r"(b), "r"(c) : "memory"); }
__device__ __forceinline__ void mbar_expect(uint32_t b, uint32_t bytes) { asm volatile("mbarrier.arrive.expect_tx.shared::cta.b64 _, [%0], %1;" :: "r"(b), "r"(bytes) : "memory"); }
__device__ __forceinline__ void mbar_arrive(uint32_t b) { asm volatile("mbarrier.arrive.shared::cta.b64 _, [%0];" :: "r"(b) : "memory"); }
__device__ __forceinline__ void mbar_wait(uint32_t b, uint32_t ph) {
    asm volatile("{\n.reg .pred p;\nW: mbarrier.try_wait.parity.shared::cta.b64 p, [%0], %1;\n@!p bra W;\n}" :: "r"(b), "r"(ph) : "memory");
}
__device__ __forceinline__ void mbar_waitb(uint32_t b, uint32_t ph) {
    asm volatile("{\n.reg .pred p;\n.reg .u32 n;\nmov.u32 n, 0;\n"
                 "W: mbarrier.try_wait.parity.shared::cta.b64 p, [%0], %1;\n@p bra D;\n"
                 "add.u32 n, n, 1;\nsetp.lt.u32 p, n, 0x100000;\n@p bra W;\ntrap;\nD:\n}" :: "r"(b), "r"(ph) : "memory");
}
__device__ __forceinline__ uint32_t mbar_test(uint32_t b, uint32_t ph) {
    uint32_t ok;
    asm volatile("{\n.reg .pred p;\nmbarrier.test_wait.parity.shared::cta.b64 p, [%1], %2;\nselp.u32 %0, 1, 0, p;\n}" : "=r"(ok) : "r"(b), "r"(ph) : "memory");
    return ok;
}
__device__ __forceinline__ void bar_sync(int id, int n) { asm volatile("bar.sync %0, %1;" :: "r"(id), "r"(n) : "memory"); }
__device__ __forceinline__ void bar_arrive(int id, int n) { asm volatile("bar.arrive %0, %1;" :: "r"(id), "r"(n) : "memory"); }
__device__ __forceinline__ uint32_t peer_addr(uint32_t a, uint32_t rank) { uint32_t r; asm("mapa.shared::cluster.u32 %0, %1, %2;" : "=r"(r) : "r"(a), "r"(rank)); return r; }
__device__ __forceinline__ void st_async1(uint32_t a, float x, uint32_t bar) {
    asm volatile("st.async.weak.shared::cluster.mbarrier::complete_tx::bytes.f32 [%0], %1, [%2];" :: "r"(a), "f"(x), "r"(bar) : "memory");
}
__device__ __forceinline__ void st_async2(uint32_t a, float x, float y, uint32_t bar) {
    asm volatile("st.async.weak.shared::cluster.mbarrier::complete_tx::bytes.v2.f32 [%0], {%1, %2}, [%3];" :: "r"(a), "f"(x), "f"(y), "r"(bar) : "memory");
}
__device__ __forceinline__ uint32_t gtime() { uint32_t t; asm volatile("mov.u32 %0, %%globaltimer_lo;" : "=r"(t)); return t; }
__device__ __forceinline__ void fence_gpu() { asm volatile("fence.acq_rel.gpu;" ::: "memory"); }

__device__ __forceinline__ uint32_t enc(uint32_t b) { uint32_t r; asm("max.u32 %0, %1, 1;" : "=r"(r) : "r"(b)); return r; }
__device__ __forceinline__ uint32_t encf(float f) { return enc(__float_as_uint(f)); }
__device__ __forceinline__ void st_x1(uint32_t* p, uint32_t v) { asm volatile("st.relaxed.gpu.global.u32 [%0], %1;" :: "l"(p), "r"(v) : "memory"); }
__device__ __forceinline__ void st_x4(void* p, uint32_t a, uint32_t b, uint32_t c, uint32_t d) {
    asm volatile("st.relaxed.gpu.global.v4.u32 [%0], {%1, %2, %3, %4};" :: "l"(p), "r"(a), "r"(b), "r"(c), "r"(d) : "memory");
}
__device__ __forceinline__ void st2_x1(uint32_t* p, uint32_t v) { st_x1(p, v); st_x1(p + 1024, v); }
__device__ __forceinline__ void st2_x4(uint32_t* p, uint32_t a, uint32_t b, uint32_t c, uint32_t d) { st_x4(p, a, b, c, d); st_x4(p + 1024, a, b, c, d); }
__device__ __forceinline__ int near_off(int b, uint32_t cls) { return b * 4096 + (((__popc(b & 0x2C) ^ cls) & 1) << 10); }
__device__ __forceinline__ void ld_x(uint32_t& v, const void* p) { asm volatile("ld.relaxed.gpu.global.u32 %0, [%1];" : "=r"(v) : "l"(p) : "memory"); }
__device__ __forceinline__ void ld_x(uint4& v, const void* p) {
    asm volatile("ld.relaxed.gpu.global.v4.u32 {%0, %1, %2, %3}, [%4];" : "=r"(v.x), "=r"(v.y), "=r"(v.z), "=r"(v.w) : "l"(p) : "memory");
}
__device__ __forceinline__ void ld_x(uint2& v, const void* p) { asm volatile("ld.relaxed.gpu.global.v2.u32 {%0, %1}, [%2];" : "=r"(v.x), "=r"(v.y) : "l"(p) : "memory"); }
__device__ __forceinline__ uint32_t minw(uint32_t v) { return v; }
__device__ __forceinline__ uint32_t minw(const uint2& v) { return min(v.x, v.y); }
__device__ __forceinline__ uint32_t minw(const uint4& v) { return min(__vimin3_u32(v.x, v.y, v.z), v.w); }
template <int N> __device__ __forceinline__ uint32_t mint(const uint32_t* m) {
    if constexpr (N == 1) return m[0];
    else if constexpr (N == 2) return min(m[0], m[1]);
    else return __vimin3_u32(mint<(N + 2) / 3>(m), mint<(N + 1) / 3>(m + (N + 2) / 3), mint<N / 3>(m + (N + 2) / 3 + (N + 1) / 3));
}

template <int STRIDE, int S4 = 4 * STRIDE, typename T, int N>
__device__ __forceinline__ void poll_start(T (&v)[N], const void* base) {
#pragma unroll
    for (int i = 0; i < N; i++) ld_x(v[i], (const uint8_t*)base + (i & 3) * STRIDE + (i >> 2) * S4);
}
struct Nop { __device__ void operator()() const {} };
template <int STRIDE, int SLEEP, bool STARTED = false, int S4 = 4 * STRIDE, typename T, int N, typename F = Nop>
__device__ __forceinline__ void poll(T (&v)[N], const void* base, F idle = F()) {
    if (!STARTED) { poll_start<STRIDE, S4>(v, base); idle(); }
#pragma unroll 1
    for (uint32_t it = 0;; it++) {
        uint32_t m[N];
#pragma unroll
        for (int i = 0; i < N; i++) m[i] = minw(v[i]);
        if (__all_sync(0xffffffffu, mint<N>(m) != 0)) break;
        if (SLEEP && it > 0) __nanosleep(SLEEP);
#pragma unroll
        for (int i = 0; i < N; i++) if (!m[i]) ld_x(v[i], (const uint8_t*)base + (i & 3) * STRIDE + (i >> 2) * S4);
        idle();
        if (it > SPIN_LIMIT) __trap();
    }
}

__device__ __forceinline__ float bflo(uint32_t w) { return __uint_as_float(w << 16); }
__device__ __forceinline__ float bfhi(uint32_t w) { return __uint_as_float(w & 0xffff0000u); }
__device__ __forceinline__ uint32_t pack2(float lo, float hi) {
    uint32_t r; asm("cvt.rn.bf16x2.f32 %0, %1, %2;" : "=r"(r) : "f"(hi), "f"(lo)); return r;
}
__device__ __forceinline__ float rbf(float x) { return __uint_as_float(pack2(0.f, x)); }
__device__ __forceinline__ float sumlo(const uint32_t (&v)[8]) { return ((bflo(v[0]) + bflo(v[1])) + (bflo(v[2]) + bflo(v[3]))) + ((bflo(v[4]) + bflo(v[5])) + (bflo(v[6]) + bflo(v[7]))); }
__device__ __forceinline__ float sumhi(const uint32_t (&v)[8]) { return ((bfhi(v[0]) + bfhi(v[1])) + (bfhi(v[2]) + bfhi(v[3]))) + ((bfhi(v[4]) + bfhi(v[5])) + (bfhi(v[6]) + bfhi(v[7]))); }
__device__ __forceinline__ float ex2(float x) { float r; asm("ex2.approx.ftz.f32 %0, %1;" : "=f"(r) : "f"(x)); return r; }
__device__ __forceinline__ float shx(float v, int m) { return __shfl_xor_sync(0xffffffffu, v, m); }
__device__ __forceinline__ uint4 lds128(uint32_t a) { uint4 v; asm volatile("ld.shared.v4.u32 {%0, %1, %2, %3}, [%4];" : "=r"(v.x), "=r"(v.y), "=r"(v.z), "=r"(v.w) : "r"(a) : "memory"); return v; }
__device__ __forceinline__ uint32_t lds32(uint32_t a) { uint32_t v; asm volatile("ld.shared.u32 %0, [%1];" : "=r"(v) : "r"(a) : "memory"); return v; }
__device__ __forceinline__ void sts32(uint32_t a, uint32_t v) { asm volatile("st.shared.u32 [%0], %1;" :: "r"(a), "r"(v) : "memory"); }
__device__ __forceinline__ void sts16(uint32_t a, uint32_t v) { asm volatile("st.shared.u16 [%0], %1;" :: "r"(a), "h"((uint16_t)v) : "memory"); }
__device__ __forceinline__ int frag_off(int k) { return (k >> 5) * 64 + ((k >> 1) & 3) * 16 + ((k >> 4) & 1) * 8 + ((k >> 3) & 1) * 4 + (k & 1) * 2; }

template <bool TRANS>
__device__ __forceinline__ uint4 ldsm(uint32_t a) {
    uint4 r;
    if (TRANS) asm volatile("ldmatrix.sync.aligned.m8n8.x4.trans.shared.b16 {%0, %1, %2, %3}, [%4];" : "=r"(r.x), "=r"(r.y), "=r"(r.z), "=r"(r.w) : "r"(a) : "memory");
    else asm volatile("ldmatrix.sync.aligned.m8n8.x4.shared.b16 {%0, %1, %2, %3}, [%4];" : "=r"(r.x), "=r"(r.y), "=r"(r.z), "=r"(r.w) : "r"(a) : "memory");
    return r;
}
__device__ __forceinline__ void mma(float (&c)[4], uint32_t a0, uint32_t a1, uint32_t a2, uint32_t a3, uint32_t b0, uint32_t b1) {
    asm volatile("mma.sync.aligned.m16n8k16.row.col.f32.bf16.bf16.f32 {%0,%1,%2,%3}, {%4,%5,%6,%7}, {%8,%9}, {%0,%1,%2,%3};"
                 : "+f"(c[0]), "+f"(c[1]), "+f"(c[2]), "+f"(c[3]) : "r"(a0), "r"(a1), "r"(a2), "r"(a3), "r"(b0), "r"(b1));
}
template <bool TRANS, typename F>
__device__ __forceinline__ void load8(uint4 (&a)[8], F addr) {
    __syncwarp();
#pragma unroll
    for (int s = 0; s < 8; s++) a[s] = ldsm<TRANS>(addr(s));
}
__device__ __forceinline__ void mma8(float (&c)[4], const uint4 (&a)[8], const uint4 (&b)[4]) {
    float e[4][4];
#pragma unroll
    for (int s = 0; s < 8; s++) {
        if (s < 4) e[s][0] = e[s][1] = e[s][2] = e[s][3] = 0.f;
        mma(e[s & 3], a[s].x, a[s].y, a[s].z, a[s].w, (s & 1) ? b[s >> 1].z : b[s >> 1].x, (s & 1) ? b[s >> 1].w : b[s >> 1].y);
    }
#pragma unroll
    for (int i = 0; i < 4; i++) c[i] = (e[0][i] + e[1][i]) + (e[2][i] + e[3][i]);
}
__device__ __forceinline__ void ldfrag(uint4 (&b)[4], uint32_t a) {
    asm volatile("ld.shared.v4.u32 {%0,%1,%2,%3}, [%16];\nld.shared.v4.u32 {%4,%5,%6,%7}, [%16+64];\n"
                 "ld.shared.v4.u32 {%8,%9,%10,%11}, [%16+128];\nld.shared.v4.u32 {%12,%13,%14,%15}, [%16+192];\n"
                 : "=r"(b[0].x), "=r"(b[0].y), "=r"(b[0].z), "=r"(b[0].w), "=r"(b[1].x), "=r"(b[1].y), "=r"(b[1].z), "=r"(b[1].w),
                   "=r"(b[2].x), "=r"(b[2].y), "=r"(b[2].z), "=r"(b[2].w), "=r"(b[3].x), "=r"(b[3].y), "=r"(b[3].z), "=r"(b[3].w) : "r"(a) : "memory");
}
__device__ __forceinline__ void quad_pair(float x, float y, int t, float& lo, float& hi) {
    const float k = ((t & 1) ? y : x) + shx((t & 1) ? x : y, 1);
    lo = k + shx(k, 2); hi = shx(k, 4) + shx(k, 6);
}
__device__ __forceinline__ void pin(uint32_t& x) { asm volatile("" : "+r"(x)); }
template <typename T> __device__ __forceinline__ void pin(T*& x) { asm volatile("" : "+l"(x)); }
__device__ __forceinline__ float4 ldsf4(uint32_t a) { const uint4 v = lds128(a); return make_float4(__uint_as_float(v.x), __uint_as_float(v.y), __uint_as_float(v.z), __uint_as_float(v.w)); }
__device__ __forceinline__ float sum4(const float4& f) { return (f.x + f.y) + (f.z + f.w); }
__device__ __forceinline__ void stsf(uint32_t a, float v) { sts32(a, __float_as_uint(v)); }

__device__ __forceinline__ void wg_fence() { asm volatile("wgmma.fence.sync.aligned;" ::: "memory"); }
__device__ __forceinline__ void wg_commit() { asm volatile("wgmma.commit_group.sync.aligned;" ::: "memory"); }
__device__ __forceinline__ void wg_wait1() { asm volatile("wgmma.wait_group.sync.aligned 1;" ::: "memory"); }
__device__ __forceinline__ void wg_wait0() { asm volatile("wgmma.wait_group.sync.aligned 0;" ::: "memory"); }
#define R8(o) "+f"(d[o]), "+f"(d[o + 1]), "+f"(d[o + 2]), "+f"(d[o + 3]), "+f"(d[o + 4]), "+f"(d[o + 5]), "+f"(d[o + 6]), "+f"(d[o + 7])
__device__ __forceinline__ void wgmma_rs_n32(float (&d)[16], const uint4& a, uint64_t db, int acc) {
    asm volatile("{\n.reg .pred p;\nsetp.ne.b32 p, %21, 0;\n"
        "wgmma.mma_async.sync.aligned.m64n32k16.f32.bf16.bf16 "
        "{%0,%1,%2,%3,%4,%5,%6,%7,%8,%9,%10,%11,%12,%13,%14,%15}, {%16,%17,%18,%19}, %20, p, 1, 1, 0;\n}"
        : R8(0), R8(8) : "r"(a.x), "r"(a.y), "r"(a.z), "r"(a.w), "l"(db), "r"(acc));
}
#define PV_LO "{%0,%1,%2,%3,%4,%5,%6,%7,%8,%9,%10,%11,%12,%13,%14,%15,%16,%17,%18,%19,%20,%21,%22,%23,%24,%25,%26,%27,%28,%29,%30,%31,%32,%33,%34,%35,%36,%37,%38,%39,%40,%41,%42,%43,%44,%45,%46,%47,%48,%49,%50,%51,%52,%53,%54,%55,%56,%57,%58,%59,%60,%61,%62,%63}, "
#define PV_HI "{%64,%65,%66,%67,%68,%69,%70,%71,%72,%73,%74,%75,%76,%77,%78,%79,%80,%81,%82,%83,%84,%85,%86,%87,%88,%89,%90,%91,%92,%93,%94,%95,%96,%97,%98,%99,%100,%101,%102,%103,%104,%105,%106,%107,%108,%109,%110,%111,%112,%113,%114,%115,%116,%117,%118,%119,%120,%121,%122,%123,%124,%125,%126,%127}, "
__device__ __forceinline__ void wgmma_pv(float (&d)[128], const uint4& a, uint32_t blo, int acc) {
    asm volatile("{\n.reg .pred p;\n.reg .b32 u0, u1, u2, u3, t;\n.reg .b64 d0, d1, d2, d3;\nsetp.ne.b32 p, %133, 0;\n"
        "mov.b64 d0, {%132, 0x40000100};\nadd.u32 t, %132, 512;\nmov.b64 d1, {t, 0x40000100};\n"
        "add.u32 t, %132, 128;\nmov.b64 d2, {t, 0x40000100};\nadd.u32 t, %132, 640;\nmov.b64 d3, {t, 0x40000100};\n"
        "wgmma.fence.sync.aligned;\n"
        "wgmma.mma_async.sync.aligned.m64n128k16.f32.bf16.bf16 " PV_LO "{%128, u0, %129, u1}, d0, p, 1, 1, 1;\n"
        "wgmma.mma_async.sync.aligned.m64n128k16.f32.bf16.bf16 " PV_LO "{%130, u2, %131, u3}, d1, 1, 1, 1, 1;\n"
        "wgmma.commit_group.sync.aligned;\n"
        "wgmma.mma_async.sync.aligned.m64n128k16.f32.bf16.bf16 " PV_HI "{%128, u0, %129, u1}, d2, p, 1, 1, 1;\n"
        "wgmma.mma_async.sync.aligned.m64n128k16.f32.bf16.bf16 " PV_HI "{%130, u2, %131, u3}, d3, 1, 1, 1, 1;\n"
        "wgmma.commit_group.sync.aligned;\n}"
        : R8(0), R8(8), R8(16), R8(24), R8(32), R8(40), R8(48), R8(56), R8(64), R8(72), R8(80), R8(88), R8(96), R8(104), R8(112), R8(120)
        : "r"(a.x), "r"(a.y), "r"(a.z), "r"(a.w), "r"(blo), "r"(acc) : "memory");
}

template <int NW>
__device__ __forceinline__ void ln_stats(float s, float q, float sh, float* scr, int w, int lane, int bar, float& mean_b, float& sd_b) {
#pragma unroll
    for (int o = 16; o; o >>= 1) { s += shx(s, o); q += shx(q, o); }
    constexpr float n = 512.f / NW;
    if (lane == 0) { scr[w] = sh + s * (1.f / n); scr[NW + w] = q - s * s * (1.f / n); }
    bar_sync(bar, NW * 32);
    float mu = 0.f, m2 = 0.f;
#pragma unroll
    for (int i = 0; i < NW; i++) { mu += scr[i]; m2 += scr[NW + i]; }
    mu *= 1.f / NW;
#pragma unroll
    for (int i = 0; i < NW; i++) { const float d = scr[i] - mu; m2 = fmaf(n * d, d, m2); }
    mean_b = rbf(mu);
    sd_b = rbf(sqrtf(rbf(rbf(fmaxf(m2, 0.f) * (1.f / 512.f)) + 1e-5f)));
}
__device__ __forceinline__ float ln_mod(float x, float mean_b, float sd_b, float c, float s) {
    return rbf(rbf(__fdividef(rbf(x - mean_b), sd_b)) * rbf(1.f + c)) + s;
}

__global__ void __cluster_dims__(2, 1, 1) __launch_bounds__(NTHREADS, 1)
fused_kernel(const __grid_constant__ First F, __nv_bfloat16* __restrict__ out, uint32_t* __restrict__ gs, const __grid_constant__ Maps M) {
    extern __shared__ __align__(1024) uint8_t sm[];
    const uint32_t sb = s2u(sm);
    const int tid = threadIdx.x, lane = tid & 31;
    const int j = blockIdx.x, rk = j & 1;
    const int g = lane >> 2, t = lane & 3;
    const int r8 = lane & 7, lb3 = (lane >> 3) & 1, lb4 = lane >> 4;
    uint64_t pol;
    asm("createpolicy.fractional.L2::evict_first.b64 %0, 1.0;" : "=l"(pol));
    {
        auto cpa = [&](uint32_t d, const uint8_t* s) {
            asm volatile("cp.async.cg.shared.global.L2::cache_hint.L2::128B [%0], [%1], 16, %2;" :: "r"(d), "l"(s), "l"(pol) : "memory");
        };
        const uint32_t ut = threadIdx.x, uj = blockIdx.x;
        const uint8_t* w = F.w[ut >= 128];
        if (ut < 128) {
            const uint32_t dq = (sb + ut * 16) ^ ((ut * 2) & 0x70);
            const uint8_t* sq = w + (uint32_t)(((uj & 1) * 256 + (ut >> 3)) * 8192 + (uj >> 1) * 128 + (ut & 7) * 16);
#pragma unroll
            for (int i = 0; i < 4 * NCP; i++) cpa(dq + 4 * 32768 + i * 2048, sq + i * 131072);
        } else if (ut < 384) {
            const uint32_t dm = (sb + ut * 16) ^ ((ut * 2) & 0x10);
            const uint8_t* sa = w + (uint32_t)(((uj >> 5) * 128 + (ut >> 1) - 64) * 6144 + (uj & 31) * 32 + (ut & 1) * 16);
            cpa(dm + SM_XA - 2048, sa); cpa(dm + SM_XA + 2048, sa + 1024);
        }
        else if (ut == 480 && uj < 64) asm volatile("prefetch.global.L2 [%0];" :: "l"(F.v[(uj >> 3) & 1] + (uj & 7) * 64));
    }
    const int warp = __shfl_sync(0xffffffffu, tid >> 5, 0);
    const __nv_bfloat16* const xin = F.v[0];
    uint32_t* const pl = gs + (warp < 2 ? (B_PR + (j >> 5)) * 4096 + (j & 31) * 32 : G_E1 + j * 8192) + (warp & 1) * 1024 + lane;
    if (warp < 4) st_x1(pl, 1u);
    auto BAR = [&](int i) -> uint32_t { return sb + SM_BAR + i * 8; };
    const uint32_t a16 = (r8 + 8 * lb4) * 32 + ((lb3 ^ (r8 >> 2)) * 16);
    const uint32_t a128 = (r8 + 8 * lb4) * 128 + ((((warp & 3) * 2 + lb3) ^ r8) * 16);
    auto ldcls = [&]() -> uint32_t { return *(const volatile uint32_t*)(sm + SM_CLS); };
    auto clear_head = [&]() {
        st2_x1(gs + (B_HA + ((j >> 4) & 1) * 2 + lb4) * 4096 + (j >> 5) * 256 + (j & 15) * 16 + (lane & 15), 0u);
        st2_x4(gs + (B_QA + rk * 8 + ((j >> 1) & 1) * 4 + (j >> 5)) * 4096 + g * 128 + ((j >> 2) & 7) * 16 + t * 4, 0u, 0u, 0u, 0u);
        if (lane < 8) st2_x1(gs + B_RD * 4096 + j * 8 + lane, 0u);
    };
    auto tma = [&](uint32_t dst, const CUtensorMap* mp, uint32_t bar, int c0, int c1, int c2, int c3) {
        asm volatile("{\n.reg .pred p;\nelect.sync _|p, 0xffffffff;\n"
                     "@p cp.async.bulk.tensor.4d.shared::cluster.global.mbarrier::complete_tx::bytes.L2::cache_hint [%0], [%1, {%3, %4, %5, %6}], [%2], %7;\n}"
                     :: "r"(dst), "l"(mp), "r"(bar), "r"(c0), "r"(c1), "r"(c2), "r"(c3), "l"(pol) : "memory");
    };
    if (warp <= 12 || warp == 15) {
        const int grp = warp == 12 ? 0 : warp == 15 ? 13 : warp + 1;
        const uint32_t cnt = grp < 10 ? 1 : grp < 13 ? 4 : 8;
        if (lane == 0) {
#pragma unroll
            for (int i = 0; i < 8; i++) mbar_init(BAR(grp * 8 + i), (i < 2 && grp == 0) ? (i ? 128 : 256) : cnt);
        }
        __syncwarp();
        if (grp < 10 && lane < 8 && (grp || lane > NCP)) mbar_expect(BAR(grp * 8 + lane), grp >= 8 ? 4096 : grp * 8 + lane < IT_X ? 8192 : 16384);
        asm volatile("fence.mbarrier_init.release.cluster;" ::: "memory");
        __syncwarp();
        if (warp == 12) {
#pragma unroll
            for (int i = NCP + 1; i < W0; i++) tma(sb + (15 + i) * 8192, &M.m[MP_WQ], BAR(i), 0, rk * 256 + (i - 1) * 64, j >> 1, 0);
        }
    } else if (warp == 13) {
        if (lane < NMAPS) asm volatile("prefetch.tensormap [%0];" :: "l"(&M.m[lane]) : "memory");
    } else if (warp == 14) {
        clear_head();
    }
    __syncthreads();
    uint32_t in1 = 0, in2 = 0;
    if (warp < 4) { in1 = *(const uint32_t*)(xin + 2 * tid); in2 = *(const uint32_t*)(xin + 256 + 2 * tid); }
    else if (warp < 12) in1 = *(const uint32_t*)(F.v[1] + 2 * (tid - 128));
    if (warp < 12) asm volatile("cp.async.mbarrier.arrive.noinc.shared::cta.b64 [%0];" :: "r"(BAR(warp < 4)) : "memory");
    asm volatile("barrier.cluster.arrive.relaxed.aligned;" ::: "memory");

    if (warp >= 12) {
    asm volatile("setmaxnreg.dec.sync.aligned.u32 64;");
    if (warp == 12) {
        static_assert(W0 > NCP && W0 <= 5 && NCP >= 1 && NCP <= 4, "W0");
        const uint2* sched = M.sched[j < NFF ? 0 : j < J_RED ? 1 : 2];
        uint2 en = sched[W0];
        const uint32_t t0 = gtime();
        const uint32_t sp = __reduce_or_sync(0xffffffffu, sb);
        const int cx = (j >> 1) * 64 + (j < NFF ? 0 : 1024 - NFF * 32);
#pragma unroll 1
        for (int i = W0; en.x; i++) {
            const uint32_t e = en.x, tn = t0 + (int16_t)en.y, mp = (en.y >> 16) & 15, st = (en.y >> 20) * 64;
            en = sched[i + 1];
            if (mp == MP_MODB && j >= J_END) break;
            uint32_t c0 = mp == MP_WO ? (j & 7) * 64 : mp > MP_WO ? cx : 0;
            uint32_t c1 = mp == MP_CKV ? 0 : mp == MP_DOWN ? j * 32 : st + (mp == MP_WUV ? (j & 3) * 32 : mp == MP_WO ? (j >> 3) * 256 : rk * 256);
            uint32_t c2 = mp < MP_CKV ? j >> 1 : mp == MP_CKV ? rk * 4 : mp == MP_WUV ? (j >> 2) * 2 : mp == MP_DOWN ? st >> 4 : 0;
            uint32_t c3 = mp == MP_CKV ? st * 2 + (j & ~1) : 0;
            uint32_t dst = sp + ((e << 7) & 0x3e000), bar = sp + SM_BAR + (e & 63) * 8;
            const uint32_t w0 = (e >> 8) & 0x3f8, w1 = (e >> 15) & 0x3f8, w2 = (e >> 22) & 0x3f8, bb = sp + SM_BAR - 8;
            const CUtensorMap* pm = &M.m[mp];
            pin(dst); pin(bar); pin(c0); pin(c1); pin(c2); pin(c3); pin(pm);
            if (w0) mbar_wait(bb + w0, 0);
            if (w2) {
                mbar_wait(bb + w2, 0);
                while (!__any_sync(0xffffffffu, mbar_test(bb + w1, 0) | ((int)(gtime() - tn) > 0))) {}
            } else if (w1) mbar_wait(bb + w1, 0);
            tma(dst, pm, bar, c0, c1, c2, c3);
        }
    } else if (warp == 13) {
#pragma unroll
        for (int i = 0; i < 2; i++) st_x4(gs + (B_ML + rk * 16 + i * 8 + g) * 4096 + (t >> 1) * 1024 + (j >> 1) * 8 + (t & 1) * 4, 0u, 0u, 0u, 0u);
        if (lane < 16) st2_x4(gs + (B_E2 + (j >> 4)) * 4096 + (j & 15) * 64 + lane * 4, 0u, 0u, 0u, 0u);
        st2_x1(gs + (B_E3 + (j >> 5)) * 4096 + (j & 31) * 32 + lane, 0u);
        if (lane < 8) st2_x1(gs + B_MB * 4096 + j * 8 + lane, 0u);
        if (j < NFF) {
#pragma unroll
            for (int i = 0; i < 2; i++) st2_x4(gs + (B_E5 + i * 8 + g) * 4096 + j * 16 + t * 4, 0u, 0u, 0u, 0u);
        }
        bar_sync(9, 64);
        const uint32_t cs = ldcls();
#pragma unroll 1
        for (int i = 0; i < 32; i++) {
            st_x4(gs + G_E1 + j * 8192 + (i >> 3) * 2048 + ((((cs >> 1) ^ (i >> 3)) & 1) << 10) + (i & 7) * 128 + lane * 4, 0u, 0u, 0u, 0u);
            __nanosleep(JAN_SLEEP);
        }
        fence_gpu();
        if (lane < 8) st2_x1(gs + B_RD * 4096 + j * 8 + lane, 1u + (cs >> 1));
        if (lane == 0) TRACE(41);
        uint32_t rd[4];
        mbar_wait(BAR(IT_CKV + RD_ITEM), 0);
        poll<1024, RD_SLEEP>(rd, gs + near_off(B_RD, cs) + lane * 8);
#pragma unroll
        for (int i = 0; i < 4; i++) {
            const uint32_t m = __ballot_sync(0xffffffffu, rd[i] == 2u);
            if (lane == 0) sts32(sb + SM_CLS + 16 + i * 4, m);
        }
        __syncwarp();
        if (lane < 8) mbar_arrive(BAR(JD));
        if (lane == 0) TRACE(42);
    } else if (warp == 14) {
        uint2 ml[2];
        mbar_waitb(BAR(JD), 0);
        const uint32_t cls = ldcls();
        mbar_waitb(BAR(PF0 + 2 * NUNITS - 1), 0);
        __nanosleep(ML_DELAY);
        const uint32_t* pl2 = gs + near_off(B_ML + (j >> 2), cls) + lane * 8;
        const uint32_t wa = sb + SM_W + lb4 * 64 + t * 16 + (g & 3) * 4;
        poll_start<1024>(ml, pl2);
        uint32_t w0 = 0, w1 = 0, redo = 0;
        bool first = true;
#pragma unroll 1
        for (uint32_t it = 0;; it++) {
            const bool p0 = minw(ml[0]) != 0, p1 = minw(ml[1]) != 0;
            const int n = __popc(__ballot_sync(0xffffffffu, p0)) + __popc(__ballot_sync(0xffffffffu, p1));
            const uint32_t x0 = ml[0].x, x1 = ml[1].x;
            if (n < 64) {
                if (!p0) ld_x(ml[0], pl2);
                if (!p1) ld_x(ml[1], pl2 + 256);
            }
            if (n == 64 || (first && n >= E1_EARLY)) {
                auto ord = [](int x) { return x ^ ((x >> 31) & 0x7fffffff); };
                const int o0 = ord(x0), o1 = ord(x1);
                const float mm = __int_as_float(ord(__reduce_max_sync(0xffffffffu, max(p0 ? o0 : INT_MIN, p1 ? o1 : INT_MIN))));
                const float lo = __int_as_float(ord(__reduce_min_sync(0xffffffffu, min(p0 ? o0 : INT_MAX, p1 ? o1 : INT_MAX))));
                const uint32_t v0 = pack2(ex2((p0 ? __uint_as_float(x0) : lo) - mm), 0.f), v1 = pack2(ex2((p1 ? __uint_as_float(x1) : lo) - mm), 0.f);
                redo = !first && __any_sync(0xffffffffu, v0 != w0 || v1 != w1);
                w0 = v0; w1 = v1;
                sts32(wa - redo * (SM_W - SM_W2), w0 * 0x10001u); sts32(wa - redo * (SM_W - SM_W2) + 128, w1 * 0x10001u);
                if (first) bar_arrive(3, 416);
                first = false;
                if (n == 64) break;
            }
            if (it > SPIN_LIMIT) __trap();
        }
        if (lane == 0) TRACE_Q(37);
        float L = bflo(w0) * __uint_as_float(ml[0].y) + bflo(w1) * __uint_as_float(ml[1].y);
#pragma unroll
        for (int o = 16; o; o >>= 1) L += shx(L, o);
        if (lane == 0) *(float2*)(sm + SM_FQ) = make_float2(__frcp_rn(L), __uint_as_float(redo));
        __syncwarp();
        if (lane < 8) mbar_arrive(BAR(WR));
        if (lane == 0) TRACE(10);
        bar_sync(4, 288);
        clear_head();
        if (j < NFF) {
            uint32_t ya = sb + SM_Y + lane * 16, sa = peer_addr(sb + SM_RED + 2048 + rk * 8, lane & 1), tb = peer_addr(BAR(MBB), lane & 1);
            pin(ya); pin(sa); pin(tb);
            bar_sync(7, 288);
            const float4 y0 = ldsf4(ya), y1 = ldsf4(ya + 512);
            float s = sum4(y0) + sum4(y1);
            float q = (fmaf(y0.x, y0.x, y0.y * y0.y) + fmaf(y0.z, y0.z, y0.w * y0.w)) + (fmaf(y1.x, y1.x, y1.y * y1.y) + fmaf(y1.z, y1.z, y1.w * y1.w));
#pragma unroll
            for (int o = 16; o; o >>= 1) { s += shx(s, o); q += shx(q, o); }
            if (lane < 2) st_async2(sa, s, q, tb);
        }
    } else if (warp == 15) {
        mbar_waitb(BAR(IT_X - 1), 0);
        if (j < J_END) mbar_waitb(BAR(j < NFF ? NITEMS - 1 : MBB), 0);
    }
    } else if (warp < 4) {
        float* scr = (float*)(sm + SM_SCR);
        uint32_t cls;
        {
            uint2 ha[8];
            uint32_t best = 0xffffffffu;
            sts32(sb + SM_SCR + 64 + warp * 4, best);
            const float sh = __shfl_sync(0xffffffffu, bflo(in1), 0);
            const float v0 = bflo(in1) - sh, v1 = bfhi(in1) - sh, v2 = bflo(in2) - sh, v3 = bfhi(in2) - sh;
            float mb, sd;
            ln_stats<4>((v0 + v1) + (v2 + v3), (v0 * v0 + v1 * v1) + (v2 * v2 + v3 * v3), sh, scr, warp, lane, 2, mb, sd);
            if (!rk) in2 = in1;
#pragma unroll 1
            for (int i = 0; i < NPROBE; i++) {
                uint32_t t0, t1, o;
                asm volatile("mov.u32 %0, %%clock;" : "=r"(t0));
                asm volatile("atom.relaxed.gpu.global.exch.b32 %0, [%1], %2;" : "=r"(o) : "l"(pl), "r"(2u + i) : "memory");
                asm volatile("{\n.reg .pred p;\nsetp.ne.u32 p, %1, 0x1234567;\nmov.u32 %0, 0;\n@p mov.u32 %0, %%clock;\n}" : "=r"(t1) : "r"(o));
                best = min(best, t1 - t0);
                sts32(sb + SM_SCR + 64 + warp * 4, best);
                if (__all_sync(0xffffffffu, min(best, lds32(sb + SM_SCR + 64 + (warp ^ 1) * 4)) < NEAR_CLK)) break;
            }
            bar_sync(2, 128);
            const uint4 lt = *(const uint4*)(scr + 16);
            cls = NUMA ? ((lt.y < lt.x) ^ (__popc((B_PR + (j >> 5)) & 0x2C) & 1)) | (lt.w < lt.z) << 1 : 0;
            if (warp == 0) { if (lane == 0) sts32(sb + SM_CLS, cls); bar_arrive(9, 64); }
            if (tid == 0) TRACE(38);
            asm volatile("barrier.cluster.wait.aligned;" ::: "memory");
            mbar_wait(BAR(IT_MODA), 0);
            if (HA_DELAY) __nanosleep(HA_DELAY);
            poll<1024, H_SLEEP, false, 16384>(ha, gs + near_off(B_HA + rk * 2, cls) + 2 * tid);
            auto rsum = [](uint32_t a, uint32_t b, uint32_t c, uint32_t d) { return rbf((__uint_as_float(a) + __uint_as_float(b)) + (__uint_as_float(c) + __uint_as_float(d))); };
            sts32(sb + SM_FV + frag_off(2 * tid),
                  pack2(ln_mod(bflo(in2), mb, sd, rsum(ha[4].x, ha[5].x, ha[6].x, ha[7].x), rsum(ha[0].x, ha[1].x, ha[2].x, ha[3].x)),
                        ln_mod(bfhi(in2), mb, sd, rsum(ha[4].y, ha[5].y, ha[6].y, ha[7].y), rsum(ha[0].y, ha[1].y, ha[2].y, ha[3].y))));
            bar_arrive(5, 384);
            mbar_wait(BAR(QB), 0);
            if (tid < 64) {
                const float* qx = (const float*)(sm + SM_QX) + tid;
                sts16(sb + SM_FQ + frag_off(tid), pack2((qx[0] + qx[64]) + (qx[128] + qx[192]), 0.f));
            }
            bar_arrive(6, 384);
        }
        asm volatile("setmaxnreg.inc.sync.aligned.u32 192;");
        float acc[128];
        float M = 0.f;
        uint32_t pa = sb + SM_XA + warp * 512 + lane * 16, ma = sb + SM_MX + (warp * 8 + g) * 4, pf = BAR(PF0);
        uint32_t blo = __reduce_or_sync(0xffffffffu, (((sb + SM_U) & 0x3FFFFu) >> 4) | 0x400000u);
        uint32_t* e1[4];
#pragma unroll
        for (int i = 0; i < 4; i++) e1[i] = gs + G_E1 + (warp * 8 + g) * 4 * 8192 + (rk * 2 + (j >> 6)) * 2048 + ((j >> 1) & 31) * 32 + t * 4;
#pragma unroll 1
        for (int h = 0; h < 2 * NUNITS; h++) {
            mbar_wait(pf, 0);
            const float m = __uint_as_float(lds32(ma));
            const uint4 pn = lds128(pa);
            wg_wait0();
#pragma unroll
            for (int i = 0; i < 128; i++) asm volatile("" : "+f"(acc[i]) :: "memory");
            if (h == 0) M = m;
            uint32_t b2 = 0x3f803f80u;
            if (__builtin_expect(__any_sync(0xffffffffu, m != M), 0)) {
                const float Mn = fmaxf(M, m), alpha = ex2(M - Mn), beta = ex2(m - Mn);
                M = Mn;
                b2 = pack2(beta, beta);
#pragma unroll
                for (int jj = 0; jj < 32; jj++) { acc[4 * jj] *= alpha; acc[4 * jj + 1] *= alpha; }
            }
            auto mul2 = [](uint32_t x, uint32_t y) { uint32_t r; asm("mul.rn.bf16x2 %0, %1, %2;" : "=r"(r) : "r"(x), "r"(y)); return r; };
            const uint4 p = make_uint4(mul2(pn.x, b2), mul2(pn.y, b2), mul2(pn.z, b2), mul2(pn.w, b2));
            if (tid == 0 && (h & 1)) TRACE_Q(48 + (h >> 1));
            wgmma_pv(acc, p, blo, h);
            if (lane == 0 && h > 0 && !(h & 1)) mbar_arrive(BAR(EB_UNIT0 + (h >> 1) - 1));
            blo += h == 11 ? -11 * 1024 : 1024;
            pa += (h == 5 || h == 11) ? -5 * 2048 : 2048;
            ma += 128; pf += 8;
            if (h == 2 * NUNITS - 3) {
                mbar_wait(BAR(JD), 0);
                const uint32_t hm = (*(const uint32_t*)(sm + SM_CLS + 16 + warp * 4) >> (g * 4)) ^ ((j >> 6) ? 15u : 0u);
#pragma unroll
                for (int i = 0; i < 4; i++) e1[i] += ((hm >> i) & 1) << 10;
            }
        }
#pragma unroll
        for (int vv = 0; vv < 2; vv++) {
            if (vv && M == 1.f) __trap();
            if (vv) wg_wait0(); else wg_wait1();
#pragma unroll
            for (int i = 0; i < 64; i++) asm volatile("" : "+f"(acc[vv * 64 + i]) :: "memory");
            if (tid == 0 && !vv) TRACE_Q(63);
#pragma unroll
            for (int i = 0; i < 4; i++) {
                const float* a = &acc[vv * 64 + i * 16];
                st_x4(e1[i] + i * 8192 + vv * 16, enc(pack2(a[0], a[1])), enc(pack2(a[4], a[5])), enc(pack2(a[8], a[9])), enc(pack2(a[12], a[13])));
            }
        }
        bar_arrive(3, 416);
        if (tid == 0) TRACE_Q(17);
        if (j < NFF) {
            uint4 a[16];
            const uint32_t ad = sb + SM_U + B_DN * 32768 + warp * 8192 + (r8 + 8 * lb4) * 128 + (lb3 ^ r8) * 16;
            uint32_t rl = sb + SM_RED + lane * 16;
            uint32_t* p5 = gs + (B_E5 + warp * 4 + (t >> 1)) * 4096 + j * 16 + (t & 1) * 8 + g;
            pin(rl); pin(p5);
            if (lane == 0) mbar_expect(BAR(MBB), 4);
            auto ldd = [&]() {
#pragma unroll
                for (int s = 0; s < 16; s++) a[s] = ldsm<true>((ad ^ ((s & 3) * 32)) + (s >> 2) * 2048);
            };
            const uint32_t db = BAR(IT_DOWN + (warp >> 1));
            mbar_wait(BAR(MBB), 0);
            const float4 st = ldsf4(sb + SM_RED + 2048);
            const bool hd = __all_sync(0xffffffffu, mbar_test(db, 0));
            if (hd) ldd();
            const float mu = (st.x + st.z) * (1.f / 512.f);
            float rstd;
            asm volatile("rsqrt.approx.ftz.f32 %0, %1;" : "=f"(rstd) : "f"(fmaxf(fmaf(-mu, mu, (st.y + st.w) * (1.f / 512.f)), 0.f) + 1e-5f));
            mbar_wait(BAR(QB), 1);
            if (tid == 0) TRACE(25);
            const float4 f0 = ldsf4(rl), f2 = ldsf4(rl + 1024), f1 = ldsf4(rl + 512), f3 = ldsf4(rl + 1536);
            const float gg = fmaf(rstd, fmaf(-mu, f0.z + f2.z, (f0.x + f0.y) + (f2.x + f2.y)), f0.w + f2.w);
            const float uu = fmaf(rstd, fmaf(-mu, f1.z + f3.z, (f1.x + f1.y) + (f3.x + f3.y)), f1.w + f3.w);
            const float hh = __fdividef(gg * uu, 1.f + ex2(-gg * fmaf(gg * gg, 0.10294324f, 2.3022082f)));
            uint32_t hb[4];
#pragma unroll
            for (int i = 0; i < 4; i++) hb[i] = pack2(__shfl_sync(0xffffffffu, hh, 2 * t + 8 * i), __shfl_sync(0xffffffffu, hh, 2 * t + 8 * i + 1));
            if (!hd) { mbar_wait(db, 0); ldd(); }
#pragma unroll
            for (int i = 0; i < 2; i++) {
                uint32_t res = 0;
#pragma unroll
                for (int k = 0; k < 4; k++) {
                    float c[4] = {0.f, 0.f, 0.f, 0.f};
                    const uint4 &x = a[i * 8 + k], &y = a[i * 8 + k + 4];
                    mma(c, x.x, x.y, x.z, x.w, hb[0], hb[1]);
                    mma(c, y.x, y.y, y.z, y.w, hb[2], hb[3]);
                    if (t == k) res = pack2(c[0], c[2]);
                }
                st2_x1(p5 + i * 8192, enc(res));
            }
            if (tid == 0) { TRACE(27); TRACE_GT(47); }
        } else if (j < J_END) {
            uint4 a[8], b[4];
            float c[4], e[4];
            const bool own = (warp >> 1) == rk;
            const uint32_t xa = sb + SM_FV + (warp & 1) * 64 + g * 8;
            if (lane == 0) mbar_expect(BAR(MBB), own ? 64 : 0);
#pragma unroll
            for (int i = 0; i < 2; i++) {
                ldfrag(b, sb + SM_FS + rk * 512 + i * 256 + t * 16);
                mbar_wait(BAR(IT_X + i), 0);
                const uint32_t ab = sb + SM_U + B_X * 32768 + i * 16384 + a128;
                load8<true>(a, [&](int s) { return ab + s * 2048; });
                mma8(i ? e : c, a, b);
            }
            c[0] += e[0]; c[2] += e[2];
            if (!own) {
                if (t == 0) st_async2(peer_addr(xa, rk ^ 1), c[0], c[2], peer_addr(BAR(MBB), rk ^ 1));
            } else {
                mbar_wait(BAR(MBB), 0);
                const float2 pp = *(const float2*)(sm + (xa - sb));
                const float mine = t ? c[2] + pp.y : c[0] + pp.x, other = shx(mine, 4);
                const uint32_t w = (warp & 1) * 8 + t * 4 + (g >> 1), val = enc(pack2(mine, other));
                if (t < 2 && !(g & 1)) {
                    if (j < J_RED) st2_x1(gs + B_MB * 4096 + (j - NFF) * 16 + w, val);
                    else sts32(sb + SM_FV + 256 + w * 4, val);
                }
                __syncwarp();
                if (j >= J_RED && lane < 4) mbar_arrive(BAR(QB));
                if (lane == 0) TRACE(11);
            }
        }
    } else {
        const int u8 = tid - 128, w8 = warp - 4;
        const int v = w8 >> 2, wq4 = w8 & 3;
        {
            const float c0 = bflo(in1), c1 = bfhi(in1);
            sts32(sb + SM_FS + frag_off(2 * u8), pack2(__fdividef(c0, 1.f + __expf(-c0)), __fdividef(c1, 1.f + __expf(-c1))));
        }
        bar_sync(1, 256);
        asm volatile("barrier.cluster.wait.aligned;" ::: "memory");
        uint4 a[8], b[4]; float c[4];
        if (w8 < 2) {
            ldfrag(b, sb + SM_FS + (j >> 5) * 256 + t * 16);
            mbar_wait(BAR(IT_MODA), 0);
            if (u8 == 0) TRACE(12);
            const uint32_t ab = sb + SM_XA + w8 * 4096 + a16;
            load8<true>(a, [&](int s) { return ab + s * 512; });
            mma8(c, a, b);
            if (t < 2) st2_x1(gs + (B_HA + ((j >> 4) & 1) * 2 + w8) * 4096 + (j >> 5) * 256 + (j & 15) * 16 + t * 8 + g, encf(t ? c[2] : c[0]));
        }
        {
            mbar_wait(BAR(IT_WQ + 2 * v <= NCP ? 1 : IT_WQ + 2 * v), 0); mbar_wait(BAR(IT_WQ + 2 * v + 1 <= NCP ? 1 : IT_WQ + 2 * v + 1), 0);
            const uint32_t ab = sb + SM_U + 4 * 32768 + v * 16384 + a128;
            load8<true>(a, [&](int s) { return ab + s * 2048; });
            if (lane == 0) mbar_arrive(BAR(EB_WQ));
            bar_sync(5, 384);
            if (u8 == 0) TRACE(13);
            ldfrag(b, sb + SM_FV + v * 256 + t * 16);
            mma8(c, a, b);
            if (t < 2) {
                const float qv = t ? c[2] : c[0];
                const uint32_t qa_ = sb + SM_QX + ((rk * 2 + v) * 64 + wq4 * 16 + t * 8 + g) * 4;
                asm volatile("st.async.weak.shared::cluster.mbarrier::complete_tx::bytes.f32 [%0], %1, [%2];"
                             :: "r"(peer_addr(qa_, rk ^ 1)), "f"(qv), "r"(peer_addr(BAR(QB), rk ^ 1)) : "memory");
                sts32(qa_, __float_as_uint(qv));
            }
            __syncwarp();
            if (lane == 0) mbar_expect(BAR(QB), 64);
        }
        {
            mbar_wait(BAR(IT_WUK + v), 0); mbar_wait(BAR(IT_WUK + v + 2), 0);
            const uint32_t ab = sb + SM_U + 5 * 32768 + (w8 * 16 + r8 + 8 * lb3) * 128;
            const uint32_t x16 = (lb4 ^ r8) * 16;
            load8<false>(a, [&](int s) { return ab + (s & 1) * 16384 + (x16 ^ ((s >> 1) * 32)); });
            bar_sync(6, 384);
            if (u8 == 0) TRACE(14);
            b[0] = lds128(sb + SM_FQ + t * 16); b[1] = lds128(sb + SM_FQ + 64 + t * 16);
            float e[4] = {0.f, 0.f, 0.f, 0.f};
            c[0] = c[1] = c[2] = c[3] = 0.f;
#pragma unroll
            for (int k = 0; k < 4; k++) {
                const uint32_t b0 = (k & 1) ? b[k >> 1].z : b[k >> 1].x, b1 = (k & 1) ? b[k >> 1].w : b[k >> 1].y;
                mma(c, a[2 * k].x, a[2 * k].y, a[2 * k].z, a[2 * k].w, b0, b1);
                mma(e, a[2 * k + 1].x, a[2 * k + 1].y, a[2 * k + 1].z, a[2 * k + 1].w, b0, b1);
            }
            const float mine = ((t & 1) ? ((t & 2) ? e[2] : e[0]) : ((t & 2) ? c[2] : c[0])) * 0.12751743f;
            const float other = shx(mine, 4);
            if (!(g & 1)) st2_x1(gs + (B_QA + rk * 8 + ((j >> 1) & 1) * 4 + (j >> 5)) * 4096 + w8 * 128 + ((j >> 2) & 7) * 16 + (g >> 1) * 4 + t, enc(pack2(mine, other)));
            if (u8 == 0) TRACE(15);
        }
        const uint32_t cls = ldcls();
        __nanosleep(QA_DELAY);
        {
            uint4 qb[8];
            const uint32_t* pq = gs + near_off(B_QA + rk * 8 + wq4, cls) + lane * 4;
            const uint32_t* pq2 = gs + near_off(B_QA + rk * 8 + 4 + wq4, cls) + lane * 4;
            if (lane == 0) {
                mbar_expect(BAR(QT), 4096);
                asm volatile("cp.async.bulk.shared::cluster.global.mbarrier::complete_tx::bytes [%0], [%1], 4096, [%2];"
                             :: "r"(sb + SM_U + 5 * 32768 + w8 * 4096), "l"(gs + near_off(B_QA + rk * 8 + w8, cls)), "r"(BAR(QT)) : "memory");
            }
            const uint32_t qs = sb + SM_U + 5 * 32768 + wq4 * 4096 + lane * 16;
            mbar_wait(BAR(QT), 0);
#pragma unroll
            for (int i = 0; i < 8; i++) { a[i] = lds128(qs + i * 512); qb[i] = lds128(qs + 16384 + i * 512); }
            poll<512, QA_SLEEP, true>(a, pq);
            poll<512, QA_SLEEP, true>(qb, pq2);
            if (lane == 0) mbar_arrive(BAR(EB_WUK));
            auto add2 = [](uint32_t x, uint32_t y) { uint32_t r; asm("add.rn.bf16x2 %0, %1, %2;" : "=r"(r) : "r"(x), "r"(y)); return r; };
#pragma unroll
            for (int i = 0; i < 8; i++) a[i] = make_uint4(add2(a[i].x, qb[i].x), add2(a[i].y, qb[i].y), add2(a[i].z, qb[i].z), add2(a[i].w, qb[i].w));
        }
        if (u8 == 0) TRACE(8);
        {
            float m = -INFINITY, l = 0.f;
            uint32_t xl = sb + SM_XB + w8 * 2048 + lane * 16, xr = peer_addr(xl, rk ^ 1), bsr = peer_addr(BAR(SF0 + v), rk ^ 1);
            uint32_t pa = sb + SM_XA + v * 2048 + wq4 * 512 + lane * 16, ma = sb + SM_MX + v * 128 + (wq4 * 8 + g) * 4;
            uint32_t fb = BAR(IT_CKV + v * 2), sf = BAR(SF0 + v);
            uint32_t dlo = __reduce_or_sync(0xffffffffu, (((sb + SM_U + v * 16384) & 0x3FFFFu) >> 4) | 0x10000u);
            if (STAG && v) __nanosleep(STAG);
#pragma unroll 1
            for (int n = 0; n < NUNITS; n++) {
                float d[2][16], sc[8];
#pragma unroll
                for (int i = 0; i < 2; i++) {
                    mbar_wait(fb + i * 8, 0);
                    wg_fence();
#pragma unroll
                    for (int s = 0; s < 8; s++) wgmma_rs_n32(d[i], a[s], (0x40000080ull << 32) | (dlo + i * 512 + (s >> 2) * 64 + (s & 3) * 2), s);
                    wg_commit();
                }
#pragma unroll
                for (int i = 0; i < 2; i++) {
                    if (i) wg_wait0(); else wg_wait1();
#pragma unroll
                    for (int k = 0; k < 16; k++) asm volatile("" : "+f"(d[i][k]) :: "memory");
                    sc[4 * i] = d[i][0] + d[i][6]; sc[4 * i + 1] = d[i][1] + d[i][7]; sc[4 * i + 2] = d[i][8] + d[i][14]; sc[4 * i + 3] = d[i][9] + d[i][15];
                    asm volatile("st.async.weak.shared::cluster.mbarrier::complete_tx::bytes.v4.f32 [%0], {%1, %2, %3, %4}, [%5];"
                                 :: "r"(xr + i * 1024), "f"(sc[4 * i]), "f"(sc[4 * i + 1]), "f"(sc[4 * i + 2]), "f"(sc[4 * i + 3]), "r"(bsr) : "memory");
                }
                if (u8 == 128) TRACE_Q(56 + (n < 6 ? n : -40));
                if (n >= 3) mbar_wait(BAR(EB_UNIT0 + n - 3), 0);
                dlo += n == 5 ? -5 * 2048 : 2048;
                fb += 32; xr ^= 512; bsr += 16;
                pin(fb); pin(xr); pin(bsr);
                mbar_wait(sf, 0);
                const float4 x = ldsf4(xl), y = ldsf4(xl + 1024);
                sc[0] += x.x; sc[1] += x.y; sc[2] += x.z; sc[3] += x.w; sc[4] += y.x; sc[5] += y.y; sc[6] += y.z; sc[7] += y.w;
                float pr[8];
#pragma unroll
                for (int i = 0; i < 8; i++) pr[i] = ex2(sc[i] - m);
                float mx = fmaxf(fmaxf(fmaxf(sc[0], sc[1]), fmaxf(sc[2], sc[3])), fmaxf(fmaxf(sc[4], sc[5]), fmaxf(sc[6], sc[7])));
                if (__builtin_expect(__any_sync(0xffffffffu, mx > m), 0)) {
                    mx = fmaxf(mx, shx(mx, 1));
                    mx = fmaxf(mx, shx(mx, 2));
                    const float mn = fmaxf(m, ceilf(mx * 0.0625f) * 16.f);
                    l *= ex2(m - mn);
                    m = mn;
#pragma unroll
                    for (int i = 0; i < 8; i++) pr[i] = ex2(sc[i] - m);
                }
                stsf(ma, m);
                asm volatile("st.shared.v4.u32 [%0], {%1, %2, %3, %4};" :: "r"(pa), "r"(pack2(pr[0], pr[1])), "r"(pack2(pr[2], pr[3])),
                             "r"(pack2(pr[4], pr[5])), "r"(pack2(pr[6], pr[7])) : "memory");
                __syncwarp();
                if (lane == 0) mbar_arrive(sf + (PF0 - SF0) * 8);
                l += ((pr[0] + pr[1]) + (pr[2] + pr[3])) + ((pr[4] + pr[5]) + (pr[6] + pr[7]));
                xl ^= 512; sf += 16; ma += 256; pa += (n == 2 || n == 5) ? -8192 : 4096;
            }
            l += shx(l, 1);
            l += shx(l, 2);
            float2* mlx = (float2*)(sm + SM_MX + 2048) + wq4 * 8 + g;
            if (v == 0) { *mlx = make_float2(m, l); bar_arrive(11, 256); }
            else {
                mbar_wait(BAR(JD), 0);
                bar_sync(11, 256);
                const float2 o = *mlx;
                const float mn = fmaxf(m, o.x);
                l = l * ex2(m - mn) + o.y * ex2(o.x - mn);
                if ((wq4 >> 1) == rk) st_x4(gs + (B_ML + wq4 * 8 + g) * 4096 + (t >> 1) * 1024 + (j >> 1) * 8 + (t & 1) * 4, encf(mn), encf(l), 1u, 1u);
            }
        }
        const int pi = j < NFF ? rk * 128 + w8 * 16 + (lane & 15) : ((j - J_RED) & 15) * 16 + v * 8 + lb4 * 4 + wq4;
        const uint32_t xw = *(const uint32_t*)(xin + 2 * pi);
        const uint32_t* pm = gs + near_off(B_MB, cls) + pi;
        const uint32_t* pb = gs + near_off(B_E2 + (j >> 4), cls) + (((j >> 3) & 1) * 2 + lb4) * 256 + (lane & 15) * 2;
        pin(pm); pin(pb);
        {
            const uint32_t ab = sb + SM_U + B_WUV * 32768 + v * 4096 + a128;
            uint32_t pa = sb + SM_PB + wq4 * 320 + frag_off(64 * v + 32 * (g >> 2) + 16 * (t & 1) + 8 * (t >> 1) + 2 * (g & 3));
            uint32_t fa = sb + SM_PB + g * 320 + t * 16;
            const uint32_t* pe = gs + G_E1 + j * 8192 + (w8 >> 1) * 2048 + ((((cls >> 1) ^ (w8 >> 1)) & 1) << 10) + (((w8 & 1) * 16 + t) * 8 + g) * 4;
            uint32_t* p2 = gs + (B_E2 + (j >> 4)) * 4096 + (t >> 1) * 1024 + (j & 12) * 64 + w8 * 32 + (j & 3) * 8 + (g & 6) + (t & 1);
            pin(pa); pin(fa); pin(pe); pin(p2);
            const uint32_t mk = (g & 1) ? 0xffff0000u : 0x0000ffffu, m0 = (g & 2) ? 0u : mk, m1 = (g & 2) ? mk : 0u;
            uint4 pv[4];
            bool hv = false;
            bar_sync(3, 416);
            uint4 wa = lds128(sb + SM_W + (wq4 * 4 + t) * 16);
            uint32_t wb[8] = {wa.x & m0, wa.x & m1, wa.y & m0, wa.y & m1, wa.z & m0, wa.z & m1, wa.w & m0, wa.w & m1};
            pv[0] = pv[1] = pv[2] = pv[3] = make_uint4(0u, 0u, 0u, 0u);
            poll<512, E1_SLEEP, true>(pv, pe, [&]() {
                if (!hv) {
                    hv = __all_sync(0xffffffffu, mbar_test(BAR(IT_WUV + t), 0));
                    if (hv) load8<true>(a, [&](int s) { return ab + (s >> 1) * 8192 + (s & 1) * 2048; });
                }
            });
            if (lane == 0) TRACE_Q(48 + w8);
            if (u8 == 0) TRACE_Q(18);
            float lo, hi2;
            float2 inv;
#pragma unroll 1
            for (int pass = 0;; pass++) {
                float e[4][4];
#pragma unroll
                for (int i = 0; i < 4; i++) {
                    e[i][0] = e[i][1] = e[i][2] = e[i][3] = 0.f;
                    mma(e[i], pv[i].x, pv[i].y, pv[i].z, pv[i].w, wb[2 * i], wb[2 * i + 1]);
                }
                const float r0 = (t & 2) ? (e[0][2] + e[1][2]) + (e[2][2] + e[3][2]) : (e[0][0] + e[1][0]) + (e[2][0] + e[3][0]);
                const float r1 = (t & 2) ? (e[0][3] + e[1][3]) + (e[2][3] + e[3][3]) : (e[0][1] + e[1][1]) + (e[2][1] + e[3][1]);
                const uint32_t hi = pack2(r0, r1);
                sts32(pa, hi); sts32(pa + 1280, pack2(r0 - bflo(hi), r1 - bfhi(hi)));
                if (!hv) {
#pragma unroll 1
                    for (int i = 0; i < 4; i++) mbar_wait(BAR(IT_WUV + i), 0);
                    load8<true>(a, [&](int s) { return ab + (s >> 1) * 8192 + (s & 1) * 2048; });
                    hv = true;
                }
                bar_sync(1, 256);
                if (u8 == 0) TRACE(19);
                ldfrag(b, fa);
                mma8(c, a, b);
                mbar_wait(BAR(WR), 0);
                asm volatile("ld.shared.v2.f32 {%0, %1}, [%2];" : "=f"(inv.x), "=f"(inv.y) : "r"(sb + SM_FQ) : "memory");
                quad_pair(c[0] + c[1], c[2] + c[3], t, lo, hi2);
                if (__builtin_expect(__all_sync(0xffffffffu, pass || __float_as_uint(inv.y) == 0), 1)) break;
                wa = lds128(sb + SM_W2 + (wq4 * 4 + t) * 16);
                wb[0] = wa.x & m0; wb[1] = wa.x & m1; wb[2] = wa.y & m0; wb[3] = wa.y & m1; wb[4] = wa.z & m0; wb[5] = wa.z & m1; wb[6] = wa.w & m0; wb[7] = wa.w & m1;
                bar_sync(1, 256);
            }
            if (!(g & 1)) st_x1(p2, enc(pack2(lo * inv.x, hi2 * inv.x)));
            bar_arrive(4, 288);
            if (u8 == 0) TRACE(20);
        }
        uint32_t mb[3] = {0u, 0u, 0u};
        if (j < NFF) poll_start<1024>(mb, pm);
        uint4 a2[8];
        if (v == 0) {
            const uint32_t ab = sb + SM_U + B_WO * 32768 + a128;
            uint32_t* p3 = gs + (B_E3 + ((j >> 1) & 3)) * 4096 + (t >> 1) * 1024 + (rk * 2 + (wq4 >> 1)) * 256 + (j >> 3) * 16 + (wq4 & 1) * 8 + (t & 1) * 4 + (g >> 1);
            pin(p3);
            uint2 bb[8];
#pragma unroll
            for (int i = 0; i < 8; i++) bb[i] = make_uint2(0u, 0u);
            bool ho = false;
            auto ldo = [&]() { load8<true>(a, [&](int s) { return ab + s * 2048; }); load8<true>(a2, [&](int s) { return ab + 16384 + s * 2048; }); };
            auto idle = [&]() {
                if (!ho) {
                    ho = __all_sync(0xffffffffu, mbar_test(BAR(IT_WO + t), 0));
                    if (ho) ldo();
                }
            };
            poll<128, 0, true>(bb, pb, idle);
            if (!ho) {
#pragma unroll 1
                for (int i = 0; i < 4; i++) mbar_wait(BAR(IT_WO + i), 0);
                ldo();
            }
            if (u8 == 0) TRACE(21);
            float e[4][4];
#pragma unroll
            for (int s = 0; s < 16; s++) {
                const uint4& x = (s & 2) ? a2[(s >> 2) * 2 + (s & 1)] : a[(s >> 2) * 2 + (s & 1)];
                const uint2& y = bb[(s >> 2) * 2 + (s & 1)];
                if (s < 4) e[s][0] = e[s][1] = e[s][2] = e[s][3] = 0.f;
                mma(e[s & 3], x.x, x.y, x.z, x.w, y.x, y.y);
            }
            float lo, hi;
            quad_pair((t & 2) ? (e[2][0] + e[3][0]) + (e[2][1] + e[3][1]) : (e[0][0] + e[1][0]) + (e[0][1] + e[1][1]),
                      (t & 2) ? (e[2][2] + e[3][2]) + (e[2][3] + e[3][3]) : (e[0][2] + e[1][2]) + (e[0][3] + e[1][3]), t, lo, hi);
            if (!(g & 1)) st_x1(p3, enc(pack2(lo, hi)));
            bar_arrive(1, 256);
            if (u8 == 0) TRACE(22);
        } else bar_sync(1, 256);
        if (j < NFF) {
            const uint32_t* p3 = gs + near_off(B_E3 + rk * 2 + v, cls) + wq4 * 256 + lane;
            uint32_t za = sb + SM_FZ + lb4 * 576 + frag_off(w8 * 32 + (lane & 15) * 2);
            uint32_t fa = sb + SM_FZ + (g & 3) * 576 + lb4 * 256 + t * 16, ya = sb + SM_Y + u8 * 4;
            poll<1024, MB_SLEEP, true>(mb, pm);
            const uint32_t kk = pack2(1.f + bflo(mb[2]), 1.f + bfhi(mb[2]));
            sts32(za + 2 * 576, lb4 ? mb[1] : kk);
            uint32_t e3[8] = {0u, 0u, 0u, 0u, 0u, 0u, 0u, 0u};
            uint32_t ra = peer_addr(sb + SM_RED + (rk * 2 + v) * 512 + ((wq4 & 1) * 16 + (t >> 1) * 8 + g) * 16 + (t & 1) * 8, wq4 >> 1), tbo = peer_addr(BAR(QB), wq4 >> 1);
            pin(za); pin(fa); pin(ya); pin(ra); pin(tbo);
            if (lane == 0) mbar_expect(BAR(QB), 256);
            const uint32_t gb = BAR(IT_X + v * 2), ab = sb + SM_U + (B_X + v) * 32768 + a128;
            bool early = false, early2 = false;
            auto ldw = [&]() {
                if (!early) {
                    early = __all_sync(0xffffffffu, mbar_test(gb, 0));
                    if (early) load8<true>(a, [&](int s) { return ab + s * 2048; });
                }
                if (!early2) {
                    early2 = __all_sync(0xffffffffu, mbar_test(gb + 8, 0));
                    if (early2) load8<true>(a2, [&](int s) { return ab + 16384 + s * 2048; });
                }
            };
            poll<128, 0, true>(e3, p3, ldw);
            if (u8 == 0) TRACE(23);
            const float s0 = sumlo(e3), s1 = sumhi(e3);
            const float y0 = fmaf(bflo(mb[0]), s0 + shx(s0, 16), bflo(xw)), y1 = fmaf(bfhi(mb[0]), s1 + shx(s1, 16), bfhi(xw));
            stsf(ya, lb4 ? y1 : y0);
            const float z0 = y0 * bflo(kk), z1 = y1 * bfhi(kk);
            const uint32_t zh = pack2(z0, z1);
            sts32(za, lb4 ? pack2(z0 - bflo(zh), z1 - bfhi(zh)) : zh);
            bar_sync(7, 288);
            if (u8 == 0) TRACE(24);
            ldfrag(b, fa);
            if (!early) { mbar_wait(gb, 0); load8<true>(a, [&](int s) { return ab + s * 2048; }); }
            {
                float e[4][4];
#pragma unroll
                for (int s = 0; s < 16; s++) {
                    if (s == 8 && !early2) { mbar_wait(gb + 8, 0); load8<true>(a2, [&](int q) { return ab + 16384 + q * 2048; }); }
                    const uint4& x = s < 8 ? a[s] : a2[s & 7];
                    const uint4& y = b[(s >> 1) & 3];
                    float (&d)[4] = e[(s >> 3) * 2 + (s & 1)];
                    if (!(s & 6)) d[0] = d[1] = d[2] = d[3] = 0.f;
                    mma(d, x.x, x.y, x.z, x.w, (s & 1) ? y.z : y.x, (s & 1) ? y.w : y.y);
                }
                const bool hi = t >> 1;
                const float k0 = hi ? e[2][2] + e[3][2] : e[0][0] + e[1][0], k1 = hi ? e[2][3] + e[3][3] : e[0][1] + e[1][1];
                const float o0 = hi ? e[2][0] + e[3][0] : e[0][2] + e[1][2], o1 = hi ? e[2][1] + e[3][1] : e[0][3] + e[1][3];
                st_async2(ra, k0 + shx(o0, 2), k1 + shx(o1, 2), tbo);
            }
        } else if (j >= J_RED && j < J_END) {
            uint32_t ga[1], e3[1];
            poll<0, MB_SLEEP>(ga, pm);
            poll<0, 100>(e3, gs + near_off(B_E3 + (pi >> 6), cls) + (pi & 48) * 16 + (lane & 15) * 16 + (pi & 15));
            float y0 = bflo(e3[0]), y1 = bfhi(e3[0]);
#pragma unroll
            for (int o = 8; o; o >>= 1) { y0 += shx(y0, o); y1 += shx(y1, o); }
            y0 = fmaf(bflo(ga[0]), y0, bflo(xw)); y1 = fmaf(bfhi(ga[0]), y1, bfhi(xw));
            uint32_t gb = 0;
            auto ldg = [&]() { if (__all_sync(0xffffffffu, mbar_test(BAR(QB), 1))) gb = lds32(sb + SM_FV + 256 + (pi & 15) * 4); };
            uint32_t* po = (uint32_t*)out + pi;
            pin(po);
            const uint32_t nz = lane < NFF / 2 ? 0u : 0x80008000u;
            uint2 yv[2] = {make_uint2(nz, nz), make_uint2(nz, nz)};
            poll<NFF * 32, 0, true>(yv, gs + near_off(B_E5 + j - J_RED, cls) + lane * 16 + w8 * 2, ldg);
            if (u8 == 0) TRACE(26);
            const float l0 = bflo(yv[0].x) + bflo(yv[1].x), h0 = bfhi(yv[0].x) + bfhi(yv[1].x);
            const float l1 = bflo(yv[0].y) + bflo(yv[1].y), h1 = bfhi(yv[0].y) + bfhi(yv[1].y);
            float s0 = (lb4 ? h0 : l0) + shx(lb4 ? l0 : h0, 16), s1 = (lb4 ? h1 : l1) + shx(lb4 ? l1 : h1, 16);
#pragma unroll
            for (int o = 8; o; o >>= 1) { s0 += shx(s0, o); s1 += shx(s1, o); }
            if (__any_sync(0xffffffffu, !gb)) { mbar_wait(BAR(QB), 1); ldg(); }
            if (!(lane & 15)) *po = pack2(fmaf(bflo(gb), s0, y0), fmaf(bfhi(gb), s1, y1));
            if (u8 == 0) TRACE(27);
        }
    }
}

typedef CUresult (*EncFn)(CUtensorMap*, CUtensorMapDataType, cuuint32_t, void*, const cuuint64_t*, const cuuint64_t*,
                          const cuuint32_t*, const cuuint32_t*, CUtensorMapInterleave, CUtensorMapSwizzle,
                          CUtensorMapL2promotion, CUtensorMapFloatOOBfill);

void make_map(EncFn enc_fn, CUtensorMap* m, const void* p, cuuint64_t d0, cuuint64_t d1, cuuint64_t d2, cuuint64_t d3,
              cuuint64_t s1, cuuint64_t s2, cuuint64_t s3, cuuint32_t b0, cuuint32_t b1, cuuint32_t b2, cuuint32_t b3, CUtensorMapSwizzle sw) {
    const cuuint64_t dims[4] = {d0, d1, d2, d3}, strides[3] = {s1, s2, s3};
    const cuuint32_t box[4] = {b0, b1, b2, b3}, es[4] = {1, 1, 1, 1};
    enc_fn(m, CU_TENSOR_MAP_DATA_TYPE_BFLOAT16, 4, (void*)p, dims, strides, box, es,
           CU_TENSOR_MAP_INTERLEAVE_NONE, sw, CU_TENSOR_MAP_L2_PROMOTION_L2_64B, CU_TENSOR_MAP_FLOAT_OOB_FILL_NONE);
}

uint32_t* scratch = nullptr;

struct Tune { const char* win; const char* late; int tau, t_off; const char* tail[3][4]; };
Tune tune = {"66666666655555555555555555555522222222222",
             "00000000000000000888888888888888888888888", 320, -240,
             {{"VVVVOOOOguguDD", "zzzzzzzzzzzzzz", "77779999999966", "addd7dddd888na"},
              {"VMVMVVOOOO", "zzzzzzzzzz", "8888889999", "2999998bbb"},
              {"VVVVOOOOMM", "zzzzzzzzzz", "9999999988", "aeee1fffki"}}};
bool ready = false;

}

extern "C" void kernel_launch(void* const* d_in, const int* in_sizes, int n_in, void* d_out, int out_size) {
    (void)in_sizes; (void)n_in; (void)out_size;
    static Maps maps;
    static const void* cached[12] = {};
    bool same = ready;
    for (int i = 0; i < 12 && same; i++) same = cached[i] == d_in[i];
    if (!same) {
        void* fn = nullptr;
        cudaDriverEntryPointQueryResult qr;
        cudaGetDriverEntryPoint("cuTensorMapEncodeTiled", &fn, cudaEnableDefault, &qr);
        EncFn e = (EncFn)fn;
        const CUtensorMapSwizzle S128 = CU_TENSOR_MAP_SWIZZLE_128B;
        make_map(e, &maps.m[MP_WQ], d_in[2], 64, 512, 64, 1, 8192, 128, 8192, 64, 64, 1, 1, S128);
        make_map(e, &maps.m[MP_WUK], d_in[3], 64, 512, 64, 1, 8192, 128, 8192, 64, 64, 1, 1, S128);
        make_map(e, &maps.m[MP_CKV], d_in[1], 64, 8, 8, 4096, 1024, 128, 8192, 64, 8, 4, 2, S128);
        make_map(e, &maps.m[MP_MODB], d_in[11], 3072, 512, 1, 1, 6144, 6144, 6144, 64, 128, 1, 1, S128);
        make_map(e, &maps.m[MP_WUV], d_in[4], 64, 512, 64, 1, 8192, 128, 8192, 64, 32, 2, 1, S128);
        make_map(e, &maps.m[MP_WO], d_in[5], 512, 4096, 1, 1, 1024, 1024, 1024, 64, 64, 1, 1, S128);
        make_map(e, &maps.m[MP_GATE], d_in[7], 1792, 512, 1, 1, 3584, 3584, 3584, 64, 128, 1, 1, S128);
        make_map(e, &maps.m[MP_UP], d_in[8], 1792, 512, 1, 1, 3584, 3584, 3584, 64, 128, 1, 1, S128);
        make_map(e, &maps.m[MP_DOWN], d_in[9], 64, 1792, 8, 1, 1024, 128, 1024, 64, 32, 4, 1, S128);
        for (int r = 0; r < 3; r++) {
            int ids[56], cnt[128] = {}, tn = tune.t_off - (W0 - 1) * tune.tau;
            uint2* sc = maps.sched[r];
            auto dig = [](char ch) { return ch >= 'a' ? ch - 'a' + 10 : ch >= 'A' ? ch - 'A' + 36 : ch - '0'; };
            for (int i = 0; i < 56; i++) sc[i] = make_uint2(0u, 0u);
            for (int i = 0;; i++) {
                int id = i, buf, dep, w, wl;
                if (i < IT_WUV) {
                    const int u = (i - IT_CKV) >> 2;
                    buf = i < IT_CKV ? 4 + ((i - 1) >> 2) : u % 6;
                    dep = i < IT_CKV || u < 4 ? -1 : u < 6 ? EB_WQ + u - 4 : EB_UNIT0 + u - 6;
                    w = dig(tune.win[i]); wl = dig(tune.late[i]);
                    if (i) tn += tune.tau;
                } else {
                    const char ch = tune.tail[r][0][i - IT_WUV];
                    if (!ch) break;
                    buf = ch == 'V' ? B_WUV : ch == 'O' ? B_WO : ch == 'D' ? B_DN : ch == 'u' ? B_X + 1 : B_X;
                    id = (ch == 'V' ? IT_WUV : ch == 'O' ? IT_WO : ch == 'D' ? IT_DOWN : ch == 'u' ? IT_X + 2 : IT_X) + cnt[(int)ch]++;
                    dep = EB_UNIT0 + (buf < 2 ? buf + 6 : buf);
                    w = dig(tune.tail[r][1][i - IT_WUV]); wl = dig(tune.tail[r][2][i - IT_WUV]);
                    tn += 32 * dig(tune.tail[r][3][i - IT_WUV]);
                }
                if (id < IT_X ? (id - 1) & 3 : (id - IT_X) & 1) dep = -1;
                ids[i] = id;
                auto back = [&](int d) { return i < d ? 0 : (ids[i - d] && ids[i - d] <= NCP ? 1 : ids[i - d]) + 1; };
                sc[i].x = id | (buf * 4 + (id < IT_X ? (id - 1) & 3 : ((id - IT_X) & 1) * 2)) << 6 | (dep + 1) << 11 | (w > 32 ? NEVER + 1 : back(w)) << 18 | (wl ? back(wl) : 0) << 25;
                const int mp = id < IT_CKV ? MP_WQ + ((id - 1) >> 2) : id < IT_WUV ? MP_CKV : id < IT_WO ? MP_WUV : id < IT_X ? MP_WO
                             : id >= IT_DOWN ? MP_DOWN : r ? MP_MODB : MP_GATE + ((id - IT_X) >> 1);
                const int step = mp == MP_CKV ? id - IT_CKV : mp == MP_WUV ? (id - IT_WUV) * 2 : mp == MP_DOWN ? id - IT_DOWN : id < IT_X ? (id - 1) & 3 : ((id - IT_X) & 1) * 2;
                sc[i].y = (tn & 0xffff) | (mp & 15) << 16 | step << 20;
            }
        }
        cudaGetSymbolAddress((void**)&scratch, g_scratch);
        scratch = (uint32_t*)(((uintptr_t)scratch + (2u << 20) - 1) & ~(uintptr_t)((2u << 20) - 1));
        cudaFuncSetAttribute(fused_kernel, cudaFuncAttributeMaxDynamicSharedMemorySize, SM_TOTAL);
        for (int i = 0; i < 12; i++) cached[i] = d_in[i];
        ready = true;
    }
    const First f = {{(const uint8_t*)d_in[2], (const uint8_t*)d_in[11]}, {(const __nv_bfloat16*)d_in[0], (const __nv_bfloat16*)d_in[10]}};
    fused_kernel<<<NCTA, NTHREADS, SM_TOTAL>>>(f, (__nv_bfloat16*)d_out, scratch, maps);
}
```

```cpp
#include <cuda_runtime.h>
#include <cuda_bf16.h>
#include <cuda.h>
#include <stdint.h>
#include <limits.h>

namespace {

constexpr int NCTA = 128;
constexpr int NTHREADS = 512;
constexpr int NUNITS = 8;
constexpr int NFF = 56, J_RED = 104, J_END = 120;
constexpr uint32_t SPIN_LIMIT = 1u << 22;

#define NEAR_CLK 390
#define E1_EARLY 50
#define STAG 300
#define NUMA 1
#define NPROBE 5
#define NCP 2
#define W0 4
#define RD_ITEM 15
#define JAN_SLEEP 100
#define RD_SLEEP 400
#define HA_DELAY 200
#define H_SLEEP 100
#define QA_DELAY 600
#define QA_SLEEP 200
#define ML_DELAY 300
#define E1_SLEEP 50
#define MB_SLEEP 100
constexpr int B_WUV = 2, B_WO = 3, B_X = 4  , B_DN = 0;

constexpr int SM_U = 0;
constexpr int SM_XA = 6 * 32768;
constexpr int SM_XB = SM_XA + 12288;
constexpr int SM_MX = SM_XB + 16384;
constexpr int SM_FZ = SM_XB + 8192;
constexpr int SM_PB = SM_XB;
constexpr int SM_Y = SM_XB + 12288;
constexpr int SM_RED = SM_XB + 4096;
constexpr int SM_FS = SM_XB + 20480;
constexpr int SM_FV = SM_FS + 1024;
constexpr int SM_QX = SM_XA + 8192;
constexpr int SM_FQ = SM_FV + 512;
constexpr int SM_CLS = SM_FQ + 128;
constexpr int SM_W = SM_FQ + 256;
constexpr int SM_W2 = SM_MX + 2304;
constexpr int SM_SCR = SM_XA + 9216;
constexpr int SM_TR = SM_XB + 19456;
constexpr int SM_BAR = SM_W + 256;
constexpr int SM_TOTAL = SM_BAR + 1024;
static_assert(SM_TOTAL <= 232448, "smem");

enum { IT_MODA = 0, IT_WQ = 1, IT_WUK = 5, IT_CKV = 9, IT_WUV = 41, IT_WO = 45, IT_X = 49  , IT_DOWN = 53, NITEMS = 55,
       NEVER = 63,
       SF0 = 64,
       PF0 = 80,
       EB_UNIT0 = 96, MBB = 103,
       EB_WQ = 104, EB_WUK, QT, QB, JD, WR };

enum { MP_WQ = 0, MP_WUK, MP_CKV, MP_WUV, MP_DOWN, MP_WO, MP_GATE, MP_UP, MP_MODB, NMAPS };
struct First { const uint8_t* w[2]; const __nv_bfloat16* v[2]; };
struct Maps { CUtensorMap m[NMAPS]; uint2 sched[3][56]; };

enum { B_HA = 0,
       B_MB = 6,
       B_RD = 7,
       B_E2 = 8,
       B_QA = 16,
       B_ML = 32,
       B_E5 = 64,
       B_E3 = 80,
       B_PR = 96,
       B_TR = 100 };
constexpr int G_E1 = 1 << 19;
constexpr int G_TR = B_TR * 4096;
__device__ __align__(1024) uint32_t g_scratch[(8 << 20) / 4];

#define TRACE(slot) do {} while (0)
#define TRACE_Q(slot) do {} while (0)
#define TRACE_GT(slot) do {} while (0)

__device__ __forceinline__ uint32_t s2u(const void* p) { return (uint32_t)__cvta_generic_to_shared(p); }
__device__ __forceinline__ void mbar_init(uint32_t b, int c) { asm volatile("mbarrier.init.shared::cta.b64 [%0], %1;" :: "r"(b), "r"(c) : "memory"); }
__device__ __forceinline__ void mbar_expect(uint32_t b, uint32_t bytes) { asm volatile("mbarrier.arrive.expect_tx.shared::cta.b64 _, [%0], %1;" :: "r"(b), "r"(bytes) : "memory"); }
__device__ __forceinline__ void mbar_arrive(uint32_t b) { asm volatile("mbarrier.arrive.shared::cta.b64 _, [%0];" :: "r"(b) : "memory"); }
__device__ __forceinline__ void mbar_wait(uint32_t b, uint32_t ph) {
    asm volatile("{\n.reg .pred p;\nW: mbarrier.try_wait.parity.shared::cta.b64 p, [%0], %1;\n@!p bra W;\n}" :: "r"(b), "r"(ph) : "memory");
}
__device__ __forceinline__ void mbar_waitb(uint32_t b, uint32_t ph) {
    asm volatile("{\n.reg .pred p;\n.reg .u32 n;\nmov.u32 n, 0;\n"
                 "W: mbarrier.try_wait.parity.shared::cta.b64 p, [%0], %1;\n@p bra D;\n"
                 "add.u32 n, n, 1;\nsetp.lt.u32 p, n, 0x100000;\n@p bra W;\ntrap;\nD:\n}" :: "r"(b), "r"(ph) : "memory");
}
__device__ __forceinline__ uint32_t mbar_test(uint32_t b, uint32_t ph) {
    uint32_t ok;
    asm volatile("{\n.reg .pred p;\nmbarrier.test_wait.parity.shared::cta.b64 p, [%1], %2;\nselp.u32 %0, 1, 0, p;\n}" : "=r"(ok) : "r"(b), "r"(ph) : "memory");
    return ok;
}
__device__ __forceinline__ void bar_sync(int id, int n) { asm volatile("bar.sync %0, %1;" :: "r"(id), "r"(n) : "memory"); }
__device__ __forceinline__ void bar_arrive(int id, int n) { asm volatile("bar.arrive %0, %1;" :: "r"(id), "r"(n) : "memory"); }
__device__ __forceinline__ uint32_t peer_addr(uint32_t a, uint32_t rank) { uint32_t r; asm("mapa.shared::cluster.u32 %0, %1, %2;" : "=r"(r) : "r"(a), "r"(rank)); return r; }
__device__ __forceinline__ void st_async2(uint32_t a, float x, float y, uint32_t bar) {
    asm volatile("st.async.weak.shared::cluster.mbarrier::complete_tx::bytes.v2.f32 [%0], {%1, %2}, [%3];" :: "r"(a), "f"(x), "f"(y), "r"(bar) : "memory");
}
__device__ __forceinline__ uint32_t gtime() { uint32_t t; asm volatile("mov.u32 %0, %%globaltimer_lo;" : "=r"(t)); return t; }
__device__ __forceinline__ void fence_gpu() { asm volatile("fence.acq_rel.gpu;" ::: "memory"); }

__device__ __forceinline__ uint32_t enc(uint32_t b) { uint32_t r; asm("max.u32 %0, %1, 1;" : "=r"(r) : "r"(b)); return r; }
__device__ __forceinline__ uint32_t encf(float f) { return enc(__float_as_uint(f)); }
__device__ __forceinline__ void st_x1(uint32_t* p, uint32_t v) { asm volatile("st.relaxed.gpu.global.u32 [%0], %1;" :: "l"(p), "r"(v) : "memory"); }
__device__ __forceinline__ void st_x4(void* p, uint32_t a, uint32_t b, uint32_t c, uint32_t d) {
    asm volatile("st.relaxed.gpu.global.v4.u32 [%0], {%1, %2, %3, %4};" :: "l"(p), "r"(a), "r"(b), "r"(c), "r"(d) : "memory");
}
__device__ __forceinline__ void st2_x1(uint32_t* p, uint32_t v) { st_x1(p, v); st_x1(p + 1024, v); }
__device__ __forceinline__ void st2_x4(uint32_t* p, uint32_t a, uint32_t b, uint32_t c, uint32_t d) { st_x4(p, a, b, c, d); st_x4(p + 1024, a, b, c, d); }
__device__ __forceinline__ int near_off(int b, uint32_t cls) { return b * 4096 + (((__popc(b & 0x2C) ^ cls) & 1) << 10); }
__device__ __forceinline__ void ld_x(uint32_t& v, const void* p) { asm volatile("ld.relaxed.gpu.global.u32 %0, [%1];" : "=r"(v) : "l"(p) : "memory"); }
__device__ __forceinline__ void ld_x(uint4& v, const void* p) {
    asm volatile("ld.relaxed.gpu.global.v4.u32 {%0, %1, %2, %3}, [%4];" : "=r"(v.x), "=r"(v.y), "=r"(v.z), "=r"(v.w) : "l"(p) : "memory");
}
__device__ __forceinline__ void ld_x(uint2& v, const void* p) { asm volatile("ld.relaxed.gpu.global.v2.u32 {%0, %1}, [%2];" : "=r"(v.x), "=r"(v.y) : "l"(p) : "memory"); }
__device__ __forceinline__ uint32_t minw(uint32_t v) { return v; }
__device__ __forceinline__ uint32_t minw(const uint2& v) { return min(v.x, v.y); }
__device__ __forceinline__ uint32_t minw(const uint4& v) { return min(__vimin3_u32(v.x, v.y, v.z), v.w); }
template <int N> __device__ __forceinline__ uint32_t mint(const uint32_t* m) {
    if constexpr (N == 1) return m[0];
    else if constexpr (N == 2) return min(m[0], m[1]);
    else return __vimin3_u32(mint<(N + 2) / 3>(m), mint<(N + 1) / 3>(m + (N + 2) / 3), mint<N / 3>(m + (N + 2) / 3 + (N + 1) / 3));
}

template <int STRIDE, int S4 = 4 * STRIDE, typename T, int N>
__device__ __forceinline__ void poll_start(T (&v)[N], const void* base) {
#pragma unroll
    for (int i = 0; i < N; i++) ld_x(v[i], (const uint8_t*)base + (i & 3) * STRIDE + (i >> 2) * S4);
}
struct Nop { __device__ void operator()() const {} };
template <int STRIDE, int SLEEP, bool STARTED = false, int S4 = 4 * STRIDE, typename T, int N, typename F = Nop>
__device__ __forceinline__ void poll(T (&v)[N], const void* base, F idle = F()) {
    if (!STARTED) { poll_start<STRIDE, S4>(v, base); idle(); }
#pragma unroll 1
    for (uint32_t it = 0;; it++) {
        uint32_t m[N];
#pragma unroll
        for (int i = 0; i < N; i++) m[i] = minw(v[i]);
        if (__all_sync(0xffffffffu, mint<N>(m) != 0)) break;
        if (SLEEP && it > 0) __nanosleep(SLEEP);
#pragma unroll
        for (int i = 0; i < N; i++) if (!m[i]) ld_x(v[i], (const uint8_t*)base + (i & 3) * STRIDE + (i >> 2) * S4);
        idle();
        if (it > SPIN_LIMIT) __trap();
    }
}

__device__ __forceinline__ float bflo(uint32_t w) { return __uint_as_float(w << 16); }
__device__ __forceinline__ float bfhi(uint32_t w) { return __uint_as_float(w & 0xffff0000u); }
__device__ __forceinline__ uint32_t pack2(float lo, float hi) {
    uint32_t r; asm("cvt.rn.bf16x2.f32 %0, %1, %2;" : "=r"(r) : "f"(hi), "f"(lo)); return r;
}
__device__ __forceinline__ float rbf(float x) { return __uint_as_float(pack2(0.f, x)); }
__device__ __forceinline__ float sumlo(const uint32_t (&v)[8]) { return ((bflo(v[0]) + bflo(v[1])) + (bflo(v[2]) + bflo(v[3]))) + ((bflo(v[4]) + bflo(v[5])) + (bflo(v[6]) + bflo(v[7]))); }
__device__ __forceinline__ float sumhi(const uint32_t (&v)[8]) { return ((bfhi(v[0]) + bfhi(v[1])) + (bfhi(v[2]) + bfhi(v[3]))) + ((bfhi(v[4]) + bfhi(v[5])) + (bfhi(v[6]) + bfhi(v[7]))); }
__device__ __forceinline__ float ex2(float x) { float r; asm("ex2.approx.ftz.f32 %0, %1;" : "=f"(r) : "f"(x)); return r; }
__device__ __forceinline__ float shx(float v, int m) { return __shfl_xor_sync(0xffffffffu, v, m); }
__device__ __forceinline__ uint4 lds128(uint32_t a) { uint4 v; asm volatile("ld.shared.v4.u32 {%0, %1, %2, %3}, [%4];" : "=r"(v.x), "=r"(v.y), "=r"(v.z), "=r"(v.w) : "r"(a) : "memory"); return v; }
__device__ __forceinline__ uint32_t lds32(uint32_t a) { uint32_t v; asm volatile("ld.shared.u32 %0, [%1];" : "=r"(v) : "r"(a) : "memory"); return v; }
__device__ __forceinline__ void sts32(uint32_t a, uint32_t v) { asm volatile("st.shared.u32 [%0], %1;" :: "r"(a), "r"(v) : "memory"); }
__device__ __forceinline__ void sts16(uint32_t a, uint32_t v) { asm volatile("st.shared.u16 [%0], %1;" :: "r"(a), "h"((uint16_t)v) : "memory"); }
__device__ __forceinline__ int frag_off(int k) { return (k >> 5) * 64 + ((k >> 1) & 3) * 16 + ((k >> 4) & 1) * 8 + ((k >> 3) & 1) * 4 + (k & 1) * 2; }

template <bool TRANS>
__device__ __forceinline__ uint4 ldsm(uint32_t a) {
    uint4 r;
    if (TRANS) asm volatile("ldmatrix.sync.aligned.m8n8.x4.trans.shared.b16 {%0, %1, %2, %3}, [%4];" : "=r"(r.x), "=r"(r.y), "=r"(r.z), "=r"(r.w) : "r"(a) : "memory");
    else asm volatile("ldmatrix.sync.aligned.m8n8.x4.shared.b16 {%0, %1, %2, %3}, [%4];" : "=r"(r.x), "=r"(r.y), "=r"(r.z), "=r"(r.w) : "r"(a) : "memory");
    return r;
}
__device__ __forceinline__ void mma(float (&c)[4], uint32_t a0, uint32_t a1, uint32_t a2, uint32_t a3, uint32_t b0, uint32_t b1) {
    asm volatile("mma.sync.aligned.m16n8k16.row.col.f32.bf16.bf16.f32 {%0,%1,%2,%3}, {%4,%5,%6,%7}, {%8,%9}, {%0,%1,%2,%3};"
                 : "+f"(c[0]), "+f"(c[1]), "+f"(c[2]), "+f"(c[3]) : "r"(a0), "r"(a1), "r"(a2), "r"(a3), "r"(b0), "r"(b1));
}
template <bool TRANS, typename F>
__device__ __forceinline__ void load8(uint4 (&a)[8], F addr) {
    __syncwarp();
#pragma unroll
    for (int s = 0; s < 8; s++) a[s] = ldsm<TRANS>(addr(s));
}
__device__ __forceinline__ void mma8(float (&c)[4], const uint4 (&a)[8], const uint4 (&b)[4]) {
    float e[4][4];
#pragma unroll
    for (int s = 0; s < 8; s++) {
        if (s < 4) e[s][0] = e[s][1] = e[s][2] = e[s][3] = 0.f;
        mma(e[s & 3], a[s].x, a[s].y, a[s].z, a[s].w, (s & 1) ? b[s >> 1].z : b[s >> 1].x, (s & 1) ? b[s >> 1].w : b[s >> 1].y);
    }
#pragma unroll
    for (int i = 0; i < 4; i++) c[i] = (e[0][i] + e[1][i]) + (e[2][i] + e[3][i]);
}
__device__ __forceinline__ void ldfrag(uint4 (&b)[4], uint32_t a) {
    asm volatile("ld.shared.v4.u32 {%0,%1,%2,%3}, [%16];\nld.shared.v4.u32 {%4,%5,%6,%7}, [%16+64];\n"
                 "ld.shared.v4.u32 {%8,%9,%10,%11}, [%16+128];\nld.shared.v4.u32 {%12,%13,%14,%15}, [%16+192];\n"
                 : "=r"(b[0].x), "=r"(b[0].y), "=r"(b[0].z), "=r"(b[0].w), "=r"(b[1].x), "=r"(b[1].y), "=r"(b[1].z), "=r"(b[1].w),
                   "=r"(b[2].x), "=r"(b[2].y), "=r"(b[2].z), "=r"(b[2].w), "=r"(b[3].x), "=r"(b[3].y), "=r"(b[3].z), "=r"(b[3].w) : "r"(a) : "memory");
}
__device__ __forceinline__ void quad_pair(float x, float y, int t, float& lo, float& hi) {
    const float k = ((t & 1) ? y : x) + shx((t & 1) ? x : y, 1);
    lo = k + shx(k, 2); hi = shx(k, 4) + shx(k, 6);
}
__device__ __forceinline__ void pin(uint32_t& x) { asm volatile("" : "+r"(x)); }
template <typename T> __device__ __forceinline__ void pin(T*& x) { asm volatile("" : "+l"(x)); }
__device__ __forceinline__ float4 ldsf4(uint32_t a) { const uint4 v = lds128(a); return make_float4(__uint_as_float(v.x), __uint_as_float(v.y), __uint_as_float(v.z), __uint_as_float(v.w)); }
__device__ __forceinline__ float sum4(const float4& f) { return (f.x + f.y) + (f.z + f.w); }
__device__ __forceinline__ void stsf(uint32_t a, float v) { sts32(a, __float_as_uint(v)); }

__device__ __forceinline__ void wg_fence() { asm volatile("wgmma.fence.sync.aligned;" ::: "memory"); }
__device__ __forceinline__ void wg_commit() { asm volatile("wgmma.commit_group.sync.aligned;" ::: "memory"); }
__device__ __forceinline__ void wg_wait1() { asm volatile("wgmma.wait_group.sync.aligned 1;" ::: "memory"); }
__device__ __forceinline__ void wg_wait0() { asm volatile("wgmma.wait_group.sync.aligned 0;" ::: "memory"); }
#define R8(o) "+f"(d[o]), "+f"(d[o + 1]), "+f"(d[o + 2]), "+f"(d[o + 3]), "+f"(d[o + 4]), "+f"(d[o + 5]), "+f"(d[o + 6]), "+f"(d[o + 7])
__device__ __forceinline__ void wgmma_rs_n32(float (&d)[16], const uint4& a, uint64_t db, int acc) {
    asm volatile("{\n.reg .pred p;\nsetp.ne.b32 p, %21, 0;\n"
        "wgmma.mma_async.sync.aligned.m64n32k16.f32.bf16.bf16 "
        "{%0,%1,%2,%3,%4,%5,%6,%7,%8,%9,%10,%11,%12,%13,%14,%15}, {%16,%17,%18,%19}, %20, p, 1, 1, 0;\n}"
        : R8(0), R8(8) : "r"(a.x), "r"(a.y), "r"(a.z), "r"(a.w), "l"(db), "r"(acc));
}
#define PV_LO "{%0,%1,%2,%3,%4,%5,%6,%7,%8,%9,%10,%11,%12,%13,%14,%15,%16,%17,%18,%19,%20,%21,%22,%23,%24,%25,%26,%27,%28,%29,%30,%31,%32,%33,%34,%35,%36,%37,%38,%39,%40,%41,%42,%43,%44,%45,%46,%47,%48,%49,%50,%51,%52,%53,%54,%55,%56,%57,%58,%59,%60,%61,%62,%63}, "
#define PV_HI "{%64,%65,%66,%67,%68,%69,%70,%71,%72,%73,%74,%75,%76,%77,%78,%79,%80,%81,%82,%83,%84,%85,%86,%87,%88,%89,%90,%91,%92,%93,%94,%95,%96,%97,%98,%99,%100,%101,%102,%103,%104,%105,%106,%107,%108,%109,%110,%111,%112,%113,%114,%115,%116,%117,%118,%119,%120,%121,%122,%123,%124,%125,%126,%127}, "
__device__ __forceinline__ void wgmma_pv(float (&d)[128], const uint4& a, uint32_t blo, int acc) {
    asm volatile("{\n.reg .pred p;\n.reg .b32 u0, u1, u2, u3, t;\n.reg .b64 d0, d1, d2, d3;\nsetp.ne.b32 p, %133, 0;\n"
        "mov.b64 d0, {%132, 0x40000100};\nadd.u32 t, %132, 512;\nmov.b64 d1, {t, 0x40000100};\n"
        "add.u32 t, %132, 128;\nmov.b64 d2, {t, 0x40000100};\nadd.u32 t, %132, 640;\nmov.b64 d3, {t, 0x40000100};\n"
        "wgmma.fence.sync.aligned;\n"
        "wgmma.mma_async.sync.aligned.m64n128k16.f32.bf16.bf16 " PV_LO "{%128, u0, %129, u1}, d0, p, 1, 1, 1;\n"
        "wgmma.mma_async.sync.aligned.m64n128k16.f32.bf16.bf16 " PV_LO "{%130, u2, %131, u3}, d1, 1, 1, 1, 1;\n"
        "wgmma.commit_group.sync.aligned;\n"
        "wgmma.mma_async.sync.aligned.m64n128k16.f32.bf16.bf16 " PV_HI "{%128, u0, %129, u1}, d2, p, 1, 1, 1;\n"
        "wgmma.mma_async.sync.aligned.m64n128k16.f32.bf16.bf16 " PV_HI "{%130, u2, %131, u3}, d3, 1, 1, 1, 1;\n"
        "wgmma.commit_group.sync.aligned;\n}"
        : R8(0), R8(8), R8(16), R8(24), R8(32), R8(40), R8(48), R8(56), R8(64), R8(72), R8(80), R8(88), R8(96), R8(104), R8(112), R8(120)
        : "r"(a.x), "r"(a.y), "r"(a.z), "r"(a.w), "r"(blo), "r"(acc) : "memory");
}

template <int NW>
__device__ __forceinline__ void ln_stats(float s, float q, float sh, float* scr, int w, int lane, int bar, float& mean_b, float& sd_b) {
#pragma unroll
    for (int o = 16; o; o >>= 1) { s += shx(s, o); q += shx(q, o); }
    constexpr float n = 512.f / NW;
    if (lane == 0) { scr[w] = sh + s * (1.f / n); scr[NW + w] = q - s * s * (1.f / n); }
    bar_sync(bar, NW * 32);
    float mu = 0.f, m2 = 0.f;
#pragma unroll
    for (int i = 0; i < NW; i++) { mu += scr[i]; m2 += scr[NW + i]; }
    mu *= 1.f / NW;
#pragma unroll
    for (int i = 0; i < NW; i++) { const float d = scr[i] - mu; m2 = fmaf(n * d, d, m2); }
    mean_b = rbf(mu);
    sd_b = rbf(sqrtf(rbf(rbf(fmaxf(m2, 0.f) * (1.f / 512.f)) + 1e-5f)));
}
__device__ __forceinline__ float ln_mod(float x, float mean_b, float sd_b, float c, float s) {
    return rbf(rbf(__fdividef(rbf(x - mean_b), sd_b)) * rbf(1.f + c)) + s;
}

__global__ void __cluster_dims__(2, 1, 1) __launch_bounds__(NTHREADS, 1)
fused_kernel(const __grid_constant__ First F, __nv_bfloat16* __restrict__ out, uint32_t* __restrict__ gs, const __grid_constant__ Maps M) {
    extern __shared__ __align__(1024) uint8_t sm[];
    const uint32_t sb = s2u(sm);
    const int tid = threadIdx.x, lane = tid & 31;
    const int j = blockIdx.x, rk = j & 1;
    const int g = lane >> 2, t = lane & 3;
    const int r8 = lane & 7, lb3 = (lane >> 3) & 1, lb4 = lane >> 4;
    uint64_t pol;
    asm("createpolicy.fractional.L2::evict_first.b64 %0, 1.0;" : "=l"(pol));
    {
        auto cpa = [&](uint32_t d, const uint8_t* s) {
            asm volatile("cp.async.cg.shared.global.L2::cache_hint.L2::128B [%0], [%1], 16, %2;" :: "r"(d), "l"(s), "l"(pol) : "memory");
        };
        const uint32_t ut = threadIdx.x, uj = blockIdx.x;
        const uint8_t* w = F.w[ut >= 128];
        if (ut < 128) {
            const uint32_t dq = (sb + ut * 16) ^ ((ut * 2) & 0x70);
            const uint8_t* sq = w + (uint32_t)(((uj & 1) * 256 + (ut >> 3)) * 8192 + (uj >> 1) * 128 + (ut & 7) * 16);
#pragma unroll
            for (int i = 0; i < 4 * NCP; i++) cpa(dq + 4 * 32768 + i * 2048, sq + i * 131072);
        } else if (ut < 384) {
            const uint32_t dm = (sb + ut * 16) ^ ((ut * 2) & 0x10);
            const uint8_t* sa = w + (uint32_t)(((uj >> 5) * 128 + (ut >> 1) - 64) * 6144 + (uj & 31) * 32 + (ut & 1) * 16);
            cpa(dm + SM_XA - 2048, sa); cpa(dm + SM_XA + 2048, sa + 1024);
        }
        else if (ut == 480 && uj < 64) asm volatile("prefetch.global.L2 [%0];" :: "l"(F.v[(uj >> 3) & 1] + (uj & 7) * 64));
    }
    const int warp = __shfl_sync(0xffffffffu, tid >> 5, 0);
    const __nv_bfloat16* const xin = F.v[0];
    uint32_t* const pl = gs + (warp < 2 ? (B_PR + (j >> 5)) * 4096 + (j & 31) * 32 : G_E1 + j * 8192) + (warp & 1) * 1024 + lane;
    if (warp < 4) st_x1(pl, 1u);
    auto BAR = [&](int i) -> uint32_t { return sb + SM_BAR + i * 8; };
    const uint32_t a16 = (r8 + 8 * lb4) * 32 + ((lb3 ^ (r8 >> 2)) * 16);
    const uint32_t a128 = (r8 + 8 * lb4) * 128 + ((((warp & 3) * 2 + lb3) ^ r8) * 16);
    auto ldcls = [&]() -> uint32_t { return *(const volatile uint32_t*)(sm + SM_CLS); };
    auto clear_head = [&]() {
        st2_x1(gs + (B_HA + ((j >> 4) & 1) * 2 + lb4) * 4096 + (j >> 5) * 256 + (j & 15) * 16 + (lane & 15), 0u);
        st2_x4(gs + (B_QA + rk * 8 + ((j >> 1) & 1) * 4 + (j >> 5)) * 4096 + g * 128 + ((j >> 2) & 7) * 16 + t * 4, 0u, 0u, 0u, 0u);
        if (lane < 8) st2_x1(gs + B_RD * 4096 + j * 8 + lane, 0u);
    };
    auto tma = [&](uint32_t dst, const CUtensorMap* mp, uint32_t bar, int c0, int c1, int c2, int c3) {
        asm volatile("{\n.reg .pred p;\nelect.sync _|p, 0xffffffff;\n"
                     "@p cp.async.bulk.tensor.4d.shared::cluster.global.mbarrier::complete_tx::bytes.L2::cache_hint [%0], [%1, {%3, %4, %5, %6}], [%2], %7;\n}"
                     :: "r"(dst), "l"(mp), "r"(bar), "r"(c0), "r"(c1), "r"(c2), "r"(c3), "l"(pol) : "memory");
    };
    if (warp <= 12 || warp == 15) {
        const int grp = warp == 12 ? 0 : warp == 15 ? 13 : warp + 1;
        const uint32_t cnt = grp < 10 ? 1 : grp < 13 ? 4 : 8;
        if (lane == 0) {
#pragma unroll
            for (int i = 0; i < 8; i++) mbar_init(BAR(grp * 8 + i), (i < 2 && grp == 0) ? (i ? 128 : 256) : cnt);
        }
        __syncwarp();
        if (grp < 10 && lane < 8 && (grp || lane > NCP)) mbar_expect(BAR(grp * 8 + lane), grp >= 8 ? 4096 : grp * 8 + lane < IT_X ? 8192 : 16384);
        asm volatile("fence.mbarrier_init.release.cluster;" ::: "memory");
        __syncwarp();
        if (warp == 12) {
#pragma unroll
            for (int i = NCP + 1; i < W0; i++) tma(sb + (15 + i) * 8192, &M.m[MP_WQ], BAR(i), 0, rk * 256 + (i - 1) * 64, j >> 1, 0);
        }
    } else if (warp == 13) {
        if (lane < NMAPS) asm volatile("prefetch.tensormap [%0];" :: "l"(&M.m[lane]) : "memory");
    } else if (warp == 14) {
        clear_head();
    }
    __syncthreads();
    uint32_t in1 = 0, in2 = 0;
    if (warp < 4) { in1 = *(const uint32_t*)(xin + 2 * tid); in2 = *(const uint32_t*)(xin + 256 + 2 * tid); }
    else if (warp < 12) in1 = *(const uint32_t*)(F.v[1] + 2 * (tid - 128));
    if (warp < 12) asm volatile("cp.async.mbarrier.arrive.noinc.shared::cta.b64 [%0];" :: "r"(BAR(warp < 4)) : "memory");
    asm volatile("barrier.cluster.arrive.relaxed.aligned;" ::: "memory");

    if (warp >= 12) {
    asm volatile("setmaxnreg.dec.sync.aligned.u32 64;");
    if (warp == 12) {
        static_assert(W0 > NCP && W0 <= 5 && NCP >= 1 && NCP <= 4, "W0");
        const uint2* sched = M.sched[j < NFF ? 0 : j < J_RED ? 1 : 2];
        uint2 en = sched[W0];
        const uint32_t t0 = gtime();
        const uint32_t sp = __reduce_or_sync(0xffffffffu, sb);
        const int cx = (j >> 1) * 64 + (j < NFF ? 0 : 1024 - NFF * 32);
#pragma unroll 1
        for (int i = W0; en.x; i++) {
            const uint32_t e = en.x, tn = t0 + (int16_t)en.y, mp = (en.y >> 16) & 15, st = (en.y >> 20) * 64;
            en = sched[i + 1];
            if (mp == MP_MODB && j >= J_END) break;
            uint32_t c0 = mp == MP_WO ? (j & 7) * 64 : mp > MP_WO ? cx : 0;
            uint32_t c1 = mp == MP_CKV ? 0 : mp == MP_DOWN ? j * 32 : st + (mp == MP_WUV ? (j & 3) * 32 : mp == MP_WO ? (j >> 3) * 256 : rk * 256);
            uint32_t c2 = mp < MP_CKV ? j >> 1 : mp == MP_CKV ? rk * 4 : mp == MP_WUV ? (j >> 2) * 2 : mp == MP_DOWN ? st >> 4 : 0;
            uint32_t c3 = mp == MP_CKV ? st * 2 + (j & ~1) : 0;
            uint32_t dst = sp + ((e << 7) & 0x3e000), bar = sp + SM_BAR + (e & 63) * 8;
            const uint32_t w0 = (e >> 8) & 0x3f8, w1 = (e >> 15) & 0x3f8, w2 = (e >> 22) & 0x3f8, bb = sp + SM_BAR - 8;
            const CUtensorMap* pm = &M.m[mp];
            pin(dst); pin(bar); pin(c0); pin(c1); pin(c2); pin(c3); pin(pm);
            if (w0) mbar_wait(bb + w0, 0);
            if (w2) {
                mbar_wait(bb + w2, 0);
                while (!__any_sync(0xffffffffu, mbar_test(bb + w1, 0) | ((int)(gtime() - tn) > 0))) {}
            } else if (w1) mbar_wait(bb + w1, 0);
            tma(dst, pm, bar, c0, c1, c2, c3);
        }
    } else if (warp == 13) {
#pragma unroll
        for (int i = 0; i < 2; i++) st_x4(gs + (B_ML + rk * 16 + i * 8 + g) * 4096 + (t >> 1) * 1024 + (j >> 1) * 8 + (t & 1) * 4, 0u, 0u, 0u, 0u);
        if (lane < 16) st2_x4(gs + (B_E2 + (j >> 4)) * 4096 + (j & 15) * 64 + lane * 4, 0u, 0u, 0u, 0u);
        st2_x1(gs + (B_E3 + (j >> 5)) * 4096 + (j & 31) * 32 + lane, 0u);
        if (lane < 8) st2_x1(gs + B_MB * 4096 + j * 8 + lane, 0u);
        if (j < NFF) {
#pragma unroll
            for (int i = 0; i < 2; i++) st2_x4(gs + (B_E5 + i * 8 + g) * 4096 + j * 16 + t * 4, 0u, 0u, 0u, 0u);
        }
        bar_sync(9, 64);
        const uint32_t cs = ldcls();
#pragma unroll 1
        for (int i = 0; i < 32; i++) {
            st_x4(gs + G_E1 + j * 8192 + (i >> 3) * 2048 + ((((cs >> 1) ^ (i >> 3)) & 1) << 10) + (i & 7) * 128 + lane * 4, 0u, 0u, 0u, 0u);
            __nanosleep(JAN_SLEEP);
        }
        fence_gpu();
        if (lane < 8) st2_x1(gs + B_RD * 4096 + j * 8 + lane, 1u + (cs >> 1));
        if (lane == 0) TRACE(41);
        uint32_t rd[4];
        mbar_wait(BAR(IT_CKV + RD_ITEM), 0);
        poll<1024, RD_SLEEP>(rd, gs + near_off(B_RD, cs) + lane * 8);
#pragma unroll
        for (int i = 0; i < 4; i++) {
            const uint32_t m = __ballot_sync(0xffffffffu, rd[i] == 2u);
            if (lane == 0) sts32(sb + SM_CLS + 16 + i * 4, m);
        }
        __syncwarp();
        if (lane < 8) mbar_arrive(BAR(JD));
        if (lane == 0) TRACE(42);
    } else if (warp == 14) {
        uint2 ml[2];
        mbar_waitb(BAR(JD), 0);
        const uint32_t cls = ldcls();
        mbar_waitb(BAR(PF0 + 2 * NUNITS - 1), 0);
        __nanosleep(ML_DELAY);
        const uint32_t* pl2 = gs + near_off(B_ML + (j >> 2), cls) + lane * 8;
        const uint32_t wa = sb + SM_W + lb4 * 64 + t * 16 + (g & 3) * 4;
        poll_start<1024>(ml, pl2);
        uint32_t w0 = 0, w1 = 0, redo = 0;
        bool first = true;
#pragma unroll 1
        for (uint32_t it = 0;; it++) {
            const bool p0 = minw(ml[0]) != 0, p1 = minw(ml[1]) != 0;
            const int n = __popc(__ballot_sync(0xffffffffu, p0)) + __popc(__ballot_sync(0xffffffffu, p1));
            const uint32_t x0 = ml[0].x, x1 = ml[1].x;
            if (n < 64) {
                if (!p0) ld_x(ml[0], pl2);
                if (!p1) ld_x(ml[1], pl2 + 256);
            }
            if (n == 64 || (first && n >= E1_EARLY)) {
                auto ord = [](int x) { return x ^ ((x >> 31) & 0x7fffffff); };
                const int o0 = ord(x0), o1 = ord(x1);
                const float mm = __int_as_float(ord(__reduce_max_sync(0xffffffffu, max(p0 ? o0 : INT_MIN, p1 ? o1 : INT_MIN))));
                const float lo = __int_as_float(ord(__reduce_min_sync(0xffffffffu, min(p0 ? o0 : INT_MAX, p1 ? o1 : INT_MAX))));
                const uint32_t v0 = pack2(ex2((p0 ? __uint_as_float(x0) : lo) - mm), 0.f), v1 = pack2(ex2((p1 ? __uint_as_float(x1) : lo) - mm), 0.f);
                redo = !first && __any_sync(0xffffffffu, v0 != w0 || v1 != w1);
                w0 = v0; w1 = v1;
                sts32(wa - redo * (SM_W - SM_W2), w0 * 0x10001u); sts32(wa - redo * (SM_W - SM_W2) + 128, w1 * 0x10001u);
                if (first) bar_arrive(3, 416);
                first = false;
                if (n == 64) break;
            }
            if (it > SPIN_LIMIT) __trap();
        }
        if (lane == 0) TRACE_Q(37);
        float L = bflo(w0) * __uint_as_float(ml[0].y) + bflo(w1) * __uint_as_float(ml[1].y);
#pragma unroll
        for (int o = 16; o; o >>= 1) L += shx(L, o);
        if (lane == 0) *(float2*)(sm + SM_FQ) = make_float2(__frcp_rn(L), __uint_as_float(redo));
        __syncwarp();
        if (lane < 8) mbar_arrive(BAR(WR));
        if (lane == 0) TRACE(10);
        bar_sync(4, 288);
        clear_head();
        if (j < NFF) {
            uint32_t ya = sb + SM_Y + lane * 16, sa = peer_addr(sb + SM_RED + 2048 + rk * 8, lane & 1), tb = peer_addr(BAR(MBB), lane & 1);
            pin(ya); pin(sa); pin(tb);
            bar_sync(7, 288);
            const float4 y0 = ldsf4(ya), y1 = ldsf4(ya + 512);
            float s = sum4(y0) + sum4(y1);
            float q = (fmaf(y0.x, y0.x, y0.y * y0.y) + fmaf(y0.z, y0.z, y0.w * y0.w)) + (fmaf(y1.x, y1.x, y1.y * y1.y) + fmaf(y1.z, y1.z, y1.w * y1.w));
#pragma unroll
            for (int o = 16; o; o >>= 1) { s += shx(s, o); q += shx(q, o); }
            if (lane < 2) st_async2(sa, s, q, tb);
        }
    } else if (warp == 15) {
        mbar_waitb(BAR(IT_X - 1), 0);
        if (j < J_END) mbar_waitb(BAR(j < NFF ? NITEMS - 1 : MBB), 0);
    }
    } else if (warp < 4) {
        float* scr = (float*)(sm + SM_SCR);
        uint32_t cls;
        {
            uint2 ha[8];
            uint32_t best = 0xffffffffu;
            sts32(sb + SM_SCR + 64 + warp * 4, best);
            const float sh = __shfl_sync(0xffffffffu, bflo(in1), 0);
            const float v0 = bflo(in1) - sh, v1 = bfhi(in1) - sh, v2 = bflo(in2) - sh, v3 = bfhi(in2) - sh;
            float mb, sd;
            ln_stats<4>((v0 + v1) + (v2 + v3), (v0 * v0 + v1 * v1) + (v2 * v2 + v3 * v3), sh, scr, warp, lane, 2, mb, sd);
            if (!rk) in2 = in1;
#pragma unroll 1
            for (int i = 0; i < NPROBE; i++) {
                uint32_t t0, t1, o;
                asm volatile("mov.u32 %0, %%clock;" : "=r"(t0));
                asm volatile("atom.relaxed.gpu.global.exch.b32 %0, [%1], %2;" : "=r"(o) : "l"(pl), "r"(2u + i) : "memory");
                asm volatile("{\n.reg .pred p;\nsetp.ne.u32 p, %1, 0x1234567;\nmov.u32 %0, 0;\n@p mov.u32 %0, %%clock;\n}" : "=r"(t1) : "r"(o));
                best = min(best, t1 - t0);
                sts32(sb + SM_SCR + 64 + warp * 4, best);
                if (__all_sync(0xffffffffu, min(best, lds32(sb + SM_SCR + 64 + (warp ^ 1) * 4)) < NEAR_CLK)) break;
            }
            bar_sync(2, 128);
            const uint4 lt = *(const uint4*)(scr + 16);
            cls = NUMA ? ((lt.y < lt.x) ^ (__popc((B_PR + (j >> 5)) & 0x2C) & 1)) | (lt.w < lt.z) << 1 : 0;
            if (warp == 0) { if (lane == 0) sts32(sb + SM_CLS, cls); bar_arrive(9, 64); }
            if (tid == 0) TRACE(38);
            asm volatile("barrier.cluster.wait.aligned;" ::: "memory");
            mbar_wait(BAR(IT_MODA), 0);
            if (HA_DELAY) __nanosleep(HA_DELAY);
            poll<1024, H_SLEEP, false, 16384>(ha, gs + near_off(B_HA + rk * 2, cls) + 2 * tid);
            auto rsum = [](uint32_t a, uint32_t b, uint32_t c, uint32_t d) { return rbf((__uint_as_float(a) + __uint_as_float(b)) + (__uint_as_float(c) + __uint_as_float(d))); };
            sts32(sb + SM_FV + frag_off(2 * tid),
                  pack2(ln_mod(bflo(in2), mb, sd, rsum(ha[4].x, ha[5].x, ha[6].x, ha[7].x), rsum(ha[0].x, ha[1].x, ha[2].x, ha[3].x)),
                        ln_mod(bfhi(in2), mb, sd, rsum(ha[4].y, ha[5].y, ha[6].y, ha[7].y), rsum(ha[0].y, ha[1].y, ha[2].y, ha[3].y))));
            bar_arrive(5, 384);
            mbar_wait(BAR(QB), 0);
            if (tid < 64) {
                const float* qx = (const float*)(sm + SM_QX) + tid;
                sts16(sb + SM_FQ + frag_off(tid), pack2((qx[0] + qx[64]) + (qx[128] + qx[192]), 0.f));
            }
            bar_arrive(6, 384);
        }
        asm volatile("setmaxnreg.inc.sync.aligned.u32 192;");
        float acc[128];
        float M = 0.f;
        uint32_t pa = sb + SM_XA + warp * 512 + lane * 16, ma = sb + SM_MX + (warp * 8 + g) * 4, pf = BAR(PF0);
        uint32_t blo = __reduce_or_sync(0xffffffffu, (((sb + SM_U) & 0x3FFFFu) >> 4) | 0x400000u);
        uint32_t* e1[4];
#pragma unroll
        for (int i = 0; i < 4; i++) e1[i] = gs + G_E1 + (warp * 8 + g) * 4 * 8192 + (rk * 2 + (j >> 6)) * 2048 + ((j >> 1) & 31) * 32 + t * 4;
#pragma unroll 1
        for (int h = 0; h < 2 * NUNITS; h++) {
            mbar_wait(pf, 0);
            const float m = __uint_as_float(lds32(ma));
            const uint4 pn = lds128(pa);
            wg_wait0();
#pragma unroll
            for (int i = 0; i < 128; i++) asm volatile("" : "+f"(acc[i]) :: "memory");
            if (h == 0) M = m;
            uint32_t b2 = 0x3f803f80u;
            if (__builtin_expect(__any_sync(0xffffffffu, m != M), 0)) {
                const float Mn = fmaxf(M, m), alpha = ex2(M - Mn), beta = ex2(m - Mn);
                M = Mn;
                b2 = pack2(beta, beta);
#pragma unroll
                for (int jj = 0; jj < 32; jj++) { acc[4 * jj] *= alpha; acc[4 * jj + 1] *= alpha; }
            }
            auto mul2 = [](uint32_t x, uint32_t y) { uint32_t r; asm("mul.rn.bf16x2 %0, %1, %2;" : "=r"(r) : "r"(x), "r"(y)); return r; };
            const uint4 p = make_uint4(mul2(pn.x, b2), mul2(pn.y, b2), mul2(pn.z, b2), mul2(pn.w, b2));
            if (tid == 0 && (h & 1)) TRACE_Q(48 + (h >> 1));
            wgmma_pv(acc, p, blo, h);
            if (lane == 0 && h > 0 && !(h & 1)) mbar_arrive(BAR(EB_UNIT0 + (h >> 1) - 1));
            blo += h == 11 ? -11 * 1024 : 1024;
            pa += (h == 5 || h == 11) ? -5 * 2048 : 2048;
            ma += 128; pf += 8;
            if (h == 2 * NUNITS - 3) {
                mbar_wait(BAR(JD), 0);
                const uint32_t hm = (*(const uint32_t*)(sm + SM_CLS + 16 + warp * 4) >> (g * 4)) ^ ((j >> 6) ? 15u : 0u);
#pragma unroll
                for (int i = 0; i < 4; i++) e1[i] += ((hm >> i) & 1) << 10;
            }
        }
#pragma unroll
        for (int vv = 0; vv < 2; vv++) {
            if (vv && M == 1.f) __trap();
            if (vv) wg_wait0(); else wg_wait1();
#pragma unroll
            for (int i = 0; i < 64; i++) asm volatile("" : "+f"(acc[vv * 64 + i]) :: "memory");
            if (tid == 0 && !vv) TRACE_Q(63);
#pragma unroll
            for (int i = 0; i < 4; i++) {
                const float* a = &acc[vv * 64 + i * 16];
                st_x4(e1[i] + i * 8192 + vv * 16, enc(pack2(a[0], a[1])), enc(pack2(a[4], a[5])), enc(pack2(a[8], a[9])), enc(pack2(a[12], a[13])));
            }
        }
        bar_arrive(3, 416);
        if (tid == 0) TRACE_Q(17);
        if (j < NFF) {
            uint4 a[16];
            const uint32_t ad = sb + SM_U + B_DN * 32768 + warp * 8192 + (r8 + 8 * lb4) * 128 + (lb3 ^ r8) * 16;
            uint32_t rl = sb + SM_RED + lane * 16;
            uint32_t* p5 = gs + (B_E5 + warp * 4 + (t >> 1)) * 4096 + j * 16 + (t & 1) * 8 + g;
            pin(rl); pin(p5);
            if (lane == 0) mbar_expect(BAR(MBB), 4);
            auto ldd = [&]() {
#pragma unroll
                for (int s = 0; s < 16; s++) a[s] = ldsm<true>((ad ^ ((s & 3) * 32)) + (s >> 2) * 2048);
            };
            const uint32_t db = BAR(IT_DOWN + (warp >> 1));
            mbar_wait(BAR(MBB), 0);
            const float4 st = ldsf4(sb + SM_RED + 2048);
            const bool hd = __all_sync(0xffffffffu, mbar_test(db, 0));
            if (hd) ldd();
            const float mu = (st.x + st.z) * (1.f / 512.f);
            float rstd;
            asm volatile("rsqrt.approx.ftz.f32 %0, %1;" : "=f"(rstd) : "f"(fmaxf(fmaf(-mu, mu, (st.y + st.w) * (1.f / 512.f)), 0.f) + 1e-5f));
            mbar_wait(BAR(QB), 1);
            if (tid == 0) TRACE(25);
            const float4 f0 = ldsf4(rl), f2 = ldsf4(rl + 1024), f1 = ldsf4(rl + 512), f3 = ldsf4(rl + 1536);
            const float gg = fmaf(rstd, fmaf(-mu, f0.z + f2.z, (f0.x + f0.y) + (f2.x + f2.y)), f0.w + f2.w);
            const float uu = fmaf(rstd, fmaf(-mu, f1.z + f3.z, (f1.x + f1.y) + (f3.x + f3.y)), f1.w + f3.w);
            const float hh = __fdividef(gg * uu, 1.f + ex2(-gg * fmaf(gg * gg, 0.10294324f, 2.3022082f)));
            uint32_t hb[4];
#pragma unroll
            for (int i = 0; i < 4; i++) hb[i] = pack2(__shfl_sync(0xffffffffu, hh, 2 * t + 8 * i), __shfl_sync(0xffffffffu, hh, 2 * t + 8 * i + 1));
            if (!hd) { mbar_wait(db, 0); ldd(); }
#pragma unroll
            for (int i = 0; i < 2; i++) {
                uint32_t res = 0;
#pragma unroll
                for (int k = 0; k < 4; k++) {
                    float c[4] = {0.f, 0.f, 0.f, 0.f};
                    const uint4 &x = a[i * 8 + k], &y = a[i * 8 + k + 4];
                    mma(c, x.x, x.y, x.z, x.w, hb[0], hb[1]);
                    mma(c, y.x, y.y, y.z, y.w, hb[2], hb[3]);
                    if (t == k) res = pack2(c[0], c[2]);
                }
                st2_x1(p5 + i * 8192, enc(res));
            }
            if (tid == 0) { TRACE(27); TRACE_GT(47); }
        } else if (j < J_END) {
            uint4 a[8], b[4];
            float c[4], e[4];
            const bool own = (warp >> 1) == rk;
            const uint32_t xa = sb + SM_FV + (warp & 1) * 64 + g * 8;
            if (lane == 0) mbar_expect(BAR(MBB), own ? 64 : 0);
#pragma unroll
            for (int i = 0; i < 2; i++) {
                ldfrag(b, sb + SM_FS + rk * 512 + i * 256 + t * 16);
                mbar_wait(BAR(IT_X + i), 0);
                const uint32_t ab = sb + SM_U + B_X * 32768 + i * 16384 + a128;
                load8<true>(a, [&](int s) { return ab + s * 2048; });
                mma8(i ? e : c, a, b);
            }
            c[0] += e[0]; c[2] += e[2];
            if (!own) {
                if (t == 0) st_async2(peer_addr(xa, rk ^ 1), c[0], c[2], peer_addr(BAR(MBB), rk ^ 1));
            } else {
                mbar_wait(BAR(MBB), 0);
                const float2 pp = *(const float2*)(sm + (xa - sb));
                const float mine = t ? c[2] + pp.y : c[0] + pp.x, other = shx(mine, 4);
                const uint32_t w = (warp & 1) * 8 + t * 4 + (g >> 1), val = enc(pack2(mine, other));
                if (t < 2 && !(g & 1)) {
                    if (j < J_RED) st2_x1(gs + B_MB * 4096 + (j - NFF) * 16 + w, val);
                    else sts32(sb + SM_FV + 256 + w * 4, val);
                }
                __syncwarp();
                if (j >= J_RED && lane < 4) mbar_arrive(BAR(QB));
                if (lane == 0) TRACE(11);
            }
        }
    } else {
        const int u8 = tid - 128, w8 = warp - 4;
        const int v = w8 >> 2, wq4 = w8 & 3;
        {
            const float c0 = bflo(in1), c1 = bfhi(in1);
            sts32(sb + SM_FS + frag_off(2 * u8), pack2(__fdividef(c0, 1.f + __expf(-c0)), __fdividef(c1, 1.f + __expf(-c1))));
        }
        bar_sync(1, 256);
        asm volatile("barrier.cluster.wait.aligned;" ::: "memory");
        uint4 a[8], b[4]; float c[4];
        if (w8 < 2) {
            ldfrag(b, sb + SM_FS + (j >> 5) * 256 + t * 16);
            mbar_wait(BAR(IT_MODA), 0);
            if (u8 == 0) TRACE(12);
            const uint32_t ab = sb + SM_XA + w8 * 4096 + a16;
            load8<true>(a, [&](int s) { return ab + s * 512; });
            mma8(c, a, b);
            if (t < 2) st2_x1(gs + (B_HA + ((j >> 4) & 1) * 2 + w8) * 4096 + (j >> 5) * 256 + (j & 15) * 16 + t * 8 + g, encf(t ? c[2] : c[0]));
        }
        {
            mbar_wait(BAR(IT_WQ + 2 * v <= NCP ? 1 : IT_WQ + 2 * v), 0); mbar_wait(BAR(IT_WQ + 2 * v + 1 <= NCP ? 1 : IT_WQ + 2 * v + 1), 0);
            const uint32_t ab = sb + SM_U + 4 * 32768 + v * 16384 + a128;
            load8<true>(a, [&](int s) { return ab + s * 2048; });
            if (lane == 0) mbar_arrive(BAR(EB_WQ));
            bar_sync(5, 384);
            if (u8 == 0) TRACE(13);
            ldfrag(b, sb + SM_FV + v * 256 + t * 16);
            mma8(c, a, b);
            if (t < 2) {
                const float qv = t ? c[2] : c[0];
                const uint32_t qa_ = sb + SM_QX + ((rk * 2 + v) * 64 + wq4 * 16 + t * 8 + g) * 4;
                asm volatile("st.async.weak.shared::cluster.mbarrier::complete_tx::bytes.f32 [%0], %1, [%2];"
                             :: "r"(peer_addr(qa_, rk ^ 1)), "f"(qv), "r"(peer_addr(BAR(QB), rk ^ 1)) : "memory");
                sts32(qa_, __float_as_uint(qv));
            }
            __syncwarp();
            if (lane == 0) mbar_expect(BAR(QB), 64);
        }
        {
            mbar_wait(BAR(IT_WUK + v), 0); mbar_wait(BAR(IT_WUK + v + 2), 0);
            const uint32_t ab = sb + SM_U + 5 * 32768 + (w8 * 16 + r8 + 8 * lb3) * 128;
            const uint32_t x16 = (lb4 ^ r8) * 16;
            load8<false>(a, [&](int s) { return ab + (s & 1) * 16384 + (x16 ^ ((s >> 1) * 32)); });
            bar_sync(6, 384);
            if (u8 == 0) TRACE(14);
            b[0] = lds128(sb + SM_FQ + t * 16); b[1] = lds128(sb + SM_FQ + 64 + t * 16);
            float e[4] = {0.f, 0.f, 0.f, 0.f};
            c[0] = c[1] = c[2] = c[3] = 0.f;
#pragma unroll
            for (int k = 0; k < 4; k++) {
                const uint32_t b0 = (k & 1) ? b[k >> 1].z : b[k >> 1].x, b1 = (k & 1) ? b[k >> 1].w : b[k >> 1].y;
                mma(c, a[2 * k].x, a[2 * k].y, a[2 * k].z, a[2 * k].w, b0, b1);
                mma(e, a[2 * k + 1].x, a[2 * k + 1].y, a[2 * k + 1].z, a[2 * k + 1].w, b0, b1);
            }
            const float mine = ((t & 1) ? ((t & 2) ? e[2] : e[0]) : ((t & 2) ? c[2] : c[0])) * 0.12751743f;
            const float other = shx(mine, 4);
            if (!(g & 1)) st2_x1(gs + (B_QA + rk * 8 + ((j >> 1) & 1) * 4 + (j >> 5)) * 4096 + w8 * 128 + ((j >> 2) & 7) * 16 + (g >> 1) * 4 + t, enc(pack2(mine, other)));
            if (u8 == 0) TRACE(15);
        }
        const uint32_t cls = ldcls();
        __nanosleep(QA_DELAY);
        {
            uint4 qb[8];
            const uint32_t* pq = gs + near_off(B_QA + rk * 8 + wq4, cls) + lane * 4;
            const uint32_t* pq2 = gs + near_off(B_QA + rk * 8 + 4 + wq4, cls) + lane * 4;
            if (lane == 0) {
                mbar_expect(BAR(QT), 4096);
                asm volatile("cp.async.bulk.shared::cluster.global.mbarrier::complete_tx::bytes [%0], [%1], 4096, [%2];"
                             :: "r"(sb + SM_U + 5 * 32768 + w8 * 4096), "l"(gs + near_off(B_QA + rk * 8 + w8, cls)), "r"(BAR(QT)) : "memory");
            }
            const uint32_t qs = sb + SM_U + 5 * 32768 + wq4 * 4096 + lane * 16;
            mbar_wait(BAR(QT), 0);
#pragma unroll
            for (int i = 0; i < 8; i++) { a[i] = lds128(qs + i * 512); qb[i] = lds128(qs + 16384 + i * 512); }
            poll<512, QA_SLEEP, true>(a, pq);
            poll<512, QA_SLEEP, true>(qb, pq2);
            if (lane == 0) mbar_arrive(BAR(EB_WUK));
            auto add2 = [](uint32_t x, uint32_t y) { uint32_t r; asm("add.rn.bf16x2 %0, %1, %2;" : "=r"(r) : "r"(x), "r"(y)); return r; };
#pragma unroll
            for (int i = 0; i < 8; i++) a[i] = make_uint4(add2(a[i].x, qb[i].x), add2(a[i].y, qb[i].y), add2(a[i].z, qb[i].z), add2(a[i].w, qb[i].w));
        }
        if (u8 == 0) TRACE(8);
        {
            float m = -INFINITY, l = 0.f;
            uint32_t xl = sb + SM_XB + w8 * 2048 + lane * 16, xr = peer_addr(xl, rk ^ 1), bsr = peer_addr(BAR(SF0 + v), rk ^ 1);
            uint32_t pa = sb + SM_XA + v * 2048 + wq4 * 512 + lane * 16, ma = sb + SM_MX + v * 128 + (wq4 * 8 + g) * 4;
            uint32_t fb = BAR(IT_CKV + v * 2), sf = BAR(SF0 + v);
            uint32_t dlo = __reduce_or_sync(0xffffffffu, (((sb + SM_U + v * 16384) & 0x3FFFFu) >> 4) | 0x10000u);
            if (STAG && v) __nanosleep(STAG);
#pragma unroll 1
            for (int n = 0; n < NUNITS; n++) {
                float d[2][16], sc[8];
#pragma unroll
                for (int i = 0; i < 2; i++) {
                    mbar_wait(fb + i * 8, 0);
                    wg_fence();
#pragma unroll
                    for (int s = 0; s < 8; s++) wgmma_rs_n32(d[i], a[s], (0x40000080ull << 32) | (dlo + i * 512 + (s >> 2) * 64 + (s & 3) * 2), s);
                    wg_commit();
                }
#pragma unroll
                for (int i = 0; i < 2; i++) {
                    if (i) wg_wait0(); else wg_wait1();
#pragma unroll
                    for (int k = 0; k < 16; k++) asm volatile("" : "+f"(d[i][k]) :: "memory");
                    sc[4 * i] = d[i][0] + d[i][6]; sc[4 * i + 1] = d[i][1] + d[i][7]; sc[4 * i + 2] = d[i][8] + d[i][14]; sc[4 * i + 3] = d[i][9] + d[i][15];
                    asm volatile("st.async.weak.shared::cluster.mbarrier::complete_tx::bytes.v4.f32 [%0], {%1, %2, %3, %4}, [%5];"
                                 :: "r"(xr + i * 1024), "f"(sc[4 * i]), "f"(sc[4 * i + 1]), "f"(sc[4 * i + 2]), "f"(sc[4 * i + 3]), "r"(bsr) : "memory");
                }
                if (u8 == 128) TRACE_Q(56 + (n < 6 ? n : -40));
                if (n >= 3) mbar_wait(BAR(EB_UNIT0 + n - 3), 0);
                dlo += n == 5 ? -5 * 2048 : 2048;
                fb += 32; xr ^= 512; bsr += 16;
                pin(fb); pin(xr); pin(bsr);
                mbar_wait(sf, 0);
                const float4 x = ldsf4(xl), y = ldsf4(xl + 1024);
                sc[0] += x.x; sc[1] += x.y; sc[2] += x.z; sc[3] += x.w; sc[4] += y.x; sc[5] += y.y; sc[6] += y.z; sc[7] += y.w;
                float pr[8];
#pragma unroll
                for (int i = 0; i < 8; i++) pr[i] = ex2(sc[i] - m);
                float mx = fmaxf(fmaxf(fmaxf(sc[0], sc[1]), fmaxf(sc[2], sc[3])), fmaxf(fmaxf(sc[4], sc[5]), fmaxf(sc[6], sc[7])));
                if (__builtin_expect(__any_sync(0xffffffffu, mx > m), 0)) {
                    mx = fmaxf(mx, shx(mx, 1));
                    mx = fmaxf(mx, shx(mx, 2));
                    const float mn = fmaxf(m, ceilf(mx * 0.0625f) * 16.f);
                    l *= ex2(m - mn);
                    m = mn;
#pragma unroll
                    for (int i = 0; i < 8; i++) pr[i] = ex2(sc[i] - m);
                }
                stsf(ma, m);
                asm volatile("st.shared.v4.u32 [%0], {%1, %2, %3, %4};" :: "r"(pa), "r"(pack2(pr[0], pr[1])), "r"(pack2(pr[2], pr[3])),
                             "r"(pack2(pr[4], pr[5])), "r"(pack2(pr[6], pr[7])) : "memory");
                __syncwarp();
                if (lane == 0) mbar_arrive(sf + (PF0 - SF0) * 8);
                l += ((pr[0] + pr[1]) + (pr[2] + pr[3])) + ((pr[4] + pr[5]) + (pr[6] + pr[7]));
                xl ^= 512; sf += 16; ma += 256; pa += (n == 2 || n == 5) ? -8192 : 4096;
            }
            l += shx(l, 1);
            l += shx(l, 2);
            float2* mlx = (float2*)(sm + SM_MX + 2048) + wq4 * 8 + g;
            if (v == 0) { *mlx = make_float2(m, l); bar_arrive(11, 256); }
            else {
                mbar_wait(BAR(JD), 0);
                bar_sync(11, 256);
                const float2 o = *mlx;
                const float mn = fmaxf(m, o.x);
                l = l * ex2(m - mn) + o.y * ex2(o.x - mn);
                if ((wq4 >> 1) == rk) st_x4(gs + (B_ML + wq4 * 8 + g) * 4096 + (t >> 1) * 1024 + (j >> 1) * 8 + (t & 1) * 4, encf(mn), encf(l), 1u, 1u);
            }
        }
        const int pi = j < NFF ? rk * 128 + w8 * 16 + (lane & 15) : ((j - J_RED) & 15) * 16 + v * 8 + lb4 * 4 + wq4;
        const uint32_t xw = *(const uint32_t*)(xin + 2 * pi);
        const uint32_t* pm = gs + near_off(B_MB, cls) + pi;
        const uint32_t* pb = gs + near_off(B_E2 + (j >> 4), cls) + (((j >> 3) & 1) * 2 + lb4) * 256 + (lane & 15) * 2;
        pin(pm); pin(pb);
        {
            const uint32_t ab = sb + SM_U + B_WUV * 32768 + v * 4096 + a128;
            uint32_t pa = sb + SM_PB + wq4 * 320 + frag_off(64 * v + 32 * (g >> 2) + 16 * (t & 1) + 8 * (t >> 1) + 2 * (g & 3));
            uint32_t fa = sb + SM_PB + g * 320 + t * 16;
            const uint32_t* pe = gs + G_E1 + j * 8192 + (w8 >> 1) * 2048 + ((((cls >> 1) ^ (w8 >> 1)) & 1) << 10) + (((w8 & 1) * 16 + t) * 8 + g) * 4;
            uint32_t* p2 = gs + (B_E2 + (j >> 4)) * 4096 + (t >> 1) * 1024 + (j & 12) * 64 + w8 * 32 + (j & 3) * 8 + (g & 6) + (t & 1);
            pin(pa); pin(fa); pin(pe); pin(p2);
            const uint32_t mk = (g & 1) ? 0xffff0000u : 0x0000ffffu, m0 = (g & 2) ? 0u : mk, m1 = (g & 2) ? mk : 0u;
            uint4 pv[4];
            bool hv = false;
            bar_sync(3, 416);
            uint4 wa = lds128(sb + SM_W + (wq4 * 4 + t) * 16);
            uint32_t wb[8] = {wa.x & m0, wa.x & m1, wa.y & m0, wa.y & m1, wa.z & m0, wa.z & m1, wa.w & m0, wa.w & m1};
            pv[0] = pv[1] = pv[2] = pv[3] = make_uint4(0u, 0u, 0u, 0u);
            poll<512, E1_SLEEP, true>(pv, pe, [&]() {
                if (!hv) {
                    hv = __all_sync(0xffffffffu, mbar_test(BAR(IT_WUV + t), 0));
                    if (hv) load8<true>(a, [&](int s) { return ab + (s >> 1) * 8192 + (s & 1) * 2048; });
                }
            });
            if (lane == 0) TRACE_Q(48 + w8);
            if (u8 == 0) TRACE_Q(18);
            float lo, hi2;
            float2 inv;
#pragma unroll 1
            for (int pass = 0;; pass++) {
                float e[4][4];
#pragma unroll
                for (int i = 0; i < 4; i++) {
                    e[i][0] = e[i][1] = e[i][2] = e[i][3] = 0.f;
                    mma(e[i], pv[i].x, pv[i].y, pv[i].z, pv[i].w, wb[2 * i], wb[2 * i + 1]);
                }
                const float r0 = (t & 2) ? (e[0][2] + e[1][2]) + (e[2][2] + e[3][2]) : (e[0][0] + e[1][0]) + (e[2][0] + e[3][0]);
                const float r1 = (t & 2) ? (e[0][3] + e[1][3]) + (e[2][3] + e[3][3]) : (e[0][1] + e[1][1]) + (e[2][1] + e[3][1]);
                const uint32_t hi = pack2(r0, r1);
                sts32(pa, hi); sts32(pa + 1280, pack2(r0 - bflo(hi), r1 - bfhi(hi)));
                if (!hv) {
#pragma unroll 1
                    for (int i = 0; i < 4; i++) mbar_wait(BAR(IT_WUV + i), 0);
                    load8<true>(a, [&](int s) { return ab + (s >> 1) * 8192 + (s & 1) * 2048; });
                    hv = true;
                }
                bar_sync(1, 256);
                if (u8 == 0) TRACE(19);
                ldfrag(b, fa);
                mma8(c, a, b);
                mbar_wait(BAR(WR), 0);
                asm volatile("ld.shared.v2.f32 {%0, %1}, [%2];" : "=f"(inv.x), "=f"(inv.y) : "r"(sb + SM_FQ) : "memory");
                quad_pair(c[0] + c[1], c[2] + c[3], t, lo, hi2);
                if (__builtin_expect(__all_sync(0xffffffffu, pass || __float_as_uint(inv.y) == 0), 1)) break;
                wa = lds128(sb + SM_W2 + (wq4 * 4 + t) * 16);
                wb[0] = wa.x & m0; wb[1] = wa.x & m1; wb[2] = wa.y & m0; wb[3] = wa.y & m1; wb[4] = wa.z & m0; wb[5] = wa.z & m1; wb[6] = wa.w & m0; wb[7] = wa.w & m1;
                bar_sync(1, 256);
            }
            if (!(g & 1)) st_x1(p2, enc(pack2(lo * inv.x, hi2 * inv.x)));
            bar_arrive(4, 288);
            if (u8 == 0) TRACE(20);
        }
        uint32_t mb[3] = {0u, 0u, 0u};
        if (j < NFF) poll_start<1024>(mb, pm);
        uint4 a2[8];
        if (v == 0) {
            const uint32_t ab = sb + SM_U + B_WO * 32768 + a128;
            uint32_t* p3 = gs + (B_E3 + ((j >> 1) & 3)) * 4096 + (t >> 1) * 1024 + (rk * 2 + (wq4 >> 1)) * 256 + (j >> 3) * 16 + (wq4 & 1) * 8 + (t & 1) * 4 + (g >> 1);
            pin(p3);
            uint2 bb[8];
#pragma unroll
            for (int i = 0; i < 8; i++) bb[i] = make_uint2(0u, 0u);
            bool ho = false;
            auto ldo = [&]() { load8<true>(a, [&](int s) { return ab + s * 2048; }); load8<true>(a2, [&](int s) { return ab + 16384 + s * 2048; }); };
            auto idle = [&]() {
                if (!ho) {
                    ho = __all_sync(0xffffffffu, mbar_test(BAR(IT_WO + t), 0));
                    if (ho) ldo();
                }
            };
            poll<128, 0, true>(bb, pb, idle);
            if (!ho) {
#pragma unroll 1
                for (int i = 0; i < 4; i++) mbar_wait(BAR(IT_WO + i), 0);
                ldo();
            }
            if (u8 == 0) TRACE(21);
            float e[4][4];
#pragma unroll
            for (int s = 0; s < 16; s++) {
                const uint4& x = (s & 2) ? a2[(s >> 2) * 2 + (s & 1)] : a[(s >> 2) * 2 + (s & 1)];
                const uint2& y = bb[(s >> 2) * 2 + (s & 1)];
                if (s < 4) e[s][0] = e[s][1] = e[s][2] = e[s][3] = 0.f;
                mma(e[s & 3], x.x, x.y, x.z, x.w, y.x, y.y);
            }
            float lo, hi;
            quad_pair((t & 2) ? (e[2][0] + e[3][0]) + (e[2][1] + e[3][1]) : (e[0][0] + e[1][0]) + (e[0][1] + e[1][1]),
                      (t & 2) ? (e[2][2] + e[3][2]) + (e[2][3] + e[3][3]) : (e[0][2] + e[1][2]) + (e[0][3] + e[1][3]), t, lo, hi);
            if (!(g & 1)) st_x1(p3, enc(pack2(lo, hi)));
            bar_arrive(1, 256);
            if (u8 == 0) TRACE(22);
        } else bar_sync(1, 256);
        if (j < NFF) {
            const uint32_t* p3 = gs + near_off(B_E3 + rk * 2 + v, cls) + wq4 * 256 + lane;
            uint32_t za = sb + SM_FZ + lb4 * 576 + frag_off(w8 * 32 + (lane & 15) * 2);
            uint32_t fa = sb + SM_FZ + (g & 3) * 576 + lb4 * 256 + t * 16, ya = sb + SM_Y + u8 * 4;
            poll<1024, MB_SLEEP, true>(mb, pm);
            const uint32_t kk = pack2(1.f + bflo(mb[2]), 1.f + bfhi(mb[2]));
            sts32(za + 2 * 576, lb4 ? mb[1] : kk);
            uint32_t e3[8] = {0u, 0u, 0u, 0u, 0u, 0u, 0u, 0u};
            uint32_t ra = peer_addr(sb + SM_RED + (rk * 2 + v) * 512 + ((wq4 & 1) * 16 + (t >> 1) * 8 + g) * 16 + (t & 1) * 8, wq4 >> 1), tbo = peer_addr(BAR(QB), wq4 >> 1);
            pin(za); pin(fa); pin(ya); pin(ra); pin(tbo);
            if (lane == 0) mbar_expect(BAR(QB), 256);
            const uint32_t gb = BAR(IT_X + v * 2), ab = sb + SM_U + (B_X + v) * 32768 + a128;
            bool early = false, early2 = false;
            auto ldw = [&]() {
                if (!early) {
                    early = __all_sync(0xffffffffu, mbar_test(gb, 0));
                    if (early) load8<true>(a, [&](int s) { return ab + s * 2048; });
                }
                if (!early2) {
                    early2 = __all_sync(0xffffffffu, mbar_test(gb + 8, 0));
                    if (early2) load8<true>(a2, [&](int s) { return ab + 16384 + s * 2048; });
                }
            };
            poll<128, 0, true>(e3, p3, ldw);
            if (u8 == 0) TRACE(23);
            const float s0 = sumlo(e3), s1 = sumhi(e3);
            const float y0 = fmaf(bflo(mb[0]), s0 + shx(s0, 16), bflo(xw)), y1 = fmaf(bfhi(mb[0]), s1 + shx(s1, 16), bfhi(xw));
            stsf(ya, lb4 ? y1 : y0);
            const float z0 = y0 * bflo(kk), z1 = y1 * bfhi(kk);
            const uint32_t zh = pack2(z0, z1);
            sts32(za, lb4 ? pack2(z0 - bflo(zh), z1 - bfhi(zh)) : zh);
            bar_sync(7, 288);
            if (u8 == 0) TRACE(24);
            ldfrag(b, fa);
            if (!early) { mbar_wait(gb, 0); load8<true>(a, [&](int s) { return ab + s * 2048; }); }
            {
                float e[4][4];
#pragma unroll
                for (int s = 0; s < 16; s++) {
                    if (s == 8 && !early2) { mbar_wait(gb + 8, 0); load8<true>(a2, [&](int q) { return ab + 16384 + q * 2048; }); }
                    const uint4& x = s < 8 ? a[s] : a2[s & 7];
                    const uint4& y = b[(s >> 1) & 3];
                    float (&d)[4] = e[(s >> 3) * 2 + (s & 1)];
                    if (!(s & 6)) d[0] = d[1] = d[2] = d[3] = 0.f;
                    mma(d, x.x, x.y, x.z, x.w, (s & 1) ? y.z : y.x, (s & 1) ? y.w : y.y);
                }
                const bool hi = t >> 1;
                const float k0 = hi ? e[2][2] + e[3][2] : e[0][0] + e[1][0], k1 = hi ? e[2][3] + e[3][3] : e[0][1] + e[1][1];
                const float o0 = hi ? e[2][0] + e[3][0] : e[0][2] + e[1][2], o1 = hi ? e[2][1] + e[3][1] : e[0][3] + e[1][3];
                st_async2(ra, k0 + shx(o0, 2), k1 + shx(o1, 2), tbo);
            }
        } else if (j >= J_RED && j < J_END) {
            uint32_t ga[1], e3[1];
            poll<0, MB_SLEEP>(ga, pm);
            poll<0, 100>(e3, gs + near_off(B_E3 + (pi >> 6), cls) + (pi & 48) * 16 + (lane & 15) * 16 + (pi & 15));
            float y0 = bflo(e3[0]), y1 = bfhi(e3[0]);
#pragma unroll
            for (int o = 8; o; o >>= 1) { y0 += shx(y0, o); y1 += shx(y1, o); }
            y0 = fmaf(bflo(ga[0]), y0, bflo(xw)); y1 = fmaf(bfhi(ga[0]), y1, bfhi(xw));
            uint32_t gb = 0;
            auto ldg = [&]() { if (__all_sync(0xffffffffu, mbar_test(BAR(QB), 1))) gb = lds32(sb + SM_FV + 256 + (pi & 15) * 4); };
            uint32_t* po = (uint32_t*)out + pi;
            pin(po);
            const uint32_t nz = lane < NFF / 2 ? 0u : 0x80008000u;
            uint2 yv[2] = {make_uint2(nz, nz), make_uint2(nz, nz)};
            poll<NFF * 32, 0, true>(yv, gs + near_off(B_E5 + j - J_RED, cls) + lane * 16 + w8 * 2, ldg);
            if (u8 == 0) TRACE(26);
            const float l0 = bflo(yv[0].x) + bflo(yv[1].x), h0 = bfhi(yv[0].x) + bfhi(yv[1].x);
            const float l1 = bflo(yv[0].y) + bflo(yv[1].y), h1 = bfhi(yv[0].y) + bfhi(yv[1].y);
            float s0 = (lb4 ? h0 : l0) + shx(lb4 ? l0 : h0, 16), s1 = (lb4 ? h1 : l1) + shx(lb4 ? l1 : h1, 16);
#pragma unroll
            for (int o = 8; o; o >>= 1) { s0 += shx(s0, o); s1 += shx(s1, o); }
            if (__any_sync(0xffffffffu, !gb)) { mbar_wait(BAR(QB), 1); ldg(); }
            if (!(lane & 15)) *po = pack2(fmaf(bflo(gb), s0, y0), fmaf(bfhi(gb), s1, y1));
            if (u8 == 0) TRACE(27);
        }
    }
}

typedef CUresult (*EncFn)(CUtensorMap*, CUtensorMapDataType, cuuint32_t, void*, const cuuint64_t*, const cuuint64_t*,
                          const cuuint32_t*, const cuuint32_t*, CUtensorMapInterleave, CUtensorMapSwizzle,
                          CUtensorMapL2promotion, CUtensorMapFloatOOBfill);

void make_map(EncFn enc_fn, CUtensorMap* m, const void* p, cuuint64_t d0, cuuint64_t d1, cuuint64_t d2, cuuint64_t d3,
              cuuint64_t s1, cuuint64_t s2, cuuint64_t s3, cuuint32_t b0, cuuint32_t b1, cuuint32_t b2, cuuint32_t b3, CUtensorMapSwizzle sw) {
    const cuuint64_t dims[4] = {d0, d1, d2, d3}, strides[3] = {s1, s2, s3};
    const cuuint32_t box[4] = {b0, b1, b2, b3}, es[4] = {1, 1, 1, 1};
    enc_fn(m, CU_TENSOR_MAP_DATA_TYPE_BFLOAT16, 4, (void*)p, dims, strides, box, es,
           CU_TENSOR_MAP_INTERLEAVE_NONE, sw, CU_TENSOR_MAP_L2_PROMOTION_L2_64B, CU_TENSOR_MAP_FLOAT_OOB_FILL_NONE);
}

uint32_t* scratch = nullptr;

struct Tune { const char* win; const char* late; int tau, t_off; const char* tail[3][4]; };
Tune tune = {"66666666655555555555555555555555555533333",
             "00000000000000000000999999999999999999999", 322, -300,
             {{"VVVVOOOOguguDD", "zzzzzzzzzzzzzz", "88889999888877", "eddd0efffaaadd"},
              {"VMVMVVOOOO", "zzzzzzzzzz", "8888889999", "288888iddd"},
              {"VVVVOOOOMM", "zzzzzzzzzz", "aaaaaaaa88", "6ggg0ghhkn"}}};
bool ready = false;

}

extern "C" void kernel_launch(void* const* d_in, const int* in_sizes, int n_in, void* d_out, int out_size) {
    (void)in_sizes; (void)n_in; (void)out_size;
    static Maps maps;
    static const void* cached[12] = {};
    bool same = ready;
    for (int i = 0; i < 12 && same; i++) same = cached[i] == d_in[i];
    if (!same) {
        void* fn = nullptr;
        cudaDriverEntryPointQueryResult qr;
        cudaGetDriverEntryPoint("cuTensorMapEncodeTiled", &fn, cudaEnableDefault, &qr);
        EncFn e = (EncFn)fn;
        const CUtensorMapSwizzle S128 = CU_TENSOR_MAP_SWIZZLE_128B;
        make_map(e, &maps.m[MP_WQ], d_in[2], 64, 512, 64, 1, 8192, 128, 8192, 64, 64, 1, 1, S128);
        make_map(e, &maps.m[MP_WUK], d_in[3], 64, 512, 64, 1, 8192, 128, 8192, 64, 64, 1, 1, S128);
        make_map(e, &maps.m[MP_CKV], d_in[1], 64, 8, 8, 4096, 1024, 128, 8192, 64, 8, 4, 2, S128);
        make_map(e, &maps.m[MP_MODB], d_in[11], 3072, 512, 1, 1, 6144, 6144, 6144, 64, 128, 1, 1, S128);
        make_map(e, &maps.m[MP_WUV], d_in[4], 64, 512, 64, 1, 8192, 128, 8192, 64, 32, 2, 1, S128);
        make_map(e, &maps.m[MP_WO], d_in[5], 512, 4096, 1, 1, 1024, 1024, 1024, 64, 64, 1, 1, S128);
        make_map(e, &maps.m[MP_GATE], d_in[7], 1792, 512, 1, 1, 3584, 3584, 3584, 64, 128, 1, 1, S128);
        make_map(e, &maps.m[MP_UP], d_in[8], 1792, 512, 1, 1, 3584, 3584, 3584, 64, 128, 1, 1, S128);
        make_map(e, &maps.m[MP_DOWN], d_in[9], 64, 1792, 8, 1, 1024, 128, 1024, 64, 32, 4, 1, S128);
        for (int r = 0; r < 3; r++) {
            int ids[56], cnt[128] = {}, tn = tune.t_off - (W0 - 1) * tune.tau;
            uint2* sc = maps.sched[r];
            auto dig = [](char ch) { return ch >= 'a' ? ch - 'a' + 10 : ch >= 'A' ? ch - 'A' + 36 : ch - '0'; };
            for (int i = 0; i < 56; i++) sc[i] = make_uint2(0u, 0u);
            for (int i = 0;; i++) {
                int id = i, buf, dep, w, wl;
                if (i < IT_WUV) {
                    const int u = (i - IT_CKV) >> 2;
                    buf = i < IT_CKV ? 4 + ((i - 1) >> 2) : u % 6;
                    dep = i < IT_CKV || u < 4 ? -1 : u < 6 ? EB_WQ + u - 4 : EB_UNIT0 + u - 6;
                    w = dig(tune.win[i]); wl = dig(tune.late[i]);
                    if (i) tn += tune.tau;
                } else {
                    const char ch = tune.tail[r][0][i - IT_WUV];
                    if (!ch) break;
                    buf = ch == 'V' ? B_WUV : ch == 'O' ? B_WO : ch == 'D' ? B_DN : ch == 'u' ? B_X + 1 : B_X;
                    id = (ch == 'V' ? IT_WUV : ch == 'O' ? IT_WO : ch == 'D' ? IT_DOWN : ch == 'u' ? IT_X + 2 : IT_X) + cnt[(int)ch]++;
                    dep = EB_UNIT0 + (buf < 2 ? buf + 6 : buf);
                    w = dig(tune.tail[r][1][i - IT_WUV]); wl = dig(tune.tail[r][2][i - IT_WUV]);
                    tn += 32 * dig(tune.tail[r][3][i - IT_WUV]);
                }
                if (id < IT_X ? (id - 1) & 3 : (id - IT_X) & 1) dep = -1;
                ids[i] = id;
                auto back = [&](int d) { return i < d ? 0 : (ids[i - d] && ids[i - d] <= NCP ? 1 : ids[i - d]) + 1; };
                sc[i].x = id | (buf * 4 + (id < IT_X ? (id - 1) & 3 : ((id - IT_X) & 1) * 2)) << 6 | (dep + 1) << 11 | (w > 32 ? NEVER + 1 : back(w)) << 18 | (wl ? back(wl) : 0) << 25;
                const int mp = id < IT_CKV ? MP_WQ + ((id - 1) >> 2) : id < IT_WUV ? MP_CKV : id < IT_WO ? MP_WUV : id < IT_X ? MP_WO
                             : id >= IT_DOWN ? MP_DOWN : r ? MP_MODB : MP_GATE + ((id - IT_X) >> 1);
                const int step = mp == MP_CKV ? id - IT_CKV : mp == MP_WUV ? (id - IT_WUV) * 2 : mp == MP_DOWN ? id - IT_DOWN : id < IT_X ? (id - 1) & 3 : ((id - IT_X) & 1) * 2;
                sc[i].y = (tn & 0xffff) | (mp & 15) << 16 | step << 20;
            }
        }
        cudaGetSymbolAddress((void**)&scratch, g_scratch);
        scratch = (uint32_t*)(((uintptr_t)scratch + (2u << 20) - 1) & ~(uintptr_t)((2u << 20) - 1));
        cudaFuncSetAttribute(fused_kernel, cudaFuncAttributeMaxDynamicSharedMemorySize, SM_TOTAL);
        for (int i = 0; i < 12; i++) cached[i] = d_in[i];
        ready = true;
    }
    const First f = {{(const uint8_t*)d_in[2], (const uint8_t*)d_in[11]}, {(const __nv_bfloat16*)d_in[0], (const __nv_bfloat16*)d_in[10]}};
    fused_kernel<<<NCTA, NTHREADS, SM_TOTAL>>>(f, (__nv_bfloat16*)d_out, scratch, maps);
}
```

```cpp
#include <cuda_runtime.h>
#include <cuda_bf16.h>
#include <cuda.h>
#include <stdint.h>
#include <limits.h>

namespace {

constexpr int NCTA = 128;
constexpr int NTHREADS = 512;
constexpr int NUNITS = 8;
constexpr int NFF = 56, J_RED = 104, J_END = 120;
constexpr uint32_t SPIN_LIMIT = 1u << 22;

#define PROMO CU_TENSOR_MAP_L2_PROMOTION_L2_64B
#define NEAR_CLK 390
#define E1_EARLY 50
#define STAG 300
#define NUMA 1
#define NPROBE 5
#define NCP 2
#define W0 4
#define RD_ITEM 15
#define JAN_SLEEP 100
#define RD_SLEEP 400
#define HA_DELAY 200
#define H_SLEEP 100
#define QA_DELAY 600
#define QA_SLEEP 200
#define ML_DELAY 300
#define E1_SLEEP 50
#define MB_SLEEP 100
constexpr int B_WUV = 2, B_WO = 3, B_X = 4  , B_DN = 0;

constexpr int SM_U = 0;
constexpr int SM_XA = 6 * 32768;
constexpr int SM_XB = SM_XA + 12288;
constexpr int SM_MX = SM_XB + 16384;
constexpr int SM_FZ = SM_XB + 8192;
constexpr int SM_PB = SM_XB;
constexpr int SM_Y = SM_XB + 12288;
constexpr int SM_RED = SM_XB + 4096;
constexpr int SM_FS = SM_XB + 20480;
constexpr int SM_FV = SM_FS + 1024;
constexpr int SM_QX = SM_XA + 8192;
constexpr int SM_FQ = SM_FV + 512;
constexpr int SM_CLS = SM_FQ + 128;
constexpr int SM_W = SM_FQ + 256;
constexpr int SM_W2 = SM_MX + 2304;
constexpr int SM_SCR = SM_XA + 9216;
constexpr int SM_TR = SM_XB + 19456;
constexpr int SM_BAR = SM_W + 256;
constexpr int SM_TOTAL = SM_BAR + 1024;
static_assert(SM_TOTAL <= 232448, "smem");

enum { IT_MODA = 0, IT_WQ = 1, IT_WUK = 5, IT_CKV = 9, IT_WUV = 41, IT_WO = 45, IT_X = 49  , IT_DOWN = 53, NITEMS = 55,
       NEVER = 63,
       SF0 = 64,
       PF0 = 80,
       EB_UNIT0 = 96, MBB = 103,
       EB_WQ = 104, EB_WUK, QT, QB, JD, WR };

enum { MP_WQ = 0, MP_WUK, MP_CKV, MP_WUV, MP_DOWN, MP_WO, MP_GATE, MP_UP, MP_MODB, NMAPS };
struct First { const uint8_t* w[2]; const __nv_bfloat16* v[2]; };
struct Maps { CUtensorMap m[NMAPS]; uint2 sched[3][56]; };

enum { B_HA = 0,
       B_MB = 6,
       B_RD = 7,
       B_E2 = 8,
       B_QA = 16,
       B_ML = 32,
       B_E5 = 64,
       B_E3 = 80,
       B_PR = 96,
       B_TR = 100 };
constexpr int G_E1 = 1 << 19;
constexpr int G_TR = B_TR * 4096;
__device__ __align__(1024) uint32_t g_scratch[(8 << 20) / 4];

#define TRACE(slot) do {} while (0)
#define TRACE_Q(slot) do {} while (0)
#define TRACE_GT(slot) do {} while (0)

__device__ __forceinline__ uint32_t s2u(const void* p) { return (uint32_t)__cvta_generic_to_shared(p); }
__device__ __forceinline__ void mbar_init(uint32_t b, int c) { asm volatile("mbarrier.init.shared::cta.b64 [%0], %1;" :: "r"(b), "r"(c) : "memory"); }
__device__ __forceinline__ void mbar_expect(uint32_t b, uint32_t bytes) { asm volatile("mbarrier.arrive.expect_tx.shared::cta.b64 _, [%0], %1;" :: "r"(b), "r"(bytes) : "memory"); }
__device__ __forceinline__ void mbar_arrive(uint32_t b) { asm volatile("mbarrier.arrive.shared::cta.b64 _, [%0];" :: "r"(b) : "memory"); }
__device__ __forceinline__ void mbar_wait(uint32_t b, uint32_t ph) {
    asm volatile("{\n.reg .pred p;\nW: mbarrier.try_wait.parity.shared::cta.b64 p, [%0], %1;\n@!p bra W;\n}" :: "r"(b), "r"(ph) : "memory");
}
__device__ __forceinline__ void mbar_waitb(uint32_t b, uint32_t ph) {
    asm volatile("{\n.reg .pred p;\n.reg .u32 n;\nmov.u32 n, 0;\n"
                 "W: mbarrier.try_wait.parity.shared::cta.b64 p, [%0], %1;\n@p bra D;\n"
                 "add.u32 n, n, 1;\nsetp.lt.u32 p, n, 0x100000;\n@p bra W;\ntrap;\nD:\n}" :: "r"(b), "r"(ph) : "memory");
}
__device__ __forceinline__ uint32_t mbar_test(uint32_t b, uint32_t ph) {
    uint32_t ok;
    asm volatile("{\n.reg .pred p;\nmbarrier.test_wait.parity.shared::cta.b64 p, [%1], %2;\nselp.u32 %0, 1, 0, p;\n}" : "=r"(ok) : "r"(b), "r"(ph) : "memory");
    return ok;
}
__device__ __forceinline__ void bar_sync(int id, int n) { asm volatile("bar.sync %0, %1;" :: "r"(id), "r"(n) : "memory"); }
__device__ __forceinline__ void bar_arrive(int id, int n) { asm volatile("bar.arrive %0, %1;" :: "r"(id), "r"(n) : "memory"); }
__device__ __forceinline__ uint32_t peer_addr(uint32_t a, uint32_t rank) { uint32_t r; asm("mapa.shared::cluster.u32 %0, %1, %2;" : "=r"(r) : "r"(a), "r"(rank)); return r; }
__device__ __forceinline__ void st_async2(uint32_t a, float x, float y, uint32_t bar) {
    asm volatile("st.async.weak.shared::cluster.mbarrier::complete_tx::bytes.v2.f32 [%0], {%1, %2}, [%3];" :: "r"(a), "f"(x), "f"(y), "r"(bar) : "memory");
}
__device__ __forceinline__ uint32_t gtime() { uint32_t t; asm volatile("mov.u32 %0, %%globaltimer_lo;" : "=r"(t)); return t; }
__device__ __forceinline__ void fence_gpu() { asm volatile("fence.acq_rel.gpu;" ::: "memory"); }

__device__ __forceinline__ uint32_t enc(uint32_t b) { uint32_t r; asm("max.u32 %0, %1, 1;" : "=r"(r) : "r"(b)); return r; }
__device__ __forceinline__ uint32_t encf(float f) { return enc(__float_as_uint(f)); }
__device__ __forceinline__ void st_x1(uint32_t* p, uint32_t v) { asm volatile("st.relaxed.gpu.global.u32 [%0], %1;" :: "l"(p), "r"(v) : "memory"); }
__device__ __forceinline__ void st_x4(void* p, uint32_t a, uint32_t b, uint32_t c, uint32_t d) {
    asm volatile("st.relaxed.gpu.global.v4.u32 [%0], {%1, %2, %3, %4};" :: "l"(p), "r"(a), "r"(b), "r"(c), "r"(d) : "memory");
}
__device__ __forceinline__ void st2_x1(uint32_t* p, uint32_t v) { st_x1(p, v); st_x1(p + 1024, v); }
__device__ __forceinline__ void st2_x4(uint32_t* p, uint32_t a, uint32_t b, uint32_t c, uint32_t d) { st_x4(p, a, b, c, d); st_x4(p + 1024, a, b, c, d); }
__device__ __forceinline__ int near_off(int b, uint32_t cls) { return b * 4096 + (((__popc(b & 0x2C) ^ cls) & 1) << 10); }
__device__ __forceinline__ void ld_x(uint32_t& v, const void* p) { asm volatile("ld.relaxed.gpu.global.u32 %0, [%1];" : "=r"(v) : "l"(p) : "memory"); }
__device__ __forceinline__ void ld_x(uint4& v, const void* p) {
    asm volatile("ld.relaxed.gpu.global.v4.u32 {%0, %1, %2, %3}, [%4];" : "=r"(v.x), "=r"(v.y), "=r"(v.z), "=r"(v.w) : "l"(p) : "memory");
}
__device__ __forceinline__ void ld_x(uint2& v, const void* p) { asm volatile("ld.relaxed.gpu.global.v2.u32 {%0, %1}, [%2];" : "=r"(v.x), "=r"(v.y) : "l"(p) : "memory"); }
__device__ __forceinline__ uint32_t minw(uint32_t v) { return v; }
__device__ __forceinline__ uint32_t minw(const uint2& v) { return min(v.x, v.y); }
__device__ __forceinline__ uint32_t minw(const uint4& v) { return min(__vimin3_u32(v.x, v.y, v.z), v.w); }
template <int N> __device__ __forceinline__ uint32_t mint(const uint32_t* m) {
    if constexpr (N == 1) return m[0];
    else if constexpr (N == 2) return min(m[0], m[1]);
    else return __vimin3_u32(mint<(N + 2) / 3>(m), mint<(N + 1) / 3>(m + (N + 2) / 3), mint<N / 3>(m + (N + 2) / 3 + (N + 1) / 3));
}

template <int STRIDE, int S4 = 4 * STRIDE, typename T, int N>
__device__ __forceinline__ void poll_start(T (&v)[N], const void* base) {
#pragma unroll
    for (int i = 0; i < N; i++) ld_x(v[i], (const uint8_t*)base + (i & 3) * STRIDE + (i >> 2) * S4);
}
struct Nop { __device__ void operator()() const {} };
template <int STRIDE, int SLEEP, bool STARTED = false, int S4 = 4 * STRIDE, typename T, int N, typename F = Nop>
__device__ __forceinline__ void poll(T (&v)[N], const void* base, F idle = F()) {
    if (!STARTED) { poll_start<STRIDE, S4>(v, base); idle(); }
#pragma unroll 1
    for (uint32_t it = 0;; it++) {
        uint32_t m[N];
#pragma unroll
        for (int i = 0; i < N; i++) m[i] = minw(v[i]);
        if (__all_sync(0xffffffffu, mint<N>(m) != 0)) break;
        if (SLEEP && it > 0) __nanosleep(SLEEP);
#pragma unroll
        for (int i = 0; i < N; i++) if (!m[i]) ld_x(v[i], (const uint8_t*)base + (i & 3) * STRIDE + (i >> 2) * S4);
        idle();
        if (it > SPIN_LIMIT) __trap();
    }
}

__device__ __forceinline__ float bflo(uint32_t w) { return __uint_as_float(w << 16); }
__device__ __forceinline__ float bfhi(uint32_t w) { return __uint_as_float(w & 0xffff0000u); }
__device__ __forceinline__ uint32_t pack2(float lo, float hi) {
    uint32_t r; asm("cvt.rn.bf16x2.f32 %0, %1, %2;" : "=r"(r) : "f"(hi), "f"(lo)); return r;
}
__device__ __forceinline__ float rbf(float x) { return __uint_as_float(pack2(0.f, x)); }
__device__ __forceinline__ float sumlo(const uint32_t (&v)[8]) { return ((bflo(v[0]) + bflo(v[1])) + (bflo(v[2]) + bflo(v[3]))) + ((bflo(v[4]) + bflo(v[5])) + (bflo(v[6]) + bflo(v[7]))); }
__device__ __forceinline__ float sumhi(const uint32_t (&v)[8]) { return ((bfhi(v[0]) + bfhi(v[1])) + (bfhi(v[2]) + bfhi(v[3]))) + ((bfhi(v[4]) + bfhi(v[5])) + (bfhi(v[6]) + bfhi(v[7]))); }
__device__ __forceinline__ float ex2(float x) { float r; asm("ex2.approx.ftz.f32 %0, %1;" : "=f"(r) : "f"(x)); return r; }
__device__ __forceinline__ float shx(float v, int m) { return __shfl_xor_sync(0xffffffffu, v, m); }
__device__ __forceinline__ uint4 lds128(uint32_t a) { uint4 v; asm volatile("ld.shared.v4.u32 {%0, %1, %2, %3}, [%4];" : "=r"(v.x), "=r"(v.y), "=r"(v.z), "=r"(v.w) : "r"(a) : "memory"); return v; }
__device__ __forceinline__ uint32_t lds32(uint32_t a) { uint32_t v; asm volatile("ld.shared.u32 %0, [%1];" : "=r"(v) : "r"(a) : "memory"); return v; }
__device__ __forceinline__ void sts32(uint32_t a, uint32_t v) { asm volatile("st.shared.u32 [%0], %1;" :: "r"(a), "r"(v) : "memory"); }
__device__ __forceinline__ void sts16(uint32_t a, uint32_t v) { asm volatile("st.shared.u16 [%0], %1;" :: "r"(a), "h"((uint16_t)v) : "memory"); }
__device__ __forceinline__ int frag_off(int k) { return (k >> 5) * 64 + ((k >> 1) & 3) * 16 + ((k >> 4) & 1) * 8 + ((k >> 3) & 1) * 4 + (k & 1) * 2; }

template <bool TRANS>
__device__ __forceinline__ uint4 ldsm(uint32_t a) {
    uint4 r;
    if (TRANS) asm volatile("ldmatrix.sync.aligned.m8n8.x4.trans.shared.b16 {%0, %1, %2, %3}, [%4];" : "=r"(r.x), "=r"(r.y), "=r"(r.z), "=r"(r.w) : "r"(a) : "memory");
    else asm volatile("ldmatrix.sync.aligned.m8n8.x4.shared.b16 {%0, %1, %2, %3}, [%4];" : "=r"(r.x), "=r"(r.y), "=r"(r.z), "=r"(r.w) : "r"(a) : "memory");
    return r;
}
__device__ __forceinline__ void mma(float (&c)[4], uint32_t a0, uint32_t a1, uint32_t a2, uint32_t a3, uint32_t b0, uint32_t b1) {
    asm volatile("mma.sync.aligned.m16n8k16.row.col.f32.bf16.bf16.f32 {%0,%1,%2,%3}, {%4,%5,%6,%7}, {%8,%9}, {%0,%1,%2,%3};"
                 : "+f"(c[0]), "+f"(c[1]), "+f"(c[2]), "+f"(c[3]) : "r"(a0), "r"(a1), "r"(a2), "r"(a3), "r"(b0), "r"(b1));
}
template <bool TRANS, typename F>
__device__ __forceinline__ void load8(uint4 (&a)[8], F addr) {
    __syncwarp();
#pragma unroll
    for (int s = 0; s < 8; s++) a[s] = ldsm<TRANS>(addr(s));
}
__device__ __forceinline__ void mma8(float (&c)[4], const uint4 (&a)[8], const uint4 (&b)[4]) {
    float e[4][4];
#pragma unroll
    for (int s = 0; s < 8; s++) {
        if (s < 4) e[s][0] = e[s][1] = e[s][2] = e[s][3] = 0.f;
        mma(e[s & 3], a[s].x, a[s].y, a[s].z, a[s].w, (s & 1) ? b[s >> 1].z : b[s >> 1].x, (s & 1) ? b[s >> 1].w : b[s >> 1].y);
    }
#pragma unroll
    for (int i = 0; i < 4; i++) c[i] = (e[0][i] + e[1][i]) + (e[2][i] + e[3][i]);
}
__device__ __forceinline__ void ldfrag(uint4 (&b)[4], uint32_t a) {
    asm volatile("ld.shared.v4.u32 {%0,%1,%2,%3}, [%16];\nld.shared.v4.u32 {%4,%5,%6,%7}, [%16+64];\n"
                 "ld.shared.v4.u32 {%8,%9,%10,%11}, [%16+128];\nld.shared.v4.u32 {%12,%13,%14,%15}, [%16+192];\n"
                 : "=r"(b[0].x), "=r"(b[0].y), "=r"(b[0].z), "=r"(b[0].w), "=r"(b[1].x), "=r"(b[1].y), "=r"(b[1].z), "=r"(b[1].w),
                   "=r"(b[2].x), "=r"(b[2].y), "=r"(b[2].z), "=r"(b[2].w), "=r"(b[3].x), "=r"(b[3].y), "=r"(b[3].z), "=r"(b[3].w) : "r"(a) : "memory");
}
__device__ __forceinline__ void quad_pair(float x, float y, int t, float& lo, float& hi) {
    const float k = ((t & 1) ? y : x) + shx((t & 1) ? x : y, 1);
    lo = k + shx(k, 2); hi = shx(k, 4) + shx(k, 6);
}
__device__ __forceinline__ void pin(uint32_t& x) { asm volatile("" : "+r"(x)); }
template <typename T> __device__ __forceinline__ void pin(T*& x) { asm volatile("" : "+l"(x)); }
__device__ __forceinline__ float4 ldsf4(uint32_t a) { const uint4 v = lds128(a); return make_float4(__uint_as_float(v.x), __uint_as_float(v.y), __uint_as_float(v.z), __uint_as_float(v.w)); }
__device__ __forceinline__ float sum4(const float4& f) { return (f.x + f.y) + (f.z + f.w); }
__device__ __forceinline__ void stsf(uint32_t a, float v) { sts32(a, __float_as_uint(v)); }

__device__ __forceinline__ void wg_fence() { asm volatile("wgmma.fence.sync.aligned;" ::: "memory"); }
__device__ __forceinline__ void wg_commit() { asm volatile("wgmma.commit_group.sync.aligned;" ::: "memory"); }
__device__ __forceinline__ void wg_wait1() { asm volatile("wgmma.wait_group.sync.aligned 1;" ::: "memory"); }
__device__ __forceinline__ void wg_wait0() { asm volatile("wgmma.wait_group.sync.aligned 0;" ::: "memory"); }
#define R8(o) "+f"(d[o]), "+f"(d[o + 1]), "+f"(d[o + 2]), "+f"(d[o + 3]), "+f"(d[o + 4]), "+f"(d[o + 5]), "+f"(d[o + 6]), "+f"(d[o + 7])
__device__ __forceinline__ void wgmma_rs_n32(float (&d)[16], const uint4& a, uint64_t db, int acc) {
    asm volatile("{\n.reg .pred p;\nsetp.ne.b32 p, %21, 0;\n"
        "wgmma.mma_async.sync.aligned.m64n32k16.f32.bf16.bf16 "
        "{%0,%1,%2,%3,%4,%5,%6,%7,%8,%9,%10,%11,%12,%13,%14,%15}, {%16,%17,%18,%19}, %20, p, 1, 1, 0;\n}"
        : R8(0), R8(8) : "r"(a.x), "r"(a.y), "r"(a.z), "r"(a.w), "l"(db), "r"(acc));
}
#define PV_LO "{%0,%1,%2,%3,%4,%5,%6,%7,%8,%9,%10,%11,%12,%13,%14,%15,%16,%17,%18,%19,%20,%21,%22,%23,%24,%25,%26,%27,%28,%29,%30,%31,%32,%33,%34,%35,%36,%37,%38,%39,%40,%41,%42,%43,%44,%45,%46,%47,%48,%49,%50,%51,%52,%53,%54,%55,%56,%57,%58,%59,%60,%61,%62,%63}, "
#define PV_HI "{%64,%65,%66,%67,%68,%69,%70,%71,%72,%73,%74,%75,%76,%77,%78,%79,%80,%81,%82,%83,%84,%85,%86,%87,%88,%89,%90,%91,%92,%93,%94,%95,%96,%97,%98,%99,%100,%101,%102,%103,%104,%105,%106,%107,%108,%109,%110,%111,%112,%113,%114,%115,%116,%117,%118,%119,%120,%121,%122,%123,%124,%125,%126,%127}, "
__device__ __forceinline__ void wgmma_pv(float (&d)[128], const uint4& a, uint32_t blo, int acc) {
    asm volatile("{\n.reg .pred p;\n.reg .b32 u0, u1, u2, u3, t;\n.reg .b64 d0, d1, d2, d3;\nsetp.ne.b32 p, %133, 0;\n"
        "mov.b64 d0, {%132, 0x40000100};\nadd.u32 t, %132, 512;\nmov.b64 d1, {t, 0x40000100};\n"
        "add.u32 t, %132, 128;\nmov.b64 d2, {t, 0x40000100};\nadd.u32 t, %132, 640;\nmov.b64 d3, {t, 0x40000100};\n"
        "wgmma.fence.sync.aligned;\n"
        "wgmma.mma_async.sync.aligned.m64n128k16.f32.bf16.bf16 " PV_LO "{%128, u0, %129, u1}, d0, p, 1, 1, 1;\n"
        "wgmma.mma_async.sync.aligned.m64n128k16.f32.bf16.bf16 " PV_LO "{%130, u2, %131, u3}, d1, 1, 1, 1, 1;\n"
        "wgmma.commit_group.sync.aligned;\n"
        "wgmma.mma_async.sync.aligned.m64n128k16.f32.bf16.bf16 " PV_HI "{%128, u0, %129, u1}, d2, p, 1, 1, 1;\n"
        "wgmma.mma_async.sync.aligned.m64n128k16.f32.bf16.bf16 " PV_HI "{%130, u2, %131, u3}, d3, 1, 1, 1, 1;\n"
        "wgmma.commit_group.sync.aligned;\n}"
        : R8(0), R8(8), R8(16), R8(24), R8(32), R8(40), R8(48), R8(56), R8(64), R8(72), R8(80), R8(88), R8(96), R8(104), R8(112), R8(120)
        : "r"(a.x), "r"(a.y), "r"(a.z), "r"(a.w), "r"(blo), "r"(acc) : "memory");
}

template <int NW>
__device__ __forceinline__ void ln_stats(float s, float q, float sh, float* scr, int w, int lane, int bar, float& mean_b, float& sd_b) {
#pragma unroll
    for (int o = 16; o; o >>= 1) { s += shx(s, o); q += shx(q, o); }
    constexpr float n = 512.f / NW;
    if (lane == 0) { scr[w] = sh + s * (1.f / n); scr[NW + w] = q - s * s * (1.f / n); }
    bar_sync(bar, NW * 32);
    float mu = 0.f, m2 = 0.f;
#pragma unroll
    for (int i = 0; i < NW; i++) { mu += scr[i]; m2 += scr[NW + i]; }
    mu *= 1.f / NW;
#pragma unroll
    for (int i = 0; i < NW; i++) { const float d = scr[i] - mu; m2 = fmaf(n * d, d, m2); }
    mean_b = rbf(mu);
    sd_b = rbf(sqrtf(rbf(rbf(fmaxf(m2, 0.f) * (1.f / 512.f)) + 1e-5f)));
}
__device__ __forceinline__ float ln_mod(float x, float mean_b, float sd_b, float c, float s) {
    return rbf(rbf(__fdividef(rbf(x - mean_b), sd_b)) * rbf(1.f + c)) + s;
}

__global__ void __cluster_dims__(2, 1, 1) __launch_bounds__(NTHREADS, 1)
fused_kernel(const __grid_constant__ First F, __nv_bfloat16* __restrict__ out, uint32_t* __restrict__ gs, const __grid_constant__ Maps M) {
    extern __shared__ __align__(1024) uint8_t sm[];
    const uint32_t sb = s2u(sm);
    const int tid = threadIdx.x, lane = tid & 31;
    const int j = blockIdx.x, rk = j & 1;
    const int g = lane >> 2, t = lane & 3;
    const int r8 = lane & 7, lb3 = (lane >> 3) & 1, lb4 = lane >> 4;
    uint64_t pol;
    asm("createpolicy.fractional.L2::evict_first.b64 %0, 1.0;" : "=l"(pol));
    {
        auto cpa = [&](uint32_t d, const uint8_t* s) {
            asm volatile("cp.async.cg.shared.global.L2::cache_hint.L2::128B [%0], [%1], 16, %2;" :: "r"(d), "l"(s), "l"(pol) : "memory");
        };
        const uint32_t ut = threadIdx.x, uj = blockIdx.x;
        const uint8_t* w = F.w[ut >= 128];
        if (ut < 128) {
            const uint32_t dq = (sb + ut * 16) ^ ((ut * 2) & 0x70);
            const uint8_t* sq = w + (uint32_t)(((uj & 1) * 256 + (ut >> 3)) * 8192 + (uj >> 1) * 128 + (ut & 7) * 16);
#pragma unroll
            for (int i = 0; i < 4 * NCP; i++) cpa(dq + 4 * 32768 + i * 2048, sq + i * 131072);
        } else if (ut < 384) {
            const uint32_t dm = (sb + ut * 16) ^ ((ut * 2) & 0x10);
            const uint8_t* sa = w + (uint32_t)(((uj >> 5) * 128 + (ut >> 1) - 64) * 6144 + (uj & 31) * 32 + (ut & 1) * 16);
            cpa(dm + SM_XA - 2048, sa); cpa(dm + SM_XA + 2048, sa + 1024);
        }
        else if (ut == 480 && uj < 64) asm volatile("prefetch.global.L2 [%0];" :: "l"(F.v[(uj >> 3) & 1] + (uj & 7) * 64));
    }
    const int warp = __shfl_sync(0xffffffffu, tid >> 5, 0);
    const __nv_bfloat16* const xin = F.v[0];
    uint32_t* const pl = gs + (warp < 2 ? (B_PR + (j >> 5)) * 4096 + (j & 31) * 32 : G_E1 + j * 8192) + (warp & 1) * 1024 + lane;
    if (warp < 4) st_x1(pl, 1u);
    auto BAR = [&](int i) -> uint32_t { return sb + SM_BAR + i * 8; };
    const uint32_t a16 = (r8 + 8 * lb4) * 32 + ((lb3 ^ (r8 >> 2)) * 16);
    const uint32_t a128 = (r8 + 8 * lb4) * 128 + ((((warp & 3) * 2 + lb3) ^ r8) * 16);
    auto ldcls = [&]() -> uint32_t { return *(const volatile uint32_t*)(sm + SM_CLS); };
    auto clear_head = [&]() {
        st2_x1(gs + (B_HA + ((j >> 4) & 1) * 2 + lb4) * 4096 + (j >> 5) * 256 + (j & 15) * 16 + (lane & 15), 0u);
        st2_x4(gs + (B_QA + rk * 8 + ((j >> 1) & 1) * 4 + (j >> 5)) * 4096 + g * 128 + ((j >> 2) & 7) * 16 + t * 4, 0u, 0u, 0u, 0u);
        if (lane < 8) st2_x1(gs + B_RD * 4096 + j * 8 + lane, 0u);
    };
    auto tma = [&](uint32_t dst, const CUtensorMap* mp, uint32_t bar, int c0, int c1, int c2, int c3) {
        asm volatile("{\n.reg .pred p;\nelect.sync _|p, 0xffffffff;\n"
                     "@p cp.async.bulk.tensor.4d.shared::cluster.global.mbarrier::complete_tx::bytes.L2::cache_hint [%0], [%1, {%3, %4, %5, %6}], [%2], %7;\n}"
                     :: "r"(dst), "l"(mp), "r"(bar), "r"(c0), "r"(c1), "r"(c2), "r"(c3), "l"(pol) : "memory");
    };
    if (warp <= 12 || warp == 15) {
        const int grp = warp == 12 ? 0 : warp == 15 ? 13 : warp + 1;
        const uint32_t cnt = grp < 10 ? 1 : grp < 13 ? 4 : 8;
        if (lane == 0) {
#pragma unroll
            for (int i = 0; i < 8; i++) mbar_init(BAR(grp * 8 + i), (i < 2 && grp == 0) ? (i ? 128 : 256) : cnt);
        }
        __syncwarp();
        if (grp < 10 && lane < 8 && (grp || lane > NCP)) mbar_expect(BAR(grp * 8 + lane), grp >= 8 ? 4096 : grp * 8 + lane < IT_X ? 8192 : 16384);
        asm volatile("fence.mbarrier_init.release.cluster;" ::: "memory");
        __syncwarp();
        if (warp == 12) {
#pragma unroll
            for (int i = NCP + 1; i < W0; i++) tma(sb + (15 + i) * 8192, &M.m[MP_WQ], BAR(i), 0, rk * 256 + (i - 1) * 64, j >> 1, 0);
        }
    } else if (warp == 13) {
        if (lane < NMAPS) asm volatile("prefetch.tensormap [%0];" :: "l"(&M.m[lane]) : "memory");
    } else if (warp == 14) {
        clear_head();
    }
    __syncthreads();
    uint32_t in1 = 0, in2 = 0;
    if (warp < 4) { in1 = *(const uint32_t*)(xin + 2 * tid); in2 = *(const uint32_t*)(xin + 256 + 2 * tid); }
    else if (warp < 12) in1 = *(const uint32_t*)(F.v[1] + 2 * (tid - 128));
    if (warp < 12) asm volatile("cp.async.mbarrier.arrive.noinc.shared::cta.b64 [%0];" :: "r"(BAR(warp < 4)) : "memory");
    asm volatile("barrier.cluster.arrive.relaxed.aligned;" ::: "memory");

    if (warp >= 12) {
    asm volatile("setmaxnreg.dec.sync.aligned.u32 64;");
    if (warp == 12) {
        static_assert(W0 > NCP && W0 <= 5 && NCP >= 1 && NCP <= 4, "W0");
        const uint2* sched = M.sched[j < NFF ? 0 : j < J_RED ? 1 : 2];
        uint2 en = sched[W0];
        const uint32_t t0 = gtime();
        const uint32_t sp = __reduce_or_sync(0xffffffffu, sb);
        const int cx = (j >> 1) * 64 + (j < NFF ? 0 : 1024 - NFF * 32);
#pragma unroll 1
        for (int i = W0; en.x; i++) {
            uint32_t e = en.x, st = (en.y >> 20) * 64;
            const uint32_t tn = t0 + (int16_t)en.y, mp = (en.y >> 16) & 15;
            if (mp == MP_WUV || mp == MP_WUK) { st ^= (j >> 5) * (mp == MP_WUV ? 128 : 64); e ^= (j >> 5) << 6; }
            if (mp == MP_GATE || mp == MP_UP) st ^= (j & 16) * 8;
            en = sched[i + 1];
            if (mp == MP_MODB && j >= J_END) break;
            uint32_t c0 = mp == MP_WO ? (j & 7) * 64 : mp > MP_WO ? cx : 0;
            uint32_t c1 = mp == MP_CKV ? 0 : mp == MP_DOWN ? j * 32 : st + (mp == MP_WUV ? (j & 3) * 32 : mp == MP_WO ? (j >> 3) * 256 : rk * 256);
            uint32_t c2 = mp < MP_CKV ? j >> 1 : mp == MP_CKV ? rk * 4 : mp == MP_WUV ? (j >> 2) * 2 : mp == MP_DOWN ? st >> 4 : 0;
            uint32_t c3 = mp == MP_CKV ? st * 2 + (j & ~1) : 0;
            uint32_t dst = sp + ((e << 7) & 0x3e000), bar = sp + SM_BAR + (e & 63) * 8;
            const uint32_t w0 = (e >> 8) & 0x3f8, w1 = (e >> 15) & 0x3f8, w2 = (e >> 22) & 0x3f8, bb = sp + SM_BAR - 8;
            const CUtensorMap* pm = &M.m[mp];
            pin(dst); pin(bar); pin(c0); pin(c1); pin(c2); pin(c3); pin(pm);
            if (w0) mbar_wait(bb + w0, 0);
            if (w2) {
                mbar_wait(bb + w2, 0);
                while (!__any_sync(0xffffffffu, mbar_test(bb + w1, 0) | ((int)(gtime() - tn) > 0))) {}
            } else if (w1) mbar_wait(bb + w1, 0);
            tma(dst, pm, bar, c0, c1, c2, c3);
        }
    } else if (warp == 13) {
#pragma unroll
        for (int i = 0; i < 2; i++) st_x4(gs + (B_ML + rk * 16 + i * 8 + g) * 4096 + (t >> 1) * 1024 + (j >> 1) * 8 + (t & 1) * 4, 0u, 0u, 0u, 0u);
        if (lane < 16) st2_x4(gs + (B_E2 + (j >> 4)) * 4096 + (j & 15) * 64 + lane * 4, 0u, 0u, 0u, 0u);
        st2_x1(gs + (B_E3 + (j >> 5)) * 4096 + (j & 31) * 32 + lane, 0u);
        if (lane < 8) st2_x1(gs + B_MB * 4096 + j * 8 + lane, 0u);
        if (j < NFF) {
#pragma unroll
            for (int i = 0; i < 2; i++) st2_x4(gs + (B_E5 + i * 8 + g) * 4096 + j * 16 + t * 4, 0u, 0u, 0u, 0u);
        }
        bar_sync(9, 64);
        const uint32_t cs = ldcls();
#pragma unroll 1
        for (int i = 0; i < 32; i++) {
            st_x4(gs + G_E1 + j * 8192 + (i >> 3) * 2048 + ((((cs >> 1) ^ (i >> 3)) & 1) << 10) + (i & 7) * 128 + lane * 4, 0u, 0u, 0u, 0u);
            __nanosleep(JAN_SLEEP);
        }
        fence_gpu();
        if (lane < 8) st2_x1(gs + B_RD * 4096 + j * 8 + lane, 1u + (cs >> 1));
        if (lane == 0) TRACE(41);
        uint32_t rd[4];
        mbar_wait(BAR(IT_CKV + RD_ITEM), 0);
        poll<1024, RD_SLEEP>(rd, gs + near_off(B_RD, cs) + lane * 8);
#pragma unroll
        for (int i = 0; i < 4; i++) {
            const uint32_t m = __ballot_sync(0xffffffffu, rd[i] == 2u);
            if (lane == 0) sts32(sb + SM_CLS + 16 + i * 4, m);
        }
        __syncwarp();
        if (lane < 8) mbar_arrive(BAR(JD));
        if (lane == 0) TRACE(42);
    } else if (warp == 14) {
        uint2 ml[2];
        mbar_waitb(BAR(JD), 0);
        const uint32_t cls = ldcls();
        mbar_waitb(BAR(PF0 + 2 * NUNITS - 1), 0);
        __nanosleep(ML_DELAY);
        const uint32_t* pl2 = gs + near_off(B_ML + (j >> 2), cls) + lane * 8;
        const uint32_t wa = sb + SM_W + lb4 * 64 + t * 16 + (g & 3) * 4;
        poll_start<1024>(ml, pl2);
        uint32_t w0 = 0, w1 = 0, redo = 0;
        bool first = true;
#pragma unroll 1
        for (uint32_t it = 0;; it++) {
            const bool p0 = minw(ml[0]) != 0, p1 = minw(ml[1]) != 0;
            const int n = __popc(__ballot_sync(0xffffffffu, p0)) + __popc(__ballot_sync(0xffffffffu, p1));
            const uint32_t x0 = ml[0].x, x1 = ml[1].x;
            if (n < 64) {
                if (!p0) ld_x(ml[0], pl2);
                if (!p1) ld_x(ml[1], pl2 + 256);
            }
            if (n == 64 || (first && n >= E1_EARLY)) {
                auto ord = [](int x) { return x ^ ((x >> 31) & 0x7fffffff); };
                const int o0 = ord(x0), o1 = ord(x1);
                const float mm = __int_as_float(ord(__reduce_max_sync(0xffffffffu, max(p0 ? o0 : INT_MIN, p1 ? o1 : INT_MIN))));
                const float lo = __int_as_float(ord(__reduce_min_sync(0xffffffffu, min(p0 ? o0 : INT_MAX, p1 ? o1 : INT_MAX))));
                const uint32_t v0 = pack2(ex2((p0 ? __uint_as_float(x0) : lo) - mm), 0.f), v1 = pack2(ex2((p1 ? __uint_as_float(x1) : lo) - mm), 0.f);
                redo = !first && __any_sync(0xffffffffu, v0 != w0 || v1 != w1);
                w0 = v0; w1 = v1;
                sts32(wa - redo * (SM_W - SM_W2), w0 * 0x10001u); sts32(wa - redo * (SM_W - SM_W2) + 128, w1 * 0x10001u);
                if (first) bar_arrive(3, 416);
                first = false;
                if (n == 64) break;
            }
            if (it > SPIN_LIMIT) __trap();
        }
        if (lane == 0) TRACE_Q(37);
        float L = bflo(w0) * __uint_as_float(ml[0].y) + bflo(w1) * __uint_as_float(ml[1].y);
#pragma unroll
        for (int o = 16; o; o >>= 1) L += shx(L, o);
        if (lane == 0) *(float2*)(sm + SM_FQ) = make_float2(__frcp_rn(L), __uint_as_float(redo));
        __syncwarp();
        if (lane < 8) mbar_arrive(BAR(WR));
        if (lane == 0) TRACE(10);
        bar_sync(4, 288);
        clear_head();
        if (j < NFF) {
            uint32_t ya = sb + SM_Y + lane * 16, sa = peer_addr(sb + SM_RED + 2048 + rk * 8, lane & 1), tb = peer_addr(BAR(MBB), lane & 1);
            pin(ya); pin(sa); pin(tb);
            bar_sync(7, 288);
            const float4 y0 = ldsf4(ya), y1 = ldsf4(ya + 512);
            float s = sum4(y0) + sum4(y1);
            float q = (fmaf(y0.x, y0.x, y0.y * y0.y) + fmaf(y0.z, y0.z, y0.w * y0.w)) + (fmaf(y1.x, y1.x, y1.y * y1.y) + fmaf(y1.z, y1.z, y1.w * y1.w));
#pragma unroll
            for (int o = 16; o; o >>= 1) { s += shx(s, o); q += shx(q, o); }
            if (lane < 2) st_async2(sa, s, q, tb);
        }
    } else if (warp == 15) {
        mbar_waitb(BAR(IT_X - 1), 0);
        if (j < J_END) mbar_waitb(BAR(j < NFF ? NITEMS - 1 : MBB), 0);
    }
    } else if (warp < 4) {
        float* scr = (float*)(sm + SM_SCR);
        uint32_t cls;
        {
            uint2 ha[8];
            uint32_t best = 0xffffffffu;
            sts32(sb + SM_SCR + 64 + warp * 4, best);
            const float sh = __shfl_sync(0xffffffffu, bflo(in1), 0);
            const float v0 = bflo(in1) - sh, v1 = bfhi(in1) - sh, v2 = bflo(in2) - sh, v3 = bfhi(in2) - sh;
            float mb, sd;
            ln_stats<4>((v0 + v1) + (v2 + v3), (v0 * v0 + v1 * v1) + (v2 * v2 + v3 * v3), sh, scr, warp, lane, 2, mb, sd);
            if (!rk) in2 = in1;
#pragma unroll 1
            for (int i = 0; i < NPROBE; i++) {
                uint32_t t0, t1, o;
                asm volatile("mov.u32 %0, %%clock;" : "=r"(t0));
                asm volatile("atom.relaxed.gpu.global.exch.b32 %0, [%1], %2;" : "=r"(o) : "l"(pl), "r"(2u + i) : "memory");
                asm volatile("{\n.reg .pred p;\nsetp.ne.u32 p, %1, 0x1234567;\nmov.u32 %0, 0;\n@p mov.u32 %0, %%clock;\n}" : "=r"(t1) : "r"(o));
                best = min(best, t1 - t0);
                sts32(sb + SM_SCR + 64 + warp * 4, best);
                if (__all_sync(0xffffffffu, min(best, lds32(sb + SM_SCR + 64 + (warp ^ 1) * 4)) < NEAR_CLK)) break;
            }
            bar_sync(2, 128);
            const uint4 lt = *(const uint4*)(scr + 16);
            cls = NUMA ? ((lt.y < lt.x) ^ (__popc((B_PR + (j >> 5)) & 0x2C) & 1)) | (lt.w < lt.z) << 1 : 0;
            if (warp == 0) { if (lane == 0) sts32(sb + SM_CLS, cls); bar_arrive(9, 64); }
            if (tid == 0) TRACE(38);
            asm volatile("barrier.cluster.wait.aligned;" ::: "memory");
            mbar_wait(BAR(IT_MODA), 0);
            if (HA_DELAY) __nanosleep(HA_DELAY);
            poll<1024, H_SLEEP, false, 16384>(ha, gs + near_off(B_HA + rk * 2, cls) + 2 * tid);
            auto rsum = [](uint32_t a, uint32_t b, uint32_t c, uint32_t d) { return rbf((__uint_as_float(a) + __uint_as_float(b)) + (__uint_as_float(c) + __uint_as_float(d))); };
            sts32(sb + SM_FV + frag_off(2 * tid),
                  pack2(ln_mod(bflo(in2), mb, sd, rsum(ha[4].x, ha[5].x, ha[6].x, ha[7].x), rsum(ha[0].x, ha[1].x, ha[2].x, ha[3].x)),
                        ln_mod(bfhi(in2), mb, sd, rsum(ha[4].y, ha[5].y, ha[6].y, ha[7].y), rsum(ha[0].y, ha[1].y, ha[2].y, ha[3].y))));
            bar_arrive(5, 384);
            mbar_wait(BAR(QB), 0);
            if (tid < 64) {
                const float* qx = (const float*)(sm + SM_QX) + tid;
                sts16(sb + SM_FQ + frag_off(tid), pack2((qx[0] + qx[64]) + (qx[128] + qx[192]), 0.f));
            }
            bar_arrive(6, 384);
        }
        asm volatile("setmaxnreg.inc.sync.aligned.u32 192;");
        float acc[128];
        float M = 0.f;
        uint32_t pa = sb + SM_XA + warp * 512 + lane * 16, ma = sb + SM_MX + (warp * 8 + g) * 4, pf = BAR(PF0);
        uint32_t blo = __reduce_or_sync(0xffffffffu, (((sb + SM_U) & 0x3FFFFu) >> 4) | 0x400000u);
        uint32_t* e1[4];
#pragma unroll
        for (int i = 0; i < 4; i++) e1[i] = gs + G_E1 + (warp * 8 + g) * 4 * 8192 + (rk * 2 + (j >> 6)) * 2048 + ((j >> 1) & 31) * 32 + t * 4;
#pragma unroll 1
        for (int h = 0; h < 2 * NUNITS; h++) {
            mbar_wait(pf, 0);
            const float m = __uint_as_float(lds32(ma));
            const uint4 pn = lds128(pa);
            wg_wait0();
#pragma unroll
            for (int i = 0; i < 128; i++) asm volatile("" : "+f"(acc[i]) :: "memory");
            if (h == 0) M = m;
            uint32_t b2 = 0x3f803f80u;
            if (__builtin_expect(__any_sync(0xffffffffu, m != M), 0)) {
                const float Mn = fmaxf(M, m), alpha = ex2(M - Mn), beta = ex2(m - Mn);
                M = Mn;
                b2 = pack2(beta, beta);
#pragma unroll
                for (int jj = 0; jj < 32; jj++) { acc[4 * jj] *= alpha; acc[4 * jj + 1] *= alpha; }
            }
            auto mul2 = [](uint32_t x, uint32_t y) { uint32_t r; asm("mul.rn.bf16x2 %0, %1, %2;" : "=r"(r) : "r"(x), "r"(y)); return r; };
            const uint4 p = make_uint4(mul2(pn.x, b2), mul2(pn.y, b2), mul2(pn.z, b2), mul2(pn.w, b2));
            if (tid == 0 && (h & 1)) TRACE_Q(48 + (h >> 1));
            wgmma_pv(acc, p, blo, h);
            if (lane == 0 && h > 0 && !(h & 1)) mbar_arrive(BAR(EB_UNIT0 + (h >> 1) - 1));
            blo += h == 11 ? -11 * 1024 : 1024;
            pa += (h == 5 || h == 11) ? -5 * 2048 : 2048;
            ma += 128; pf += 8;
            if (h == 2 * NUNITS - 3) {
                mbar_wait(BAR(JD), 0);
                const uint32_t hm = (*(const uint32_t*)(sm + SM_CLS + 16 + warp * 4) >> (g * 4)) ^ ((j >> 6) ? 15u : 0u);
#pragma unroll
                for (int i = 0; i < 4; i++) e1[i] += ((hm >> i) & 1) << 10;
            }
        }
#pragma unroll
        for (int vv = 0; vv < 2; vv++) {
            if (vv && M == 1.f) __trap();
            if (vv) wg_wait0(); else wg_wait1();
#pragma unroll
            for (int i = 0; i < 64; i++) asm volatile("" : "+f"(acc[vv * 64 + i]) :: "memory");
            if (tid == 0 && !vv) TRACE_Q(63);
#pragma unroll
            for (int i = 0; i < 4; i++) {
                const float* a = &acc[vv * 64 + i * 16];
                st_x4(e1[i] + i * 8192 + vv * 16, enc(pack2(a[0], a[1])), enc(pack2(a[4], a[5])), enc(pack2(a[8], a[9])), enc(pack2(a[12], a[13])));
            }
        }
        bar_arrive(3, 416);
        if (tid == 0) TRACE_Q(17);
        if (j < NFF) {
            uint4 a[16];
            const uint32_t ad = sb + SM_U + B_DN * 32768 + warp * 8192 + (r8 + 8 * lb4) * 128 + (lb3 ^ r8) * 16;
            uint32_t rl = sb + SM_RED + lane * 16;
            uint32_t* p5 = gs + (B_E5 + warp * 4 + (t >> 1)) * 4096 + j * 16 + (t & 1) * 8 + g;
            pin(rl); pin(p5);
            if (lane == 0) mbar_expect(BAR(MBB), 4);
            auto ldd = [&]() {
#pragma unroll
                for (int s = 0; s < 16; s++) a[s] = ldsm<true>((ad ^ ((s & 3) * 32)) + (s >> 2) * 2048);
            };
            const uint32_t db = BAR(IT_DOWN + (warp >> 1));
            mbar_wait(BAR(MBB), 0);
            const float4 st = ldsf4(sb + SM_RED + 2048);
            const bool hd = __all_sync(0xffffffffu, mbar_test(db, 0));
            if (hd) ldd();
            const float mu = (st.x + st.z) * (1.f / 512.f);
            float rstd;
            asm volatile("rsqrt.approx.ftz.f32 %0, %1;" : "=f"(rstd) : "f"(fmaxf(fmaf(-mu, mu, (st.y + st.w) * (1.f / 512.f)), 0.f) + 1e-5f));
            mbar_wait(BAR(QB), 1);
            if (tid == 0) TRACE(25);
            const float4 f0 = ldsf4(rl), f2 = ldsf4(rl + 1024), f1 = ldsf4(rl + 512), f3 = ldsf4(rl + 1536);
            const float gg = fmaf(rstd, fmaf(-mu, f0.z + f2.z, (f0.x + f0.y) + (f2.x + f2.y)), f0.w + f2.w);
            const float uu = fmaf(rstd, fmaf(-mu, f1.z + f3.z, (f1.x + f1.y) + (f3.x + f3.y)), f1.w + f3.w);
            const float hh = __fdividef(gg * uu, 1.f + ex2(-gg * fmaf(gg * gg, 0.10294324f, 2.3022082f)));
            uint32_t hb[4];
#pragma unroll
            for (int i = 0; i < 4; i++) hb[i] = pack2(__shfl_sync(0xffffffffu, hh, 2 * t + 8 * i), __shfl_sync(0xffffffffu, hh, 2 * t + 8 * i + 1));
            if (!hd) { mbar_wait(db, 0); ldd(); }
#pragma unroll
            for (int i = 0; i < 2; i++) {
                uint32_t res = 0;
#pragma unroll
                for (int k = 0; k < 4; k++) {
                    float c[4] = {0.f, 0.f, 0.f, 0.f};
                    const uint4 &x = a[i * 8 + k], &y = a[i * 8 + k + 4];
                    mma(c, x.x, x.y, x.z, x.w, hb[0], hb[1]);
                    mma(c, y.x, y.y, y.z, y.w, hb[2], hb[3]);
                    if (t == k) res = pack2(c[0], c[2]);
                }
                st2_x1(p5 + i * 8192, enc(res));
            }
            if (tid == 0) { TRACE(27); TRACE_GT(47); }
        } else if (j < J_END) {
            uint4 a[8], b[4];
            float c[4], e[4];
            const bool own = (warp >> 1) == rk;
            const uint32_t xa = sb + SM_FV + (warp & 1) * 64 + g * 8;
            if (lane == 0) mbar_expect(BAR(MBB), own ? 64 : 0);
#pragma unroll
            for (int i = 0; i < 2; i++) {
                ldfrag(b, sb + SM_FS + rk * 512 + i * 256 + t * 16);
                mbar_wait(BAR(IT_X + i), 0);
                const uint32_t ab = sb + SM_U + B_X * 32768 + i * 16384 + a128;
                load8<true>(a, [&](int s) { return ab + s * 2048; });
                mma8(i ? e : c, a, b);
            }
            c[0] += e[0]; c[2] += e[2];
            if (!own) {
                if (t == 0) st_async2(peer_addr(xa, rk ^ 1), c[0], c[2], peer_addr(BAR(MBB), rk ^ 1));
            } else {
                mbar_wait(BAR(MBB), 0);
                const float2 pp = *(const float2*)(sm + (xa - sb));
                const float mine = t ? c[2] + pp.y : c[0] + pp.x, other = shx(mine, 4);
                const uint32_t w = (warp & 1) * 8 + t * 4 + (g >> 1), val = enc(pack2(mine, other));
                if (t < 2 && !(g & 1)) {
                    if (j < J_RED) st2_x1(gs + B_MB * 4096 + (j - NFF) * 16 + w, val);
                    else sts32(sb + SM_FV + 256 + w * 4, val);
                }
                __syncwarp();
                if (j >= J_RED && lane < 4) mbar_arrive(BAR(QB));
                if (lane == 0) TRACE(11);
            }
        }
    } else {
        const int u8 = tid - 128, w8 = warp - 4;
        const int v = w8 >> 2, wq4 = w8 & 3;
        {
            const float c0 = bflo(in1), c1 = bfhi(in1);
            sts32(sb + SM_FS + frag_off(2 * u8), pack2(__fdividef(c0, 1.f + __expf(-c0)), __fdividef(c1, 1.f + __expf(-c1))));
        }
        bar_sync(1, 256);
        asm volatile("barrier.cluster.wait.aligned;" ::: "memory");
        uint4 a[8], b[4]; float c[4];
        if (w8 < 2) {
            ldfrag(b, sb + SM_FS + (j >> 5) * 256 + t * 16);
            mbar_wait(BAR(IT_MODA), 0);
            if (u8 == 0) TRACE(12);
            const uint32_t ab = sb + SM_XA + w8 * 4096 + a16;
            load8<true>(a, [&](int s) { return ab + s * 512; });
            mma8(c, a, b);
            if (t < 2) st2_x1(gs + (B_HA + ((j >> 4) & 1) * 2 + w8) * 4096 + (j >> 5) * 256 + (j & 15) * 16 + t * 8 + g, encf(t ? c[2] : c[0]));
        }
        {
            mbar_wait(BAR(IT_WQ + 2 * v <= NCP ? 1 : IT_WQ + 2 * v), 0); mbar_wait(BAR(IT_WQ + 2 * v + 1 <= NCP ? 1 : IT_WQ + 2 * v + 1), 0);
            const uint32_t ab = sb + SM_U + 4 * 32768 + v * 16384 + a128;
            load8<true>(a, [&](int s) { return ab + s * 2048; });
            if (lane == 0) mbar_arrive(BAR(EB_WQ));
            bar_sync(5, 384);
            if (u8 == 0) TRACE(13);
            ldfrag(b, sb + SM_FV + v * 256 + t * 16);
            mma8(c, a, b);
            if (t < 2) {
                const float qv = t ? c[2] : c[0];
                const uint32_t qa_ = sb + SM_QX + ((rk * 2 + v) * 64 + wq4 * 16 + t * 8 + g) * 4;
                asm volatile("st.async.weak.shared::cluster.mbarrier::complete_tx::bytes.f32 [%0], %1, [%2];"
                             :: "r"(peer_addr(qa_, rk ^ 1)), "f"(qv), "r"(peer_addr(BAR(QB), rk ^ 1)) : "memory");
                sts32(qa_, __float_as_uint(qv));
            }
            __syncwarp();
            if (lane == 0) mbar_expect(BAR(QB), 64);
        }
        {
            mbar_wait(BAR(IT_WUK + (v ^ ((j >> 5) & 1))), 0); mbar_wait(BAR(IT_WUK + (v ^ ((j >> 5) & 1)) + 2), 0);
            const uint32_t ab = sb + SM_U + 5 * 32768 + (w8 * 16 + r8 + 8 * lb3) * 128;
            const uint32_t x16 = (lb4 ^ r8) * 16;
            load8<false>(a, [&](int s) { return ab + (s & 1) * 16384 + (x16 ^ ((s >> 1) * 32)); });
            bar_sync(6, 384);
            if (u8 == 0) TRACE(14);
            b[0] = lds128(sb + SM_FQ + t * 16); b[1] = lds128(sb + SM_FQ + 64 + t * 16);
            float e[4] = {0.f, 0.f, 0.f, 0.f};
            c[0] = c[1] = c[2] = c[3] = 0.f;
#pragma unroll
            for (int k = 0; k < 4; k++) {
                const uint32_t b0 = (k & 1) ? b[k >> 1].z : b[k >> 1].x, b1 = (k & 1) ? b[k >> 1].w : b[k >> 1].y;
                mma(c, a[2 * k].x, a[2 * k].y, a[2 * k].z, a[2 * k].w, b0, b1);
                mma(e, a[2 * k + 1].x, a[2 * k + 1].y, a[2 * k + 1].z, a[2 * k + 1].w, b0, b1);
            }
            const float mine = ((t & 1) ? ((t & 2) ? e[2] : e[0]) : ((t & 2) ? c[2] : c[0])) * 0.12751743f;
            const float other = shx(mine, 4);
            if (!(g & 1)) st2_x1(gs + (B_QA + rk * 8 + ((j >> 1) & 1) * 4 + (j >> 5)) * 4096 + w8 * 128 + ((j >> 2) & 7) * 16 + (g >> 1) * 4 + t, enc(pack2(mine, other)));
            if (u8 == 0) TRACE(15);
        }
        const uint32_t cls = ldcls();
        __nanosleep(QA_DELAY);
        {
            uint4 qb[8];
            const uint32_t* pq = gs + near_off(B_QA + rk * 8 + wq4, cls) + lane * 4;
            const uint32_t* pq2 = gs + near_off(B_QA + rk * 8 + 4 + wq4, cls) + lane * 4;
            if (lane == 0) {
                mbar_expect(BAR(QT), 4096);
                asm volatile("cp.async.bulk.shared::cluster.global.mbarrier::complete_tx::bytes [%0], [%1], 4096, [%2];"
                             :: "r"(sb + SM_U + 5 * 32768 + w8 * 4096), "l"(gs + near_off(B_QA + rk * 8 + w8, cls)), "r"(BAR(QT)) : "memory");
            }
            const uint32_t qs = sb + SM_U + 5 * 32768 + wq4 * 4096 + lane * 16;
            mbar_wait(BAR(QT), 0);
#pragma unroll
            for (int i = 0; i < 8; i++) { a[i] = lds128(qs + i * 512); qb[i] = lds128(qs + 16384 + i * 512); }
            poll<512, QA_SLEEP, true>(a, pq);
            poll<512, QA_SLEEP, true>(qb, pq2);
            if (lane == 0) mbar_arrive(BAR(EB_WUK));
            auto add2 = [](uint32_t x, uint32_t y) { uint32_t r; asm("add.rn.bf16x2 %0, %1, %2;" : "=r"(r) : "r"(x), "r"(y)); return r; };
#pragma unroll
            for (int i = 0; i < 8; i++) a[i] = make_uint4(add2(a[i].x, qb[i].x), add2(a[i].y, qb[i].y), add2(a[i].z, qb[i].z), add2(a[i].w, qb[i].w));
        }
        if (u8 == 0) TRACE(8);
        {
            float m = -INFINITY, l = 0.f;
            uint32_t xl = sb + SM_XB + w8 * 2048 + lane * 16, xr = peer_addr(xl, rk ^ 1), bsr = peer_addr(BAR(SF0 + v), rk ^ 1);
            uint32_t pa = sb + SM_XA + v * 2048 + wq4 * 512 + lane * 16, ma = sb + SM_MX + v * 128 + (wq4 * 8 + g) * 4;
            uint32_t fb = BAR(IT_CKV + v * 2), sf = BAR(SF0 + v);
            uint32_t dlo = __reduce_or_sync(0xffffffffu, (((sb + SM_U + v * 16384) & 0x3FFFFu) >> 4) | 0x10000u);
            if (STAG && v) __nanosleep(STAG);
#pragma unroll 1
            for (int n = 0; n < NUNITS; n++) {
                float d[2][16], sc[8];
#pragma unroll
                for (int i = 0; i < 2; i++) {
                    mbar_wait(fb + i * 8, 0);
                    wg_fence();
#pragma unroll
                    for (int s = 0; s < 8; s++) wgmma_rs_n32(d[i], a[s], (0x40000080ull << 32) | (dlo + i * 512 + (s >> 2) * 64 + (s & 3) * 2), s);
                    wg_commit();
                }
#pragma unroll
                for (int i = 0; i < 2; i++) {
                    if (i) wg_wait0(); else wg_wait1();
#pragma unroll
                    for (int k = 0; k < 16; k++) asm volatile("" : "+f"(d[i][k]) :: "memory");
                    sc[4 * i] = d[i][0] + d[i][6]; sc[4 * i + 1] = d[i][1] + d[i][7]; sc[4 * i + 2] = d[i][8] + d[i][14]; sc[4 * i + 3] = d[i][9] + d[i][15];
                    asm volatile("st.async.weak.shared::cluster.mbarrier::complete_tx::bytes.v4.f32 [%0], {%1, %2, %3, %4}, [%5];"
                                 :: "r"(xr + i * 1024), "f"(sc[4 * i]), "f"(sc[4 * i + 1]), "f"(sc[4 * i + 2]), "f"(sc[4 * i + 3]), "r"(bsr) : "memory");
                }
                if (u8 == 128) TRACE_Q(56 + (n < 6 ? n : -40));
                if (n >= 3) mbar_wait(BAR(EB_UNIT0 + n - 3), 0);
                dlo += n == 5 ? -5 * 2048 : 2048;
                fb += 32; xr ^= 512; bsr += 16;
                pin(fb); pin(xr); pin(bsr);
                mbar_wait(sf, 0);
                const float4 x = ldsf4(xl), y = ldsf4(xl + 1024);
                sc[0] += x.x; sc[1] += x.y; sc[2] += x.z; sc[3] += x.w; sc[4] += y.x; sc[5] += y.y; sc[6] += y.z; sc[7] += y.w;
                float pr[8];
#pragma unroll
                for (int i = 0; i < 8; i++) pr[i] = ex2(sc[i] - m);
                float mx = fmaxf(fmaxf(fmaxf(sc[0], sc[1]), fmaxf(sc[2], sc[3])), fmaxf(fmaxf(sc[4], sc[5]), fmaxf(sc[6], sc[7])));
                if (__builtin_expect(__any_sync(0xffffffffu, mx > m), 0)) {
                    mx = fmaxf(mx, shx(mx, 1));
                    mx = fmaxf(mx, shx(mx, 2));
                    const float mn = fmaxf(m, ceilf(mx * 0.0625f) * 16.f);
                    l *= ex2(m - mn);
                    m = mn;
#pragma unroll
                    for (int i = 0; i < 8; i++) pr[i] = ex2(sc[i] - m);
                }
                stsf(ma, m);
                asm volatile("st.shared.v4.u32 [%0], {%1, %2, %3, %4};" :: "r"(pa), "r"(pack2(pr[0], pr[1])), "r"(pack2(pr[2], pr[3])),
                             "r"(pack2(pr[4], pr[5])), "r"(pack2(pr[6], pr[7])) : "memory");
                __syncwarp();
                if (lane == 0) mbar_arrive(sf + (PF0 - SF0) * 8);
                l += ((pr[0] + pr[1]) + (pr[2] + pr[3])) + ((pr[4] + pr[5]) + (pr[6] + pr[7]));
                xl ^= 512; sf += 16; ma += 256; pa += (n == 2 || n == 5) ? -8192 : 4096;
            }
            l += shx(l, 1);
            l += shx(l, 2);
            float2* mlx = (float2*)(sm + SM_MX + 2048) + wq4 * 8 + g;
            if (v == 0) { *mlx = make_float2(m, l); bar_arrive(11, 256); }
            else {
                mbar_wait(BAR(JD), 0);
                bar_sync(11, 256);
                const float2 o = *mlx;
                const float mn = fmaxf(m, o.x);
                l = l * ex2(m - mn) + o.y * ex2(o.x - mn);
                if ((wq4 >> 1) == rk) st_x4(gs + (B_ML + wq4 * 8 + g) * 4096 + (t >> 1) * 1024 + (j >> 1) * 8 + (t & 1) * 4, encf(mn), encf(l), 1u, 1u);
            }
        }
        const int pi = j < NFF ? rk * 128 + w8 * 16 + (lane & 15) : ((j - J_RED) & 15) * 16 + v * 8 + lb4 * 4 + wq4;
        const uint32_t xw = *(const uint32_t*)(xin + 2 * pi);
        const uint32_t* pm = gs + near_off(B_MB, cls) + pi;
        const uint32_t* pb = gs + near_off(B_E2 + (j >> 4), cls) + (((j >> 3) & 1) * 2 + lb4) * 256 + (lane & 15) * 2;
        pin(pm); pin(pb);
        {
            const uint32_t ab = sb + SM_U + B_WUV * 32768 + v * 4096 + a128;
            uint32_t pa = sb + SM_PB + wq4 * 320 + frag_off(64 * v + 32 * (g >> 2) + 16 * (t & 1) + 8 * (t >> 1) + 2 * (g & 3));
            uint32_t fa = sb + SM_PB + g * 320 + t * 16;
            const uint32_t* pe = gs + G_E1 + j * 8192 + (w8 >> 1) * 2048 + ((((cls >> 1) ^ (w8 >> 1)) & 1) << 10) + (((w8 & 1) * 16 + t) * 8 + g) * 4;
            uint32_t* p2 = gs + (B_E2 + (j >> 4)) * 4096 + (t >> 1) * 1024 + (j & 12) * 64 + w8 * 32 + (j & 3) * 8 + (g & 6) + (t & 1);
            pin(pa); pin(fa); pin(pe); pin(p2);
            const uint32_t mk = (g & 1) ? 0xffff0000u : 0x0000ffffu, m0 = (g & 2) ? 0u : mk, m1 = (g & 2) ? mk : 0u;
            uint4 pv[4];
            bool hv = false;
            bar_sync(3, 416);
            uint4 wa = lds128(sb + SM_W + (wq4 * 4 + t) * 16);
            uint32_t wb[8] = {wa.x & m0, wa.x & m1, wa.y & m0, wa.y & m1, wa.z & m0, wa.z & m1, wa.w & m0, wa.w & m1};
            pv[0] = pv[1] = pv[2] = pv[3] = make_uint4(0u, 0u, 0u, 0u);
            poll<512, E1_SLEEP, true>(pv, pe, [&]() {
                if (!hv) {
                    hv = __all_sync(0xffffffffu, mbar_test(BAR(IT_WUV + t), 0));
                    if (hv) load8<true>(a, [&](int s) { return ab + (s >> 1) * 8192 + (s & 1) * 2048; });
                }
            });
            if (lane == 0) TRACE_Q(48 + w8);
            if (u8 == 0) TRACE_Q(18);
            float lo, hi2;
            float2 inv;
#pragma unroll 1
            for (int pass = 0;; pass++) {
                float e[4][4];
#pragma unroll
                for (int i = 0; i < 4; i++) {
                    e[i][0] = e[i][1] = e[i][2] = e[i][3] = 0.f;
                    mma(e[i], pv[i].x, pv[i].y, pv[i].z, pv[i].w, wb[2 * i], wb[2 * i + 1]);
                }
                const float r0 = (t & 2) ? (e[0][2] + e[1][2]) + (e[2][2] + e[3][2]) : (e[0][0] + e[1][0]) + (e[2][0] + e[3][0]);
                const float r1 = (t & 2) ? (e[0][3] + e[1][3]) + (e[2][3] + e[3][3]) : (e[0][1] + e[1][1]) + (e[2][1] + e[3][1]);
                const uint32_t hi = pack2(r0, r1);
                sts32(pa, hi); sts32(pa + 1280, pack2(r0 - bflo(hi), r1 - bfhi(hi)));
                if (!hv) {
#pragma unroll 1
                    for (int i = 0; i < 4; i++) mbar_wait(BAR(IT_WUV + i), 0);
                    load8<true>(a, [&](int s) { return ab + (s >> 1) * 8192 + (s & 1) * 2048; });
                    hv = true;
                }
                bar_sync(1, 256);
                if (u8 == 0) TRACE(19);
                ldfrag(b, fa);
                mma8(c, a, b);
                mbar_wait(BAR(WR), 0);
                asm volatile("ld.shared.v2.f32 {%0, %1}, [%2];" : "=f"(inv.x), "=f"(inv.y) : "r"(sb + SM_FQ) : "memory");
                quad_pair(c[0] + c[1], c[2] + c[3], t, lo, hi2);
                if (__builtin_expect(__all_sync(0xffffffffu, pass || __float_as_uint(inv.y) == 0), 1)) break;
                wa = lds128(sb + SM_W2 + (wq4 * 4 + t) * 16);
                wb[0] = wa.x & m0; wb[1] = wa.x & m1; wb[2] = wa.y & m0; wb[3] = wa.y & m1; wb[4] = wa.z & m0; wb[5] = wa.z & m1; wb[6] = wa.w & m0; wb[7] = wa.w & m1;
                bar_sync(1, 256);
            }
            if (!(g & 1)) st_x1(p2, enc(pack2(lo * inv.x, hi2 * inv.x)));
            bar_arrive(4, 288);
            if (u8 == 0) TRACE(20);
        }
        uint32_t mb[3] = {0u, 0u, 0u};
        if (j < NFF) poll_start<1024>(mb, pm);
        uint4 a2[8];
        if (v == 0) {
            const uint32_t ab = sb + SM_U + B_WO * 32768 + a128;
            uint32_t* p3 = gs + (B_E3 + ((j >> 1) & 3)) * 4096 + (t >> 1) * 1024 + (rk * 2 + (wq4 >> 1)) * 256 + (j >> 3) * 16 + (wq4 & 1) * 8 + (t & 1) * 4 + (g >> 1);
            pin(p3);
            uint2 bb[8];
#pragma unroll
            for (int i = 0; i < 8; i++) bb[i] = make_uint2(0u, 0u);
            bool ho = false;
            auto ldo = [&]() { load8<true>(a, [&](int s) { return ab + s * 2048; }); load8<true>(a2, [&](int s) { return ab + 16384 + s * 2048; }); };
            auto idle = [&]() {
                if (!ho) {
                    ho = __all_sync(0xffffffffu, mbar_test(BAR(IT_WO + t), 0));
                    if (ho) ldo();
                }
            };
            poll<128, 0, true>(bb, pb, idle);
            if (!ho) {
#pragma unroll 1
                for (int i = 0; i < 4; i++) mbar_wait(BAR(IT_WO + i), 0);
                ldo();
            }
            if (u8 == 0) TRACE(21);
            float e[4][4];
#pragma unroll
            for (int s = 0; s < 16; s++) {
                const uint4& x = (s & 2) ? a2[(s >> 2) * 2 + (s & 1)] : a[(s >> 2) * 2 + (s & 1)];
                const uint2& y = bb[(s >> 2) * 2 + (s & 1)];
                if (s < 4) e[s][0] = e[s][1] = e[s][2] = e[s][3] = 0.f;
                mma(e[s & 3], x.x, x.y, x.z, x.w, y.x, y.y);
            }
            float lo, hi;
            quad_pair((t & 2) ? (e[2][0] + e[3][0]) + (e[2][1] + e[3][1]) : (e[0][0] + e[1][0]) + (e[0][1] + e[1][1]),
                      (t & 2) ? (e[2][2] + e[3][2]) + (e[2][3] + e[3][3]) : (e[0][2] + e[1][2]) + (e[0][3] + e[1][3]), t, lo, hi);
            if (!(g & 1)) st_x1(p3, enc(pack2(lo, hi)));
            bar_arrive(1, 256);
            if (u8 == 0) TRACE(22);
        } else bar_sync(1, 256);
        if (j < NFF) {
            const uint32_t* p3 = gs + near_off(B_E3 + rk * 2 + v, cls) + wq4 * 256 + lane;
            uint32_t za = sb + SM_FZ + lb4 * 576 + frag_off(w8 * 32 + (lane & 15) * 2);
            uint32_t fa = sb + SM_FZ + (g & 3) * 576 + ((lane ^ j) & 16) * 16 + t * 16, ya = sb + SM_Y + u8 * 4;
            poll<1024, MB_SLEEP, true>(mb, pm);
            const uint32_t kk = pack2(1.f + bflo(mb[2]), 1.f + bfhi(mb[2]));
            sts32(za + 2 * 576, lb4 ? mb[1] : kk);
            uint32_t e3[8] = {0u, 0u, 0u, 0u, 0u, 0u, 0u, 0u};
            uint32_t ra = peer_addr(sb + SM_RED + (rk * 2 + v) * 512 + ((wq4 & 1) * 16 + (t >> 1) * 8 + g) * 16 + (t & 1) * 8, wq4 >> 1), tbo = peer_addr(BAR(QB), wq4 >> 1);
            pin(za); pin(fa); pin(ya); pin(ra); pin(tbo);
            if (lane == 0) mbar_expect(BAR(QB), 256);
            const uint32_t gb = BAR(IT_X + v * 2), ab = sb + SM_U + (B_X + v) * 32768 + a128;
            bool early = false, early2 = false;
            auto ldw = [&]() {
                if (!early) {
                    early = __all_sync(0xffffffffu, mbar_test(gb, 0));
                    if (early) load8<true>(a, [&](int s) { return ab + s * 2048; });
                }
                if (!early2) {
                    early2 = __all_sync(0xffffffffu, mbar_test(gb + 8, 0));
                    if (early2) load8<true>(a2, [&](int s) { return ab + 16384 + s * 2048; });
                }
            };
            poll<128, 0, true>(e3, p3, ldw);
            if (u8 == 0) TRACE(23);
            const float s0 = sumlo(e3), s1 = sumhi(e3);
            const float y0 = fmaf(bflo(mb[0]), s0 + shx(s0, 16), bflo(xw)), y1 = fmaf(bfhi(mb[0]), s1 + shx(s1, 16), bfhi(xw));
            stsf(ya, lb4 ? y1 : y0);
            const float z0 = y0 * bflo(kk), z1 = y1 * bfhi(kk);
            const uint32_t zh = pack2(z0, z1);
            sts32(za, lb4 ? pack2(z0 - bflo(zh), z1 - bfhi(zh)) : zh);
            bar_sync(7, 288);
            if (u8 == 0) TRACE(24);
            ldfrag(b, fa);
            if (!early) { mbar_wait(gb, 0); load8<true>(a, [&](int s) { return ab + s * 2048; }); }
            {
                float e[4][4];
#pragma unroll
                for (int s = 0; s < 16; s++) {
                    if (s == 8 && !early2) { mbar_wait(gb + 8, 0); load8<true>(a2, [&](int q) { return ab + 16384 + q * 2048; }); }
                    const uint4& x = s < 8 ? a[s] : a2[s & 7];
                    const uint4& y = b[(s >> 1) & 3];
                    float (&d)[4] = e[(s >> 3) * 2 + (s & 1)];
                    if (!(s & 6)) d[0] = d[1] = d[2] = d[3] = 0.f;
                    mma(d, x.x, x.y, x.z, x.w, (s & 1) ? y.z : y.x, (s & 1) ? y.w : y.y);
                }
                const bool hi = t >> 1;
                const float k0 = hi ? e[2][2] + e[3][2] : e[0][0] + e[1][0], k1 = hi ? e[2][3] + e[3][3] : e[0][1] + e[1][1];
                const float o0 = hi ? e[2][0] + e[3][0] : e[0][2] + e[1][2], o1 = hi ? e[2][1] + e[3][1] : e[0][3] + e[1][3];
                st_async2(ra, k0 + shx(o0, 2), k1 + shx(o1, 2), tbo);
            }
        } else if (j >= J_RED && j < J_END) {
            uint32_t ga[1], e3[1];
            poll<0, MB_SLEEP>(ga, pm);
            poll<0, 100>(e3, gs + near_off(B_E3 + (pi >> 6), cls) + (pi & 48) * 16 + (lane & 15) * 16 + (pi & 15));
            float y0 = bflo(e3[0]), y1 = bfhi(e3[0]);
#pragma unroll
            for (int o = 8; o; o >>= 1) { y0 += shx(y0, o); y1 += shx(y1, o); }
            y0 = fmaf(bflo(ga[0]), y0, bflo(xw)); y1 = fmaf(bfhi(ga[0]), y1, bfhi(xw));
            uint32_t gb = 0;
            auto ldg = [&]() { if (__all_sync(0xffffffffu, mbar_test(BAR(QB), 1))) gb = lds32(sb + SM_FV + 256 + (pi & 15) * 4); };
            uint32_t* po = (uint32_t*)out + pi;
            pin(po);
            const uint32_t nz = lane < NFF / 2 ? 0u : 0x80008000u;
            uint2 yv[2] = {make_uint2(nz, nz), make_uint2(nz, nz)};
            poll<NFF * 32, 0, true>(yv, gs + near_off(B_E5 + j - J_RED, cls) + lane * 16 + w8 * 2, ldg);
            if (u8 == 0) TRACE(26);
            const float l0 = bflo(yv[0].x) + bflo(yv[1].x), h0 = bfhi(yv[0].x) + bfhi(yv[1].x);
            const float l1 = bflo(yv[0].y) + bflo(yv[1].y), h1 = bfhi(yv[0].y) + bfhi(yv[1].y);
            float s0 = (lb4 ? h0 : l0) + shx(lb4 ? l0 : h0, 16), s1 = (lb4 ? h1 : l1) + shx(lb4 ? l1 : h1, 16);
#pragma unroll
            for (int o = 8; o; o >>= 1) { s0 += shx(s0, o); s1 += shx(s1, o); }
            if (__any_sync(0xffffffffu, !gb)) { mbar_wait(BAR(QB), 1); ldg(); }
            if (!(lane & 15)) *po = pack2(fmaf(bflo(gb), s0, y0), fmaf(bfhi(gb), s1, y1));
            if (u8 == 0) TRACE(27);
        }
    }
}

typedef CUresult (*EncFn)(CUtensorMap*, CUtensorMapDataType, cuuint32_t, void*, const cuuint64_t*, const cuuint64_t*,
                          const cuuint32_t*, const cuuint32_t*, CUtensorMapInterleave, CUtensorMapSwizzle,
                          CUtensorMapL2promotion, CUtensorMapFloatOOBfill);

void make_map(EncFn enc_fn, CUtensorMap* m, const void* p, cuuint64_t d0, cuuint64_t d1, cuuint64_t d2, cuuint64_t d3,
              cuuint64_t s1, cuuint64_t s2, cuuint64_t s3, cuuint32_t b0, cuuint32_t b1, cuuint32_t b2, cuuint32_t b3, CUtensorMapSwizzle sw) {
    const cuuint64_t dims[4] = {d0, d1, d2, d3}, strides[3] = {s1, s2, s3};
    const cuuint32_t box[4] = {b0, b1, b2, b3}, es[4] = {1, 1, 1, 1};
    enc_fn(m, CU_TENSOR_MAP_DATA_TYPE_BFLOAT16, 4, (void*)p, dims, strides, box, es,
           CU_TENSOR_MAP_INTERLEAVE_NONE, sw, PROMO, CU_TENSOR_MAP_FLOAT_OOB_FILL_NONE);
}

uint32_t* scratch = nullptr;

struct Tune { const char* win; const char* late; int tau, t_off; const char* tail[3][4]; };
Tune tune = {"66666666655555555555555555555555555533333",
             "00000000000000000000999999999999999999999", 322, -300,
             {{"VVVVOOOOguguDD", "zzzzzzzzzzzzzz", "88889999888877", "eddd0efffaaadd"},
              {"VMVMVVOOOO", "zzzzzzzzzz", "8888889999", "288888iddd"},
              {"VVVVOOOOMM", "zzzzzzzzzz", "aaaaaaaa88", "6ggg0ghhkn"}}};
bool ready = false;

}

extern "C" void kernel_launch(void* const* d_in, const int* in_sizes, int n_in, void* d_out, int out_size) {
    (void)in_sizes; (void)n_in; (void)out_size;
    static Maps maps;
    static const void* cached[12] = {};
    bool same = ready;
    for (int i = 0; i < 12 && same; i++) same = cached[i] == d_in[i];
    if (!same) {
        void* fn = nullptr;
        cudaDriverEntryPointQueryResult qr;
        cudaGetDriverEntryPoint("cuTensorMapEncodeTiled", &fn, cudaEnableDefault, &qr);
        EncFn e = (EncFn)fn;
        const CUtensorMapSwizzle S128 = CU_TENSOR_MAP_SWIZZLE_128B;
        make_map(e, &maps.m[MP_WQ], d_in[2], 64, 512, 64, 1, 8192, 128, 8192, 64, 64, 1, 1, S128);
        make_map(e, &maps.m[MP_WUK], d_in[3], 64, 512, 64, 1, 8192, 128, 8192, 64, 64, 1, 1, S128);
        make_map(e, &maps.m[MP_CKV], d_in[1], 64, 8, 8, 4096, 1024, 128, 8192, 64, 8, 4, 2, S128);
        make_map(e, &maps.m[MP_MODB], d_in[11], 3072, 512, 1, 1, 6144, 6144, 6144, 64, 128, 1, 1, S128);
        make_map(e, &maps.m[MP_WUV], d_in[4], 64, 512, 64, 1, 8192, 128, 8192, 64, 32, 2, 1, S128);
        make_map(e, &maps.m[MP_WO], d_in[5], 512, 4096, 1, 1, 1024, 1024, 1024, 64, 64, 1, 1, S128);
        make_map(e, &maps.m[MP_GATE], d_in[7], 1792, 512, 1, 1, 3584, 3584, 3584, 64, 128, 1, 1, S128);
        make_map(e, &maps.m[MP_UP], d_in[8], 1792, 512, 1, 1, 3584, 3584, 3584, 64, 128, 1, 1, S128);
        make_map(e, &maps.m[MP_DOWN], d_in[9], 64, 1792, 8, 1, 1024, 128, 1024, 64, 32, 4, 1, S128);
        for (int r = 0; r < 3; r++) {
            int ids[56], cnt[128] = {}, tn = tune.t_off - (W0 - 1) * tune.tau;
            uint2* sc = maps.sched[r];
            auto dig = [](char ch) { return ch >= 'a' ? ch - 'a' + 10 : ch >= 'A' ? ch - 'A' + 36 : ch - '0'; };
            for (int i = 0; i < 56; i++) sc[i] = make_uint2(0u, 0u);
            for (int i = 0;; i++) {
                int id = i, buf, dep, w, wl;
                if (i < IT_WUV) {
                    const int u = (i - IT_CKV) >> 2;
                    buf = i < IT_CKV ? 4 + ((i - 1) >> 2) : u % 6;
                    dep = i < IT_CKV || u < 4 ? -1 : u < 6 ? EB_WQ + u - 4 : EB_UNIT0 + u - 6;
                    w = dig(tune.win[i]); wl = dig(tune.late[i]);
                    if (i) tn += tune.tau;
                } else {
                    const char ch = tune.tail[r][0][i - IT_WUV];
                    if (!ch) break;
                    buf = ch == 'V' ? B_WUV : ch == 'O' ? B_WO : ch == 'D' ? B_DN : ch == 'u' ? B_X + 1 : B_X;
                    id = (ch == 'V' ? IT_WUV : ch == 'O' ? IT_WO : ch == 'D' ? IT_DOWN : ch == 'u' ? IT_X + 2 : IT_X) + cnt[(int)ch]++;
                    dep = EB_UNIT0 + (buf < 2 ? buf + 6 : buf);
                    w = dig(tune.tail[r][1][i - IT_WUV]); wl = dig(tune.tail[r][2][i - IT_WUV]);
                    tn += 32 * dig(tune.tail[r][3][i - IT_WUV]);
                }
                if (id < IT_X ? (id - 1) & 3 : (id - IT_X) & 1) dep = -1;
                ids[i] = id;
                auto back = [&](int d) { return i < d ? 0 : (ids[i - d] && ids[i - d] <= NCP ? 1 : ids[i - d]) + 1; };
                sc[i].x = id | (buf * 4 + (id < IT_X ? (id - 1) & 3 : ((id - IT_X) & 1) * 2)) << 6 | (dep + 1) << 11 | (w > 32 ? NEVER + 1 : back(w)) << 18 | (wl ? back(wl) : 0) << 25;
                const int mp = id < IT_CKV ? MP_WQ + ((id - 1) >> 2) : id < IT_WUV ? MP_CKV : id < IT_WO ? MP_WUV : id < IT_X ? MP_WO
                             : id >= IT_DOWN ? MP_DOWN : r ? MP_MODB : MP_GATE + ((id - IT_X) >> 1);
                const int step = mp == MP_CKV ? id - IT_CKV : mp == MP_WUV ? (id - IT_WUV) * 2 : mp == MP_DOWN ? id - IT_DOWN : id < IT_X ? (id - 1) & 3 : ((id - IT_X) & 1) * 2;
                sc[i].y = (tn & 0xffff) | (mp & 15) << 16 | step << 20;
            }
        }
        cudaGetSymbolAddress((void**)&scratch, g_scratch);
        scratch = (uint32_t*)(((uintptr_t)scratch + (2u << 20) - 1) & ~(uintptr_t)((2u << 20) - 1));
        cudaFuncSetAttribute(fused_kernel, cudaFuncAttributeMaxDynamicSharedMemorySize, SM_TOTAL);
        for (int i = 0; i < 12; i++) cached[i] = d_in[i];
        ready = true;
    }
    const First f = {{(const uint8_t*)d_in[2], (const uint8_t*)d_in[11]}, {(const __nv_bfloat16*)d_in[0], (const __nv_bfloat16*)d_in[10]}};
    fused_kernel<<<NCTA, NTHREADS, SM_TOTAL>>>(f, (__nv_bfloat16*)d_out, scratch, maps);
}
```

```cpp
#include <cuda_runtime.h>
#include <cuda_bf16.h>
#include <cuda.h>
#include <stdint.h>
#include <limits.h>

namespace {

constexpr int NCTA = 128;
constexpr int NTHREADS = 512;
constexpr int NUNITS = 8;
constexpr int NFF = 56, J_RED = 104, J_END = 120;
constexpr uint32_t SPIN_LIMIT = 1u << 22;

#define PROMO CU_TENSOR_MAP_L2_PROMOTION_L2_64B
#define NEAR_CLK 390
#define E1_EARLY 50
#define STAG 300
#define NUMA 1
#define NPROBE 5
#define NCP 2
#define W0 4
#define RD_ITEM 15
#define JAN_SLEEP 100
#define RD_SLEEP 400
#define HA_DELAY 200
#define H_SLEEP 100
#define QA_DELAY 600
#define QA_SLEEP 200
#define ML_DELAY 300
#define E1_SLEEP 50
#define MB_SLEEP 100
constexpr int B_WUV = 2, B_WO = 3, B_X = 4  , B_DN = 0;

constexpr int SM_U = 0;
constexpr int SM_XA = 6 * 32768;
constexpr int SM_XB = SM_XA + 12288;
constexpr int SM_MX = SM_XB + 16384;
constexpr int SM_FZ = SM_XB + 8192;
constexpr int SM_PB = SM_XB;
constexpr int SM_Y = SM_XB + 12288;
constexpr int SM_RED = SM_XB + 4096;
constexpr int SM_FS = SM_XB + 20480;
constexpr int SM_FV = SM_FS + 1024;
constexpr int SM_QX = SM_XA + 8192;
constexpr int SM_FQ = SM_FV + 512;
constexpr int SM_CLS = SM_FQ + 128;
constexpr int SM_W = SM_FQ + 256;
constexpr int SM_W2 = SM_MX + 2304;
constexpr int SM_SCR = SM_XA + 9216;
constexpr int SM_TR = SM_XB + 19456;
constexpr int SM_BAR = SM_W + 256;
constexpr int SM_TOTAL = SM_BAR + 1024;
static_assert(SM_TOTAL <= 232448, "smem");

enum { IT_MODA = 0, IT_WQ = 1, IT_WUK = 5, IT_CKV = 9, IT_WUV = 41, IT_WO = 45, IT_X = 49  , IT_DOWN = 53, NITEMS = 55,
       NEVER = 63,
       SF0 = 64,
       PF0 = 80,
       EB_UNIT0 = 96, MBB = 103,
       EB_WQ = 104, EB_WUK, QT, QB, JD, WR };

enum { MP_WQ = 0, MP_WUK, MP_CKV, MP_WUV, MP_DOWN, MP_WO, MP_GATE, MP_UP, MP_MODB, NMAPS };
struct First { const uint8_t* w[2]; const __nv_bfloat16* v[2]; };
struct Maps { CUtensorMap m[NMAPS]; uint2 sched[3][56]; };

enum { B_HA = 0,
       B_MB = 6,
       B_RD = 7,
       B_E2 = 8,
       B_QA = 16,
       B_ML = 32,
       B_E5 = 64,
       B_E3 = 80,
       B_PR = 96,
       B_TR = 100 };
constexpr int G_E1 = 1 << 19;
constexpr int G_TR = B_TR * 4096;
__device__ __align__(1024) uint32_t g_scratch[(8 << 20) / 4];

#define TRACE(slot) do {} while (0)
#define TRACE_Q(slot) do {} while (0)
#define TRACE_GT(slot) do {} while (0)

__device__ __forceinline__ uint32_t s2u(const void* p) { return (uint32_t)__cvta_generic_to_shared(p); }
__device__ __forceinline__ void mbar_init(uint32_t b, int c) { asm volatile("mbarrier.init.shared::cta.b64 [%0], %1;" :: "r"(b), "r"(c) : "memory"); }
__device__ __forceinline__ void mbar_expect(uint32_t b, uint32_t bytes) { asm volatile("mbarrier.arrive.expect_tx.shared::cta.b64 _, [%0], %1;" :: "r"(b), "r"(bytes) : "memory"); }
__device__ __forceinline__ void mbar_arrive(uint32_t b) { asm volatile("mbarrier.arrive.shared::cta.b64 _, [%0];" :: "r"(b) : "memory"); }
__device__ __forceinline__ void mbar_wait(uint32_t b, uint32_t ph) {
    asm volatile("{\n.reg .pred p;\nW: mbarrier.try_wait.parity.shared::cta.b64 p, [%0], %1;\n@!p bra W;\n}" :: "r"(b), "r"(ph) : "memory");
}
__device__ __forceinline__ void mbar_waitb(uint32_t b, uint32_t ph) {
    asm volatile("{\n.reg .pred p;\n.reg .u32 n;\nmov.u32 n, 0;\n"
                 "W: mbarrier.try_wait.parity.shared::cta.b64 p, [%0], %1;\n@p bra D;\n"
                 "add.u32 n, n, 1;\nsetp.lt.u32 p, n, 0x100000;\n@p bra W;\ntrap;\nD:\n}" :: "r"(b), "r"(ph) : "memory");
}
__device__ __forceinline__ uint32_t mbar_test(uint32_t b, uint32_t ph) {
    uint32_t ok;
    asm volatile("{\n.reg .pred p;\nmbarrier.test_wait.parity.shared::cta.b64 p, [%1], %2;\nselp.u32 %0, 1, 0, p;\n}" : "=r"(ok) : "r"(b), "r"(ph) : "memory");
    return ok;
}
__device__ __forceinline__ void bar_sync(int id, int n) { asm volatile("bar.sync %0, %1;" :: "r"(id), "r"(n) : "memory"); }
__device__ __forceinline__ void bar_arrive(int id, int n) { asm volatile("bar.arrive %0, %1;" :: "r"(id), "r"(n) : "memory"); }
__device__ __forceinline__ uint32_t peer_addr(uint32_t a, uint32_t rank) { uint32_t r; asm("mapa.shared::cluster.u32 %0, %1, %2;" : "=r"(r) : "r"(a), "r"(rank)); return r; }
__device__ __forceinline__ void st_async2(uint32_t a, float x, float y, uint32_t bar) {
    asm volatile("st.async.weak.shared::cluster.mbarrier::complete_tx::bytes.v2.f32 [%0], {%1, %2}, [%3];" :: "r"(a), "f"(x), "f"(y), "r"(bar) : "memory");
}
__device__ __forceinline__ uint32_t gtime() { uint32_t t; asm volatile("mov.u32 %0, %%globaltimer_lo;" : "=r"(t)); return t; }
__device__ __forceinline__ void fence_gpu() { asm volatile("fence.acq_rel.gpu;" ::: "memory"); }

__device__ __forceinline__ uint32_t enc(uint32_t b) { uint32_t r; asm("max.u32 %0, %1, 1;" : "=r"(r) : "r"(b)); return r; }
__device__ __forceinline__ uint32_t encf(float f) { return enc(__float_as_uint(f)); }
__device__ __forceinline__ void st_x1(uint32_t* p, uint32_t v) { asm volatile("st.relaxed.gpu.global.u32 [%0], %1;" :: "l"(p), "r"(v) : "memory"); }
__device__ __forceinline__ void st_x4(void* p, uint32_t a, uint32_t b, uint32_t c, uint32_t d) {
    asm volatile("st.relaxed.gpu.global.v4.u32 [%0], {%1, %2, %3, %4};" :: "l"(p), "r"(a), "r"(b), "r"(c), "r"(d) : "memory");
}
__device__ __forceinline__ void st2_x1(uint32_t* p, uint32_t v) { st_x1(p, v); st_x1(p + 1024, v); }
__device__ __forceinline__ void st2_x4(uint32_t* p, uint32_t a, uint32_t b, uint32_t c, uint32_t d) { st_x4(p, a, b, c, d); st_x4(p + 1024, a, b, c, d); }
__device__ __forceinline__ int near_off(int b, uint32_t cls) { return b * 4096 + (((__popc(b & 0x2C) ^ cls) & 1) << 10); }
__device__ __forceinline__ void ld_x(uint32_t& v, const void* p) { asm volatile("ld.relaxed.gpu.global.u32 %0, [%1];" : "=r"(v) : "l"(p) : "memory"); }
__device__ __forceinline__ void ld_x(uint4& v, const void* p) {
    asm volatile("ld.relaxed.gpu.global.v4.u32 {%0, %1, %2, %3}, [%4];" : "=r"(v.x), "=r"(v.y), "=r"(v.z), "=r"(v.w) : "l"(p) : "memory");
}
__device__ __forceinline__ void ld_x(uint2& v, const void* p) { asm volatile("ld.relaxed.gpu.global.v2.u32 {%0, %1}, [%2];" : "=r"(v.x), "=r"(v.y) : "l"(p) : "memory"); }
__device__ __forceinline__ uint32_t minw(uint32_t v) { return v; }
__device__ __forceinline__ uint32_t minw(const uint2& v) { return min(v.x, v.y); }
__device__ __forceinline__ uint32_t minw(const uint4& v) { return min(__vimin3_u32(v.x, v.y, v.z), v.w); }
template <int N> __device__ __forceinline__ uint32_t mint(const uint32_t* m) {
    if constexpr (N == 1) return m[0];
    else if constexpr (N == 2) return min(m[0], m[1]);
    else return __vimin3_u32(mint<(N + 2) / 3>(m), mint<(N + 1) / 3>(m + (N + 2) / 3), mint<N / 3>(m + (N + 2) / 3 + (N + 1) / 3));
}

template <int STRIDE, int S4 = 4 * STRIDE, typename T, int N>
__device__ __forceinline__ void poll_start(T (&v)[N], const void* base) {
#pragma unroll
    for (int i = 0; i < N; i++) ld_x(v[i], (const uint8_t*)base + (i & 3) * STRIDE + (i >> 2) * S4);
}
struct Nop { __device__ void operator()() const {} };
template <int STRIDE, int SLEEP, bool STARTED = false, int S4 = 4 * STRIDE, typename T, int N, typename F = Nop>
__device__ __forceinline__ void poll(T (&v)[N], const void* base, F idle = F()) {
    if (!STARTED) { poll_start<STRIDE, S4>(v, base); idle(); }
#pragma unroll 1
    for (uint32_t it = 0;; it++) {
        uint32_t m[N];
#pragma unroll
        for (int i = 0; i < N; i++) m[i] = minw(v[i]);
        if (__all_sync(0xffffffffu, mint<N>(m) != 0)) break;
        if (SLEEP && it > 0) __nanosleep(SLEEP);
#pragma unroll
        for (int i = 0; i < N; i++) if (!m[i]) ld_x(v[i], (const uint8_t*)base + (i & 3) * STRIDE + (i >> 2) * S4);
        idle();
        if (it > SPIN_LIMIT) __trap();
    }
}

__device__ __forceinline__ float bflo(uint32_t w) { return __uint_as_float(w << 16); }
__device__ __forceinline__ float bfhi(uint32_t w) { return __uint_as_float(w & 0xffff0000u); }
__device__ __forceinline__ uint32_t pack2(float lo, float hi) {
    uint32_t r; asm("cvt.rn.bf16x2.f32 %0, %1, %2;" : "=r"(r) : "f"(hi), "f"(lo)); return r;
}
__device__ __forceinline__ float rbf(float x) { return __uint_as_float(pack2(0.f, x)); }
__device__ __forceinline__ float sumlo(const uint32_t (&v)[8]) { return ((bflo(v[0]) + bflo(v[1])) + (bflo(v[2]) + bflo(v[3]))) + ((bflo(v[4]) + bflo(v[5])) + (bflo(v[6]) + bflo(v[7]))); }
__device__ __forceinline__ float sumhi(const uint32_t (&v)[8]) { return ((bfhi(v[0]) + bfhi(v[1])) + (bfhi(v[2]) + bfhi(v[3]))) + ((bfhi(v[4]) + bfhi(v[5])) + (bfhi(v[6]) + bfhi(v[7]))); }
__device__ __forceinline__ float ex2(float x) { float r; asm("ex2.approx.ftz.f32 %0, %1;" : "=f"(r) : "f"(x)); return r; }
__device__ __forceinline__ float shx(float v, int m) { return __shfl_xor_sync(0xffffffffu, v, m); }
__device__ __forceinline__ uint4 lds128(uint32_t a) { uint4 v; asm volatile("ld.shared.v4.u32 {%0, %1, %2, %3}, [%4];" : "=r"(v.x), "=r"(v.y), "=r"(v.z), "=r"(v.w) : "r"(a) : "memory"); return v; }
__device__ __forceinline__ uint32_t lds32(uint32_t a) { uint32_t v; asm volatile("ld.shared.u32 %0, [%1];" : "=r"(v) : "r"(a) : "memory"); return v; }
__device__ __forceinline__ void sts32(uint32_t a, uint32_t v) { asm volatile("st.shared.u32 [%0], %1;" :: "r"(a), "r"(v) : "memory"); }
__device__ __forceinline__ void sts16(uint32_t a, uint32_t v) { asm volatile("st.shared.u16 [%0], %1;" :: "r"(a), "h"((uint16_t)v) : "memory"); }
__device__ __forceinline__ int frag_off(int k) { return (k >> 5) * 64 + ((k >> 1) & 3) * 16 + ((k >> 4) & 1) * 8 + ((k >> 3) & 1) * 4 + (k & 1) * 2; }

template <bool TRANS>
__device__ __forceinline__ uint4 ldsm(uint32_t a) {
    uint4 r;
    if (TRANS) asm volatile("ldmatrix.sync.aligned.m8n8.x4.trans.shared.b16 {%0, %1, %2, %3}, [%4];" : "=r"(r.x), "=r"(r.y), "=r"(r.z), "=r"(r.w) : "r"(a) : "memory");
    else asm volatile("ldmatrix.sync.aligned.m8n8.x4.shared.b16 {%0, %1, %2, %3}, [%4];" : "=r"(r.x), "=r"(r.y), "=r"(r.z), "=r"(r.w) : "r"(a) : "memory");
    return r;
}
__device__ __forceinline__ void mma(float (&c)[4], uint32_t a0, uint32_t a1, uint32_t a2, uint32_t a3, uint32_t b0, uint32_t b1) {
    asm volatile("mma.sync.aligned.m16n8k16.row.col.f32.bf16.bf16.f32 {%0,%1,%2,%3}, {%4,%5,%6,%7}, {%8,%9}, {%0,%1,%2,%3};"
                 : "+f"(c[0]), "+f"(c[1]), "+f"(c[2]), "+f"(c[3]) : "r"(a0), "r"(a1), "r"(a2), "r"(a3), "r"(b0), "r"(b1));
}
template <bool TRANS, typename F>
__device__ __forceinline__ void load8(uint4 (&a)[8], F addr) {
    __syncwarp();
#pragma unroll
    for (int s = 0; s < 8; s++) a[s] = ldsm<TRANS>(addr(s));
}
__device__ __forceinline__ void mma8(float (&c)[4], const uint4 (&a)[8], const uint4 (&b)[4]) {
    float e[4][4];
#pragma unroll
    for (int s = 0; s < 8; s++) {
        if (s < 4) e[s][0] = e[s][1] = e[s][2] = e[s][3] = 0.f;
        mma(e[s & 3], a[s].x, a[s].y, a[s].z, a[s].w, (s & 1) ? b[s >> 1].z : b[s >> 1].x, (s & 1) ? b[s >> 1].w : b[s >> 1].y);
    }
#pragma unroll
    for (int i = 0; i < 4; i++) c[i] = (e[0][i] + e[1][i]) + (e[2][i] + e[3][i]);
}
__device__ __forceinline__ void ldfrag(uint4 (&b)[4], uint32_t a) {
    asm volatile("ld.shared.v4.u32 {%0,%1,%2,%3}, [%16];\nld.shared.v4.u32 {%4,%5,%6,%7}, [%16+64];\n"
                 "ld.shared.v4.u32 {%8,%9,%10,%11}, [%16+128];\nld.shared.v4.u32 {%12,%13,%14,%15}, [%16+192];\n"
                 : "=r"(b[0].x), "=r"(b[0].y), "=r"(b[0].z), "=r"(b[0].w), "=r"(b[1].x), "=r"(b[1].y), "=r"(b[1].z), "=r"(b[1].w),
                   "=r"(b[2].x), "=r"(b[2].y), "=r"(b[2].z), "=r"(b[2].w), "=r"(b[3].x), "=r"(b[3].y), "=r"(b[3].z), "=r"(b[3].w) : "r"(a) : "memory");
}
__device__ __forceinline__ void quad_pair(float x, float y, int t, float& lo, float& hi) {
    const float k = ((t & 1) ? y : x) + shx((t & 1) ? x : y, 1);
    lo = k + shx(k, 2); hi = shx(k, 4) + shx(k, 6);
}
__device__ __forceinline__ void pin(uint32_t& x) { asm volatile("" : "+r"(x)); }
template <typename T> __device__ __forceinline__ void pin(T*& x) { asm volatile("" : "+l"(x)); }
__device__ __forceinline__ float4 ldsf4(uint32_t a) { const uint4 v = lds128(a); return make_float4(__uint_as_float(v.x), __uint_as_float(v.y), __uint_as_float(v.z), __uint_as_float(v.w)); }
__device__ __forceinline__ float sum4(const float4& f) { return (f.x + f.y) + (f.z + f.w); }
__device__ __forceinline__ void stsf(uint32_t a, float v) { sts32(a, __float_as_uint(v)); }

__device__ __forceinline__ void wg_fence() { asm volatile("wgmma.fence.sync.aligned;" ::: "memory"); }
__device__ __forceinline__ void wg_commit() { asm volatile("wgmma.commit_group.sync.aligned;" ::: "memory"); }
__device__ __forceinline__ void wg_wait1() { asm volatile("wgmma.wait_group.sync.aligned 1;" ::: "memory"); }
__device__ __forceinline__ void wg_wait0() { asm volatile("wgmma.wait_group.sync.aligned 0;" ::: "memory"); }
#define R8(o) "+f"(d[o]), "+f"(d[o + 1]), "+f"(d[o + 2]), "+f"(d[o + 3]), "+f"(d[o + 4]), "+f"(d[o + 5]), "+f"(d[o + 6]), "+f"(d[o + 7])
__device__ __forceinline__ void wgmma_rs_n32(float (&d)[16], const uint4& a, uint64_t db, int acc) {
    asm volatile("{\n.reg .pred p;\nsetp.ne.b32 p, %21, 0;\n"
        "wgmma.mma_async.sync.aligned.m64n32k16.f32.bf16.bf16 "
        "{%0,%1,%2,%3,%4,%5,%6,%7,%8,%9,%10,%11,%12,%13,%14,%15}, {%16,%17,%18,%19}, %20, p, 1, 1, 0;\n}"
        : R8(0), R8(8) : "r"(a.x), "r"(a.y), "r"(a.z), "r"(a.w), "l"(db), "r"(acc));
}
#define PV_LO "{%0,%1,%2,%3,%4,%5,%6,%7,%8,%9,%10,%11,%12,%13,%14,%15,%16,%17,%18,%19,%20,%21,%22,%23,%24,%25,%26,%27,%28,%29,%30,%31,%32,%33,%34,%35,%36,%37,%38,%39,%40,%41,%42,%43,%44,%45,%46,%47,%48,%49,%50,%51,%52,%53,%54,%55,%56,%57,%58,%59,%60,%61,%62,%63}, "
#define PV_HI "{%64,%65,%66,%67,%68,%69,%70,%71,%72,%73,%74,%75,%76,%77,%78,%79,%80,%81,%82,%83,%84,%85,%86,%87,%88,%89,%90,%91,%92,%93,%94,%95,%96,%97,%98,%99,%100,%101,%102,%103,%104,%105,%106,%107,%108,%109,%110,%111,%112,%113,%114,%115,%116,%117,%118,%119,%120,%121,%122,%123,%124,%125,%126,%127}, "
__device__ __forceinline__ void wgmma_pv(float (&d)[128], const uint4& a, uint32_t blo, int acc) {
    asm volatile("{\n.reg .pred p;\n.reg .b32 u0, u1, u2, u3, t;\n.reg .b64 d0, d1, d2, d3;\nsetp.ne.b32 p, %133, 0;\n"
        "mov.b64 d0, {%132, 0x40000100};\nadd.u32 t, %132, 512;\nmov.b64 d1, {t, 0x40000100};\n"
        "add.u32 t, %132, 128;\nmov.b64 d2, {t, 0x40000100};\nadd.u32 t, %132, 640;\nmov.b64 d3, {t, 0x40000100};\n"
        "wgmma.fence.sync.aligned;\n"
        "wgmma.mma_async.sync.aligned.m64n128k16.f32.bf16.bf16 " PV_LO "{%128, u0, %129, u1}, d0, p, 1, 1, 1;\n"
        "wgmma.mma_async.sync.aligned.m64n128k16.f32.bf16.bf16 " PV_LO "{%130, u2, %131, u3}, d1, 1, 1, 1, 1;\n"
        "wgmma.commit_group.sync.aligned;\n"
        "wgmma.mma_async.sync.aligned.m64n128k16.f32.bf16.bf16 " PV_HI "{%128, u0, %129, u1}, d2, p, 1, 1, 1;\n"
        "wgmma.mma_async.sync.aligned.m64n128k16.f32.bf16.bf16 " PV_HI "{%130, u2, %131, u3}, d3, 1, 1, 1, 1;\n"
        "wgmma.commit_group.sync.aligned;\n}"
        : R8(0), R8(8), R8(16), R8(24), R8(32), R8(40), R8(48), R8(56), R8(64), R8(72), R8(80), R8(88), R8(96), R8(104), R8(112), R8(120)
        : "r"(a.x), "r"(a.y), "r"(a.z), "r"(a.w), "r"(blo), "r"(acc) : "memory");
}

template <int NW>
__device__ __forceinline__ void ln_stats(float s, float q, float sh, float* scr, int w, int lane, int bar, float& mean_b, float& sd_b) {
#pragma unroll
    for (int o = 16; o; o >>= 1) { s += shx(s, o); q += shx(q, o); }
    constexpr float n = 512.f / NW;
    if (lane == 0) { scr[w] = sh + s * (1.f / n); scr[NW + w] = q - s * s * (1.f / n); }
    bar_sync(bar, NW * 32);
    float mu = 0.f, m2 = 0.f;
#pragma unroll
    for (int i = 0; i < NW; i++) { mu += scr[i]; m2 += scr[NW + i]; }
    mu *= 1.f / NW;
#pragma unroll
    for (int i = 0; i < NW; i++) { const float d = scr[i] - mu; m2 = fmaf(n * d, d, m2); }
    mean_b = rbf(mu);
    sd_b = rbf(sqrtf(rbf(rbf(fmaxf(m2, 0.f) * (1.f / 512.f)) + 1e-5f)));
}
__device__ __forceinline__ float ln_mod(float x, float mean_b, float sd_b, float c, float s) {
    return rbf(rbf(__fdividef(rbf(x - mean_b), sd_b)) * rbf(1.f + c)) + s;
}

__global__ void __cluster_dims__(2, 1, 1) __launch_bounds__(NTHREADS, 1)
fused_kernel(const __grid_constant__ First F, __nv_bfloat16* __restrict__ out, uint32_t* __restrict__ gs, const __grid_constant__ Maps M) {
    extern __shared__ __align__(1024) uint8_t sm[];
    const uint32_t sb = s2u(sm);
    const int tid = threadIdx.x, lane = tid & 31;
    const int j = blockIdx.x, rk = j & 1;
    const int g = lane >> 2, t = lane & 3;
    const int r8 = lane & 7, lb3 = (lane >> 3) & 1, lb4 = lane >> 4;
    uint64_t pol;
    asm("createpolicy.fractional.L2::evict_first.b64 %0, 1.0;" : "=l"(pol));
    {
        auto cpa = [&](uint32_t d, const uint8_t* s) {
            asm volatile("cp.async.cg.shared.global.L2::cache_hint.L2::128B [%0], [%1], 16, %2;" :: "r"(d), "l"(s), "l"(pol) : "memory");
        };
        const uint32_t ut = threadIdx.x, uj = blockIdx.x;
        const uint8_t* w = F.w[ut >= 128];
        if (ut < 128) {
            const uint32_t dq = (sb + ut * 16) ^ ((ut * 2) & 0x70);
            const uint8_t* sq = w + (uint32_t)(((uj & 1) * 256 + (ut >> 3)) * 8192 + (uj >> 1) * 128 + (ut & 7) * 16);
#pragma unroll
            for (int i = 0; i < 4 * NCP; i++) cpa(dq + 4 * 32768 + i * 2048, sq + i * 131072);
        } else if (ut < 384) {
            const uint32_t dm = (sb + ut * 16) ^ ((ut * 2) & 0x10);
            const uint8_t* sa = w + (uint32_t)(((uj >> 5) * 128 + (ut >> 1) - 64) * 6144 + (uj & 31) * 32 + (ut & 1) * 16);
            cpa(dm + SM_XA - 2048, sa); cpa(dm + SM_XA + 2048, sa + 1024);
        }
        else if (ut == 480 && uj < 64) asm volatile("prefetch.global.L2 [%0];" :: "l"(F.v[(uj >> 3) & 1] + (uj & 7) * 64));
    }
    const int warp = __shfl_sync(0xffffffffu, tid >> 5, 0);
    const __nv_bfloat16* const xin = F.v[0];
    uint32_t* const pl = gs + (warp < 2 ? (B_PR + (j >> 5)) * 4096 + (j & 31) * 32 : G_E1 + j * 8192) + (warp & 1) * 1024 + lane;
    if (warp < 4) st_x1(pl, 1u);
    auto BAR = [&](int i) -> uint32_t { return sb + SM_BAR + i * 8; };
    const uint32_t a16 = (r8 + 8 * lb4) * 32 + ((lb3 ^ (r8 >> 2)) * 16);
    const uint32_t a128 = (r8 + 8 * lb4) * 128 + ((((warp & 3) * 2 + lb3) ^ r8) * 16);
    auto ldcls = [&]() -> uint32_t { return *(const volatile uint32_t*)(sm + SM_CLS); };
    auto clear_head = [&]() {
        st2_x1(gs + (B_HA + ((j >> 4) & 1) * 2 + lb4) * 4096 + (j >> 5) * 256 + (j & 15) * 16 + (lane & 15), 0u);
        st2_x4(gs + (B_QA + rk * 8 + ((j >> 1) & 1) * 4 + (j >> 5)) * 4096 + g * 128 + ((j >> 2) & 7) * 16 + t * 4, 0u, 0u, 0u, 0u);
        if (lane < 8) st2_x1(gs + B_RD * 4096 + j * 8 + lane, 0u);
    };
    auto tma = [&](uint32_t dst, const CUtensorMap* mp, uint32_t bar, int c0, int c1, int c2, int c3) {
        asm volatile("{\n.reg .pred p;\nelect.sync _|p, 0xffffffff;\n"
                     "@p cp.async.bulk.tensor.4d.shared::cluster.global.mbarrier::complete_tx::bytes.L2::cache_hint [%0], [%1, {%3, %4, %5, %6}], [%2], %7;\n}"
                     :: "r"(dst), "l"(mp), "r"(bar), "r"(c0), "r"(c1), "r"(c2), "r"(c3), "l"(pol) : "memory");
    };
    if (warp <= 12 || warp == 15) {
        const int grp = warp == 12 ? 0 : warp == 15 ? 13 : warp + 1;
        const uint32_t cnt = grp < 10 ? 1 : grp < 13 ? 4 : 8;
        if (lane == 0) {
#pragma unroll
            for (int i = 0; i < 8; i++) mbar_init(BAR(grp * 8 + i), (i < 2 && grp == 0) ? (i ? 128 : 256) : cnt);
        }
        __syncwarp();
        if (grp < 10 && lane < 8 && (grp || lane > NCP)) mbar_expect(BAR(grp * 8 + lane), grp >= 8 ? 4096 : grp * 8 + lane < IT_X ? 8192 : 16384);
        asm volatile("fence.mbarrier_init.release.cluster;" ::: "memory");
        __syncwarp();
        if (warp == 12) {
#pragma unroll
            for (int i = NCP + 1; i < W0; i++) tma(sb + (15 + i) * 8192, &M.m[MP_WQ], BAR(i), 0, rk * 256 + (i - 1) * 64, j >> 1, 0);
        }
    } else if (warp == 13) {
        if (lane < NMAPS) asm volatile("prefetch.tensormap [%0];" :: "l"(&M.m[lane]) : "memory");
    } else if (warp == 14) {
        clear_head();
    }
    __syncthreads();
    uint32_t in1 = 0, in2 = 0;
    if (warp < 4) { in1 = *(const uint32_t*)(xin + 2 * tid); in2 = *(const uint32_t*)(xin + 256 + 2 * tid); }
    else if (warp < 12) in1 = *(const uint32_t*)(F.v[1] + 2 * (tid - 128));
    if (warp < 12) asm volatile("cp.async.mbarrier.arrive.noinc.shared::cta.b64 [%0];" :: "r"(BAR(warp < 4)) : "memory");
    asm volatile("barrier.cluster.arrive.relaxed.aligned;" ::: "memory");

    if (warp >= 12) {
    asm volatile("setmaxnreg.dec.sync.aligned.u32 64;");
    if (warp == 12) {
        static_assert(W0 > NCP && W0 <= 5 && NCP >= 1 && NCP <= 4, "W0");
        const uint2* sched = M.sched[j < NFF ? 0 : j < J_RED ? 1 : 2];
        uint2 en = sched[W0];
        const uint32_t t0 = gtime();
        const uint32_t sp = __reduce_or_sync(0xffffffffu, sb);
        const int cx = (j >> 1) * 64 + (j < NFF ? 0 : 1024 - NFF * 32);
#pragma unroll 1
        for (int i = W0; en.x; i++) {
            uint32_t e = en.x, st = (en.y >> 20) * 64;
            const uint32_t tn = t0 + (int16_t)en.y, mp = (en.y >> 16) & 15;
            if (mp == MP_WUV || mp == MP_WUK) { st ^= (j >> 5) * (mp == MP_WUV ? 128 : 64); e ^= (j >> 5) << 6; }
            if (mp == MP_GATE || mp == MP_UP) st ^= (j & 16) * 8;
            en = sched[i + 1];
            if (mp == MP_MODB && j >= J_END) break;
            uint32_t c0 = mp == MP_WO ? (j & 7) * 64 : mp > MP_WO ? cx : 0;
            uint32_t c1 = mp == MP_CKV ? 0 : mp == MP_DOWN ? j * 32 : st + (mp == MP_WUV ? (j & 3) * 32 : mp == MP_WO ? (j >> 3) * 256 : rk * 256);
            uint32_t c2 = mp < MP_CKV ? j >> 1 : mp == MP_CKV ? rk * 4 : mp == MP_WUV ? (j >> 2) * 2 : mp == MP_DOWN ? st >> 4 : 0;
            uint32_t c3 = mp == MP_CKV ? st * 2 + (j & ~1) : 0;
            uint32_t dst = sp + ((e << 7) & 0x3e000), bar = sp + SM_BAR + (e & 63) * 8;
            const uint32_t w0 = (e >> 8) & 0x3f8, w1 = (e >> 15) & 0x3f8, w2 = (e >> 22) & 0x3f8, bb = sp + SM_BAR - 8;
            const CUtensorMap* pm = &M.m[mp];
            pin(dst); pin(bar); pin(c0); pin(c1); pin(c2); pin(c3); pin(pm);
            if (w0) mbar_wait(bb + w0, 0);
            if (w2) {
                mbar_wait(bb + w2, 0);
                while (!__any_sync(0xffffffffu, mbar_test(bb + w1, 0) | ((int)(gtime() - tn) > 0))) {}
            } else if (w1) mbar_wait(bb + w1, 0);
            tma(dst, pm, bar, c0, c1, c2, c3);
        }
    } else if (warp == 13) {
#pragma unroll
        for (int i = 0; i < 2; i++) st_x4(gs + (B_ML + rk * 16 + i * 8 + g) * 4096 + (t >> 1) * 1024 + (j >> 1) * 8 + (t & 1) * 4, 0u, 0u, 0u, 0u);
        if (lane < 16) st2_x4(gs + (B_E2 + (j >> 4)) * 4096 + (j & 15) * 64 + lane * 4, 0u, 0u, 0u, 0u);
        st2_x1(gs + (B_E3 + (j >> 5)) * 4096 + (j & 31) * 32 + lane, 0u);
        if (lane < 8) st2_x1(gs + B_MB * 4096 + j * 8 + lane, 0u);
        if (j < NFF) {
#pragma unroll
            for (int i = 0; i < 2; i++) st2_x4(gs + (B_E5 + i * 8 + g) * 4096 + j * 16 + t * 4, 0u, 0u, 0u, 0u);
        }
        bar_sync(9, 64);
        const uint32_t cs = ldcls();
#pragma unroll 1
        for (int i = 0; i < 32; i++) {
            st_x4(gs + G_E1 + j * 8192 + (i >> 3) * 2048 + ((((cs >> 1) ^ (i >> 3)) & 1) << 10) + (i & 7) * 128 + lane * 4, 0u, 0u, 0u, 0u);
            __nanosleep(JAN_SLEEP);
        }
        fence_gpu();
        if (lane < 8) st2_x1(gs + B_RD * 4096 + j * 8 + lane, 1u + (cs >> 1));
        if (lane == 0) TRACE(41);
        uint32_t rd[4];
        mbar_wait(BAR(IT_CKV + RD_ITEM), 0);
        poll<1024, RD_SLEEP>(rd, gs + near_off(B_RD, cs) + lane * 8);
#pragma unroll
        for (int i = 0; i < 4; i++) {
            const uint32_t m = __ballot_sync(0xffffffffu, rd[i] == 2u);
            if (lane == 0) sts32(sb + SM_CLS + 16 + i * 4, m);
        }
        __syncwarp();
        if (lane < 8) mbar_arrive(BAR(JD));
        if (lane == 0) TRACE(42);
    } else if (warp == 14) {
        uint2 ml[2];
        mbar_waitb(BAR(JD), 0);
        const uint32_t cls = ldcls();
        mbar_waitb(BAR(PF0 + 2 * NUNITS - 1), 0);
        __nanosleep(ML_DELAY);
        const uint32_t* pl2 = gs + near_off(B_ML + (j >> 2), cls) + lane * 8;
        const uint32_t wa = sb + SM_W + lb4 * 64 + t * 16 + (g & 3) * 4;
        poll_start<1024>(ml, pl2);
        uint32_t w0 = 0, w1 = 0, redo = 0;
        bool first = true;
#pragma unroll 1
        for (uint32_t it = 0;; it++) {
            const bool p0 = minw(ml[0]) != 0, p1 = minw(ml[1]) != 0;
            const int n = __popc(__ballot_sync(0xffffffffu, p0)) + __popc(__ballot_sync(0xffffffffu, p1));
            const uint32_t x0 = ml[0].x, x1 = ml[1].x;
            if (n < 64) {
                if (!p0) ld_x(ml[0], pl2);
                if (!p1) ld_x(ml[1], pl2 + 256);
            }
            if (n == 64 || (first && n >= E1_EARLY)) {
                auto ord = [](int x) { return x ^ ((x >> 31) & 0x7fffffff); };
                const int o0 = ord(x0), o1 = ord(x1);
                const float mm = __int_as_float(ord(__reduce_max_sync(0xffffffffu, max(p0 ? o0 : INT_MIN, p1 ? o1 : INT_MIN))));
                const float lo = __int_as_float(ord(__reduce_min_sync(0xffffffffu, min(p0 ? o0 : INT_MAX, p1 ? o1 : INT_MAX))));
                const uint32_t v0 = pack2(ex2((p0 ? __uint_as_float(x0) : lo) - mm), 0.f), v1 = pack2(ex2((p1 ? __uint_as_float(x1) : lo) - mm), 0.f);
                redo = !first && __any_sync(0xffffffffu, v0 != w0 || v1 != w1);
                w0 = v0; w1 = v1;
                sts32(wa - redo * (SM_W - SM_W2), w0 * 0x10001u); sts32(wa - redo * (SM_W - SM_W2) + 128, w1 * 0x10001u);
                if (first) bar_arrive(3, 416);
                first = false;
                if (n == 64) break;
            }
            if (it > SPIN_LIMIT) __trap();
        }
        if (lane == 0) TRACE_Q(37);
        float L = bflo(w0) * __uint_as_float(ml[0].y) + bflo(w1) * __uint_as_float(ml[1].y);
#pragma unroll
        for (int o = 16; o; o >>= 1) L += shx(L, o);
        if (lane == 0) *(float2*)(sm + SM_FQ) = make_float2(__frcp_rn(L), __uint_as_float(redo));
        __syncwarp();
        if (lane < 8) mbar_arrive(BAR(WR));
        if (lane == 0) TRACE(10);
        bar_sync(4, 416);
        clear_head();
        if (j < NFF) {
            uint32_t ya = sb + SM_Y + lane * 16, sa = peer_addr(sb + SM_RED + 2048 + rk * 8, lane & 1), tb = peer_addr(BAR(MBB), lane & 1);
            pin(ya); pin(sa); pin(tb);
            bar_sync(7, 288);
            const float4 y0 = ldsf4(ya), y1 = ldsf4(ya + 512);
            float s = sum4(y0) + sum4(y1);
            float q = (fmaf(y0.x, y0.x, y0.y * y0.y) + fmaf(y0.z, y0.z, y0.w * y0.w)) + (fmaf(y1.x, y1.x, y1.y * y1.y) + fmaf(y1.z, y1.z, y1.w * y1.w));
#pragma unroll
            for (int o = 16; o; o >>= 1) { s += shx(s, o); q += shx(q, o); }
            if (lane < 2) st_async2(sa, s, q, tb);
        }
    } else if (warp == 15) {
        mbar_waitb(BAR(IT_X - 1), 0);
        if (j < J_END) mbar_waitb(BAR(j < NFF ? NITEMS - 1 : MBB), 0);
    }
    } else if (warp < 4) {
        float* scr = (float*)(sm + SM_SCR);
        uint32_t cls;
        {
            uint2 ha[8];
            uint32_t best = 0xffffffffu;
            sts32(sb + SM_SCR + 64 + warp * 4, best);
            const float sh = __shfl_sync(0xffffffffu, bflo(in1), 0);
            const float v0 = bflo(in1) - sh, v1 = bfhi(in1) - sh, v2 = bflo(in2) - sh, v3 = bfhi(in2) - sh;
            float mb, sd;
            ln_stats<4>((v0 + v1) + (v2 + v3), (v0 * v0 + v1 * v1) + (v2 * v2 + v3 * v3), sh, scr, warp, lane, 2, mb, sd);
            if (!rk) in2 = in1;
#pragma unroll 1
            for (int i = 0; i < NPROBE; i++) {
                uint32_t t0, t1, o;
                asm volatile("mov.u32 %0, %%clock;" : "=r"(t0));
                asm volatile("atom.relaxed.gpu.global.exch.b32 %0, [%1], %2;" : "=r"(o) : "l"(pl), "r"(2u + i) : "memory");
                asm volatile("{\n.reg .pred p;\nsetp.ne.u32 p, %1, 0x1234567;\nmov.u32 %0, 0;\n@p mov.u32 %0, %%clock;\n}" : "=r"(t1) : "r"(o));
                best = min(best, t1 - t0);
                sts32(sb + SM_SCR + 64 + warp * 4, best);
                if (__all_sync(0xffffffffu, min(best, lds32(sb + SM_SCR + 64 + (warp ^ 1) * 4)) < NEAR_CLK)) break;
            }
            bar_sync(2, 128);
            const uint4 lt = *(const uint4*)(scr + 16);
            cls = NUMA ? ((lt.y < lt.x) ^ (__popc((B_PR + (j >> 5)) & 0x2C) & 1)) | (lt.w < lt.z) << 1 : 0;
            if (warp == 0) { if (lane == 0) sts32(sb + SM_CLS, cls); bar_arrive(9, 64); }
            if (tid == 0) TRACE(38);
            asm volatile("barrier.cluster.wait.aligned;" ::: "memory");
            mbar_wait(BAR(IT_MODA), 0);
            if (HA_DELAY) __nanosleep(HA_DELAY);
            poll<1024, H_SLEEP, false, 16384>(ha, gs + near_off(B_HA + rk * 2, cls) + 2 * tid);
            auto rsum = [](uint32_t a, uint32_t b, uint32_t c, uint32_t d) { return rbf((__uint_as_float(a) + __uint_as_float(b)) + (__uint_as_float(c) + __uint_as_float(d))); };
            sts32(sb + SM_FV + frag_off(2 * tid),
                  pack2(ln_mod(bflo(in2), mb, sd, rsum(ha[4].x, ha[5].x, ha[6].x, ha[7].x), rsum(ha[0].x, ha[1].x, ha[2].x, ha[3].x)),
                        ln_mod(bfhi(in2), mb, sd, rsum(ha[4].y, ha[5].y, ha[6].y, ha[7].y), rsum(ha[0].y, ha[1].y, ha[2].y, ha[3].y))));
            bar_arrive(5, 384);
            mbar_wait(BAR(QB), 0);
            if (tid < 64) {
                const float* qx = (const float*)(sm + SM_QX) + tid;
                sts16(sb + SM_FQ + frag_off(tid), pack2((qx[0] + qx[64]) + (qx[128] + qx[192]), 0.f));
            }
            bar_arrive(6, 384);
        }
        asm volatile("setmaxnreg.inc.sync.aligned.u32 192;");
        float acc[128];
        float M = 0.f;
        uint32_t pa = sb + SM_XA + warp * 512 + lane * 16, ma = sb + SM_MX + (warp * 8 + g) * 4, pf = BAR(PF0);
        uint32_t blo = __reduce_or_sync(0xffffffffu, (((sb + SM_U) & 0x3FFFFu) >> 4) | 0x400000u);
        uint32_t* e1[4];
#pragma unroll
        for (int i = 0; i < 4; i++) e1[i] = gs + G_E1 + (warp * 8 + g) * 4 * 8192 + (rk * 2 + (j >> 6)) * 2048 + ((j >> 1) & 31) * 32 + t * 4;
#pragma unroll 1
        for (int h = 0; h < 2 * NUNITS; h++) {
            mbar_wait(pf, 0);
            const float m = __uint_as_float(lds32(ma));
            const uint4 pn = lds128(pa);
            wg_wait0();
#pragma unroll
            for (int i = 0; i < 128; i++) asm volatile("" : "+f"(acc[i]) :: "memory");
            if (h == 0) M = m;
            uint32_t b2 = 0x3f803f80u;
            if (__builtin_expect(__any_sync(0xffffffffu, m != M), 0)) {
                const float Mn = fmaxf(M, m), alpha = ex2(M - Mn), beta = ex2(m - Mn);
                M = Mn;
                b2 = pack2(beta, beta);
#pragma unroll
                for (int jj = 0; jj < 32; jj++) { acc[4 * jj] *= alpha; acc[4 * jj + 1] *= alpha; }
            }
            auto mul2 = [](uint32_t x, uint32_t y) { uint32_t r; asm("mul.rn.bf16x2 %0, %1, %2;" : "=r"(r) : "r"(x), "r"(y)); return r; };
            const uint4 p = make_uint4(mul2(pn.x, b2), mul2(pn.y, b2), mul2(pn.z, b2), mul2(pn.w, b2));
            if (tid == 0 && (h & 1)) TRACE_Q(48 + (h >> 1));
            wgmma_pv(acc, p, blo, h);
            if (lane == 0 && h > 0 && !(h & 1)) mbar_arrive(BAR(EB_UNIT0 + (h >> 1) - 1));
            blo += h == 11 ? -11 * 1024 : 1024;
            pa += (h == 5 || h == 11) ? -5 * 2048 : 2048;
            ma += 128; pf += 8;
            if (h == 2 * NUNITS - 3) {
                mbar_wait(BAR(JD), 0);
                const uint32_t hm = (*(const uint32_t*)(sm + SM_CLS + 16 + warp * 4) >> (g * 4)) ^ ((j >> 6) ? 15u : 0u);
#pragma unroll
                for (int i = 0; i < 4; i++) e1[i] += ((hm >> i) & 1) << 10;
            }
        }
#pragma unroll
        for (int vv = 0; vv < 2; vv++) {
            if (vv && M == 1.f) __trap();
            if (vv) wg_wait0(); else wg_wait1();
#pragma unroll
            for (int i = 0; i < 64; i++) asm volatile("" : "+f"(acc[vv * 64 + i]) :: "memory");
            if (tid == 0 && !vv) TRACE_Q(63);
#pragma unroll
            for (int i = 0; i < 4; i++) {
                const float* a = &acc[vv * 64 + i * 16];
                st_x4(e1[i] + i * 8192 + vv * 16, enc(pack2(a[0], a[1])), enc(pack2(a[4], a[5])), enc(pack2(a[8], a[9])), enc(pack2(a[12], a[13])));
            }
        }
        bar_arrive(3, 416);
        if (tid == 0) TRACE_Q(17);
#pragma unroll 1
        for (int pass = 0;; pass++) {
            if (j >= NFF && j < J_END && pass == (j >= J_RED)) {
                uint4 a[8], b[4];
                float c[4], e[4];
                const bool own = (warp >> 1) == rk;
                const uint32_t xa = sb + SM_FV + (warp & 1) * 64 + g * 8;
                if (lane == 0) mbar_expect(BAR(MBB), own ? 64 : 0);
#pragma unroll
                for (int i = 0; i < 2; i++) {
                    ldfrag(b, sb + SM_FS + rk * 512 + i * 256 + t * 16);
                    mbar_wait(BAR(IT_X + i), 0);
                    const uint32_t ab = sb + SM_U + B_X * 32768 + i * 16384 + a128;
                    load8<true>(a, [&](int s) { return ab + s * 2048; });
                    mma8(i ? e : c, a, b);
                }
                c[0] += e[0]; c[2] += e[2];
                if (!own) {
                    if (t == 0) st_async2(peer_addr(xa, rk ^ 1), c[0], c[2], peer_addr(BAR(MBB), rk ^ 1));
                } else {
                    mbar_wait(BAR(MBB), 0);
                    const float2 pp = *(const float2*)(sm + (xa - sb));
                    const float mine = t ? c[2] + pp.y : c[0] + pp.x, other = shx(mine, 4);
                    const uint32_t w = (warp & 1) * 8 + t * 4 + (g >> 1), val = enc(pack2(mine, other));
                    if (t < 2 && !(g & 1)) {
                        if (j < J_RED) st2_x1(gs + B_MB * 4096 + (j - NFF) * 16 + w, val);
                        else sts32(sb + SM_FV + 256 + w * 4, val);
                    }
                    __syncwarp();
                    if (j >= J_RED && lane < 4) mbar_arrive(BAR(QB));
                    if (lane == 0) TRACE(11);
                }
            }
            if (pass) break;
            uint4 a[8], a2[8];
            const uint32_t ab = sb + SM_U + B_WO * 32768 + a128;
            uint32_t* p3 = gs + (B_E3 + ((j >> 1) & 3)) * 4096 + (t >> 1) * 1024 + (rk * 2 + (warp >> 1)) * 256 + (j >> 3) * 16 + (warp & 1) * 8 + (t & 1) * 4 + (g >> 1);
            const uint32_t* pb = gs + near_off(B_E2 + (j >> 4), cls) + (((j >> 3) & 1) * 2 + lb4) * 256 + (lane & 15) * 2;
            pin(p3); pin(pb);
            uint2 bb[8];
#pragma unroll
            for (int i = 0; i < 8; i++) bb[i] = make_uint2(0u, 0u);
            bool h0 = false, h1 = false;
            auto idle = [&]() {
                if (!h0) {
                    h0 = __all_sync(0xffffffffu, mbar_test(BAR(IT_WO + (t & 1)), 0));
                    if (h0) load8<true>(a, [&](int s) { return ab + s * 2048; });
                }
                if (!h1) {
                    h1 = __all_sync(0xffffffffu, mbar_test(BAR(IT_WO + 2 + (t & 1)), 0));
                    if (h1) load8<true>(a2, [&](int s) { return ab + 16384 + s * 2048; });
                }
            };
            bar_sync(4, 416);
            idle();
            poll<128, 0, true>(bb, pb, idle);
            if (tid == 0) TRACE(21);
            float e[4][4];
#pragma unroll
            for (int s = 0; s < 16; s++) {
                if (s == 0 && !h0) { mbar_wait(BAR(IT_WO), 0); mbar_wait(BAR(IT_WO + 1), 0); load8<true>(a, [&](int q) { return ab + q * 2048; }); }
                if (s == 0 && !h1) { mbar_wait(BAR(IT_WO + 2), 0); mbar_wait(BAR(IT_WO + 3), 0); load8<true>(a2, [&](int q) { return ab + 16384 + q * 2048; }); }
                const int z = (s & 1) | (s & 2) << 2 | (s >> 2) << 1;
                const uint4& x = z < 8 ? a[z] : a2[z & 7];
                float (&d)[4] = e[(z >> 3) * 2 + (z & 1)];
                if (!(z & 6)) d[0] = d[1] = d[2] = d[3] = 0.f;
                mma(d, x.x, x.y, x.z, x.w, bb[z & 7].x, bb[z & 7].y);
            }
            float lo, hi;
            quad_pair((t & 2) ? (e[2][0] + e[3][0]) + (e[2][1] + e[3][1]) : (e[0][0] + e[1][0]) + (e[0][1] + e[1][1]),
                      (t & 2) ? (e[2][2] + e[3][2]) + (e[2][3] + e[3][3]) : (e[0][2] + e[1][2]) + (e[0][3] + e[1][3]), t, lo, hi);
            if (!(g & 1)) st_x1(p3, enc(pack2(lo, hi)));
            if (j < NFF || (j >= J_RED && j < J_END)) bar_arrive(8, 384);
            if (tid == 0) TRACE(22);
        }
        if (j < NFF) {
            uint4 a[16];
            const uint32_t ad = sb + SM_U + B_DN * 32768 + warp * 8192 + (r8 + 8 * lb4) * 128 + (lb3 ^ r8) * 16;
            uint32_t rl = sb + SM_RED + lane * 16;
            uint32_t* p5 = gs + (B_E5 + warp * 4 + (t >> 1)) * 4096 + j * 16 + (t & 1) * 8 + g;
            pin(rl); pin(p5);
            if (lane == 0) mbar_expect(BAR(MBB), 4);
            auto ldd = [&]() {
#pragma unroll
                for (int s = 0; s < 16; s++) a[s] = ldsm<true>((ad ^ ((s & 3) * 32)) + (s >> 2) * 2048);
            };
            const uint32_t db = BAR(IT_DOWN + (warp >> 1));
            mbar_wait(BAR(MBB), 0);
            const float4 st = ldsf4(sb + SM_RED + 2048);
            const bool hd = __all_sync(0xffffffffu, mbar_test(db, 0));
            if (hd) ldd();
            const float mu = (st.x + st.z) * (1.f / 512.f);
            float rstd;
            asm volatile("rsqrt.approx.ftz.f32 %0, %1;" : "=f"(rstd) : "f"(fmaxf(fmaf(-mu, mu, (st.y + st.w) * (1.f / 512.f)), 0.f) + 1e-5f));
            mbar_wait(BAR(QB), 1);
            if (tid == 0) TRACE(25);
            const float4 f0 = ldsf4(rl), f2 = ldsf4(rl + 1024), f1 = ldsf4(rl + 512), f3 = ldsf4(rl + 1536);
            const float gg = fmaf(rstd, fmaf(-mu, f0.z + f2.z, (f0.x + f0.y) + (f2.x + f2.y)), f0.w + f2.w);
            const float uu = fmaf(rstd, fmaf(-mu, f1.z + f3.z, (f1.x + f1.y) + (f3.x + f3.y)), f1.w + f3.w);
            const float hh = __fdividef(gg * uu, 1.f + ex2(-gg * fmaf(gg * gg, 0.10294324f, 2.3022082f)));
            uint32_t hb[4];
#pragma unroll
            for (int i = 0; i < 4; i++) hb[i] = pack2(__shfl_sync(0xffffffffu, hh, 2 * t + 8 * i), __shfl_sync(0xffffffffu, hh, 2 * t + 8 * i + 1));
            if (!hd) { mbar_wait(db, 0); ldd(); }
#pragma unroll
            for (int i = 0; i < 2; i++) {
                uint32_t res = 0;
#pragma unroll
                for (int k = 0; k < 4; k++) {
                    float c[4] = {0.f, 0.f, 0.f, 0.f};
                    const uint4 &x = a[i * 8 + k], &y = a[i * 8 + k + 4];
                    mma(c, x.x, x.y, x.z, x.w, hb[0], hb[1]);
                    mma(c, y.x, y.y, y.z, y.w, hb[2], hb[3]);
                    if (t == k) res = pack2(c[0], c[2]);
                }
                st2_x1(p5 + i * 8192, enc(res));
            }
            if (tid == 0) { TRACE(27); TRACE_GT(47); }
        }
    } else {
        const int u8 = tid - 128, w8 = warp - 4;
        const int v = w8 >> 2, wq4 = w8 & 3;
        {
            const float c0 = bflo(in1), c1 = bfhi(in1);
            sts32(sb + SM_FS + frag_off(2 * u8), pack2(__fdividef(c0, 1.f + __expf(-c0)), __fdividef(c1, 1.f + __expf(-c1))));
        }
        bar_sync(1, 256);
        asm volatile("barrier.cluster.wait.aligned;" ::: "memory");
        uint4 a[8], b[4]; float c[4];
        if (w8 < 2) {
            ldfrag(b, sb + SM_FS + (j >> 5) * 256 + t * 16);
            mbar_wait(BAR(IT_MODA), 0);
            if (u8 == 0) TRACE(12);
            const uint32_t ab = sb + SM_XA + w8 * 4096 + a16;
            load8<true>(a, [&](int s) { return ab + s * 512; });
            mma8(c, a, b);
            if (t < 2) st2_x1(gs + (B_HA + ((j >> 4) & 1) * 2 + w8) * 4096 + (j >> 5) * 256 + (j & 15) * 16 + t * 8 + g, encf(t ? c[2] : c[0]));
        }
        {
            mbar_wait(BAR(IT_WQ + 2 * v <= NCP ? 1 : IT_WQ + 2 * v), 0); mbar_wait(BAR(IT_WQ + 2 * v + 1 <= NCP ? 1 : IT_WQ + 2 * v + 1), 0);
            const uint32_t ab = sb + SM_U + 4 * 32768 + v * 16384 + a128;
            load8<true>(a, [&](int s) { return ab + s * 2048; });
            if (lane == 0) mbar_arrive(BAR(EB_WQ));
            bar_sync(5, 384);
            if (u8 == 0) TRACE(13);
            ldfrag(b, sb + SM_FV + v * 256 + t * 16);
            mma8(c, a, b);
            if (t < 2) {
                const float qv = t ? c[2] : c[0];
                const uint32_t qa_ = sb + SM_QX + ((rk * 2 + v) * 64 + wq4 * 16 + t * 8 + g) * 4;
                asm volatile("st.async.weak.shared::cluster.mbarrier::complete_tx::bytes.f32 [%0], %1, [%2];"
                             :: "r"(peer_addr(qa_, rk ^ 1)), "f"(qv), "r"(peer_addr(BAR(QB), rk ^ 1)) : "memory");
                sts32(qa_, __float_as_uint(qv));
            }
            __syncwarp();
            if (lane == 0) mbar_expect(BAR(QB), 64);
        }
        {
            mbar_wait(BAR(IT_WUK + (v ^ ((j >> 5) & 1))), 0); mbar_wait(BAR(IT_WUK + (v ^ ((j >> 5) & 1)) + 2), 0);
            const uint32_t ab = sb + SM_U + 5 * 32768 + (w8 * 16 + r8 + 8 * lb3) * 128;
            const uint32_t x16 = (lb4 ^ r8) * 16;
            load8<false>(a, [&](int s) { return ab + (s & 1) * 16384 + (x16 ^ ((s >> 1) * 32)); });
            bar_sync(6, 384);
            if (u8 == 0) TRACE(14);
            b[0] = lds128(sb + SM_FQ + t * 16); b[1] = lds128(sb + SM_FQ + 64 + t * 16);
            float e[4] = {0.f, 0.f, 0.f, 0.f};
            c[0] = c[1] = c[2] = c[3] = 0.f;
#pragma unroll
            for (int k = 0; k < 4; k++) {
                const uint32_t b0 = (k & 1) ? b[k >> 1].z : b[k >> 1].x, b1 = (k & 1) ? b[k >> 1].w : b[k >> 1].y;
                mma(c, a[2 * k].x, a[2 * k].y, a[2 * k].z, a[2 * k].w, b0, b1);
                mma(e, a[2 * k + 1].x, a[2 * k + 1].y, a[2 * k + 1].z, a[2 * k + 1].w, b0, b1);
            }
            const float mine = ((t & 1) ? ((t & 2) ? e[2] : e[0]) : ((t & 2) ? c[2] : c[0])) * 0.12751743f;
            const float other = shx(mine, 4);
            if (!(g & 1)) st2_x1(gs + (B_QA + rk * 8 + ((j >> 1) & 1) * 4 + (j >> 5)) * 4096 + w8 * 128 + ((j >> 2) & 7) * 16 + (g >> 1) * 4 + t, enc(pack2(mine, other)));
            if (u8 == 0) TRACE(15);
        }
        const uint32_t cls = ldcls();
        __nanosleep(QA_DELAY);
        {
            uint4 qb[8];
            const uint32_t* pq = gs + near_off(B_QA + rk * 8 + wq4, cls) + lane * 4;
            const uint32_t* pq2 = gs + near_off(B_QA + rk * 8 + 4 + wq4, cls) + lane * 4;
            if (lane == 0) {
                mbar_expect(BAR(QT), 4096);
                asm volatile("cp.async.bulk.shared::cluster.global.mbarrier::complete_tx::bytes [%0], [%1], 4096, [%2];"
                             :: "r"(sb + SM_U + 5 * 32768 + w8 * 4096), "l"(gs + near_off(B_QA + rk * 8 + w8, cls)), "r"(BAR(QT)) : "memory");
            }
            const uint32_t qs = sb + SM_U + 5 * 32768 + wq4 * 4096 + lane * 16;
            mbar_wait(BAR(QT), 0);
#pragma unroll
            for (int i = 0; i < 8; i++) { a[i] = lds128(qs + i * 512); qb[i] = lds128(qs + 16384 + i * 512); }
            poll<512, QA_SLEEP, true>(a, pq);
            poll<512, QA_SLEEP, true>(qb, pq2);
            if (lane == 0) mbar_arrive(BAR(EB_WUK));
            auto add2 = [](uint32_t x, uint32_t y) { uint32_t r; asm("add.rn.bf16x2 %0, %1, %2;" : "=r"(r) : "r"(x), "r"(y)); return r; };
#pragma unroll
            for (int i = 0; i < 8; i++) a[i] = make_uint4(add2(a[i].x, qb[i].x), add2(a[i].y, qb[i].y), add2(a[i].z, qb[i].z), add2(a[i].w, qb[i].w));
        }
        if (u8 == 0) TRACE(8);
        {
            float m = -INFINITY, l = 0.f;
            uint32_t xl = sb + SM_XB + w8 * 2048 + lane * 16, xr = peer_addr(xl, rk ^ 1), bsr = peer_addr(BAR(SF0 + v), rk ^ 1);
            uint32_t pa = sb + SM_XA + v * 2048 + wq4 * 512 + lane * 16, ma = sb + SM_MX + v * 128 + (wq4 * 8 + g) * 4;
            uint32_t fb = BAR(IT_CKV + v * 2), sf = BAR(SF0 + v);
            uint32_t dlo = __reduce_or_sync(0xffffffffu, (((sb + SM_U + v * 16384) & 0x3FFFFu) >> 4) | 0x10000u);
            if (STAG && v) __nanosleep(STAG);
#pragma unroll 1
            for (int n = 0; n < NUNITS; n++) {
                float d[2][16], sc[8];
#pragma unroll
                for (int i = 0; i < 2; i++) {
                    mbar_wait(fb + i * 8, 0);
                    wg_fence();
#pragma unroll
                    for (int s = 0; s < 8; s++) wgmma_rs_n32(d[i], a[s], (0x40000080ull << 32) | (dlo + i * 512 + (s >> 2) * 64 + (s & 3) * 2), s);
                    wg_commit();
                }
#pragma unroll
                for (int i = 0; i < 2; i++) {
                    if (i) wg_wait0(); else wg_wait1();
#pragma unroll
                    for (int k = 0; k < 16; k++) asm volatile("" : "+f"(d[i][k]) :: "memory");
                    sc[4 * i] = d[i][0] + d[i][6]; sc[4 * i + 1] = d[i][1] + d[i][7]; sc[4 * i + 2] = d[i][8] + d[i][14]; sc[4 * i + 3] = d[i][9] + d[i][15];
                    asm volatile("st.async.weak.shared::cluster.mbarrier::complete_tx::bytes.v4.f32 [%0], {%1, %2, %3, %4}, [%5];"
                                 :: "r"(xr + i * 1024), "f"(sc[4 * i]), "f"(sc[4 * i + 1]), "f"(sc[4 * i + 2]), "f"(sc[4 * i + 3]), "r"(bsr) : "memory");
                }
                if (u8 == 128) TRACE_Q(56 + (n < 6 ? n : -40));
                if (n >= 3) mbar_wait(BAR(EB_UNIT0 + n - 3), 0);
                dlo += n == 5 ? -5 * 2048 : 2048;
                fb += 32; xr ^= 512; bsr += 16;
                pin(fb); pin(xr); pin(bsr);
                mbar_wait(sf, 0);
                const float4 x = ldsf4(xl), y = ldsf4(xl + 1024);
                sc[0] += x.x; sc[1] += x.y; sc[2] += x.z; sc[3] += x.w; sc[4] += y.x; sc[5] += y.y; sc[6] += y.z; sc[7] += y.w;
                float pr[8];
#pragma unroll
                for (int i = 0; i < 8; i++) pr[i] = ex2(sc[i] - m);
                float mx = fmaxf(fmaxf(fmaxf(sc[0], sc[1]), fmaxf(sc[2], sc[3])), fmaxf(fmaxf(sc[4], sc[5]), fmaxf(sc[6], sc[7])));
                if (__builtin_expect(__any_sync(0xffffffffu, mx > m), 0)) {
                    mx = fmaxf(mx, shx(mx, 1));
                    mx = fmaxf(mx, shx(mx, 2));
                    const float mn = fmaxf(m, ceilf(mx * 0.0625f) * 16.f);
                    l *= ex2(m - mn);
                    m = mn;
#pragma unroll
                    for (int i = 0; i < 8; i++) pr[i] = ex2(sc[i] - m);
                }
                stsf(ma, m);
                asm volatile("st.shared.v4.u32 [%0], {%1, %2, %3, %4};" :: "r"(pa), "r"(pack2(pr[0], pr[1])), "r"(pack2(pr[2], pr[3])),
                             "r"(pack2(pr[4], pr[5])), "r"(pack2(pr[6], pr[7])) : "memory");
                __syncwarp();
                if (lane == 0) mbar_arrive(sf + (PF0 - SF0) * 8);
                l += ((pr[0] + pr[1]) + (pr[2] + pr[3])) + ((pr[4] + pr[5]) + (pr[6] + pr[7]));
                xl ^= 512; sf += 16; ma += 256; pa += (n == 2 || n == 5) ? -8192 : 4096;
            }
            l += shx(l, 1);
            l += shx(l, 2);
            float2* mlx = (float2*)(sm + SM_MX + 2048) + wq4 * 8 + g;
            if (v == 0) { *mlx = make_float2(m, l); bar_arrive(11, 256); }
            else {
                mbar_wait(BAR(JD), 0);
                bar_sync(11, 256);
                const float2 o = *mlx;
                const float mn = fmaxf(m, o.x);
                l = l * ex2(m - mn) + o.y * ex2(o.x - mn);
                if ((wq4 >> 1) == rk) st_x4(gs + (B_ML + wq4 * 8 + g) * 4096 + (t >> 1) * 1024 + (j >> 1) * 8 + (t & 1) * 4, encf(mn), encf(l), 1u, 1u);
            }
        }
        const int pi = j < NFF ? rk * 128 + w8 * 16 + (lane & 15) : ((j - J_RED) & 15) * 16 + v * 8 + lb4 * 4 + wq4;
        const uint32_t xw = *(const uint32_t*)(xin + 2 * pi);
        const uint32_t* pm = gs + near_off(B_MB, cls) + pi;
        {
            const uint32_t ab = sb + SM_U + B_WUV * 32768 + v * 4096 + a128;
            uint32_t pa = sb + SM_PB + wq4 * 320 + frag_off(64 * v + 32 * (g >> 2) + 16 * (t & 1) + 8 * (t >> 1) + 2 * (g & 3));
            uint32_t fa = sb + SM_PB + g * 320 + t * 16;
            const uint32_t* pe = gs + G_E1 + j * 8192 + (w8 >> 1) * 2048 + ((((cls >> 1) ^ (w8 >> 1)) & 1) << 10) + (((w8 & 1) * 16 + t) * 8 + g) * 4;
            uint32_t* p2 = gs + (B_E2 + (j >> 4)) * 4096 + (t >> 1) * 1024 + (j & 12) * 64 + w8 * 32 + (j & 3) * 8 + (g & 6) + (t & 1);
            pin(pa); pin(fa); pin(pe); pin(p2);
            const uint32_t mk = (g & 1) ? 0xffff0000u : 0x0000ffffu, m0 = (g & 2) ? 0u : mk, m1 = (g & 2) ? mk : 0u;
            uint4 pv[4];
            bool hv = false;
            bar_sync(3, 416);
            uint4 wa = lds128(sb + SM_W + (wq4 * 4 + t) * 16);
            uint32_t wb[8] = {wa.x & m0, wa.x & m1, wa.y & m0, wa.y & m1, wa.z & m0, wa.z & m1, wa.w & m0, wa.w & m1};
            pv[0] = pv[1] = pv[2] = pv[3] = make_uint4(0u, 0u, 0u, 0u);
            poll<512, E1_SLEEP, true>(pv, pe, [&]() {
                if (!hv) {
                    hv = __all_sync(0xffffffffu, mbar_test(BAR(IT_WUV + t), 0));
                    if (hv) load8<true>(a, [&](int s) { return ab + (s >> 1) * 8192 + (s & 1) * 2048; });
                }
            });
            if (lane == 0) TRACE_Q(48 + w8);
            if (u8 == 0) TRACE_Q(18);
            float lo, hi2;
            float2 inv;
#pragma unroll 1
            for (int pass = 0;; pass++) {
                float e[4][4];
#pragma unroll
                for (int i = 0; i < 4; i++) {
                    e[i][0] = e[i][1] = e[i][2] = e[i][3] = 0.f;
                    mma(e[i], pv[i].x, pv[i].y, pv[i].z, pv[i].w, wb[2 * i], wb[2 * i + 1]);
                }
                const float r0 = (t & 2) ? (e[0][2] + e[1][2]) + (e[2][2] + e[3][2]) : (e[0][0] + e[1][0]) + (e[2][0] + e[3][0]);
                const float r1 = (t & 2) ? (e[0][3] + e[1][3]) + (e[2][3] + e[3][3]) : (e[0][1] + e[1][1]) + (e[2][1] + e[3][1]);
                const uint32_t hi = pack2(r0, r1);
                sts32(pa, hi); sts32(pa + 1280, pack2(r0 - bflo(hi), r1 - bfhi(hi)));
                if (!hv) {
#pragma unroll 1
                    for (int i = 0; i < 4; i++) mbar_wait(BAR(IT_WUV + i), 0);
                    load8<true>(a, [&](int s) { return ab + (s >> 1) * 8192 + (s & 1) * 2048; });
                    hv = true;
                }
                bar_sync(1, 256);
                if (u8 == 0) TRACE(19);
                ldfrag(b, fa);
                mma8(c, a, b);
                mbar_wait(BAR(WR), 0);
                asm volatile("ld.shared.v2.f32 {%0, %1}, [%2];" : "=f"(inv.x), "=f"(inv.y) : "r"(sb + SM_FQ) : "memory");
                quad_pair(c[0] + c[1], c[2] + c[3], t, lo, hi2);
                if (__builtin_expect(__all_sync(0xffffffffu, pass || __float_as_uint(inv.y) == 0), 1)) break;
                wa = lds128(sb + SM_W2 + (wq4 * 4 + t) * 16);
                wb[0] = wa.x & m0; wb[1] = wa.x & m1; wb[2] = wa.y & m0; wb[3] = wa.y & m1; wb[4] = wa.z & m0; wb[5] = wa.z & m1; wb[6] = wa.w & m0; wb[7] = wa.w & m1;
                bar_sync(1, 256);
            }
            if (!(g & 1)) st_x1(p2, enc(pack2(lo * inv.x, hi2 * inv.x)));
            bar_arrive(4, 416);
            if (u8 == 0) TRACE(20);
        }
        if (j < NFF) {
            const uint32_t* p3 = gs + near_off(B_E3 + rk * 2 + v, cls) + wq4 * 256 + lane;
            uint32_t za = sb + SM_FZ + lb4 * 576 + frag_off(w8 * 32 + (lane & 15) * 2);
            uint32_t fa = sb + SM_FZ + (g & 3) * 576 + ((lane ^ j) & 16) * 16 + t * 16, ya = sb + SM_Y + u8 * 4;
            uint32_t mb[3];
            uint4 a2[8];
            poll<1024, MB_SLEEP>(mb, pm);
            const uint32_t kk = pack2(1.f + bflo(mb[2]), 1.f + bfhi(mb[2]));
            sts32(za + 2 * 576, lb4 ? mb[1] : kk);
            uint32_t e3[8] = {0u, 0u, 0u, 0u, 0u, 0u, 0u, 0u};
            uint32_t ra = peer_addr(sb + SM_RED + (rk * 2 + v) * 512 + ((wq4 & 1) * 16 + (t >> 1) * 8 + g) * 16 + (t & 1) * 8, wq4 >> 1), tbo = peer_addr(BAR(QB), wq4 >> 1);
            pin(za); pin(fa); pin(ya); pin(ra); pin(tbo);
            if (lane == 0) mbar_expect(BAR(QB), 256);
            const uint32_t gb = BAR(IT_X + v * 2), ab = sb + SM_U + (B_X + v) * 32768 + a128;
            bool early = false, early2 = false;
            auto ldw = [&]() {
                if (!early) {
                    early = __all_sync(0xffffffffu, mbar_test(gb, 0));
                    if (early) load8<true>(a, [&](int s) { return ab + s * 2048; });
                }
                if (!early2) {
                    early2 = __all_sync(0xffffffffu, mbar_test(gb + 8, 0));
                    if (early2) load8<true>(a2, [&](int s) { return ab + 16384 + s * 2048; });
                }
            };
            bar_sync(8, 384);
            poll<128, 0, true>(e3, p3, ldw);
            if (u8 == 0) TRACE(23);
            const float s0 = sumlo(e3), s1 = sumhi(e3);
            const float y0 = fmaf(bflo(mb[0]), s0 + shx(s0, 16), bflo(xw)), y1 = fmaf(bfhi(mb[0]), s1 + shx(s1, 16), bfhi(xw));
            stsf(ya, lb4 ? y1 : y0);
            const float z0 = y0 * bflo(kk), z1 = y1 * bfhi(kk);
            const uint32_t zh = pack2(z0, z1);
            sts32(za, lb4 ? pack2(z0 - bflo(zh), z1 - bfhi(zh)) : zh);
            bar_sync(7, 288);
            if (u8 == 0) TRACE(24);
            ldfrag(b, fa);
            if (!early) { mbar_wait(gb, 0); load8<true>(a, [&](int s) { return ab + s * 2048; }); }
            {
                float e[4][4];
#pragma unroll
                for (int s = 0; s < 16; s++) {
                    if (s == 8 && !early2) { mbar_wait(gb + 8, 0); load8<true>(a2, [&](int q) { return ab + 16384 + q * 2048; }); }
                    const uint4& x = s < 8 ? a[s] : a2[s & 7];
                    const uint4& y = b[(s >> 1) & 3];
                    float (&d)[4] = e[(s >> 3) * 2 + (s & 1)];
                    if (!(s & 6)) d[0] = d[1] = d[2] = d[3] = 0.f;
                    mma(d, x.x, x.y, x.z, x.w, (s & 1) ? y.z : y.x, (s & 1) ? y.w : y.y);
                }
                const bool hi = t >> 1;
                const float k0 = hi ? e[2][2] + e[3][2] : e[0][0] + e[1][0], k1 = hi ? e[2][3] + e[3][3] : e[0][1] + e[1][1];
                const float o0 = hi ? e[2][0] + e[3][0] : e[0][2] + e[1][2], o1 = hi ? e[2][1] + e[3][1] : e[0][3] + e[1][3];
                st_async2(ra, k0 + shx(o0, 2), k1 + shx(o1, 2), tbo);
            }
        } else if (j >= J_RED && j < J_END) {
            uint32_t ga[1], e3[1];
            poll<0, MB_SLEEP>(ga, pm);
            bar_sync(8, 384);
            poll<0, 100>(e3, gs + near_off(B_E3 + (pi >> 6), cls) + (pi & 48) * 16 + (lane & 15) * 16 + (pi & 15));
            float y0 = bflo(e3[0]), y1 = bfhi(e3[0]);
#pragma unroll
            for (int o = 8; o; o >>= 1) { y0 += shx(y0, o); y1 += shx(y1, o); }
            y0 = fmaf(bflo(ga[0]), y0, bflo(xw)); y1 = fmaf(bfhi(ga[0]), y1, bfhi(xw));
            uint32_t gb = 0;
            auto ldg = [&]() { if (__all_sync(0xffffffffu, mbar_test(BAR(QB), 1))) gb = lds32(sb + SM_FV + 256 + (pi & 15) * 4); };
            uint32_t* po = (uint32_t*)out + pi;
            pin(po);
            const uint32_t nz = lane < NFF / 2 ? 0u : 0x80008000u;
            uint2 yv[2] = {make_uint2(nz, nz), make_uint2(nz, nz)};
            poll<NFF * 32, 0, true>(yv, gs + near_off(B_E5 + j - J_RED, cls) + lane * 16 + w8 * 2, ldg);
            if (u8 == 0) TRACE(26);
            const float l0 = bflo(yv[0].x) + bflo(yv[1].x), h0 = bfhi(yv[0].x) + bfhi(yv[1].x);
            const float l1 = bflo(yv[0].y) + bflo(yv[1].y), h1 = bfhi(yv[0].y) + bfhi(yv[1].y);
            float s0 = (lb4 ? h0 : l0) + shx(lb4 ? l0 : h0, 16), s1 = (lb4 ? h1 : l1) + shx(lb4 ? l1 : h1, 16);
#pragma unroll
            for (int o = 8; o; o >>= 1) { s0 += shx(s0, o); s1 += shx(s1, o); }
            if (__any_sync(0xffffffffu, !gb)) { mbar_wait(BAR(QB), 1); ldg(); }
            if (!(lane & 15)) *po = pack2(fmaf(bflo(gb), s0, y0), fmaf(bfhi(gb), s1, y1));
            if (u8 == 0) TRACE(27);
        }
    }
}

typedef CUresult (*EncFn)(CUtensorMap*, CUtensorMapDataType, cuuint32_t, void*, const cuuint64_t*, const cuuint64_t*,
                          const cuuint32_t*, const cuuint32_t*, CUtensorMapInterleave, CUtensorMapSwizzle,
                          CUtensorMapL2promotion, CUtensorMapFloatOOBfill);

void make_map(EncFn enc_fn, CUtensorMap* m, const void* p, cuuint64_t d0, cuuint64_t d1, cuuint64_t d2, cuuint64_t d3,
              cuuint64_t s1, cuuint64_t s2, cuuint64_t s3, cuuint32_t b0, cuuint32_t b1, cuuint32_t b2, cuuint32_t b3, CUtensorMapSwizzle sw) {
    const cuuint64_t dims[4] = {d0, d1, d2, d3}, strides[3] = {s1, s2, s3};
    const cuuint32_t box[4] = {b0, b1, b2, b3}, es[4] = {1, 1, 1, 1};
    enc_fn(m, CU_TENSOR_MAP_DATA_TYPE_BFLOAT16, 4, (void*)p, dims, strides, box, es,
           CU_TENSOR_MAP_INTERLEAVE_NONE, sw, PROMO, CU_TENSOR_MAP_FLOAT_OOB_FILL_NONE);
}

uint32_t* scratch = nullptr;

struct Tune { const char* win; const char* late; int tau, t_off; const char* tail[3][4]; };
Tune tune = {"66666666655555555555555555555555555533333",
             "00000000000000000000999999999999999999999", 322, -300,
             {{"VVVVOOOOguguDD", "zzzzzzzzzzzzzz", "88889999888877", "eddd0efffaaadd"},
              {"VMVMVVOOOO", "zzzzzzzzzz", "8888889999", "288888iddd"},
              {"VVVVOOOOMM", "zzzzzzzzzz", "aaaaaaaa88", "6ggg0ghhkn"}}};
bool ready = false;

}

extern "C" void kernel_launch(void* const* d_in, const int* in_sizes, int n_in, void* d_out, int out_size) {
    (void)in_sizes; (void)n_in; (void)out_size;
    static Maps maps;
    static const void* cached[12] = {};
    bool same = ready;
    for (int i = 0; i < 12 && same; i++) same = cached[i] == d_in[i];
    if (!same) {
        void* fn = nullptr;
        cudaDriverEntryPointQueryResult qr;
        cudaGetDriverEntryPoint("cuTensorMapEncodeTiled", &fn, cudaEnableDefault, &qr);
        EncFn e = (EncFn)fn;
        const CUtensorMapSwizzle S128 = CU_TENSOR_MAP_SWIZZLE_128B;
        make_map(e, &maps.m[MP_WQ], d_in[2], 64, 512, 64, 1, 8192, 128, 8192, 64, 64, 1, 1, S128);
        make_map(e, &maps.m[MP_WUK], d_in[3], 64, 512, 64, 1, 8192, 128, 8192, 64, 64, 1, 1, S128);
        make_map(e, &maps.m[MP_CKV], d_in[1], 64, 8, 8, 4096, 1024, 128, 8192, 64, 8, 4, 2, S128);
        make_map(e, &maps.m[MP_MODB], d_in[11], 3072, 512, 1, 1, 6144, 6144, 6144, 64, 128, 1, 1, S128);
        make_map(e, &maps.m[MP_WUV], d_in[4], 64, 512, 64, 1, 8192, 128, 8192, 64, 32, 2, 1, S128);
        make_map(e, &maps.m[MP_WO], d_in[5], 512, 4096, 1, 1, 1024, 1024, 1024, 64, 64, 1, 1, S128);
        make_map(e, &maps.m[MP_GATE], d_in[7], 1792, 512, 1, 1, 3584, 3584, 3584, 64, 128, 1, 1, S128);
        make_map(e, &maps.m[MP_UP], d_in[8], 1792, 512, 1, 1, 3584, 3584, 3584, 64, 128, 1, 1, S128);
        make_map(e, &maps.m[MP_DOWN], d_in[9], 64, 1792, 8, 1, 1024, 128, 1024, 64, 32, 4, 1, S128);
        for (int r = 0; r < 3; r++) {
            int ids[56], cnt[128] = {}, tn = tune.t_off - (W0 - 1) * tune.tau;
            uint2* sc = maps.sched[r];
            auto dig = [](char ch) { return ch >= 'a' ? ch - 'a' + 10 : ch >= 'A' ? ch - 'A' + 36 : ch - '0'; };
            for (int i = 0; i < 56; i++) sc[i] = make_uint2(0u, 0u);
            for (int i = 0;; i++) {
                int id = i, buf, dep, w, wl;
                if (i < IT_WUV) {
                    const int u = (i - IT_CKV) >> 2;
                    buf = i < IT_CKV ? 4 + ((i - 1) >> 2) : u % 6;
                    dep = i < IT_CKV || u < 4 ? -1 : u < 6 ? EB_WQ + u - 4 : EB_UNIT0 + u - 6;
                    w = dig(tune.win[i]); wl = dig(tune.late[i]);
                    if (i) tn += tune.tau;
                } else {
                    const char ch = tune.tail[r][0][i - IT_WUV];
                    if (!ch) break;
                    buf = ch == 'V' ? B_WUV : ch == 'O' ? B_WO : ch == 'D' ? B_DN : ch == 'u' ? B_X + 1 : B_X;
                    id = (ch == 'V' ? IT_WUV : ch == 'O' ? IT_WO : ch == 'D' ? IT_DOWN : ch == 'u' ? IT_X + 2 : IT_X) + cnt[(int)ch]++;
                    dep = EB_UNIT0 + (buf < 2 ? buf + 6 : buf);
                    w = dig(tune.tail[r][1][i - IT_WUV]); wl = dig(tune.tail[r][2][i - IT_WUV]);
                    tn += 32 * dig(tune.tail[r][3][i - IT_WUV]);
                }
                if (id < IT_X ? (id - 1) & 3 : (id - IT_X) & 1) dep = -1;
                ids[i] = id;
                auto back = [&](int d) { return i < d ? 0 : (ids[i - d] && ids[i - d] <= NCP ? 1 : ids[i - d]) + 1; };
                sc[i].x = id | (buf * 4 + (id < IT_X ? (id - 1) & 3 : ((id - IT_X) & 1) * 2)) << 6 | (dep + 1) << 11 | (w > 32 ? NEVER + 1 : back(w)) << 18 | (wl ? back(wl) : 0) << 25;
                const int mp = id < IT_CKV ? MP_WQ + ((id - 1) >> 2) : id < IT_WUV ? MP_CKV : id < IT_WO ? MP_WUV : id < IT_X ? MP_WO
                             : id >= IT_DOWN ? MP_DOWN : r ? MP_MODB : MP_GATE + ((id - IT_X) >> 1);
                const int step = mp == MP_CKV ? id - IT_CKV : mp == MP_WUV ? (id - IT_WUV) * 2 : mp == MP_DOWN ? id - IT_DOWN : id < IT_X ? (id - 1) & 3 : ((id - IT_X) & 1) * 2;
                sc[i].y = (tn & 0xffff) | (mp & 15) << 16 | step << 20;
            }
        }
        cudaGetSymbolAddress((void**)&scratch, g_scratch);
        scratch = (uint32_t*)(((uintptr_t)scratch + (2u << 20) - 1) & ~(uintptr_t)((2u << 20) - 1));
        cudaFuncSetAttribute(fused_kernel, cudaFuncAttributeMaxDynamicSharedMemorySize, SM_TOTAL);
        for (int i = 0; i < 12; i++) cached[i] = d_in[i];
        ready = true;
    }
    const First f = {{(const uint8_t*)d_in[2], (const uint8_t*)d_in[11]}, {(const __nv_bfloat16*)d_in[0], (const __nv_bfloat16*)d_in[10]}};
    fused_kernel<<<NCTA, NTHREADS, SM_TOTAL>>>(f, (__nv_bfloat16*)d_out, scratch, maps);
}
```

```cpp
#include <cuda_runtime.h>
#include <cuda_bf16.h>
#include <cuda.h>
#include <stdint.h>
#include <limits.h>

namespace {

constexpr int NCTA = 128;
constexpr int NTHREADS = 512;
constexpr int NUNITS = 8;
constexpr int NFF = 56, J_RED = 104, J_END = 120;
constexpr uint32_t SPIN_LIMIT = 1u << 22;

#define PROMO CU_TENSOR_MAP_L2_PROMOTION_L2_64B
#define NEAR_CLK 390
#define E1_EARLY 50
#define STAG 300
#define NUMA 1
#define NPROBE 5
#define NCP 2
#define W0 4
#define RD_ITEM 15
#define JAN_SLEEP 100
#define RD_SLEEP 400
#define HA_DELAY 200
#define H_SLEEP 100
#define QA_DELAY 600
#define QA_SLEEP 200
#define ML_DELAY 300
#define E1_SLEEP 50
#define MB_SLEEP 100
constexpr int B_WUV = 2, B_WO = 3, B_X = 4  , B_DN = 0;

constexpr int SM_U = 0;
constexpr int SM_XA = 6 * 32768;
constexpr int SM_XB = SM_XA + 12288;
constexpr int SM_MX = SM_XB + 16384;
constexpr int SM_FZ = SM_XB + 8192;
constexpr int SM_PB = SM_XB;
constexpr int SM_Y = SM_XB + 12288;
constexpr int SM_RED = SM_XB + 4096;
constexpr int SM_FS = SM_XB + 20480;
constexpr int SM_FV = SM_FS + 1024;
constexpr int SM_QX = SM_XA + 8192;
constexpr int SM_FQ = SM_FV + 512;
constexpr int SM_CLS = SM_FQ + 128;
constexpr int SM_W = SM_FQ + 256;
constexpr int SM_W2 = SM_MX + 2304;
constexpr int SM_SCR = SM_XA + 9216;
constexpr int SM_TR = SM_XB + 19456;
constexpr int SM_BAR = SM_W + 256;
constexpr int SM_TOTAL = SM_BAR + 1024;
static_assert(SM_TOTAL <= 232448, "smem");

enum { IT_MODA = 0, IT_WQ = 1, IT_WUK = 5, IT_CKV = 9, IT_WUV = 41, IT_WO = 45, IT_X = 49  , IT_DOWN = 53, NITEMS = 55,
       NEVER = 63,
       SF0 = 64,
       PF0 = 80,
       EB_UNIT0 = 96, MBB = 103,
       EB_WQ = 104, EB_WUK, QT, QB, JD, WR };

enum { MP_WQ = 0, MP_WUK, MP_CKV, MP_WUV, MP_DOWN, MP_WO, MP_GATE, MP_UP, MP_MODB, NMAPS };
struct First { const uint8_t* w[2]; const __nv_bfloat16* v[2]; };
struct Maps { CUtensorMap m[NMAPS]; uint2 sched[3][56]; };

enum { B_HA = 0,
       B_MB = 6,
       B_RD = 7,
       B_E2 = 8,
       B_QA = 16,
       B_ML = 32,
       B_E5 = 64,
       B_E3 = 80,
       B_PR = 96,
       B_TR = 100 };
constexpr int G_E1 = 1 << 19;
constexpr int G_TR = B_TR * 4096;
__device__ __align__(1024) uint32_t g_scratch[(8 << 20) / 4];

#define TRACE(slot) do {} while (0)
#define TRACE_Q(slot) do {} while (0)
#define TRACE_GT(slot) do {} while (0)

__device__ __forceinline__ uint32_t s2u(const void* p) { return (uint32_t)__cvta_generic_to_shared(p); }
__device__ __forceinline__ void mbar_init(uint32_t b, int c) { asm volatile("mbarrier.init.shared::cta.b64 [%0], %1;" :: "r"(b), "r"(c) : "memory"); }
__device__ __forceinline__ void mbar_expect(uint32_t b, uint32_t bytes) { asm volatile("mbarrier.arrive.expect_tx.shared::cta.b64 _, [%0], %1;" :: "r"(b), "r"(bytes) : "memory"); }
__device__ __forceinline__ void mbar_arrive(uint32_t b) { asm volatile("mbarrier.arrive.shared::cta.b64 _, [%0];" :: "r"(b) : "memory"); }
__device__ __forceinline__ void mbar_wait(uint32_t b, uint32_t ph) {
    asm volatile("{\n.reg .pred p;\nW: mbarrier.try_wait.parity.shared::cta.b64 p, [%0], %1;\n@!p bra W;\n}" :: "r"(b), "r"(ph) : "memory");
}
__device__ __forceinline__ void mbar_waitb(uint32_t b, uint32_t ph) {
    asm volatile("{\n.reg .pred p;\n.reg .u32 n;\nmov.u32 n, 0;\n"
                 "W: mbarrier.try_wait.parity.shared::cta.b64 p, [%0], %1;\n@p bra D;\n"
                 "add.u32 n, n, 1;\nsetp.lt.u32 p, n, 0x100000;\n@p bra W;\ntrap;\nD:\n}" :: "r"(b), "r"(ph) : "memory");
}
__device__ __forceinline__ uint32_t mbar_test(uint32_t b, uint32_t ph) {
    uint32_t ok;
    asm volatile("{\n.reg .pred p;\nmbarrier.test_wait.parity.shared::cta.b64 p, [%1], %2;\nselp.u32 %0, 1, 0, p;\n}" : "=r"(ok) : "r"(b), "r"(ph) : "memory");
    return ok;
}
__device__ __forceinline__ void bar_sync(int id, int n) { asm volatile("bar.sync %0, %1;" :: "r"(id), "r"(n) : "memory"); }
__device__ __forceinline__ void bar_arrive(int id, int n) { asm volatile("bar.arrive %0, %1;" :: "r"(id), "r"(n) : "memory"); }
__device__ __forceinline__ uint32_t peer_addr(uint32_t a, uint32_t rank) { uint32_t r; asm("mapa.shared::cluster.u32 %0, %1, %2;" : "=r"(r) : "r"(a), "r"(rank)); return r; }
__device__ __forceinline__ void st_async2(uint32_t a, float x, float y, uint32_t bar) {
    asm volatile("st.async.weak.shared::cluster.mbarrier::complete_tx::bytes.v2.f32 [%0], {%1, %2}, [%3];" :: "r"(a), "f"(x), "f"(y), "r"(bar) : "memory");
}
__device__ __forceinline__ uint32_t gtime() { uint32_t t; asm volatile("mov.u32 %0, %%globaltimer_lo;" : "=r"(t)); return t; }
__device__ __forceinline__ void fence_gpu() { asm volatile("fence.acq_rel.gpu;" ::: "memory"); }

__device__ __forceinline__ uint32_t enc(uint32_t b) { uint32_t r; asm("max.u32 %0, %1, 1;" : "=r"(r) : "r"(b)); return r; }
__device__ __forceinline__ uint32_t encf(float f) { return enc(__float_as_uint(f)); }
__device__ __forceinline__ void st_x1(uint32_t* p, uint32_t v) { asm volatile("st.relaxed.gpu.global.u32 [%0], %1;" :: "l"(p), "r"(v) : "memory"); }
__device__ __forceinline__ void st_x4(void* p, uint32_t a, uint32_t b, uint32_t c, uint32_t d) {
    asm volatile("st.relaxed.gpu.global.v4.u32 [%0], {%1, %2, %3, %4};" :: "l"(p), "r"(a), "r"(b), "r"(c), "r"(d) : "memory");
}
__device__ __forceinline__ void st2_x1(uint32_t* p, uint32_t v) { st_x1(p, v); st_x1(p + 1024, v); }
__device__ __forceinline__ void st2_x4(uint32_t* p, uint32_t a, uint32_t b, uint32_t c, uint32_t d) { st_x4(p, a, b, c, d); st_x4(p + 1024, a, b, c, d); }
__device__ __forceinline__ int near_off(int b, uint32_t cls) { return b * 4096 + (((__popc(b & 0x2C) ^ cls) & 1) << 10); }
__device__ __forceinline__ void ld_x(uint32_t& v, const void* p) { asm volatile("ld.relaxed.gpu.global.u32 %0, [%1];" : "=r"(v) : "l"(p) : "memory"); }
__device__ __forceinline__ void ld_x(uint4& v, const void* p) {
    asm volatile("ld.relaxed.gpu.global.v4.u32 {%0, %1, %2, %3}, [%4];" : "=r"(v.x), "=r"(v.y), "=r"(v.z), "=r"(v.w) : "l"(p) : "memory");
}
__device__ __forceinline__ void ld_x(uint2& v, const void* p) { asm volatile("ld.relaxed.gpu.global.v2.u32 {%0, %1}, [%2];" : "=r"(v.x), "=r"(v.y) : "l"(p) : "memory"); }
__device__ __forceinline__ uint32_t minw(uint32_t v) { return v; }
__device__ __forceinline__ uint32_t minw(const uint2& v) { return min(v.x, v.y); }
__device__ __forceinline__ uint32_t minw(const uint4& v) { return min(__vimin3_u32(v.x, v.y, v.z), v.w); }
template <int N> __device__ __forceinline__ uint32_t mint(const uint32_t* m) {
    if constexpr (N == 1) return m[0];
    else if constexpr (N == 2) return min(m[0], m[1]);
    else return __vimin3_u32(mint<(N + 2) / 3>(m), mint<(N + 1) / 3>(m + (N + 2) / 3), mint<N / 3>(m + (N + 2) / 3 + (N + 1) / 3));
}

template <int STRIDE, int S4 = 4 * STRIDE, typename T, int N>
__device__ __forceinline__ void poll_start(T (&v)[N], const void* base) {
#pragma unroll
    for (int i = 0; i < N; i++) ld_x(v[i], (const uint8_t*)base + (i & 3) * STRIDE + (i >> 2) * S4);
}
struct Nop { __device__ void operator()() const {} };
template <int STRIDE, int SLEEP, bool STARTED = false, int S4 = 4 * STRIDE, typename T, int N, typename F = Nop>
__device__ __forceinline__ void poll(T (&v)[N], const void* base, F idle = F()) {
    if (!STARTED) { poll_start<STRIDE, S4>(v, base); idle(); }
#pragma unroll 1
    for (uint32_t it = 0;; it++) {
        uint32_t m[N];
#pragma unroll
        for (int i = 0; i < N; i++) m[i] = minw(v[i]);
        if (__all_sync(0xffffffffu, mint<N>(m) != 0)) break;
        if (SLEEP && it > 0) __nanosleep(SLEEP);
#pragma unroll
        for (int i = 0; i < N; i++) if (!m[i]) ld_x(v[i], (const uint8_t*)base + (i & 3) * STRIDE + (i >> 2) * S4);
        idle();
        if (it > SPIN_LIMIT) __trap();
    }
}

__device__ __forceinline__ float bflo(uint32_t w) { return __uint_as_float(w << 16); }
__device__ __forceinline__ float bfhi(uint32_t w) { return __uint_as_float(w & 0xffff0000u); }
__device__ __forceinline__ uint32_t pack2(float lo, float hi) {
    uint32_t r; asm("cvt.rn.bf16x2.f32 %0, %1, %2;" : "=r"(r) : "f"(hi), "f"(lo)); return r;
}
__device__ __forceinline__ float rbf(float x) { return __uint_as_float(pack2(0.f, x)); }
__device__ __forceinline__ float sumlo(const uint32_t (&v)[8]) { return ((bflo(v[0]) + bflo(v[1])) + (bflo(v[2]) + bflo(v[3]))) + ((bflo(v[4]) + bflo(v[5])) + (bflo(v[6]) + bflo(v[7]))); }
__device__ __forceinline__ float sumhi(const uint32_t (&v)[8]) { return ((bfhi(v[0]) + bfhi(v[1])) + (bfhi(v[2]) + bfhi(v[3]))) + ((bfhi(v[4]) + bfhi(v[5])) + (bfhi(v[6]) + bfhi(v[7]))); }
__device__ __forceinline__ float ex2(float x) { float r; asm("ex2.approx.ftz.f32 %0, %1;" : "=f"(r) : "f"(x)); return r; }
__device__ __forceinline__ float shx(float v, int m) { return __shfl_xor_sync(0xffffffffu, v, m); }
__device__ __forceinline__ uint4 lds128(uint32_t a) { uint4 v; asm volatile("ld.shared.v4.u32 {%0, %1, %2, %3}, [%4];" : "=r"(v.x), "=r"(v.y), "=r"(v.z), "=r"(v.w) : "r"(a) : "memory"); return v; }
__device__ __forceinline__ uint32_t lds32(uint32_t a) { uint32_t v; asm volatile("ld.shared.u32 %0, [%1];" : "=r"(v) : "r"(a) : "memory"); return v; }
__device__ __forceinline__ void sts32(uint32_t a, uint32_t v) { asm volatile("st.shared.u32 [%0], %1;" :: "r"(a), "r"(v) : "memory"); }
__device__ __forceinline__ void sts16(uint32_t a, uint32_t v) { asm volatile("st.shared.u16 [%0], %1;" :: "r"(a), "h"((uint16_t)v) : "memory"); }
__device__ __forceinline__ int frag_off(int k) { return (k >> 5) * 64 + ((k >> 1) & 3) * 16 + ((k >> 4) & 1) * 8 + ((k >> 3) & 1) * 4 + (k & 1) * 2; }

template <bool TRANS>
__device__ __forceinline__ uint4 ldsm(uint32_t a) {
    uint4 r;
    if (TRANS) asm volatile("ldmatrix.sync.aligned.m8n8.x4.trans.shared.b16 {%0, %1, %2, %3}, [%4];" : "=r"(r.x), "=r"(r.y), "=r"(r.z), "=r"(r.w) : "r"(a) : "memory");
    else asm volatile("ldmatrix.sync.aligned.m8n8.x4.shared.b16 {%0, %1, %2, %3}, [%4];" : "=r"(r.x), "=r"(r.y), "=r"(r.z), "=r"(r.w) : "r"(a) : "memory");
    return r;
}
__device__ __forceinline__ void mma(float (&c)[4], uint32_t a0, uint32_t a1, uint32_t a2, uint32_t a3, uint32_t b0, uint32_t b1) {
    asm volatile("mma.sync.aligned.m16n8k16.row.col.f32.bf16.bf16.f32 {%0,%1,%2,%3}, {%4,%5,%6,%7}, {%8,%9}, {%0,%1,%2,%3};"
                 : "+f"(c[0]), "+f"(c[1]), "+f"(c[2]), "+f"(c[3]) : "r"(a0), "r"(a1), "r"(a2), "r"(a3), "r"(b0), "r"(b1));
}
template <bool TRANS, typename F>
__device__ __forceinline__ void load8(uint4 (&a)[8], F addr) {
    __syncwarp();
#pragma unroll
    for (int s = 0; s < 8; s++) a[s] = ldsm<TRANS>(addr(s));
}
__device__ __forceinline__ void mma8(float (&c)[4], const uint4 (&a)[8], const uint4 (&b)[4]) {
    float e[4][4];
#pragma unroll
    for (int s = 0; s < 8; s++) {
        if (s < 4) e[s][0] = e[s][1] = e[s][2] = e[s][3] = 0.f;
        mma(e[s & 3], a[s].x, a[s].y, a[s].z, a[s].w, (s & 1) ? b[s >> 1].z : b[s >> 1].x, (s & 1) ? b[s >> 1].w : b[s >> 1].y);
    }
#pragma unroll
    for (int i = 0; i < 4; i++) c[i] = (e[0][i] + e[1][i]) + (e[2][i] + e[3][i]);
}
__device__ __forceinline__ void ldfrag(uint4 (&b)[4], uint32_t a) {
    asm volatile("ld.shared.v4.u32 {%0,%1,%2,%3}, [%16];\nld.shared.v4.u32 {%4,%5,%6,%7}, [%16+64];\n"
                 "ld.shared.v4.u32 {%8,%9,%10,%11}, [%16+128];\nld.shared.v4.u32 {%12,%13,%14,%15}, [%16+192];\n"
                 : "=r"(b[0].x), "=r"(b[0].y), "=r"(b[0].z), "=r"(b[0].w), "=r"(b[1].x), "=r"(b[1].y), "=r"(b[1].z), "=r"(b[1].w),
                   "=r"(b[2].x), "=r"(b[2].y), "=r"(b[2].z), "=r"(b[2].w), "=r"(b[3].x), "=r"(b[3].y), "=r"(b[3].z), "=r"(b[3].w) : "r"(a) : "memory");
}
__device__ __forceinline__ void quad_pair(float x, float y, int t, float& lo, float& hi) {
    const float k = ((t & 1) ? y : x) + shx((t & 1) ? x : y, 1);
    lo = k + shx(k, 2); hi = shx(k, 4) + shx(k, 6);
}
__device__ __forceinline__ void pin(uint32_t& x) { asm volatile("" : "+r"(x)); }
template <typename T> __device__ __forceinline__ void pin(T*& x) { asm volatile("" : "+l"(x)); }
__device__ __forceinline__ float4 ldsf4(uint32_t a) { const uint4 v = lds128(a); return make_float4(__uint_as_float(v.x), __uint_as_float(v.y), __uint_as_float(v.z), __uint_as_float(v.w)); }
__device__ __forceinline__ float sum4(const float4& f) { return (f.x + f.y) + (f.z + f.w); }
__device__ __forceinline__ void stsf(uint32_t a, float v) { sts32(a, __float_as_uint(v)); }

__device__ __forceinline__ void wg_fence() { asm volatile("wgmma.fence.sync.aligned;" ::: "memory"); }
__device__ __forceinline__ void wg_commit() { asm volatile("wgmma.commit_group.sync.aligned;" ::: "memory"); }
__device__ __forceinline__ void wg_wait1() { asm volatile("wgmma.wait_group.sync.aligned 1;" ::: "memory"); }
__device__ __forceinline__ void wg_wait0() { asm volatile("wgmma.wait_group.sync.aligned 0;" ::: "memory"); }
#define R8(o) "+f"(d[o]), "+f"(d[o + 1]), "+f"(d[o + 2]), "+f"(d[o + 3]), "+f"(d[o + 4]), "+f"(d[o + 5]), "+f"(d[o + 6]), "+f"(d[o + 7])
__device__ __forceinline__ void wgmma_rs_n32(float (&d)[16], const uint4& a, uint64_t db, int acc) {
    asm volatile("{\n.reg .pred p;\nsetp.ne.b32 p, %21, 0;\n"
        "wgmma.mma_async.sync.aligned.m64n32k16.f32.bf16.bf16 "
        "{%0,%1,%2,%3,%4,%5,%6,%7,%8,%9,%10,%11,%12,%13,%14,%15}, {%16,%17,%18,%19}, %20, p, 1, 1, 0;\n}"
        : R8(0), R8(8) : "r"(a.x), "r"(a.y), "r"(a.z), "r"(a.w), "l"(db), "r"(acc));
}
#define PV_LO "{%0,%1,%2,%3,%4,%5,%6,%7,%8,%9,%10,%11,%12,%13,%14,%15,%16,%17,%18,%19,%20,%21,%22,%23,%24,%25,%26,%27,%28,%29,%30,%31,%32,%33,%34,%35,%36,%37,%38,%39,%40,%41,%42,%43,%44,%45,%46,%47,%48,%49,%50,%51,%52,%53,%54,%55,%56,%57,%58,%59,%60,%61,%62,%63}, "
#define PV_HI "{%64,%65,%66,%67,%68,%69,%70,%71,%72,%73,%74,%75,%76,%77,%78,%79,%80,%81,%82,%83,%84,%85,%86,%87,%88,%89,%90,%91,%92,%93,%94,%95,%96,%97,%98,%99,%100,%101,%102,%103,%104,%105,%106,%107,%108,%109,%110,%111,%112,%113,%114,%115,%116,%117,%118,%119,%120,%121,%122,%123,%124,%125,%126,%127}, "
__device__ __forceinline__ void wgmma_pv(float (&d)[128], const uint4& a, uint32_t blo, int acc) {
    asm volatile("{\n.reg .pred p;\n.reg .b32 u0, u1, u2, u3, t;\n.reg .b64 d0, d1, d2, d3;\nsetp.ne.b32 p, %133, 0;\n"
        "mov.b64 d0, {%132, 0x40000100};\nadd.u32 t, %132, 512;\nmov.b64 d1, {t, 0x40000100};\n"
        "add.u32 t, %132, 128;\nmov.b64 d2, {t, 0x40000100};\nadd.u32 t, %132, 640;\nmov.b64 d3, {t, 0x40000100};\n"
        "wgmma.fence.sync.aligned;\n"
        "wgmma.mma_async.sync.aligned.m64n128k16.f32.bf16.bf16 " PV_LO "{%128, u0, %129, u1}, d0, p, 1, 1, 1;\n"
        "wgmma.mma_async.sync.aligned.m64n128k16.f32.bf16.bf16 " PV_LO "{%130, u2, %131, u3}, d1, 1, 1, 1, 1;\n"
        "wgmma.commit_group.sync.aligned;\n"
        "wgmma.mma_async.sync.aligned.m64n128k16.f32.bf16.bf16 " PV_HI "{%128, u0, %129, u1}, d2, p, 1, 1, 1;\n"
        "wgmma.mma_async.sync.aligned.m64n128k16.f32.bf16.bf16 " PV_HI "{%130, u2, %131, u3}, d3, 1, 1, 1, 1;\n"
        "wgmma.commit_group.sync.aligned;\n}"
        : R8(0), R8(8), R8(16), R8(24), R8(32), R8(40), R8(48), R8(56), R8(64), R8(72), R8(80), R8(88), R8(96), R8(104), R8(112), R8(120)
        : "r"(a.x), "r"(a.y), "r"(a.z), "r"(a.w), "r"(blo), "r"(acc) : "memory");
}

template <int NW>
__device__ __forceinline__ void ln_stats(float s, float q, float sh, float* scr, int w, int lane, int bar, float& mean_b, float& sd_b) {
#pragma unroll
    for (int o = 16; o; o >>= 1) { s += shx(s, o); q += shx(q, o); }
    constexpr float n = 512.f / NW;
    if (lane == 0) { scr[w] = sh + s * (1.f / n); scr[NW + w] = q - s * s * (1.f / n); }
    bar_sync(bar, NW * 32);
    float mu = 0.f, m2 = 0.f;
#pragma unroll
    for (int i = 0; i < NW; i++) { mu += scr[i]; m2 += scr[NW + i]; }
    mu *= 1.f / NW;
#pragma unroll
    for (int i = 0; i < NW; i++) { const float d = scr[i] - mu; m2 = fmaf(n * d, d, m2); }
    mean_b = rbf(mu);
    sd_b = rbf(sqrtf(rbf(rbf(fmaxf(m2, 0.f) * (1.f / 512.f)) + 1e-5f)));
}
__device__ __forceinline__ float ln_mod(float x, float mean_b, float sd_b, float c, float s) {
    return rbf(rbf(__fdividef(rbf(x - mean_b), sd_b)) * rbf(1.f + c)) + s;
}

__global__ void __cluster_dims__(2, 1, 1) __launch_bounds__(NTHREADS, 1)
fused_kernel(const __grid_constant__ First F, __nv_bfloat16* __restrict__ out, uint32_t* __restrict__ gs, const __grid_constant__ Maps M) {
    extern __shared__ __align__(1024) uint8_t sm[];
    const uint32_t sb = s2u(sm);
    const int tid = threadIdx.x, lane = tid & 31;
    const int j = blockIdx.x, rk = j & 1;
    const int g = lane >> 2, t = lane & 3;
    const int r8 = lane & 7, lb3 = (lane >> 3) & 1, lb4 = lane >> 4;
    uint64_t pol;
    asm("createpolicy.fractional.L2::evict_first.b64 %0, 1.0;" : "=l"(pol));
    {
        auto cpa = [&](uint32_t d, const uint8_t* s) {
            asm volatile("cp.async.cg.shared.global.L2::cache_hint.L2::128B [%0], [%1], 16, %2;" :: "r"(d), "l"(s), "l"(pol) : "memory");
        };
        const uint32_t ut = threadIdx.x, uj = blockIdx.x;
        const uint8_t* w = F.w[ut >= 128];
        if (ut < 128) {
            const uint32_t dq = (sb + ut * 16) ^ ((ut * 2) & 0x70);
            const uint8_t* sq = w + (uint32_t)(((uj & 1) * 256 + (ut >> 3)) * 8192 + (uj >> 1) * 128 + (ut & 7) * 16);
#pragma unroll
            for (int i = 0; i < 4 * NCP; i++) cpa(dq + 4 * 32768 + i * 2048, sq + i * 131072);
        } else if (ut < 384) {
            const uint32_t dm = (sb + ut * 16) ^ ((ut * 2) & 0x10);
            const uint8_t* sa = w + (uint32_t)(((uj >> 5) * 128 + (ut >> 1) - 64) * 6144 + (uj & 31) * 32 + (ut & 1) * 16);
            cpa(dm + SM_XA - 2048, sa); cpa(dm + SM_XA + 2048, sa + 1024);
        }
        else if (ut == 480 && uj < 64) asm volatile("prefetch.global.L2 [%0];" :: "l"(F.v[(uj >> 3) & 1] + (uj & 7) * 64));
    }
    const int warp = __shfl_sync(0xffffffffu, tid >> 5, 0);
    const __nv_bfloat16* const xin = F.v[0];
    uint32_t* const pl = gs + (warp < 2 ? (B_PR + (j >> 5)) * 4096 + (j & 31) * 32 : G_E1 + j * 8192) + (warp & 1) * 1024 + lane;
    if (warp < 4) st_x1(pl, 1u);
    auto BAR = [&](int i) -> uint32_t { return sb + SM_BAR + i * 8; };
    const uint32_t a16 = (r8 + 8 * lb4) * 32 + ((lb3 ^ (r8 >> 2)) * 16);
    const uint32_t a128 = (r8 + 8 * lb4) * 128 + ((((warp & 3) * 2 + lb3) ^ r8) * 16);
    auto ldcls = [&]() -> uint32_t { return *(const volatile uint32_t*)(sm + SM_CLS); };
    auto clear_head = [&]() {
        st2_x1(gs + (B_HA + ((j >> 4) & 1) * 2 + lb4) * 4096 + (j >> 5) * 256 + (j & 15) * 16 + (lane & 15), 0u);
        st2_x4(gs + (B_QA + rk * 8 + ((j >> 1) & 1) * 4 + (j >> 5)) * 4096 + g * 128 + ((j >> 2) & 7) * 16 + t * 4, 0u, 0u, 0u, 0u);
        if (lane < 8) st2_x1(gs + B_RD * 4096 + j * 8 + lane, 0u);
    };
    auto tma = [&](uint32_t dst, const CUtensorMap* mp, uint32_t bar, int c0, int c1, int c2, int c3) {
        asm volatile("{\n.reg .pred p;\nelect.sync _|p, 0xffffffff;\n"
                     "@p cp.async.bulk.tensor.4d.shared::cluster.global.mbarrier::complete_tx::bytes.L2::cache_hint [%0], [%1, {%3, %4, %5, %6}], [%2], %7;\n}"
                     :: "r"(dst), "l"(mp), "r"(bar), "r"(c0), "r"(c1), "r"(c2), "r"(c3), "l"(pol) : "memory");
    };
    if (warp <= 12 || warp == 15) {
        const int grp = warp == 12 ? 0 : warp == 15 ? 13 : warp + 1;
        const uint32_t cnt = grp < 10 ? 1 : grp < 13 ? 4 : 8;
        if (lane == 0) {
#pragma unroll
            for (int i = 0; i < 8; i++) mbar_init(BAR(grp * 8 + i), (i < 2 && grp == 0) ? (i ? 128 : 256) : cnt);
        }
        __syncwarp();
        if (grp < 10 && lane < 8 && (grp || lane > NCP)) mbar_expect(BAR(grp * 8 + lane), grp >= 8 ? 4096 : grp * 8 + lane < IT_X ? 8192 : 16384);
        asm volatile("fence.mbarrier_init.release.cluster;" ::: "memory");
        __syncwarp();
        if (warp == 12) {
#pragma unroll
            for (int i = NCP + 1; i < W0; i++) tma(sb + (15 + i) * 8192, &M.m[MP_WQ], BAR(i), 0, rk * 256 + (i - 1) * 64, j >> 1, 0);
        }
    } else if (warp == 13) {
        if (lane < NMAPS) asm volatile("prefetch.tensormap [%0];" :: "l"(&M.m[lane]) : "memory");
    } else if (warp == 14) {
        clear_head();
    }
    __syncthreads();
    uint32_t in1 = 0, in2 = 0;
    if (warp < 4) { in1 = *(const uint32_t*)(xin + 2 * tid); in2 = *(const uint32_t*)(xin + 256 + 2 * tid); }
    else if (warp < 12) in1 = *(const uint32_t*)(F.v[1] + 2 * (tid - 128));
    if (warp < 12) asm volatile("cp.async.mbarrier.arrive.noinc.shared::cta.b64 [%0];" :: "r"(BAR(warp < 4)) : "memory");
    asm volatile("barrier.cluster.arrive.relaxed.aligned;" ::: "memory");

    if (warp >= 12) {
    asm volatile("setmaxnreg.dec.sync.aligned.u32 64;");
    if (warp == 12) {
        static_assert(W0 > NCP && W0 <= 5 && NCP >= 1 && NCP <= 4, "W0");
        const uint2* sched = M.sched[j < NFF ? 0 : j < J_RED ? 1 : 2];
        uint2 en = sched[W0];
        const uint32_t t0 = gtime();
        const uint32_t sp = __reduce_or_sync(0xffffffffu, sb);
        const int cx = (j >> 1) * 64 + (j < NFF ? 0 : 1024 - NFF * 32);
#pragma unroll 1
        for (int i = W0; en.x; i++) {
            uint32_t e = en.x, st = (en.y >> 20) * 64;
            const uint32_t tn = t0 + (int16_t)en.y, mp = (en.y >> 16) & 15;
            if (mp == MP_WUV || mp == MP_WUK) { st ^= (j >> 5) * (mp == MP_WUV ? 128 : 64); e ^= (j >> 5) << 6; }
            if (mp == MP_GATE || mp == MP_UP) st ^= (j & 16) * 8;
            en = sched[i + 1];
            if (mp == MP_MODB && j >= J_END) break;
            uint32_t c0 = mp == MP_WO ? (j & 7) * 64 : mp > MP_WO ? cx : 0;
            uint32_t c1 = mp == MP_CKV ? 0 : mp == MP_DOWN ? j * 32 : st + (mp == MP_WUV ? (j & 3) * 32 : mp == MP_WO ? (j >> 3) * 256 : rk * 256);
            uint32_t c2 = mp < MP_CKV ? j >> 1 : mp == MP_CKV ? rk * 4 : mp == MP_WUV ? (j >> 2) * 2 : mp == MP_DOWN ? st >> 4 : 0;
            uint32_t c3 = mp == MP_CKV ? st * 2 + (j & ~1) : 0;
            uint32_t dst = sp + ((e << 7) & 0x3e000), bar = sp + SM_BAR + (e & 63) * 8;
            const uint32_t w0 = (e >> 8) & 0x3f8, w1 = (e >> 15) & 0x3f8, w2 = (e >> 22) & 0x3f8, bb = sp + SM_BAR - 8;
            const CUtensorMap* pm = &M.m[mp];
            pin(dst); pin(bar); pin(c0); pin(c1); pin(c2); pin(c3); pin(pm);
            if (w0) mbar_wait(bb + w0, 0);
            if (w2) {
                mbar_wait(bb + w2, 0);
                while (!__any_sync(0xffffffffu, mbar_test(bb + w1, 0) | ((int)(gtime() - tn) > 0))) {}
            } else if (w1) mbar_wait(bb + w1, 0);
            tma(dst, pm, bar, c0, c1, c2, c3);
        }
    } else if (warp == 13) {
#pragma unroll
        for (int i = 0; i < 2; i++) st_x4(gs + (B_ML + rk * 16 + i * 8 + g) * 4096 + (t >> 1) * 1024 + (j >> 1) * 8 + (t & 1) * 4, 0u, 0u, 0u, 0u);
        if (lane < 16) st2_x4(gs + (B_E2 + (j >> 4)) * 4096 + (j & 15) * 64 + lane * 4, 0u, 0u, 0u, 0u);
        st2_x1(gs + (B_E3 + (j >> 5)) * 4096 + (j & 31) * 32 + lane, 0u);
        if (lane < 8) st2_x1(gs + B_MB * 4096 + j * 8 + lane, 0u);
        if (j < NFF) {
#pragma unroll
            for (int i = 0; i < 2; i++) st2_x4(gs + (B_E5 + i * 8 + g) * 4096 + j * 16 + t * 4, 0u, 0u, 0u, 0u);
        }
        bar_sync(9, 64);
        const uint32_t cs = ldcls();
#pragma unroll 1
        for (int i = 0; i < 32; i++) {
            st_x4(gs + G_E1 + j * 8192 + (i >> 3) * 2048 + ((((cs >> 1) ^ (i >> 3)) & 1) << 10) + (i & 7) * 128 + lane * 4, 0u, 0u, 0u, 0u);
            __nanosleep(JAN_SLEEP);
        }
        fence_gpu();
        if (lane < 8) st2_x1(gs + B_RD * 4096 + j * 8 + lane, 1u + (cs >> 1));
        if (lane == 0) TRACE(41);
        uint32_t rd[4];
        mbar_wait(BAR(IT_CKV + RD_ITEM), 0);
        poll<1024, RD_SLEEP>(rd, gs + near_off(B_RD, cs) + lane * 8);
#pragma unroll
        for (int i = 0; i < 4; i++) {
            const uint32_t m = __ballot_sync(0xffffffffu, rd[i] == 2u);
            if (lane == 0) sts32(sb + SM_CLS + 16 + i * 4, m);
        }
        __syncwarp();
        if (lane < 8) mbar_arrive(BAR(JD));
        if (lane == 0) TRACE(42);
    } else if (warp == 14) {
        uint2 ml[2];
        mbar_waitb(BAR(JD), 0);
        const uint32_t cls = ldcls();
        mbar_waitb(BAR(PF0 + 2 * NUNITS - 1), 0);
        __nanosleep(ML_DELAY);
        const uint32_t* pl2 = gs + near_off(B_ML + (j >> 2), cls) + lane * 8;
        const uint32_t wa = sb + SM_W + lb4 * 64 + t * 16 + (g & 3) * 4;
        poll_start<1024>(ml, pl2);
        uint32_t w0 = 0, w1 = 0, redo = 0;
        bool first = true;
#pragma unroll 1
        for (uint32_t it = 0;; it++) {
            const bool p0 = minw(ml[0]) != 0, p1 = minw(ml[1]) != 0;
            const int n = __popc(__ballot_sync(0xffffffffu, p0)) + __popc(__ballot_sync(0xffffffffu, p1));
            const uint32_t x0 = ml[0].x, x1 = ml[1].x;
            if (n < 64) {
                if (!p0) ld_x(ml[0], pl2);
                if (!p1) ld_x(ml[1], pl2 + 256);
            }
            if (n == 64 || (first && n >= E1_EARLY)) {
                auto ord = [](int x) { return x ^ ((x >> 31) & 0x7fffffff); };
                const int o0 = ord(x0), o1 = ord(x1);
                const float mm = __int_as_float(ord(__reduce_max_sync(0xffffffffu, max(p0 ? o0 : INT_MIN, p1 ? o1 : INT_MIN))));
                const float lo = __int_as_float(ord(__reduce_min_sync(0xffffffffu, min(p0 ? o0 : INT_MAX, p1 ? o1 : INT_MAX))));
                const uint32_t v0 = pack2(ex2((p0 ? __uint_as_float(x0) : lo) - mm), 0.f), v1 = pack2(ex2((p1 ? __uint_as_float(x1) : lo) - mm), 0.f);
                redo = !first && __any_sync(0xffffffffu, v0 != w0 || v1 != w1);
                w0 = v0; w1 = v1;
                sts32(wa - redo * (SM_W - SM_W2), w0 * 0x10001u); sts32(wa - redo * (SM_W - SM_W2) + 128, w1 * 0x10001u);
                if (first) bar_arrive(3, 416);
                first = false;
                if (n == 64) break;
            }
            if (it > SPIN_LIMIT) __trap();
        }
        if (lane == 0) TRACE_Q(37);
        float L = bflo(w0) * __uint_as_float(ml[0].y) + bflo(w1) * __uint_as_float(ml[1].y);
#pragma unroll
        for (int o = 16; o; o >>= 1) L += shx(L, o);
        if (lane == 0) *(float2*)(sm + SM_FQ) = make_float2(__frcp_rn(L), __uint_as_float(redo));
        __syncwarp();
        if (lane < 8) mbar_arrive(BAR(WR));
        if (lane == 0) TRACE(10);
        bar_sync(4, 416);
        clear_head();
        if (j < NFF) {
            uint32_t ya = sb + SM_Y + lane * 16, sa = peer_addr(sb + SM_RED + 2048 + rk * 8, lane & 1), tb = peer_addr(BAR(MBB), lane & 1);
            pin(ya); pin(sa); pin(tb);
            bar_sync(7, 288);
            const float4 y0 = ldsf4(ya), y1 = ldsf4(ya + 512);
            float s = sum4(y0) + sum4(y1);
            float q = (fmaf(y0.x, y0.x, y0.y * y0.y) + fmaf(y0.z, y0.z, y0.w * y0.w)) + (fmaf(y1.x, y1.x, y1.y * y1.y) + fmaf(y1.z, y1.z, y1.w * y1.w));
#pragma unroll
            for (int o = 16; o; o >>= 1) { s += shx(s, o); q += shx(q, o); }
            if (lane < 2) st_async2(sa, s, q, tb);
        }
    } else if (warp == 15) {
        mbar_waitb(BAR(IT_X - 1), 0);
        if (j < J_END) mbar_waitb(BAR(j < NFF ? NITEMS - 1 : MBB), 0);
    }
    } else if (warp < 4) {
        float* scr = (float*)(sm + SM_SCR);
        uint32_t cls;
        {
            uint2 ha[8];
            uint32_t best = 0xffffffffu;
            sts32(sb + SM_SCR + 64 + warp * 4, best);
            const float sh = __shfl_sync(0xffffffffu, bflo(in1), 0);
            const float v0 = bflo(in1) - sh, v1 = bfhi(in1) - sh, v2 = bflo(in2) - sh, v3 = bfhi(in2) - sh;
            float mb, sd;
            ln_stats<4>((v0 + v1) + (v2 + v3), (v0 * v0 + v1 * v1) + (v2 * v2 + v3 * v3), sh, scr, warp, lane, 2, mb, sd);
            if (!rk) in2 = in1;
#pragma unroll 1
            for (int i = 0; i < NPROBE; i++) {
                uint32_t t0, t1, o;
                asm volatile("mov.u32 %0, %%clock;" : "=r"(t0));
                asm volatile("atom.relaxed.gpu.global.exch.b32 %0, [%1], %2;" : "=r"(o) : "l"(pl), "r"(2u + i) : "memory");
                asm volatile("{\n.reg .pred p;\nsetp.ne.u32 p, %1, 0x1234567;\nmov.u32 %0, 0;\n@p mov.u32 %0, %%clock;\n}" : "=r"(t1) : "r"(o));
                best = min(best, t1 - t0);
                sts32(sb + SM_SCR + 64 + warp * 4, best);
                if (__all_sync(0xffffffffu, min(best, lds32(sb + SM_SCR + 64 + (warp ^ 1) * 4)) < NEAR_CLK)) break;
            }
            bar_sync(2, 128);
            const uint4 lt = *(const uint4*)(scr + 16);
            cls = NUMA ? ((lt.y < lt.x) ^ (__popc((B_PR + (j >> 5)) & 0x2C) & 1)) | (lt.w < lt.z) << 1 : 0;
            if (warp == 0) { if (lane == 0) sts32(sb + SM_CLS, cls); bar_arrive(9, 64); }
            if (tid == 0) TRACE(38);
            asm volatile("barrier.cluster.wait.aligned;" ::: "memory");
            mbar_wait(BAR(IT_MODA), 0);
            if (HA_DELAY) __nanosleep(HA_DELAY);
            poll<1024, H_SLEEP, false, 16384>(ha, gs + near_off(B_HA + rk * 2, cls) + 2 * tid);
            auto rsum = [](uint32_t a, uint32_t b, uint32_t c, uint32_t d) { return rbf((__uint_as_float(a) + __uint_as_float(b)) + (__uint_as_float(c) + __uint_as_float(d))); };
            sts32(sb + SM_FV + frag_off(2 * tid),
                  pack2(ln_mod(bflo(in2), mb, sd, rsum(ha[4].x, ha[5].x, ha[6].x, ha[7].x), rsum(ha[0].x, ha[1].x, ha[2].x, ha[3].x)),
                        ln_mod(bfhi(in2), mb, sd, rsum(ha[4].y, ha[5].y, ha[6].y, ha[7].y), rsum(ha[0].y, ha[1].y, ha[2].y, ha[3].y))));
            bar_arrive(5, 384);
            mbar_wait(BAR(QB), 0);
            if (tid < 64) {
                const float* qx = (const float*)(sm + SM_QX) + tid;
                sts16(sb + SM_FQ + frag_off(tid), pack2((qx[0] + qx[64]) + (qx[128] + qx[192]), 0.f));
            }
            bar_arrive(6, 384);
        }
        asm volatile("setmaxnreg.inc.sync.aligned.u32 192;");
        float acc[128];
        float M = 0.f;
        uint32_t pa = sb + SM_XA + warp * 512 + lane * 16, ma = sb + SM_MX + (warp * 8 + g) * 4, pf = BAR(PF0);
        uint32_t blo = __reduce_or_sync(0xffffffffu, (((sb + SM_U) & 0x3FFFFu) >> 4) | 0x400000u);
        uint32_t* e1[4];
#pragma unroll
        for (int i = 0; i < 4; i++) e1[i] = gs + G_E1 + (warp * 8 + g) * 4 * 8192 + (rk * 2 + (j >> 6)) * 2048 + ((j >> 1) & 31) * 32 + t * 4;
#pragma unroll 1
        for (int h = 0; h < 2 * NUNITS; h++) {
            mbar_wait(pf, 0);
            const float m = __uint_as_float(lds32(ma));
            const uint4 pn = lds128(pa);
            wg_wait0();
#pragma unroll
            for (int i = 0; i < 128; i++) asm volatile("" : "+f"(acc[i]) :: "memory");
            if (h == 0) M = m;
            uint32_t b2 = 0x3f803f80u;
            if (__builtin_expect(__any_sync(0xffffffffu, m != M), 0)) {
                const float Mn = fmaxf(M, m), alpha = ex2(M - Mn), beta = ex2(m - Mn);
                M = Mn;
                b2 = pack2(beta, beta);
#pragma unroll
                for (int jj = 0; jj < 32; jj++) { acc[4 * jj] *= alpha; acc[4 * jj + 1] *= alpha; }
            }
            auto mul2 = [](uint32_t x, uint32_t y) { uint32_t r; asm("mul.rn.bf16x2 %0, %1, %2;" : "=r"(r) : "r"(x), "r"(y)); return r; };
            const uint4 p = make_uint4(mul2(pn.x, b2), mul2(pn.y, b2), mul2(pn.z, b2), mul2(pn.w, b2));
            if (tid == 0 && (h & 1)) TRACE_Q(48 + (h >> 1));
            wgmma_pv(acc, p, blo, h);
            if (lane == 0 && h > 0 && !(h & 1)) mbar_arrive(BAR(EB_UNIT0 + (h >> 1) - 1));
            blo += h == 11 ? -11 * 1024 : 1024;
            pa += (h == 5 || h == 11) ? -5 * 2048 : 2048;
            ma += 128; pf += 8;
            if (h == 2 * NUNITS - 3) {
                mbar_wait(BAR(JD), 0);
                const uint32_t hm = (*(const uint32_t*)(sm + SM_CLS + 16 + warp * 4) >> (g * 4)) ^ ((j >> 6) ? 15u : 0u);
#pragma unroll
                for (int i = 0; i < 4; i++) e1[i] += ((hm >> i) & 1) << 10;
            }
        }
#pragma unroll
        for (int vv = 0; vv < 2; vv++) {
            if (vv && M == 1.f) __trap();
            if (vv) wg_wait0(); else wg_wait1();
#pragma unroll
            for (int i = 0; i < 64; i++) asm volatile("" : "+f"(acc[vv * 64 + i]) :: "memory");
            if (tid == 0 && !vv) TRACE_Q(63);
#pragma unroll
            for (int i = 0; i < 4; i++) {
                const float* a = &acc[vv * 64 + i * 16];
                st_x4(e1[i] + i * 8192 + vv * 16, enc(pack2(a[0], a[1])), enc(pack2(a[4], a[5])), enc(pack2(a[8], a[9])), enc(pack2(a[12], a[13])));
            }
        }
        bar_arrive(3, 416);
        if (tid == 0) TRACE_Q(17);
#pragma unroll 1
        for (int pass = 0;; pass++) {
            if (j >= NFF && j < J_END && pass == (j >= J_RED)) {
                uint4 a[8], b[4];
                float c[4], e[4];
                const bool own = (warp >> 1) == rk;
                const uint32_t xa = sb + SM_FV + (warp & 1) * 64 + g * 8;
                if (lane == 0) mbar_expect(BAR(MBB), own ? 64 : 0);
#pragma unroll
                for (int i = 0; i < 2; i++) {
                    ldfrag(b, sb + SM_FS + rk * 512 + i * 256 + t * 16);
                    mbar_wait(BAR(IT_X + i), 0);
                    const uint32_t ab = sb + SM_U + B_X * 32768 + i * 16384 + a128;
                    load8<true>(a, [&](int s) { return ab + s * 2048; });
                    mma8(i ? e : c, a, b);
                }
                c[0] += e[0]; c[2] += e[2];
                if (!own) {
                    if (t == 0) st_async2(peer_addr(xa, rk ^ 1), c[0], c[2], peer_addr(BAR(MBB), rk ^ 1));
                } else {
                    mbar_wait(BAR(MBB), 0);
                    const float2 pp = *(const float2*)(sm + (xa - sb));
                    const float mine = t ? c[2] + pp.y : c[0] + pp.x, other = shx(mine, 4);
                    const uint32_t w = (warp & 1) * 8 + t * 4 + (g >> 1), val = enc(pack2(mine, other));
                    if (t < 2 && !(g & 1)) {
                        if (j < J_RED) st2_x1(gs + B_MB * 4096 + (j - NFF) * 16 + w, val);
                        else sts32(sb + SM_FV + 256 + w * 4, val);
                    }
                    __syncwarp();
                    if (j >= J_RED && lane < 4) mbar_arrive(BAR(QB));
                    if (lane == 0) TRACE(11);
                }
            }
            if (pass) break;
            uint4 a[8], a2[8];
            const uint32_t ab = sb + SM_U + B_WO * 32768 + a128;
            uint32_t* p3 = gs + (B_E3 + ((j >> 1) & 3)) * 4096 + (t >> 1) * 1024 + (rk * 2 + (warp >> 1)) * 256 + (j >> 3) * 16 + (warp & 1) * 8 + (t & 1) * 4 + (g >> 1);
            const uint32_t* pb = gs + near_off(B_E2 + (j >> 4), cls) + (((j >> 3) & 1) * 2 + lb4) * 256 + (lane & 15) * 2;
            pin(p3); pin(pb);
            uint2 bb[8];
#pragma unroll
            for (int i = 0; i < 8; i++) bb[i] = make_uint2(0u, 0u);
            bool h0 = false, h1 = false;
            auto idle = [&]() {
                if (!h0) {
                    h0 = __all_sync(0xffffffffu, mbar_test(BAR(IT_WO + (t & 1)), 0));
                    if (h0) load8<true>(a, [&](int s) { return ab + s * 2048; });
                }
                if (!h1) {
                    h1 = __all_sync(0xffffffffu, mbar_test(BAR(IT_WO + 2 + (t & 1)), 0));
                    if (h1) load8<true>(a2, [&](int s) { return ab + 16384 + s * 2048; });
                }
            };
            bar_sync(4, 416);
            idle();
            poll<128, 0, true>(bb, pb, idle);
            if (tid == 0) TRACE(21);
            float e[4][4];
#pragma unroll
            for (int s = 0; s < 16; s++) {
                if (s == 0 && !h0) { mbar_wait(BAR(IT_WO), 0); mbar_wait(BAR(IT_WO + 1), 0); load8<true>(a, [&](int q) { return ab + q * 2048; }); }
                if (s == 0 && !h1) { mbar_wait(BAR(IT_WO + 2), 0); mbar_wait(BAR(IT_WO + 3), 0); load8<true>(a2, [&](int q) { return ab + 16384 + q * 2048; }); }
                const int z = (s & 1) | (s & 2) << 2 | (s >> 2) << 1;
                const uint4& x = z < 8 ? a[z] : a2[z & 7];
                float (&d)[4] = e[(z >> 3) * 2 + (z & 1)];
                if (!(z & 6)) d[0] = d[1] = d[2] = d[3] = 0.f;
                mma(d, x.x, x.y, x.z, x.w, bb[z & 7].x, bb[z & 7].y);
            }
            float lo, hi;
            quad_pair((t & 2) ? (e[2][0] + e[3][0]) + (e[2][1] + e[3][1]) : (e[0][0] + e[1][0]) + (e[0][1] + e[1][1]),
                      (t & 2) ? (e[2][2] + e[3][2]) + (e[2][3] + e[3][3]) : (e[0][2] + e[1][2]) + (e[0][3] + e[1][3]), t, lo, hi);
            if (!(g & 1)) st_x1(p3, enc(pack2(lo, hi)));
            if (j < NFF) bar_arrive(8, 384); else if (j >= J_RED && j < J_END) bar_arrive(8, 192);
            if (tid == 0) TRACE(22);
        }
        if (j < NFF) {
            uint4 a[16];
            const uint32_t ad = sb + SM_U + B_DN * 32768 + warp * 8192 + (r8 + 8 * lb4) * 128 + (lb3 ^ r8) * 16;
            uint32_t rl = sb + SM_RED + lane * 16;
            uint32_t* p5 = gs + (B_E5 + warp * 4 + (t >> 1)) * 4096 + j * 16 + (t & 1) * 8 + g;
            pin(rl); pin(p5);
            if (lane == 0) mbar_expect(BAR(MBB), 4);
            auto ldd = [&]() {
#pragma unroll
                for (int s = 0; s < 16; s++) a[s] = ldsm<true>((ad ^ ((s & 3) * 32)) + (s >> 2) * 2048);
            };
            const uint32_t db = BAR(IT_DOWN + (warp >> 1));
            mbar_wait(BAR(MBB), 0);
            const float4 st = ldsf4(sb + SM_RED + 2048);
            const bool hd = __all_sync(0xffffffffu, mbar_test(db, 0));
            if (hd) ldd();
            const float mu = (st.x + st.z) * (1.f / 512.f);
            float rstd;
            asm volatile("rsqrt.approx.ftz.f32 %0, %1;" : "=f"(rstd) : "f"(fmaxf(fmaf(-mu, mu, (st.y + st.w) * (1.f / 512.f)), 0.f) + 1e-5f));
            mbar_wait(BAR(QB), 1);
            if (tid == 0) TRACE(25);
            const float4 f0 = ldsf4(rl), f2 = ldsf4(rl + 1024), f1 = ldsf4(rl + 512), f3 = ldsf4(rl + 1536);
            const float gg = fmaf(rstd, fmaf(-mu, f0.z + f2.z, (f0.x + f0.y) + (f2.x + f2.y)), f0.w + f2.w);
            const float uu = fmaf(rstd, fmaf(-mu, f1.z + f3.z, (f1.x + f1.y) + (f3.x + f3.y)), f1.w + f3.w);
            const float hh = __fdividef(gg * uu, 1.f + ex2(-gg * fmaf(gg * gg, 0.10294324f, 2.3022082f)));
            uint32_t hb[4];
#pragma unroll
            for (int i = 0; i < 4; i++) hb[i] = pack2(__shfl_sync(0xffffffffu, hh, 2 * t + 8 * i), __shfl_sync(0xffffffffu, hh, 2 * t + 8 * i + 1));
            if (!hd) { mbar_wait(db, 0); ldd(); }
#pragma unroll
            for (int i = 0; i < 2; i++) {
                uint32_t res = 0;
#pragma unroll
                for (int k = 0; k < 4; k++) {
                    float c[4] = {0.f, 0.f, 0.f, 0.f};
                    const uint4 &x = a[i * 8 + k], &y = a[i * 8 + k + 4];
                    mma(c, x.x, x.y, x.z, x.w, hb[0], hb[1]);
                    mma(c, y.x, y.y, y.z, y.w, hb[2], hb[3]);
                    if (t == k) res = pack2(c[0], c[2]);
                }
                st2_x1(p5 + i * 8192, enc(res));
            }
            if (tid == 0) { TRACE(27); TRACE_GT(47); }
        }
    } else {
        const int u8 = tid - 128, w8 = warp - 4;
        const int v = w8 >> 2, wq4 = w8 & 3;
        {
            const float c0 = bflo(in1), c1 = bfhi(in1);
            sts32(sb + SM_FS + frag_off(2 * u8), pack2(__fdividef(c0, 1.f + __expf(-c0)), __fdividef(c1, 1.f + __expf(-c1))));
        }
        bar_sync(1, 256);
        asm volatile("barrier.cluster.wait.aligned;" ::: "memory");
        uint4 a[8], b[4]; float c[4];
        if (w8 < 2) {
            ldfrag(b, sb + SM_FS + (j >> 5) * 256 + t * 16);
            mbar_wait(BAR(IT_MODA), 0);
            if (u8 == 0) TRACE(12);
            const uint32_t ab = sb + SM_XA + w8 * 4096 + a16;
            load8<true>(a, [&](int s) { return ab + s * 512; });
            mma8(c, a, b);
            if (t < 2) st2_x1(gs + (B_HA + ((j >> 4) & 1) * 2 + w8) * 4096 + (j >> 5) * 256 + (j & 15) * 16 + t * 8 + g, encf(t ? c[2] : c[0]));
        }
        {
            mbar_wait(BAR(IT_WQ + 2 * v <= NCP ? 1 : IT_WQ + 2 * v), 0); mbar_wait(BAR(IT_WQ + 2 * v + 1 <= NCP ? 1 : IT_WQ + 2 * v + 1), 0);
            const uint32_t ab = sb + SM_U + 4 * 32768 + v * 16384 + a128;
            load8<true>(a, [&](int s) { return ab + s * 2048; });
            if (lane == 0) mbar_arrive(BAR(EB_WQ));
            bar_sync(5, 384);
            if (u8 == 0) TRACE(13);
            ldfrag(b, sb + SM_FV + v * 256 + t * 16);
            mma8(c, a, b);
            if (t < 2) {
                const float qv = t ? c[2] : c[0];
                const uint32_t qa_ = sb + SM_QX + ((rk * 2 + v) * 64 + wq4 * 16 + t * 8 + g) * 4;
                asm volatile("st.async.weak.shared::cluster.mbarrier::complete_tx::bytes.f32 [%0], %1, [%2];"
                             :: "r"(peer_addr(qa_, rk ^ 1)), "f"(qv), "r"(peer_addr(BAR(QB), rk ^ 1)) : "memory");
                sts32(qa_, __float_as_uint(qv));
            }
            __syncwarp();
            if (lane == 0) mbar_expect(BAR(QB), 64);
        }
        {
            mbar_wait(BAR(IT_WUK + (v ^ ((j >> 5) & 1))), 0); mbar_wait(BAR(IT_WUK + (v ^ ((j >> 5) & 1)) + 2), 0);
            const uint32_t ab = sb + SM_U + 5 * 32768 + (w8 * 16 + r8 + 8 * lb3) * 128;
            const uint32_t x16 = (lb4 ^ r8) * 16;
            load8<false>(a, [&](int s) { return ab + (s & 1) * 16384 + (x16 ^ ((s >> 1) * 32)); });
            bar_sync(6, 384);
            if (u8 == 0) TRACE(14);
            b[0] = lds128(sb + SM_FQ + t * 16); b[1] = lds128(sb + SM_FQ + 64 + t * 16);
            float e[4] = {0.f, 0.f, 0.f, 0.f};
            c[0] = c[1] = c[2] = c[3] = 0.f;
#pragma unroll
            for (int k = 0; k < 4; k++) {
                const uint32_t b0 = (k & 1) ? b[k >> 1].z : b[k >> 1].x, b1 = (k & 1) ? b[k >> 1].w : b[k >> 1].y;
                mma(c, a[2 * k].x, a[2 * k].y, a[2 * k].z, a[2 * k].w, b0, b1);
                mma(e, a[2 * k + 1].x, a[2 * k + 1].y, a[2 * k + 1].z, a[2 * k + 1].w, b0, b1);
            }
            const float mine = ((t & 1) ? ((t & 2) ? e[2] : e[0]) : ((t & 2) ? c[2] : c[0])) * 0.12751743f;
            const float other = shx(mine, 4);
            if (!(g & 1)) st2_x1(gs + (B_QA + rk * 8 + ((j >> 1) & 1) * 4 + (j >> 5)) * 4096 + w8 * 128 + ((j >> 2) & 7) * 16 + (g >> 1) * 4 + t, enc(pack2(mine, other)));
            if (u8 == 0) TRACE(15);
        }
        const uint32_t cls = ldcls();
        __nanosleep(QA_DELAY);
        {
            uint4 qb[8];
            const uint32_t* pq = gs + near_off(B_QA + rk * 8 + wq4, cls) + lane * 4;
            const uint32_t* pq2 = gs + near_off(B_QA + rk * 8 + 4 + wq4, cls) + lane * 4;
            if (lane == 0) {
                mbar_expect(BAR(QT), 4096);
                asm volatile("cp.async.bulk.shared::cluster.global.mbarrier::complete_tx::bytes [%0], [%1], 4096, [%2];"
                             :: "r"(sb + SM_U + 5 * 32768 + w8 * 4096), "l"(gs + near_off(B_QA + rk * 8 + w8, cls)), "r"(BAR(QT)) : "memory");
            }
            const uint32_t qs = sb + SM_U + 5 * 32768 + wq4 * 4096 + lane * 16;
            mbar_wait(BAR(QT), 0);
#pragma unroll
            for (int i = 0; i < 8; i++) { a[i] = lds128(qs + i * 512); qb[i] = lds128(qs + 16384 + i * 512); }
            poll<512, QA_SLEEP, true>(a, pq);
            poll<512, QA_SLEEP, true>(qb, pq2);
            if (lane == 0) mbar_arrive(BAR(EB_WUK));
            auto add2 = [](uint32_t x, uint32_t y) { uint32_t r; asm("add.rn.bf16x2 %0, %1, %2;" : "=r"(r) : "r"(x), "r"(y)); return r; };
#pragma unroll
            for (int i = 0; i < 8; i++) a[i] = make_uint4(add2(a[i].x, qb[i].x), add2(a[i].y, qb[i].y), add2(a[i].z, qb[i].z), add2(a[i].w, qb[i].w));
        }
        if (u8 == 0) TRACE(8);
        {
            float m = -INFINITY, l = 0.f;
            uint32_t xl = sb + SM_XB + w8 * 2048 + lane * 16, xr = peer_addr(xl, rk ^ 1), bsr = peer_addr(BAR(SF0 + v), rk ^ 1);
            uint32_t pa = sb + SM_XA + v * 2048 + wq4 * 512 + lane * 16, ma = sb + SM_MX + v * 128 + (wq4 * 8 + g) * 4;
            uint32_t fb = BAR(IT_CKV + v * 2), sf = BAR(SF0 + v);
            uint32_t dlo = __reduce_or_sync(0xffffffffu, (((sb + SM_U + v * 16384) & 0x3FFFFu) >> 4) | 0x10000u);
            if (STAG && v) __nanosleep(STAG);
#pragma unroll 1
            for (int n = 0; n < NUNITS; n++) {
                float d[2][16], sc[8];
#pragma unroll
                for (int i = 0; i < 2; i++) {
                    mbar_wait(fb + i * 8, 0);
                    wg_fence();
#pragma unroll
                    for (int s = 0; s < 8; s++) wgmma_rs_n32(d[i], a[s], (0x40000080ull << 32) | (dlo + i * 512 + (s >> 2) * 64 + (s & 3) * 2), s);
                    wg_commit();
                }
#pragma unroll
                for (int i = 0; i < 2; i++) {
                    if (i) wg_wait0(); else wg_wait1();
#pragma unroll
                    for (int k = 0; k < 16; k++) asm volatile("" : "+f"(d[i][k]) :: "memory");
                    sc[4 * i] = d[i][0] + d[i][6]; sc[4 * i + 1] = d[i][1] + d[i][7]; sc[4 * i + 2] = d[i][8] + d[i][14]; sc[4 * i + 3] = d[i][9] + d[i][15];
                    asm volatile("st.async.weak.shared::cluster.mbarrier::complete_tx::bytes.v4.f32 [%0], {%1, %2, %3, %4}, [%5];"
                                 :: "r"(xr + i * 1024), "f"(sc[4 * i]), "f"(sc[4 * i + 1]), "f"(sc[4 * i + 2]), "f"(sc[4 * i + 3]), "r"(bsr) : "memory");
                }
                if (u8 == 128) TRACE_Q(56 + (n < 6 ? n : -40));
                if (n >= 3) mbar_wait(BAR(EB_UNIT0 + n - 3), 0);
                dlo += n == 5 ? -5 * 2048 : 2048;
                fb += 32; xr ^= 512; bsr += 16;
                pin(fb); pin(xr); pin(bsr);
                mbar_wait(sf, 0);
                const float4 x = ldsf4(xl), y = ldsf4(xl + 1024);
                sc[0] += x.x; sc[1] += x.y; sc[2] += x.z; sc[3] += x.w; sc[4] += y.x; sc[5] += y.y; sc[6] += y.z; sc[7] += y.w;
                float pr[8];
#pragma unroll
                for (int i = 0; i < 8; i++) pr[i] = ex2(sc[i] - m);
                float mx = fmaxf(fmaxf(fmaxf(sc[0], sc[1]), fmaxf(sc[2], sc[3])), fmaxf(fmaxf(sc[4], sc[5]), fmaxf(sc[6], sc[7])));
                if (__builtin_expect(__any_sync(0xffffffffu, mx > m), 0)) {
                    mx = fmaxf(mx, shx(mx, 1));
                    mx = fmaxf(mx, shx(mx, 2));
                    const float mn = fmaxf(m, ceilf(mx * 0.0625f) * 16.f);
                    l *= ex2(m - mn);
                    m = mn;
#pragma unroll
                    for (int i = 0; i < 8; i++) pr[i] = ex2(sc[i] - m);
                }
                stsf(ma, m);
                asm volatile("st.shared.v4.u32 [%0], {%1, %2, %3, %4};" :: "r"(pa), "r"(pack2(pr[0], pr[1])), "r"(pack2(pr[2], pr[3])),
                             "r"(pack2(pr[4], pr[5])), "r"(pack2(pr[6], pr[7])) : "memory");
                __syncwarp();
                if (lane == 0) mbar_arrive(sf + (PF0 - SF0) * 8);
                l += ((pr[0] + pr[1]) + (pr[2] + pr[3])) + ((pr[4] + pr[5]) + (pr[6] + pr[7]));
                xl ^= 512; sf += 16; ma += 256; pa += (n == 2 || n == 5) ? -8192 : 4096;
            }
            l += shx(l, 1);
            l += shx(l, 2);
            float2* mlx = (float2*)(sm + SM_MX + 2048) + wq4 * 8 + g;
            if (v == 0) { *mlx = make_float2(m, l); bar_arrive(11, 256); }
            else {
                mbar_wait(BAR(JD), 0);
                bar_sync(11, 256);
                const float2 o = *mlx;
                const float mn = fmaxf(m, o.x);
                l = l * ex2(m - mn) + o.y * ex2(o.x - mn);
                if ((wq4 >> 1) == rk) st_x4(gs + (B_ML + wq4 * 8 + g) * 4096 + (t >> 1) * 1024 + (j >> 1) * 8 + (t & 1) * 4, encf(mn), encf(l), 1u, 1u);
            }
        }
        const int pi = j < NFF ? rk * 128 + w8 * 16 + (lane & 15) : ((j - J_RED) & 15) * 16 + (w8 & 1) * 8 + g;
        const uint32_t xw = *(const uint32_t*)(xin + 2 * pi);
        const uint32_t* pm = gs + near_off(B_MB, cls) + pi;
        {
            const uint32_t ab = sb + SM_U + B_WUV * 32768 + v * 4096 + a128;
            uint32_t pa = sb + SM_PB + wq4 * 320 + frag_off(64 * v + 32 * (g >> 2) + 16 * (t & 1) + 8 * (t >> 1) + 2 * (g & 3));
            uint32_t fa = sb + SM_PB + g * 320 + t * 16;
            const uint32_t* pe = gs + G_E1 + j * 8192 + (w8 >> 1) * 2048 + ((((cls >> 1) ^ (w8 >> 1)) & 1) << 10) + (((w8 & 1) * 16 + t) * 8 + g) * 4;
            uint32_t* p2 = gs + (B_E2 + (j >> 4)) * 4096 + (t >> 1) * 1024 + (j & 12) * 64 + w8 * 32 + (j & 3) * 8 + (g & 6) + (t & 1);
            pin(pa); pin(fa); pin(pe); pin(p2);
            const uint32_t mk = (g & 1) ? 0xffff0000u : 0x0000ffffu, m0 = (g & 2) ? 0u : mk, m1 = (g & 2) ? mk : 0u;
            uint4 pv[4];
            bool hv = false;
            bar_sync(3, 416);
            uint4 wa = lds128(sb + SM_W + (wq4 * 4 + t) * 16);
            uint32_t wb[8] = {wa.x & m0, wa.x & m1, wa.y & m0, wa.y & m1, wa.z & m0, wa.z & m1, wa.w & m0, wa.w & m1};
            pv[0] = pv[1] = pv[2] = pv[3] = make_uint4(0u, 0u, 0u, 0u);
            poll<512, E1_SLEEP, true>(pv, pe, [&]() {
                if (!hv) {
                    hv = __all_sync(0xffffffffu, mbar_test(BAR(IT_WUV + t), 0));
                    if (hv) load8<true>(a, [&](int s) { return ab + (s >> 1) * 8192 + (s & 1) * 2048; });
                }
            });
            if (lane == 0) TRACE_Q(48 + w8);
            if (u8 == 0) TRACE_Q(18);
            float lo, hi2;
            float2 inv;
#pragma unroll 1
            for (int pass = 0;; pass++) {
                float e[4][4];
#pragma unroll
                for (int i = 0; i < 4; i++) {
                    e[i][0] = e[i][1] = e[i][2] = e[i][3] = 0.f;
                    mma(e[i], pv[i].x, pv[i].y, pv[i].z, pv[i].w, wb[2 * i], wb[2 * i + 1]);
                }
                const float r0 = (t & 2) ? (e[0][2] + e[1][2]) + (e[2][2] + e[3][2]) : (e[0][0] + e[1][0]) + (e[2][0] + e[3][0]);
                const float r1 = (t & 2) ? (e[0][3] + e[1][3]) + (e[2][3] + e[3][3]) : (e[0][1] + e[1][1]) + (e[2][1] + e[3][1]);
                const uint32_t hi = pack2(r0, r1);
                sts32(pa, hi); sts32(pa + 1280, pack2(r0 - bflo(hi), r1 - bfhi(hi)));
                if (!hv) {
#pragma unroll 1
                    for (int i = 0; i < 4; i++) mbar_wait(BAR(IT_WUV + i), 0);
                    load8<true>(a, [&](int s) { return ab + (s >> 1) * 8192 + (s & 1) * 2048; });
                    hv = true;
                }
                bar_sync(1, 256);
                if (u8 == 0) TRACE(19);
                ldfrag(b, fa);
                mma8(c, a, b);
                mbar_wait(BAR(WR), 0);
                asm volatile("ld.shared.v2.f32 {%0, %1}, [%2];" : "=f"(inv.x), "=f"(inv.y) : "r"(sb + SM_FQ) : "memory");
                quad_pair(c[0] + c[1], c[2] + c[3], t, lo, hi2);
                if (__builtin_expect(__all_sync(0xffffffffu, pass || __float_as_uint(inv.y) == 0), 1)) break;
                wa = lds128(sb + SM_W2 + (wq4 * 4 + t) * 16);
                wb[0] = wa.x & m0; wb[1] = wa.x & m1; wb[2] = wa.y & m0; wb[3] = wa.y & m1; wb[4] = wa.z & m0; wb[5] = wa.z & m1; wb[6] = wa.w & m0; wb[7] = wa.w & m1;
                bar_sync(1, 256);
            }
            if (!(g & 1)) st_x1(p2, enc(pack2(lo * inv.x, hi2 * inv.x)));
            bar_arrive(4, 416);
            if (u8 == 0) TRACE(20);
        }
        if (j < NFF) {
            const uint32_t* p3 = gs + near_off(B_E3 + rk * 2 + v, cls) + wq4 * 256 + lane;
            uint32_t za = sb + SM_FZ + lb4 * 576 + frag_off(w8 * 32 + (lane & 15) * 2);
            uint32_t fa = sb + SM_FZ + (g & 3) * 576 + ((lane ^ j) & 16) * 16 + t * 16, ya = sb + SM_Y + u8 * 4;
            uint32_t mb[3];
            uint4 a2[8];
            poll<1024, MB_SLEEP>(mb, pm);
            const uint32_t kk = pack2(1.f + bflo(mb[2]), 1.f + bfhi(mb[2]));
            sts32(za + 2 * 576, lb4 ? mb[1] : kk);
            uint32_t e3[8] = {0u, 0u, 0u, 0u, 0u, 0u, 0u, 0u};
            uint32_t ra = peer_addr(sb + SM_RED + (rk * 2 + v) * 512 + ((wq4 & 1) * 16 + (t >> 1) * 8 + g) * 16 + (t & 1) * 8, wq4 >> 1), tbo = peer_addr(BAR(QB), wq4 >> 1);
            pin(za); pin(fa); pin(ya); pin(ra); pin(tbo);
            if (lane == 0) mbar_expect(BAR(QB), 256);
            const uint32_t gb = BAR(IT_X + v * 2), ab = sb + SM_U + (B_X + v) * 32768 + a128;
            bool early = false, early2 = false;
            auto ldw = [&]() {
                if (!early) {
                    early = __all_sync(0xffffffffu, mbar_test(gb, 0));
                    if (early) load8<true>(a, [&](int s) { return ab + s * 2048; });
                }
                if (!early2) {
                    early2 = __all_sync(0xffffffffu, mbar_test(gb + 8, 0));
                    if (early2) load8<true>(a2, [&](int s) { return ab + 16384 + s * 2048; });
                }
            };
            bar_sync(8, 384);
            poll<128, 0, true>(e3, p3, ldw);
            if (u8 == 0) TRACE(23);
            const float s0 = sumlo(e3), s1 = sumhi(e3);
            const float y0 = fmaf(bflo(mb[0]), s0 + shx(s0, 16), bflo(xw)), y1 = fmaf(bfhi(mb[0]), s1 + shx(s1, 16), bfhi(xw));
            stsf(ya, lb4 ? y1 : y0);
            const float z0 = y0 * bflo(kk), z1 = y1 * bfhi(kk);
            const uint32_t zh = pack2(z0, z1);
            sts32(za, lb4 ? pack2(z0 - bflo(zh), z1 - bfhi(zh)) : zh);
            bar_sync(7, 288);
            if (u8 == 0) TRACE(24);
            ldfrag(b, fa);
            if (!early) { mbar_wait(gb, 0); load8<true>(a, [&](int s) { return ab + s * 2048; }); }
            {
                float e[4][4];
#pragma unroll
                for (int s = 0; s < 16; s++) {
                    if (s == 8 && !early2) { mbar_wait(gb + 8, 0); load8<true>(a2, [&](int q) { return ab + 16384 + q * 2048; }); }
                    const uint4& x = s < 8 ? a[s] : a2[s & 7];
                    const uint4& y = b[(s >> 1) & 3];
                    float (&d)[4] = e[(s >> 3) * 2 + (s & 1)];
                    if (!(s & 6)) d[0] = d[1] = d[2] = d[3] = 0.f;
                    mma(d, x.x, x.y, x.z, x.w, (s & 1) ? y.z : y.x, (s & 1) ? y.w : y.y);
                }
                const bool hi = t >> 1;
                const float k0 = hi ? e[2][2] + e[3][2] : e[0][0] + e[1][0], k1 = hi ? e[2][3] + e[3][3] : e[0][1] + e[1][1];
                const float o0 = hi ? e[2][0] + e[3][0] : e[0][2] + e[1][2], o1 = hi ? e[2][1] + e[3][1] : e[0][3] + e[1][3];
                st_async2(ra, k0 + shx(o0, 2), k1 + shx(o1, 2), tbo);
            }
        } else if (j >= J_RED && j < J_END && w8 < 2) {
            uint32_t ga[1], e3[4];
            poll<0, MB_SLEEP>(ga, pm);
            bar_sync(8, 192);
            poll<64, 100>(e3, gs + near_off(B_E3 + (pi >> 6), cls) + (pi & 48) * 16 + t * 64 + (pi & 15));
            float y0 = (bflo(e3[0]) + bflo(e3[1])) + (bflo(e3[2]) + bflo(e3[3])), y1 = (bfhi(e3[0]) + bfhi(e3[1])) + (bfhi(e3[2]) + bfhi(e3[3]));
#pragma unroll
            for (int o = 1; o < 4; o <<= 1) { y0 += shx(y0, o); y1 += shx(y1, o); }
            const int col = g + (t & 1) * 8;
            y0 = __shfl_sync(0xffffffffu, (t & 1) ? fmaf(bfhi(ga[0]), y1, bfhi(xw)) : fmaf(bflo(ga[0]), y0, bflo(xw)), (col >> 1) * 4 + (col & 1));
            uint32_t gb = 0;
            auto ldg = [&]() { if (__all_sync(0xffffffffu, mbar_test(BAR(QB), 1))) gb = lds32(sb + SM_FV + 256 + w8 * 32 + (col >> 1) * 4); };
            uint16_t* po = (uint16_t*)out + (j - J_RED) * 32 + w8 * 16 + col;
            pin(po);
            uint32_t yv[NFF / 4];
            poll<256, 0>(yv, gs + near_off(B_E5 + j - J_RED, cls) + t * 16 + w8 * 8 + g, ldg);
            if (u8 == 0) TRACE(26);
            const uint32_t one = (g & 1) ? 0x3f800000u : 0x00003f80u;
            float e[4][4];
#pragma unroll
            for (int i = 0; i < 4; i++) {
                e[i][0] = e[i][1] = e[i][2] = e[i][3] = 0.f;
                mma(e[i], yv[4 * i], yv[4 * i + 1], i < 3 ? yv[(4 * i + 2) % (NFF / 4)] : 0u, i < 3 ? yv[(4 * i + 3) % (NFF / 4)] : 0u, one, one);
            }
            const float s = (t & 1) ? ((e[0][1] + e[0][3]) + (e[1][1] + e[1][3])) + ((e[2][1] + e[2][3]) + (e[3][1] + e[3][3]))
                                    : ((e[0][0] + e[0][2]) + (e[1][0] + e[1][2])) + ((e[2][0] + e[2][2]) + (e[3][0] + e[3][2]));
            if (__any_sync(0xffffffffu, !gb)) { mbar_wait(BAR(QB), 1); ldg(); }
            if (t < 2) *po = (uint16_t)pack2(fmaf((col & 1) ? bfhi(gb) : bflo(gb), s, y0), 0.f);
            if (u8 == 0) TRACE(27);
        }
    }
}

typedef CUresult (*EncFn)(CUtensorMap*, CUtensorMapDataType, cuuint32_t, void*, const cuuint64_t*, const cuuint64_t*,
                          const cuuint32_t*, const cuuint32_t*, CUtensorMapInterleave, CUtensorMapSwizzle,
                          CUtensorMapL2promotion, CUtensorMapFloatOOBfill);

void make_map(EncFn enc_fn, CUtensorMap* m, const void* p, cuuint64_t d0, cuuint64_t d1, cuuint64_t d2, cuuint64_t d3,
              cuuint64_t s1, cuuint64_t s2, cuuint64_t s3, cuuint32_t b0, cuuint32_t b1, cuuint32_t b2, cuuint32_t b3, CUtensorMapSwizzle sw) {
    const cuuint64_t dims[4] = {d0, d1, d2, d3}, strides[3] = {s1, s2, s3};
    const cuuint32_t box[4] = {b0, b1, b2, b3}, es[4] = {1, 1, 1, 1};
    enc_fn(m, CU_TENSOR_MAP_DATA_TYPE_BFLOAT16, 4, (void*)p, dims, strides, box, es,
           CU_TENSOR_MAP_INTERLEAVE_NONE, sw, PROMO, CU_TENSOR_MAP_FLOAT_OOB_FILL_NONE);
}

uint32_t* scratch = nullptr;

struct Tune { const char* win; const char* late; int tau, t_off; const char* tail[3][4]; };
Tune tune = {"66666666655555555555555555555555555533333",
             "00000000000000000000999999999999999999999", 322, -300,
             {{"VVVVOOOOguguDD", "zzzzzzzzzzzzzz", "88889999888877", "eddd0efffaaadd"},
              {"VMVMVVOOOO", "zzzzzzzzzz", "8888889999", "288888iddd"},
              {"VVVVOOOOMM", "zzzzzzzzzz", "aaaaaaaa88", "6ggg0ghhkn"}}};
bool ready = false;

}

extern "C" void kernel_launch(void* const* d_in, const int* in_sizes, int n_in, void* d_out, int out_size) {
    (void)in_sizes; (void)n_in; (void)out_size;
    static Maps maps;
    static const void* cached[12] = {};
    bool same = ready;
    for (int i = 0; i < 12 && same; i++) same = cached[i] == d_in[i];
    if (!same) {
        void* fn = nullptr;
        cudaDriverEntryPointQueryResult qr;
        cudaGetDriverEntryPoint("cuTensorMapEncodeTiled", &fn, cudaEnableDefault, &qr);
        EncFn e = (EncFn)fn;
        const CUtensorMapSwizzle S128 = CU_TENSOR_MAP_SWIZZLE_128B;
        make_map(e, &maps.m[MP_WQ], d_in[2], 64, 512, 64, 1, 8192, 128, 8192, 64, 64, 1, 1, S128);
        make_map(e, &maps.m[MP_WUK], d_in[3], 64, 512, 64, 1, 8192, 128, 8192, 64, 64, 1, 1, S128);
        make_map(e, &maps.m[MP_CKV], d_in[1], 64, 8, 8, 4096, 1024, 128, 8192, 64, 8, 4, 2, S128);
        make_map(e, &maps.m[MP_MODB], d_in[11], 3072, 512, 1, 1, 6144, 6144, 6144, 64, 128, 1, 1, S128);
        make_map(e, &maps.m[MP_WUV], d_in[4], 64, 512, 64, 1, 8192, 128, 8192, 64, 32, 2, 1, S128);
        make_map(e, &maps.m[MP_WO], d_in[5], 512, 4096, 1, 1, 1024, 1024, 1024, 64, 64, 1, 1, S128);
        make_map(e, &maps.m[MP_GATE], d_in[7], 1792, 512, 1, 1, 3584, 3584, 3584, 64, 128, 1, 1, S128);
        make_map(e, &maps.m[MP_UP], d_in[8], 1792, 512, 1, 1, 3584, 3584, 3584, 64, 128, 1, 1, S128);
        make_map(e, &maps.m[MP_DOWN], d_in[9], 64, 1792, 8, 1, 1024, 128, 1024, 64, 32, 4, 1, S128);
        for (int r = 0; r < 3; r++) {
            int ids[56], cnt[128] = {}, tn = tune.t_off - (W0 - 1) * tune.tau;
            uint2* sc = maps.sched[r];
            auto dig = [](char ch) { return ch >= 'a' ? ch - 'a' + 10 : ch >= 'A' ? ch - 'A' + 36 : ch - '0'; };
            for (int i = 0; i < 56; i++) sc[i] = make_uint2(0u, 0u);
            for (int i = 0;; i++) {
                int id = i, buf, dep, w, wl;
                if (i < IT_WUV) {
                    const int u = (i - IT_CKV) >> 2;
                    buf = i < IT_CKV ? 4 + ((i - 1) >> 2) : u % 6;
                    dep = i < IT_CKV || u < 4 ? -1 : u < 6 ? EB_WQ + u - 4 : EB_UNIT0 + u - 6;
                    w = dig(tune.win[i]); wl = dig(tune.late[i]);
                    if (i) tn += tune.tau;
                } else {
                    const char ch = tune.tail[r][0][i - IT_WUV];
                    if (!ch) break;
                    buf = ch == 'V' ? B_WUV : ch == 'O' ? B_WO : ch == 'D' ? B_DN : ch == 'u' ? B_X + 1 : B_X;
                    id = (ch == 'V' ? IT_WUV : ch == 'O' ? IT_WO : ch == 'D' ? IT_DOWN : ch == 'u' ? IT_X + 2 : IT_X) + cnt[(int)ch]++;
                    dep = EB_UNIT0 + (buf < 2 ? buf + 6 : buf);
                    w = dig(tune.tail[r][1][i - IT_WUV]); wl = dig(tune.tail[r][2][i - IT_WUV]);
                    tn += 32 * dig(tune.tail[r][3][i - IT_WUV]);
                }
                if (id < IT_X ? (id - 1) & 3 : (id - IT_X) & 1) dep = -1;
                ids[i] = id;
                auto back = [&](int d) { return i < d ? 0 : (ids[i - d] && ids[i - d] <= NCP ? 1 : ids[i - d]) + 1; };
                sc[i].x = id | (buf * 4 + (id < IT_X ? (id - 1) & 3 : ((id - IT_X) & 1) * 2)) << 6 | (dep + 1) << 11 | (w > 32 ? NEVER + 1 : back(w)) << 18 | (wl ? back(wl) : 0) << 25;
                const int mp = id < IT_CKV ? MP_WQ + ((id - 1) >> 2) : id < IT_WUV ? MP_CKV : id < IT_WO ? MP_WUV : id < IT_X ? MP_WO
                             : id >= IT_DOWN ? MP_DOWN : r ? MP_MODB : MP_GATE + ((id - IT_X) >> 1);
                const int step = mp == MP_CKV ? id - IT_CKV : mp == MP_WUV ? (id - IT_WUV) * 2 : mp == MP_DOWN ? id - IT_DOWN : id < IT_X ? (id - 1) & 3 : ((id - IT_X) & 1) * 2;
                sc[i].y = (tn & 0xffff) | (mp & 15) << 16 | step << 20;
            }
        }
        cudaGetSymbolAddress((void**)&scratch, g_scratch);
        scratch = (uint32_t*)(((uintptr_t)scratch + (2u << 20) - 1) & ~(uintptr_t)((2u << 20) - 1));
        cudaFuncSetAttribute(fused_kernel, cudaFuncAttributeMaxDynamicSharedMemorySize, SM_TOTAL);
        for (int i = 0; i < 12; i++) cached[i] = d_in[i];
        ready = true;
    }
    const First f = {{(const uint8_t*)d_in[2], (const uint8_t*)d_in[11]}, {(const __nv_bfloat16*)d_in[0], (const __nv_bfloat16*)d_in[10]}};
    fused_kernel<<<NCTA, NTHREADS, SM_TOTAL>>>(f, (__nv_bfloat16*)d_out, scratch, maps);
}
```

```cpp
#include <cuda_runtime.h>
#include <cuda_bf16.h>
#include <cuda.h>
#include <stdint.h>
#include <limits.h>

namespace {

constexpr int NCTA = 128;
constexpr int NTHREADS = 512;
constexpr int NUNITS = 8;
constexpr int NFF = 56, J_RED = 104, J_END = 120;
constexpr uint32_t SPIN_LIMIT = 1u << 22;

#define PROMO CU_TENSOR_MAP_L2_PROMOTION_L2_64B
#define NEAR_CLK 390
#define E1_EARLY 50
#define STAG 300
#define NUMA 1
#define NPROBE 5
#define NCP 2
#define W0 4
#define RD_ITEM 15
#define JAN_SLEEP 100
#define RD_SLEEP 400
#define HA_DELAY 200
#define H_SLEEP 100
#define QA_DELAY 600
#define QA_SLEEP 200
#define ML_DELAY 300
#define E1_SLEEP 50
#define MB_SLEEP 100
constexpr int B_WUV = 2, B_WO = 3, B_X = 4  , B_DN = 0;

constexpr int SM_U = 0;
constexpr int SM_XA = 6 * 32768;
constexpr int SM_XB = SM_XA + 12288;
constexpr int SM_MX = SM_XB + 16384;
constexpr int SM_FZ = SM_XB + 8192;
constexpr int SM_PB = SM_XB;
constexpr int SM_Y = SM_XB + 12288;
constexpr int SM_RED = SM_XB + 4096;
constexpr int SM_FS = SM_XB + 20480;
constexpr int SM_FV = SM_FS + 1024;
constexpr int SM_QX = SM_XA + 8192;
constexpr int SM_FQ = SM_FV + 512;
constexpr int SM_CLS = SM_FQ + 128;
constexpr int SM_W = SM_FQ + 256;
constexpr int SM_W2 = SM_MX + 2304;
constexpr int SM_SCR = SM_XA + 9216;
constexpr int SM_TR = SM_XB + 19456;
constexpr int SM_BAR = SM_W + 256;
constexpr int SM_TOTAL = SM_BAR + 1024;
static_assert(SM_TOTAL <= 232448, "smem");

enum { IT_MODA = 0, IT_WQ = 1, IT_WUK = 5, IT_CKV = 9, IT_WUV = 41, IT_WO = 45, IT_X = 49  , IT_DOWN = 53, NITEMS = 57,
       NEVER = 63,
       SF0 = 64,
       PF0 = 80,
       EB_UNIT0 = 96, MBB = 103,
       EB_WQ = 104, EB_WUK, QT, QB, JD, WR };

enum { MP_WQ = 0, MP_WUK, MP_CKV, MP_WUV, MP_DOWN, MP_WO, MP_GATE, MP_UP, MP_MODB, NMAPS };
struct First { const uint8_t* w[2]; const __nv_bfloat16* v[2]; };
struct Maps { CUtensorMap m[NMAPS]; uint2 sched[3][58]; };

enum { B_HA = 0,
       B_MB = 6,
       B_RD = 7,
       B_E2 = 8,
       B_QA = 16,
       B_ML = 32,
       B_E5 = 64,
       B_E3 = 80,
       B_PR = 96,
       B_TR = 100 };
constexpr int G_E1 = 1 << 19;
constexpr int G_TR = B_TR * 4096;
__device__ __align__(1024) uint32_t g_scratch[(8 << 20) / 4];

#define TRACE(slot) do {} while (0)
#define TRACE_Q(slot) do {} while (0)
#define TRACE_GT(slot) do {} while (0)

__device__ __forceinline__ uint32_t s2u(const void* p) { return (uint32_t)__cvta_generic_to_shared(p); }
__device__ __forceinline__ void mbar_init(uint32_t b, int c) { asm volatile("mbarrier.init.shared::cta.b64 [%0], %1;" :: "r"(b), "r"(c) : "memory"); }
__device__ __forceinline__ void mbar_expect(uint32_t b, uint32_t bytes) { asm volatile("mbarrier.arrive.expect_tx.shared::cta.b64 _, [%0], %1;" :: "r"(b), "r"(bytes) : "memory"); }
__device__ __forceinline__ void mbar_arrive(uint32_t b) { asm volatile("mbarrier.arrive.shared::cta.b64 _, [%0];" :: "r"(b) : "memory"); }
__device__ __forceinline__ void mbar_wait(uint32_t b, uint32_t ph) {
    asm volatile("{\n.reg .pred p;\nW: mbarrier.try_wait.parity.shared::cta.b64 p, [%0], %1;\n@!p bra W;\n}" :: "r"(b), "r"(ph) : "memory");
}
__device__ __forceinline__ void mbar_waitb(uint32_t b, uint32_t ph) {
    asm volatile("{\n.reg .pred p;\n.reg .u32 n;\nmov.u32 n, 0;\n"
                 "W: mbarrier.try_wait.parity.shared::cta.b64 p, [%0], %1;\n@p bra D;\n"
                 "add.u32 n, n, 1;\nsetp.lt.u32 p, n, 0x100000;\n@p bra W;\ntrap;\nD:\n}" :: "r"(b), "r"(ph) : "memory");
}
__device__ __forceinline__ uint32_t mbar_test(uint32_t b, uint32_t ph) {
    uint32_t ok;
    asm volatile("{\n.reg .pred p;\nmbarrier.test_wait.parity.shared::cta.b64 p, [%1], %2;\nselp.u32 %0, 1, 0, p;\n}" : "=r"(ok) : "r"(b), "r"(ph) : "memory");
    return ok;
}
__device__ __forceinline__ void bar_sync(int id, int n) { asm volatile("bar.sync %0, %1;" :: "r"(id), "r"(n) : "memory"); }
__device__ __forceinline__ void bar_arrive(int id, int n) { asm volatile("bar.arrive %0, %1;" :: "r"(id), "r"(n) : "memory"); }
__device__ __forceinline__ uint32_t peer_addr(uint32_t a, uint32_t rank) { uint32_t r; asm("mapa.shared::cluster.u32 %0, %1, %2;" : "=r"(r) : "r"(a), "r"(rank)); return r; }
__device__ __forceinline__ void st_async2(uint32_t a, float x, float y, uint32_t bar) {
    asm volatile("st.async.weak.shared::cluster.mbarrier::complete_tx::bytes.v2.f32 [%0], {%1, %2}, [%3];" :: "r"(a), "f"(x), "f"(y), "r"(bar) : "memory");
}
__device__ __forceinline__ uint32_t gtime() { uint32_t t; asm volatile("mov.u32 %0, %%globaltimer_lo;" : "=r"(t)); return t; }
__device__ __forceinline__ void fence_gpu() { asm volatile("fence.acq_rel.gpu;" ::: "memory"); }

__device__ __forceinline__ uint32_t enc(uint32_t b) { uint32_t r; asm("max.u32 %0, %1, 1;" : "=r"(r) : "r"(b)); return r; }
__device__ __forceinline__ uint32_t encf(float f) { return enc(__float_as_uint(f)); }
__device__ __forceinline__ void st_x1(uint32_t* p, uint32_t v) { asm volatile("st.relaxed.gpu.global.u32 [%0], %1;" :: "l"(p), "r"(v) : "memory"); }
__device__ __forceinline__ void st_x4(void* p, uint32_t a, uint32_t b, uint32_t c, uint32_t d) {
    asm volatile("st.relaxed.gpu.global.v4.u32 [%0], {%1, %2, %3, %4};" :: "l"(p), "r"(a), "r"(b), "r"(c), "r"(d) : "memory");
}
__device__ __forceinline__ void st2_x1(uint32_t* p, uint32_t v) { st_x1(p, v); st_x1(p + 1024, v); }
__device__ __forceinline__ void st2_x4(uint32_t* p, uint32_t a, uint32_t b, uint32_t c, uint32_t d) { st_x4(p, a, b, c, d); st_x4(p + 1024, a, b, c, d); }
__device__ __forceinline__ int near_off(int b, uint32_t cls) { return b * 4096 + (((__popc(b & 0x2C) ^ cls) & 1) << 10); }
__device__ __forceinline__ void ld_x(uint32_t& v, const void* p) { asm volatile("ld.relaxed.gpu.global.u32 %0, [%1];" : "=r"(v) : "l"(p) : "memory"); }
__device__ __forceinline__ void ld_x(uint4& v, const void* p) {
    asm volatile("ld.relaxed.gpu.global.v4.u32 {%0, %1, %2, %3}, [%4];" : "=r"(v.x), "=r"(v.y), "=r"(v.z), "=r"(v.w) : "l"(p) : "memory");
}
__device__ __forceinline__ void ld_x(uint2& v, const void* p) { asm volatile("ld.relaxed.gpu.global.v2.u32 {%0, %1}, [%2];" : "=r"(v.x), "=r"(v.y) : "l"(p) : "memory"); }
__device__ __forceinline__ uint32_t minw(uint32_t v) { return v; }
__device__ __forceinline__ uint32_t minw(const uint2& v) { return min(v.x, v.y); }
__device__ __forceinline__ uint32_t minw(const uint4& v) { return min(__vimin3_u32(v.x, v.y, v.z), v.w); }
template <int N> __device__ __forceinline__ uint32_t mint(const uint32_t* m) {
    if constexpr (N == 1) return m[0];
    else if constexpr (N == 2) return min(m[0], m[1]);
    else return __vimin3_u32(mint<(N + 2) / 3>(m), mint<(N + 1) / 3>(m + (N + 2) / 3), mint<N / 3>(m + (N + 2) / 3 + (N + 1) / 3));
}

template <int STRIDE, int S4 = 4 * STRIDE, typename T, int N>
__device__ __forceinline__ void poll_start(T (&v)[N], const void* base) {
#pragma unroll
    for (int i = 0; i < N; i++) ld_x(v[i], (const uint8_t*)base + (i & 3) * STRIDE + (i >> 2) * S4);
}
struct Nop { __device__ void operator()() const {} };
template <int STRIDE, int SLEEP, bool STARTED = false, int S4 = 4 * STRIDE, typename T, int N, typename F = Nop>
__device__ __forceinline__ void poll(T (&v)[N], const void* base, F idle = F()) {
    if (!STARTED) { poll_start<STRIDE, S4>(v, base); idle(); }
#pragma unroll 1
    for (uint32_t it = 0;; it++) {
        uint32_t m[N];
#pragma unroll
        for (int i = 0; i < N; i++) m[i] = minw(v[i]);
        if (__all_sync(0xffffffffu, mint<N>(m) != 0)) break;
        if (SLEEP && it > 0) __nanosleep(SLEEP);
#pragma unroll
        for (int i = 0; i < N; i++) if (!m[i]) ld_x(v[i], (const uint8_t*)base + (i & 3) * STRIDE + (i >> 2) * S4);
        idle();
        if (it > SPIN_LIMIT) __trap();
    }
}

__device__ __forceinline__ float bflo(uint32_t w) { return __uint_as_float(w << 16); }
__device__ __forceinline__ float bfhi(uint32_t w) { return __uint_as_float(w & 0xffff0000u); }
__device__ __forceinline__ uint32_t pack2(float lo, float hi) {
    uint32_t r; asm("cvt.rn.bf16x2.f32 %0, %1, %2;" : "=r"(r) : "f"(hi), "f"(lo)); return r;
}
__device__ __forceinline__ float rbf(float x) { return __uint_as_float(pack2(0.f, x)); }
__device__ __forceinline__ float sumlo(const uint32_t (&v)[8]) { return ((bflo(v[0]) + bflo(v[1])) + (bflo(v[2]) + bflo(v[3]))) + ((bflo(v[4]) + bflo(v[5])) + (bflo(v[6]) + bflo(v[7]))); }
__device__ __forceinline__ float sumhi(const uint32_t (&v)[8]) { return ((bfhi(v[0]) + bfhi(v[1])) + (bfhi(v[2]) + bfhi(v[3]))) + ((bfhi(v[4]) + bfhi(v[5])) + (bfhi(v[6]) + bfhi(v[7]))); }
__device__ __forceinline__ float ex2(float x) { float r; asm("ex2.approx.ftz.f32 %0, %1;" : "=f"(r) : "f"(x)); return r; }
__device__ __forceinline__ float shx(float v, int m) { return __shfl_xor_sync(0xffffffffu, v, m); }
__device__ __forceinline__ uint4 lds128(uint32_t a) { uint4 v; asm volatile("ld.shared.v4.u32 {%0, %1, %2, %3}, [%4];" : "=r"(v.x), "=r"(v.y), "=r"(v.z), "=r"(v.w) : "r"(a) : "memory"); return v; }
__device__ __forceinline__ uint32_t lds32(uint32_t a) { uint32_t v; asm volatile("ld.shared.u32 %0, [%1];" : "=r"(v) : "r"(a) : "memory"); return v; }
__device__ __forceinline__ void sts32(uint32_t a, uint32_t v) { asm volatile("st.shared.u32 [%0], %1;" :: "r"(a), "r"(v) : "memory"); }
__device__ __forceinline__ void sts16(uint32_t a, uint32_t v) { asm volatile("st.shared.u16 [%0], %1;" :: "r"(a), "h"((uint16_t)v) : "memory"); }
__device__ __forceinline__ int frag_off(int k) { return (k >> 5) * 64 + ((k >> 1) & 3) * 16 + ((k >> 4) & 1) * 8 + ((k >> 3) & 1) * 4 + (k & 1) * 2; }

template <bool TRANS>
__device__ __forceinline__ uint4 ldsm(uint32_t a) {
    uint4 r;
    if (TRANS) asm volatile("ldmatrix.sync.aligned.m8n8.x4.trans.shared.b16 {%0, %1, %2, %3}, [%4];" : "=r"(r.x), "=r"(r.y), "=r"(r.z), "=r"(r.w) : "r"(a) : "memory");
    else asm volatile("ldmatrix.sync.aligned.m8n8.x4.shared.b16 {%0, %1, %2, %3}, [%4];" : "=r"(r.x), "=r"(r.y), "=r"(r.z), "=r"(r.w) : "r"(a) : "memory");
    return r;
}
__device__ __forceinline__ void mma(float (&c)[4], uint32_t a0, uint32_t a1, uint32_t a2, uint32_t a3, uint32_t b0, uint32_t b1) {
    asm volatile("mma.sync.aligned.m16n8k16.row.col.f32.bf16.bf16.f32 {%0,%1,%2,%3}, {%4,%5,%6,%7}, {%8,%9}, {%0,%1,%2,%3};"
                 : "+f"(c[0]), "+f"(c[1]), "+f"(c[2]), "+f"(c[3]) : "r"(a0), "r"(a1), "r"(a2), "r"(a3), "r"(b0), "r"(b1));
}
template <bool TRANS, typename F>
__device__ __forceinline__ void load8(uint4 (&a)[8], F addr) {
    __syncwarp();
#pragma unroll
    for (int s = 0; s < 8; s++) a[s] = ldsm<TRANS>(addr(s));
}
__device__ __forceinline__ void mma8(float (&c)[4], const uint4 (&a)[8], const uint4 (&b)[4]) {
    float e[4][4];
#pragma unroll
    for (int s = 0; s < 8; s++) {
        if (s < 4) e[s][0] = e[s][1] = e[s][2] = e[s][3] = 0.f;
        mma(e[s & 3], a[s].x, a[s].y, a[s].z, a[s].w, (s & 1) ? b[s >> 1].z : b[s >> 1].x, (s & 1) ? b[s >> 1].w : b[s >> 1].y);
    }
#pragma unroll
    for (int i = 0; i < 4; i++) c[i] = (e[0][i] + e[1][i]) + (e[2][i] + e[3][i]);
}
__device__ __forceinline__ void ldfrag(uint4 (&b)[4], uint32_t a) {
    asm volatile("ld.shared.v4.u32 {%0,%1,%2,%3}, [%16];\nld.shared.v4.u32 {%4,%5,%6,%7}, [%16+64];\n"
                 "ld.shared.v4.u32 {%8,%9,%10,%11}, [%16+128];\nld.shared.v4.u32 {%12,%13,%14,%15}, [%16+192];\n"
                 : "=r"(b[0].x), "=r"(b[0].y), "=r"(b[0].z), "=r"(b[0].w), "=r"(b[1].x), "=r"(b[1].y), "=r"(b[1].z), "=r"(b[1].w),
                   "=r"(b[2].x), "=r"(b[2].y), "=r"(b[2].z), "=r"(b[2].w), "=r"(b[3].x), "=r"(b[3].y), "=r"(b[3].z), "=r"(b[3].w) : "r"(a) : "memory");
}
__device__ __forceinline__ void quad_pair(float x, float y, int t, float& lo, float& hi) {
    const float k = ((t & 1) ? y : x) + shx((t & 1) ? x : y, 1);
    lo = k + shx(k, 2); hi = shx(k, 4) + shx(k, 6);
}
__device__ __forceinline__ void pin(uint32_t& x) { asm volatile("" : "+r"(x)); }
template <typename T> __device__ __forceinline__ void pin(T*& x) { asm volatile("" : "+l"(x)); }
__device__ __forceinline__ float4 ldsf4(uint32_t a) { const uint4 v = lds128(a); return make_float4(__uint_as_float(v.x), __uint_as_float(v.y), __uint_as_float(v.z), __uint_as_float(v.w)); }
__device__ __forceinline__ float sum4(const float4& f) { return (f.x + f.y) + (f.z + f.w); }
__device__ __forceinline__ void stsf(uint32_t a, float v) { sts32(a, __float_as_uint(v)); }

__device__ __forceinline__ void wg_fence() { asm volatile("wgmma.fence.sync.aligned;" ::: "memory"); }
__device__ __forceinline__ void wg_commit() { asm volatile("wgmma.commit_group.sync.aligned;" ::: "memory"); }
__device__ __forceinline__ void wg_wait1() { asm volatile("wgmma.wait_group.sync.aligned 1;" ::: "memory"); }
__device__ __forceinline__ void wg_wait0() { asm volatile("wgmma.wait_group.sync.aligned 0;" ::: "memory"); }
#define R8(o) "+f"(d[o]), "+f"(d[o + 1]), "+f"(d[o + 2]), "+f"(d[o + 3]), "+f"(d[o + 4]), "+f"(d[o + 5]), "+f"(d[o + 6]), "+f"(d[o + 7])
__device__ __forceinline__ void wgmma_rs_n32(float (&d)[16], const uint4& a, uint64_t db, int acc) {
    asm volatile("{\n.reg .pred p;\nsetp.ne.b32 p, %21, 0;\n"
        "wgmma.mma_async.sync.aligned.m64n32k16.f32.bf16.bf16 "
        "{%0,%1,%2,%3,%4,%5,%6,%7,%8,%9,%10,%11,%12,%13,%14,%15}, {%16,%17,%18,%19}, %20, p, 1, 1, 0;\n}"
        : R8(0), R8(8) : "r"(a.x), "r"(a.y), "r"(a.z), "r"(a.w), "l"(db), "r"(acc));
}
#define PV_LO "{%0,%1,%2,%3,%4,%5,%6,%7,%8,%9,%10,%11,%12,%13,%14,%15,%16,%17,%18,%19,%20,%21,%22,%23,%24,%25,%26,%27,%28,%29,%30,%31,%32,%33,%34,%35,%36,%37,%38,%39,%40,%41,%42,%43,%44,%45,%46,%47,%48,%49,%50,%51,%52,%53,%54,%55,%56,%57,%58,%59,%60,%61,%62,%63}, "
#define PV_HI "{%64,%65,%66,%67,%68,%69,%70,%71,%72,%73,%74,%75,%76,%77,%78,%79,%80,%81,%82,%83,%84,%85,%86,%87,%88,%89,%90,%91,%92,%93,%94,%95,%96,%97,%98,%99,%100,%101,%102,%103,%104,%105,%106,%107,%108,%109,%110,%111,%112,%113,%114,%115,%116,%117,%118,%119,%120,%121,%122,%123,%124,%125,%126,%127}, "
__device__ __forceinline__ void wgmma_pv(float (&d)[128], const uint4& a, uint32_t blo, int acc) {
    asm volatile("{\n.reg .pred p;\n.reg .b32 u0, u1, u2, u3, t;\n.reg .b64 d0, d1, d2, d3;\nsetp.ne.b32 p, %133, 0;\n"
        "mov.b64 d0, {%132, 0x40000100};\nadd.u32 t, %132, 512;\nmov.b64 d1, {t, 0x40000100};\n"
        "add.u32 t, %132, 128;\nmov.b64 d2, {t, 0x40000100};\nadd.u32 t, %132, 640;\nmov.b64 d3, {t, 0x40000100};\n"
        "wgmma.fence.sync.aligned;\n"
        "wgmma.mma_async.sync.aligned.m64n128k16.f32.bf16.bf16 " PV_LO "{%128, u0, %129, u1}, d0, p, 1, 1, 1;\n"
        "wgmma.mma_async.sync.aligned.m64n128k16.f32.bf16.bf16 " PV_LO "{%130, u2, %131, u3}, d1, 1, 1, 1, 1;\n"
        "wgmma.commit_group.sync.aligned;\n"
        "wgmma.mma_async.sync.aligned.m64n128k16.f32.bf16.bf16 " PV_HI "{%128, u0, %129, u1}, d2, p, 1, 1, 1;\n"
        "wgmma.mma_async.sync.aligned.m64n128k16.f32.bf16.bf16 " PV_HI "{%130, u2, %131, u3}, d3, 1, 1, 1, 1;\n"
        "wgmma.commit_group.sync.aligned;\n}"
        : R8(0), R8(8), R8(16), R8(24), R8(32), R8(40), R8(48), R8(56), R8(64), R8(72), R8(80), R8(88), R8(96), R8(104), R8(112), R8(120)
        : "r"(a.x), "r"(a.y), "r"(a.z), "r"(a.w), "r"(blo), "r"(acc) : "memory");
}

template <int NW>
__device__ __forceinline__ void ln_stats(float s, float q, float sh, float* scr, int w, int lane, int bar, float& mean_b, float& sd_b) {
#pragma unroll
    for (int o = 16; o; o >>= 1) { s += shx(s, o); q += shx(q, o); }
    constexpr float n = 512.f / NW;
    if (lane == 0) { scr[w] = sh + s * (1.f / n); scr[NW + w] = q - s * s * (1.f / n); }
    bar_sync(bar, NW * 32);
    float mu = 0.f, m2 = 0.f;
#pragma unroll
    for (int i = 0; i < NW; i++) { mu += scr[i]; m2 += scr[NW + i]; }
    mu *= 1.f / NW;
#pragma unroll
    for (int i = 0; i < NW; i++) { const float d = scr[i] - mu; m2 = fmaf(n * d, d, m2); }
    mean_b = rbf(mu);
    sd_b = rbf(sqrtf(rbf(rbf(fmaxf(m2, 0.f) * (1.f / 512.f)) + 1e-5f)));
}
__device__ __forceinline__ float ln_mod(float x, float mean_b, float sd_b, float c, float s) {
    return rbf(rbf(__fdividef(rbf(x - mean_b), sd_b)) * rbf(1.f + c)) + s;
}

__global__ void __cluster_dims__(2, 1, 1) __launch_bounds__(NTHREADS, 1)
fused_kernel(const __grid_constant__ First F, __nv_bfloat16* __restrict__ out, uint32_t* __restrict__ gs, const __grid_constant__ Maps M) {
    extern __shared__ __align__(1024) uint8_t sm[];
    const uint32_t sb = s2u(sm);
    const int tid = threadIdx.x, lane = tid & 31;
    const int j = blockIdx.x, rk = j & 1;
    const int g = lane >> 2, t = lane & 3;
    const int r8 = lane & 7, lb3 = (lane >> 3) & 1, lb4 = lane >> 4;
    uint64_t pol;
    asm("createpolicy.fractional.L2::evict_first.b64 %0, 1.0;" : "=l"(pol));
    {
        auto cpa = [&](uint32_t d, const uint8_t* s) {
            asm volatile("cp.async.cg.shared.global.L2::cache_hint.L2::128B [%0], [%1], 16, %2;" :: "r"(d), "l"(s), "l"(pol) : "memory");
        };
        const uint32_t ut = threadIdx.x, uj = blockIdx.x;
        const uint8_t* w = F.w[ut >= 128];
        if (ut < 128) {
            const uint32_t dq = (sb + ut * 16) ^ ((ut * 2) & 0x70);
            const uint8_t* sq = w + (uint32_t)(((uj & 1) * 256 + (ut >> 3)) * 8192 + (uj >> 1) * 128 + (ut & 7) * 16);
#pragma unroll
            for (int i = 0; i < 4 * NCP; i++) cpa(dq + 4 * 32768 + i * 2048, sq + i * 131072);
        } else if (ut < 384) {
            const uint32_t dm = (sb + ut * 16) ^ ((ut * 2) & 0x10);
            const uint8_t* sa = w + (uint32_t)(((uj >> 5) * 128 + (ut >> 1) - 64) * 6144 + (uj & 31) * 32 + (ut & 1) * 16);
            cpa(dm + SM_XA - 2048, sa); cpa(dm + SM_XA + 2048, sa + 1024);
        }
        else if (ut == 480 && uj < 64) asm volatile("prefetch.global.L2 [%0];" :: "l"(F.v[(uj >> 3) & 1] + (uj & 7) * 64));
    }
    const int warp = __shfl_sync(0xffffffffu, tid >> 5, 0);
    const __nv_bfloat16* const xin = F.v[0];
    uint32_t* const pl = gs + (warp < 2 ? (B_PR + (j >> 5)) * 4096 + (j & 31) * 32 : G_E1 + j * 8192) + (warp & 1) * 1024 + lane;
    if (warp < 4) st_x1(pl, 1u);
    auto BAR = [&](int i) -> uint32_t { return sb + SM_BAR + i * 8; };
    const uint32_t a16 = (r8 + 8 * lb4) * 32 + ((lb3 ^ (r8 >> 2)) * 16);
    const uint32_t a128 = (r8 + 8 * lb4) * 128 + ((((warp & 3) * 2 + lb3) ^ r8) * 16);
    auto ldcls = [&]() -> uint32_t { return *(const volatile uint32_t*)(sm + SM_CLS); };
    auto clear_head = [&]() {
        st2_x1(gs + (B_HA + ((j >> 4) & 1) * 2 + lb4) * 4096 + (j >> 5) * 256 + (j & 15) * 16 + (lane & 15), 0u);
        st2_x4(gs + (B_QA + rk * 8 + ((j >> 1) & 1) * 4 + (j >> 5)) * 4096 + g * 128 + ((j >> 2) & 7) * 16 + t * 4, 0u, 0u, 0u, 0u);
        if (lane < 8) st2_x1(gs + B_RD * 4096 + j * 8 + lane, 0u);
    };
    auto tma = [&](uint32_t dst, const CUtensorMap* mp, uint32_t bar, int c0, int c1, int c2, int c3) {
        asm volatile("{\n.reg .pred p;\nelect.sync _|p, 0xffffffff;\n"
                     "@p cp.async.bulk.tensor.4d.shared::cluster.global.mbarrier::complete_tx::bytes.L2::cache_hint [%0], [%1, {%3, %4, %5, %6}], [%2], %7;\n}"
                     :: "r"(dst), "l"(mp), "r"(bar), "r"(c0), "r"(c1), "r"(c2), "r"(c3), "l"(pol) : "memory");
    };
    if (warp <= 12 || warp == 15) {
        const int grp = warp == 12 ? 0 : warp == 15 ? 13 : warp + 1;
        const uint32_t cnt = grp < 10 ? 1 : grp < 13 ? 4 : 8;
        if (lane == 0) {
#pragma unroll
            for (int i = 0; i < 8; i++) mbar_init(BAR(grp * 8 + i), (i < 2 && grp == 0) ? (i ? 128 : 256) : cnt);
        }
        __syncwarp();
        if (grp < 10 && lane < 8 && (grp || lane > NCP)) mbar_expect(BAR(grp * 8 + lane), grp >= 8 ? 4096 : (uint32_t)(grp * 8 + lane - IT_X) < 4 ? 16384 : 8192);
        asm volatile("fence.mbarrier_init.release.cluster;" ::: "memory");
        __syncwarp();
        if (warp == 12) {
#pragma unroll
            for (int i = NCP + 1; i < W0; i++) tma(sb + (15 + i) * 8192, &M.m[MP_WQ], BAR(i), 0, rk * 256 + (i - 1) * 64, j >> 1, 0);
        }
    } else if (warp == 13) {
        if (lane < NMAPS) asm volatile("prefetch.tensormap [%0];" :: "l"(&M.m[lane]) : "memory");
    } else if (warp == 14) {
        clear_head();
    }
    __syncthreads();
    uint32_t in1 = 0, in2 = 0;
    if (warp < 4) { in1 = *(const uint32_t*)(xin + 2 * tid); in2 = *(const uint32_t*)(xin + 256 + 2 * tid); }
    else if (warp < 12) in1 = *(const uint32_t*)(F.v[1] + 2 * (tid - 128));
    if (warp < 12) asm volatile("cp.async.mbarrier.arrive.noinc.shared::cta.b64 [%0];" :: "r"(BAR(warp < 4)) : "memory");
    asm volatile("barrier.cluster.arrive.relaxed.aligned;" ::: "memory");

    if (warp >= 12) {
    asm volatile("setmaxnreg.dec.sync.aligned.u32 64;");
    if (warp == 12) {
        static_assert(W0 > NCP && W0 <= 5 && NCP >= 1 && NCP <= 4, "W0");
        const uint2* sched = M.sched[j < NFF ? 0 : j < J_RED ? 1 : 2];
        uint2 en = sched[W0];
        const uint32_t t0 = gtime();
        const uint32_t sp = __reduce_or_sync(0xffffffffu, sb);
        const int cx = (j >> 1) * 64 + (j < NFF ? 0 : 1024 - NFF * 32);
#pragma unroll 1
        for (int i = W0; en.x; i++) {
            uint32_t e = en.x, st = (en.y >> 20) * 64;
            const uint32_t tn = t0 + (int16_t)en.y, mp = (en.y >> 16) & 15;
            if (mp == MP_WUV || mp == MP_WUK) { st ^= (j >> 5) * (mp == MP_WUV ? 128 : 64); e ^= (j >> 5) << 6; }
            if (mp == MP_GATE || mp == MP_UP) st ^= (j & 16) * 8;
            if (mp == MP_DOWN) { st ^= (j & 3) * 64; e ^= (j & 3) << 6; }
            en = sched[i + 1];
            if (mp == MP_MODB && j >= J_END) break;
            uint32_t c0 = mp == MP_WO ? (j & 7) * 64 : mp > MP_WO ? cx : 0;
            uint32_t c1 = mp == MP_CKV ? 0 : mp == MP_DOWN ? j * 32 : st + (mp == MP_WUV ? (j & 3) * 32 : mp == MP_WO ? (j >> 3) * 256 : rk * 256);
            uint32_t c2 = mp < MP_CKV ? j >> 1 : mp == MP_CKV ? rk * 4 : mp == MP_WUV ? (j >> 2) * 2 : mp == MP_DOWN ? st >> 5 : 0;
            uint32_t c3 = mp == MP_CKV ? st * 2 + (j & ~1) : 0;
            uint32_t dst = sp + ((e << 7) & 0x3e000), bar = sp + SM_BAR + (e & 63) * 8;
            const uint32_t w0 = (e >> 8) & 0x3f8, w1 = (e >> 15) & 0x3f8, w2 = (e >> 22) & 0x3f8, bb = sp + SM_BAR - 8;
            const CUtensorMap* pm = &M.m[mp];
            pin(dst); pin(bar); pin(c0); pin(c1); pin(c2); pin(c3); pin(pm);
            if (w0) mbar_wait(bb + w0, 0);
            if (w2) {
                mbar_wait(bb + w2, 0);
                while (!__any_sync(0xffffffffu, mbar_test(bb + w1, 0) | ((int)(gtime() - tn) > 0))) {}
            } else if (w1) mbar_wait(bb + w1, 0);
            tma(dst, pm, bar, c0, c1, c2, c3);
        }
    } else if (warp == 13) {
#pragma unroll
        for (int i = 0; i < 2; i++) st_x4(gs + (B_ML + rk * 16 + i * 8 + g) * 4096 + (t >> 1) * 1024 + (j >> 1) * 8 + (t & 1) * 4, 0u, 0u, 0u, 0u);
        if (lane < 16) st2_x4(gs + (B_E2 + (j >> 4)) * 4096 + (j & 15) * 64 + lane * 4, 0u, 0u, 0u, 0u);
        st2_x1(gs + (B_E3 + (j >> 5)) * 4096 + (j & 31) * 32 + lane, 0u);
        if (lane < 8) st2_x1(gs + B_MB * 4096 + j * 8 + lane, 0u);
        if (j < NFF) {
#pragma unroll
            for (int i = 0; i < 2; i++) st2_x4(gs + (B_E5 + i * 8 + g) * 4096 + j * 16 + t * 4, 0u, 0u, 0u, 0u);
        }
        bar_sync(9, 64);
        const uint32_t cs = ldcls();
#pragma unroll 1
        for (int i = 0; i < 32; i++) {
            st_x4(gs + G_E1 + j * 8192 + (i >> 3) * 2048 + ((((cs >> 1) ^ (i >> 3)) & 1) << 10) + (i & 7) * 128 + lane * 4, 0u, 0u, 0u, 0u);
            __nanosleep(JAN_SLEEP);
        }
        fence_gpu();
        if (lane < 8) st2_x1(gs + B_RD * 4096 + j * 8 + lane, 1u + (cs >> 1));
        if (lane == 0) TRACE(41);
        uint32_t rd[4];
        mbar_wait(BAR(IT_CKV + RD_ITEM), 0);
        poll<1024, RD_SLEEP>(rd, gs + near_off(B_RD, cs) + lane * 8);
#pragma unroll
        for (int i = 0; i < 4; i++) {
            const uint32_t m = __ballot_sync(0xffffffffu, rd[i] == 2u);
            if (lane == 0) sts32(sb + SM_CLS + 16 + i * 4, m);
        }
        __syncwarp();
        if (lane < 8) mbar_arrive(BAR(JD));
        if (lane == 0) TRACE(42);
    } else if (warp == 14) {
        uint2 ml[2];
        mbar_waitb(BAR(JD), 0);
        const uint32_t cls = ldcls();
        mbar_waitb(BAR(PF0 + 2 * NUNITS - 1), 0);
        __nanosleep(ML_DELAY);
        const uint32_t* pl2 = gs + near_off(B_ML + (j >> 2), cls) + lane * 8;
        const uint32_t wa = sb + SM_W + lb4 * 64 + t * 16 + (g & 3) * 4;
        poll_start<1024>(ml, pl2);
        uint32_t w0 = 0, w1 = 0, redo = 0;
        bool first = true;
#pragma unroll 1
        for (uint32_t it = 0;; it++) {
            const bool p0 = minw(ml[0]) != 0, p1 = minw(ml[1]) != 0;
            const int n = __popc(__ballot_sync(0xffffffffu, p0)) + __popc(__ballot_sync(0xffffffffu, p1));
            const uint32_t x0 = ml[0].x, x1 = ml[1].x;
            if (n < 64) {
                if (!p0) ld_x(ml[0], pl2);
                if (!p1) ld_x(ml[1], pl2 + 256);
            }
            if (n == 64 || (first && n >= E1_EARLY)) {
                auto ord = [](int x) { return x ^ ((x >> 31) & 0x7fffffff); };
                const int o0 = ord(x0), o1 = ord(x1);
                const float mm = __int_as_float(ord(__reduce_max_sync(0xffffffffu, max(p0 ? o0 : INT_MIN, p1 ? o1 : INT_MIN))));
                const float lo = __int_as_float(ord(__reduce_min_sync(0xffffffffu, min(p0 ? o0 : INT_MAX, p1 ? o1 : INT_MAX))));
                const uint32_t v0 = pack2(ex2((p0 ? __uint_as_float(x0) : lo) - mm), 0.f), v1 = pack2(ex2((p1 ? __uint_as_float(x1) : lo) - mm), 0.f);
                redo = !first && __any_sync(0xffffffffu, v0 != w0 || v1 != w1);
                w0 = v0; w1 = v1;
                sts32(wa - redo * (SM_W - SM_W2), w0 * 0x10001u); sts32(wa - redo * (SM_W - SM_W2) + 128, w1 * 0x10001u);
                if (first) bar_arrive(3, 416);
                first = false;
                if (n == 64) break;
            }
            if (it > SPIN_LIMIT) __trap();
        }
        if (lane == 0) TRACE_Q(37);
        float L = bflo(w0) * __uint_as_float(ml[0].y) + bflo(w1) * __uint_as_float(ml[1].y);
#pragma unroll
        for (int o = 16; o; o >>= 1) L += shx(L, o);
        if (lane == 0) *(float2*)(sm + SM_FQ) = make_float2(__frcp_rn(L), __uint_as_float(redo));
        __syncwarp();
        if (lane < 8) mbar_arrive(BAR(WR));
        if (lane == 0) TRACE(10);
        bar_sync(4, 416);
        clear_head();
        if (j < NFF) {
            uint32_t ya = sb + SM_Y + lane * 16, sa = peer_addr(sb + SM_RED + 2048 + rk * 8, lane & 1), tb = peer_addr(BAR(MBB), lane & 1);
            pin(ya); pin(sa); pin(tb);
            bar_sync(7, 288);
            const float4 y0 = ldsf4(ya), y1 = ldsf4(ya + 512);
            float s = sum4(y0) + sum4(y1);
            float q = (fmaf(y0.x, y0.x, y0.y * y0.y) + fmaf(y0.z, y0.z, y0.w * y0.w)) + (fmaf(y1.x, y1.x, y1.y * y1.y) + fmaf(y1.z, y1.z, y1.w * y1.w));
#pragma unroll
            for (int o = 16; o; o >>= 1) { s += shx(s, o); q += shx(q, o); }
            if (lane < 2) st_async2(sa, s, q, tb);
        }
    } else if (warp == 15) {
        mbar_waitb(BAR(IT_X - 1), 0);
        if (j < J_END) mbar_waitb(BAR(j < NFF ? NITEMS - 1 : MBB), 0);
    }
    } else if (warp < 4) {
        float* scr = (float*)(sm + SM_SCR);
        uint32_t cls;
        {
            uint2 ha[8];
            uint32_t best = 0xffffffffu;
            sts32(sb + SM_SCR + 64 + warp * 4, best);
            const float sh = __shfl_sync(0xffffffffu, bflo(in1), 0);
            const float v0 = bflo(in1) - sh, v1 = bfhi(in1) - sh, v2 = bflo(in2) - sh, v3 = bfhi(in2) - sh;
            float mb, sd;
            ln_stats<4>((v0 + v1) + (v2 + v3), (v0 * v0 + v1 * v1) + (v2 * v2 + v3 * v3), sh, scr, warp, lane, 2, mb, sd);
            if (!rk) in2 = in1;
#pragma unroll 1
            for (int i = 0; i < NPROBE; i++) {
                uint32_t t0, t1, o;
                asm volatile("mov.u32 %0, %%clock;" : "=r"(t0));
                asm volatile("atom.relaxed.gpu.global.exch.b32 %0, [%1], %2;" : "=r"(o) : "l"(pl), "r"(2u + i) : "memory");
                asm volatile("{\n.reg .pred p;\nsetp.ne.u32 p, %1, 0x1234567;\nmov.u32 %0, 0;\n@p mov.u32 %0, %%clock;\n}" : "=r"(t1) : "r"(o));
                best = min(best, t1 - t0);
                sts32(sb + SM_SCR + 64 + warp * 4, best);
                if (__all_sync(0xffffffffu, min(best, lds32(sb + SM_SCR + 64 + (warp ^ 1) * 4)) < NEAR_CLK)) break;
            }
            bar_sync(2, 128);
            const uint4 lt = *(const uint4*)(scr + 16);
            cls = NUMA ? ((lt.y < lt.x) ^ (__popc((B_PR + (j >> 5)) & 0x2C) & 1)) | (lt.w < lt.z) << 1 : 0;
            if (warp == 0) { if (lane == 0) sts32(sb + SM_CLS, cls); bar_arrive(9, 64); }
            if (tid == 0) TRACE(38);
            asm volatile("barrier.cluster.wait.aligned;" ::: "memory");
            mbar_wait(BAR(IT_MODA), 0);
            if (HA_DELAY) __nanosleep(HA_DELAY);
            poll<1024, H_SLEEP, false, 16384>(ha, gs + near_off(B_HA + rk * 2, cls) + 2 * tid);
            auto rsum = [](uint32_t a, uint32_t b, uint32_t c, uint32_t d) { return rbf((__uint_as_float(a) + __uint_as_float(b)) + (__uint_as_float(c) + __uint_as_float(d))); };
            sts32(sb + SM_FV + frag_off(2 * tid),
                  pack2(ln_mod(bflo(in2), mb, sd, rsum(ha[4].x, ha[5].x, ha[6].x, ha[7].x), rsum(ha[0].x, ha[1].x, ha[2].x, ha[3].x)),
                        ln_mod(bfhi(in2), mb, sd, rsum(ha[4].y, ha[5].y, ha[6].y, ha[7].y), rsum(ha[0].y, ha[1].y, ha[2].y, ha[3].y))));
            bar_arrive(5, 384);
            mbar_wait(BAR(QB), 0);
            if (tid < 64) {
                const float* qx = (const float*)(sm + SM_QX) + tid;
                sts16(sb + SM_FQ + frag_off(tid), pack2((qx[0] + qx[64]) + (qx[128] + qx[192]), 0.f));
            }
            bar_arrive(6, 384);
        }
        asm volatile("setmaxnreg.inc.sync.aligned.u32 192;");
        float acc[128];
        float M = 0.f;
        uint32_t pa = sb + SM_XA + warp * 512 + lane * 16, ma = sb + SM_MX + (warp * 8 + g) * 4, pf = BAR(PF0);
        uint32_t blo = __reduce_or_sync(0xffffffffu, (((sb + SM_U) & 0x3FFFFu) >> 4) | 0x400000u);
        uint32_t* e1[4];
#pragma unroll
        for (int i = 0; i < 4; i++) e1[i] = gs + G_E1 + (warp * 8 + g) * 4 * 8192 + (rk * 2 + (j >> 6)) * 2048 + ((j >> 1) & 31) * 32 + t * 4;
#pragma unroll 1
        for (int h = 0; h < 2 * NUNITS; h++) {
            mbar_wait(pf, 0);
            const float m = __uint_as_float(lds32(ma));
            const uint4 pn = lds128(pa);
            wg_wait0();
#pragma unroll
            for (int i = 0; i < 128; i++) asm volatile("" : "+f"(acc[i]) :: "memory");
            if (h == 0) M = m;
            uint32_t b2 = 0x3f803f80u;
            if (__builtin_expect(__any_sync(0xffffffffu, m != M), 0)) {
                const float Mn = fmaxf(M, m), alpha = ex2(M - Mn), beta = ex2(m - Mn);
                M = Mn;
                b2 = pack2(beta, beta);
#pragma unroll
                for (int jj = 0; jj < 32; jj++) { acc[4 * jj] *= alpha; acc[4 * jj + 1] *= alpha; }
            }
            auto mul2 = [](uint32_t x, uint32_t y) { uint32_t r; asm("mul.rn.bf16x2 %0, %1, %2;" : "=r"(r) : "r"(x), "r"(y)); return r; };
            const uint4 p = make_uint4(mul2(pn.x, b2), mul2(pn.y, b2), mul2(pn.z, b2), mul2(pn.w, b2));
            if (tid == 0 && (h & 1)) TRACE_Q(48 + (h >> 1));
            wgmma_pv(acc, p, blo, h);
            if (lane == 0 && h > 0 && !(h & 1)) mbar_arrive(BAR(EB_UNIT0 + (h >> 1) - 1));
            blo += h == 11 ? -11 * 1024 : 1024;
            pa += (h == 5 || h == 11) ? -5 * 2048 : 2048;
            ma += 128; pf += 8;
            if (h == 2 * NUNITS - 3) {
                mbar_wait(BAR(JD), 0);
                const uint32_t hm = (*(const uint32_t*)(sm + SM_CLS + 16 + warp * 4) >> (g * 4)) ^ ((j >> 6) ? 15u : 0u);
#pragma unroll
                for (int i = 0; i < 4; i++) e1[i] += ((hm >> i) & 1) << 10;
            }
        }
#pragma unroll
        for (int vv = 0; vv < 2; vv++) {
            if (vv && M == 1.f) __trap();
            if (vv) wg_wait0(); else wg_wait1();
#pragma unroll
            for (int i = 0; i < 64; i++) asm volatile("" : "+f"(acc[vv * 64 + i]) :: "memory");
            if (tid == 0 && !vv) TRACE_Q(63);
#pragma unroll
            for (int i = 0; i < 4; i++) {
                const float* a = &acc[vv * 64 + i * 16];
                st_x4(e1[i] + i * 8192 + vv * 16, enc(pack2(a[0], a[1])), enc(pack2(a[4], a[5])), enc(pack2(a[8], a[9])), enc(pack2(a[12], a[13])));
            }
        }
        bar_arrive(3, 416);
        if (tid == 0) TRACE_Q(17);
#pragma unroll 1
        for (int pass = 0;; pass++) {
            if (j >= NFF && j < J_END && pass == (j >= J_RED)) {
                uint4 a[8], b[4];
                float c[4], e[4];
                const bool own = (warp >> 1) == rk;
                const uint32_t xa = sb + SM_FV + (warp & 1) * 64 + g * 8;
                if (lane == 0) mbar_expect(BAR(MBB), own ? 64 : 0);
#pragma unroll
                for (int i = 0; i < 2; i++) {
                    ldfrag(b, sb + SM_FS + rk * 512 + i * 256 + t * 16);
                    mbar_wait(BAR(IT_X + i), 0);
                    const uint32_t ab = sb + SM_U + B_X * 32768 + i * 16384 + a128;
                    load8<true>(a, [&](int s) { return ab + s * 2048; });
                    mma8(i ? e : c, a, b);
                }
                c[0] += e[0]; c[2] += e[2];
                if (!own) {
                    if (t == 0) st_async2(peer_addr(xa, rk ^ 1), c[0], c[2], peer_addr(BAR(MBB), rk ^ 1));
                } else {
                    mbar_wait(BAR(MBB), 0);
                    const float2 pp = *(const float2*)(sm + (xa - sb));
                    const float mine = t ? c[2] + pp.y : c[0] + pp.x, other = shx(mine, 4);
                    const uint32_t w = (warp & 1) * 8 + t * 4 + (g >> 1), val = enc(pack2(mine, other));
                    if (t < 2 && !(g & 1)) {
                        if (j < J_RED) st2_x1(gs + B_MB * 4096 + (j - NFF) * 16 + w, val);
                        else sts32(sb + SM_FV + 256 + w * 4, val);
                    }
                    __syncwarp();
                    if (j >= J_RED && lane < 4) mbar_arrive(BAR(QB));
                    if (lane == 0) TRACE(11);
                }
            }
            if (pass) break;
            uint4 a[8], a2[8];
            const uint32_t ab = sb + SM_U + B_WO * 32768 + a128;
            uint32_t* p3 = gs + (B_E3 + ((j >> 1) & 3)) * 4096 + (t >> 1) * 1024 + (rk * 2 + (warp >> 1)) * 256 + (j >> 3) * 16 + (warp & 1) * 8 + (t & 1) * 4 + (g >> 1);
            const uint32_t* pb = gs + near_off(B_E2 + (j >> 4), cls) + (((j >> 3) & 1) * 2 + lb4) * 256 + (lane & 15) * 2;
            pin(p3); pin(pb);
            uint2 bb[8];
#pragma unroll
            for (int i = 0; i < 8; i++) bb[i] = make_uint2(0u, 0u);
            bool h0 = false, h1 = false;
            auto idle = [&]() {
                if (!h0) {
                    h0 = __all_sync(0xffffffffu, mbar_test(BAR(IT_WO + (t & 1)), 0));
                    if (h0) load8<true>(a, [&](int s) { return ab + s * 2048; });
                }
                if (!h1) {
                    h1 = __all_sync(0xffffffffu, mbar_test(BAR(IT_WO + 2 + (t & 1)), 0));
                    if (h1) load8<true>(a2, [&](int s) { return ab + 16384 + s * 2048; });
                }
            };
            bar_sync(4, 416);
            idle();
            poll<128, 0, true>(bb, pb, idle);
            if (tid == 0) TRACE(21);
            float e[4][4];
#pragma unroll
            for (int s = 0; s < 16; s++) {
                if (s == 0 && !h0) { mbar_wait(BAR(IT_WO), 0); mbar_wait(BAR(IT_WO + 1), 0); load8<true>(a, [&](int q) { return ab + q * 2048; }); }
                if (s == 0 && !h1) { mbar_wait(BAR(IT_WO + 2), 0); mbar_wait(BAR(IT_WO + 3), 0); load8<true>(a2, [&](int q) { return ab + 16384 + q * 2048; }); }
                const int z = (s & 1) | (s & 2) << 2 | (s >> 2) << 1;
                const uint4& x = z < 8 ? a[z] : a2[z & 7];
                float (&d)[4] = e[(z >> 3) * 2 + (z & 1)];
                if (!(z & 6)) d[0] = d[1] = d[2] = d[3] = 0.f;
                mma(d, x.x, x.y, x.z, x.w, bb[z & 7].x, bb[z & 7].y);
            }
            float lo, hi;
            quad_pair((t & 2) ? (e[2][0] + e[3][0]) + (e[2][1] + e[3][1]) : (e[0][0] + e[1][0]) + (e[0][1] + e[1][1]),
                      (t & 2) ? (e[2][2] + e[3][2]) + (e[2][3] + e[3][3]) : (e[0][2] + e[1][2]) + (e[0][3] + e[1][3]), t, lo, hi);
            if (!(g & 1)) st_x1(p3, enc(pack2(lo, hi)));
            if (j < NFF) bar_arrive(8, 384); else if (j >= J_RED && j < J_END) bar_arrive(8, 192);
            if (tid == 0) TRACE(22);
        }
        if (j < NFF) {
            uint4 a[16];
            const uint32_t ad = sb + SM_U + B_DN * 32768 + warp * 8192 + (r8 + 8 * lb4) * 128 + (lb3 ^ r8) * 16;
            uint32_t rl = sb + SM_RED + lane * 16;
            uint32_t* p5 = gs + (B_E5 + warp * 4 + (t >> 1)) * 4096 + j * 16 + (t & 1) * 8 + g;
            pin(rl); pin(p5);
            if (lane == 0) mbar_expect(BAR(MBB), 4);
            auto ldd = [&]() {
#pragma unroll
                for (int s = 0; s < 16; s++) a[s] = ldsm<true>((ad ^ ((s & 3) * 32)) + (s >> 2) * 2048);
            };
            const uint32_t db = BAR(IT_DOWN + (warp ^ (j & 3)));
            mbar_wait(BAR(MBB), 0);
            const float4 st = ldsf4(sb + SM_RED + 2048);
            const bool hd = __all_sync(0xffffffffu, mbar_test(db, 0));
            if (hd) ldd();
            const float mu = (st.x + st.z) * (1.f / 512.f);
            float rstd;
            asm volatile("rsqrt.approx.ftz.f32 %0, %1;" : "=f"(rstd) : "f"(fmaxf(fmaf(-mu, mu, (st.y + st.w) * (1.f / 512.f)), 0.f) + 1e-5f));
            mbar_wait(BAR(QB), 1);
            if (tid == 0) TRACE(25);
            const float4 f0 = ldsf4(rl), f2 = ldsf4(rl + 1024), f1 = ldsf4(rl + 512), f3 = ldsf4(rl + 1536);
            const float gg = fmaf(rstd, fmaf(-mu, f0.z + f2.z, (f0.x + f0.y) + (f2.x + f2.y)), f0.w + f2.w);
            const float uu = fmaf(rstd, fmaf(-mu, f1.z + f3.z, (f1.x + f1.y) + (f3.x + f3.y)), f1.w + f3.w);
            const float hh = __fdividef(gg * uu, 1.f + ex2(-gg * fmaf(gg * gg, 0.10294324f, 2.3022082f)));
            uint32_t hb[4];
#pragma unroll
            for (int i = 0; i < 4; i++) hb[i] = pack2(__shfl_sync(0xffffffffu, hh, 2 * t + 8 * i), __shfl_sync(0xffffffffu, hh, 2 * t + 8 * i + 1));
            if (!hd) { mbar_wait(db, 0); ldd(); }
#pragma unroll
            for (int i = 0; i < 2; i++) {
                uint32_t res = 0;
#pragma unroll
                for (int k = 0; k < 4; k++) {
                    float c[4] = {0.f, 0.f, 0.f, 0.f};
                    const uint4 &x = a[i * 8 + k], &y = a[i * 8 + k + 4];
                    mma(c, x.x, x.y, x.z, x.w, hb[0], hb[1]);
                    mma(c, y.x, y.y, y.z, y.w, hb[2], hb[3]);
                    if (t == k) res = pack2(c[0], c[2]);
                }
                st2_x1(p5 + i * 8192, enc(res));
            }
            if (tid == 0) { TRACE(27); TRACE_GT(47); }
        }
    } else {
        const int u8 = tid - 128, w8 = warp - 4;
        const int v = w8 >> 2, wq4 = w8 & 3;
        {
            const float c0 = bflo(in1), c1 = bfhi(in1);
            sts32(sb + SM_FS + frag_off(2 * u8), pack2(__fdividef(c0, 1.f + __expf(-c0)), __fdividef(c1, 1.f + __expf(-c1))));
        }
        bar_sync(1, 256);
        asm volatile("barrier.cluster.wait.aligned;" ::: "memory");
        uint4 a[8], b[4]; float c[4];
        if (w8 < 2) {
            ldfrag(b, sb + SM_FS + (j >> 5) * 256 + t * 16);
            mbar_wait(BAR(IT_MODA), 0);
            if (u8 == 0) TRACE(12);
            const uint32_t ab = sb + SM_XA + w8 * 4096 + a16;
            load8<true>(a, [&](int s) { return ab + s * 512; });
            mma8(c, a, b);
            if (t < 2) st2_x1(gs + (B_HA + ((j >> 4) & 1) * 2 + w8) * 4096 + (j >> 5) * 256 + (j & 15) * 16 + t * 8 + g, encf(t ? c[2] : c[0]));
        }
        {
            mbar_wait(BAR(IT_WQ + 2 * v <= NCP ? 1 : IT_WQ + 2 * v), 0); mbar_wait(BAR(IT_WQ + 2 * v + 1 <= NCP ? 1 : IT_WQ + 2 * v + 1), 0);
            const uint32_t ab = sb + SM_U + 4 * 32768 + v * 16384 + a128;
            load8<true>(a, [&](int s) { return ab + s * 2048; });
            if (lane == 0) mbar_arrive(BAR(EB_WQ));
            bar_sync(5, 384);
            if (u8 == 0) TRACE(13);
            ldfrag(b, sb + SM_FV + v * 256 + t * 16);
            mma8(c, a, b);
            if (t < 2) {
                const float qv = t ? c[2] : c[0];
                const uint32_t qa_ = sb + SM_QX + ((rk * 2 + v) * 64 + wq4 * 16 + t * 8 + g) * 4;
                asm volatile("st.async.weak.shared::cluster.mbarrier::complete_tx::bytes.f32 [%0], %1, [%2];"
                             :: "r"(peer_addr(qa_, rk ^ 1)), "f"(qv), "r"(peer_addr(BAR(QB), rk ^ 1)) : "memory");
                sts32(qa_, __float_as_uint(qv));
            }
            __syncwarp();
            if (lane == 0) mbar_expect(BAR(QB), 64);
        }
        {
            mbar_wait(BAR(IT_WUK + (v ^ ((j >> 5) & 1))), 0); mbar_wait(BAR(IT_WUK + (v ^ ((j >> 5) & 1)) + 2), 0);
            const uint32_t ab = sb + SM_U + 5 * 32768 + (w8 * 16 + r8 + 8 * lb3) * 128;
            const uint32_t x16 = (lb4 ^ r8) * 16;
            load8<false>(a, [&](int s) { return ab + (s & 1) * 16384 + (x16 ^ ((s >> 1) * 32)); });
            bar_sync(6, 384);
            if (u8 == 0) TRACE(14);
            b[0] = lds128(sb + SM_FQ + t * 16); b[1] = lds128(sb + SM_FQ + 64 + t * 16);
            float e[4] = {0.f, 0.f, 0.f, 0.f};
            c[0] = c[1] = c[2] = c[3] = 0.f;
#pragma unroll
            for (int k = 0; k < 4; k++) {
                const uint32_t b0 = (k & 1) ? b[k >> 1].z : b[k >> 1].x, b1 = (k & 1) ? b[k >> 1].w : b[k >> 1].y;
                mma(c, a[2 * k].x, a[2 * k].y, a[2 * k].z, a[2 * k].w, b0, b1);
                mma(e, a[2 * k + 1].x, a[2 * k + 1].y, a[2 * k + 1].z, a[2 * k + 1].w, b0, b1);
            }
            const float mine = ((t & 1) ? ((t & 2) ? e[2] : e[0]) : ((t & 2) ? c[2] : c[0])) * 0.12751743f;
            const float other = shx(mine, 4);
            if (!(g & 1)) st2_x1(gs + (B_QA + rk * 8 + ((j >> 1) & 1) * 4 + (j >> 5)) * 4096 + w8 * 128 + ((j >> 2) & 7) * 16 + (g >> 1) * 4 + t, enc(pack2(mine, other)));
            if (u8 == 0) TRACE(15);
        }
        const uint32_t cls = ldcls();
        __nanosleep(QA_DELAY);
        {
            uint4 qb[8];
            const uint32_t* pq = gs + near_off(B_QA + rk * 8 + wq4, cls) + lane * 4;
            const uint32_t* pq2 = gs + near_off(B_QA + rk * 8 + 4 + wq4, cls) + lane * 4;
            if (lane == 0) {
                mbar_expect(BAR(QT), 4096);
                asm volatile("cp.async.bulk.shared::cluster.global.mbarrier::complete_tx::bytes [%0], [%1], 4096, [%2];"
                             :: "r"(sb + SM_U + 5 * 32768 + w8 * 4096), "l"(gs + near_off(B_QA + rk * 8 + w8, cls)), "r"(BAR(QT)) : "memory");
            }
            const uint32_t qs = sb + SM_U + 5 * 32768 + wq4 * 4096 + lane * 16;
            mbar_wait(BAR(QT), 0);
#pragma unroll
            for (int i = 0; i < 8; i++) { a[i] = lds128(qs + i * 512); qb[i] = lds128(qs + 16384 + i * 512); }
            poll<512, QA_SLEEP, true>(a, pq);
            poll<512, QA_SLEEP, true>(qb, pq2);
            if (lane == 0) mbar_arrive(BAR(EB_WUK));
            auto add2 = [](uint32_t x, uint32_t y) { uint32_t r; asm("add.rn.bf16x2 %0, %1, %2;" : "=r"(r) : "r"(x), "r"(y)); return r; };
#pragma unroll
            for (int i = 0; i < 8; i++) a[i] = make_uint4(add2(a[i].x, qb[i].x), add2(a[i].y, qb[i].y), add2(a[i].z, qb[i].z), add2(a[i].w, qb[i].w));
        }
        if (u8 == 0) TRACE(8);
        {
            float m = -INFINITY, l = 0.f;
            uint32_t xl = sb + SM_XB + w8 * 2048 + lane * 16, xr = peer_addr(xl, rk ^ 1), bsr = peer_addr(BAR(SF0 + v), rk ^ 1);
            uint32_t pa = sb + SM_XA + v * 2048 + wq4 * 512 + lane * 16, ma = sb + SM_MX + v * 128 + (wq4 * 8 + g) * 4;
            uint32_t fb = BAR(IT_CKV + v * 2), sf = BAR(SF0 + v);
            uint32_t dlo = __reduce_or_sync(0xffffffffu, (((sb + SM_U + v * 16384) & 0x3FFFFu) >> 4) | 0x10000u);
            if (STAG && v) __nanosleep(STAG);
#pragma unroll 1
            for (int n = 0; n < NUNITS; n++) {
                float d[2][16], sc[8];
#pragma unroll
                for (int i = 0; i < 2; i++) {
                    mbar_wait(fb + i * 8, 0);
                    wg_fence();
#pragma unroll
                    for (int s = 0; s < 8; s++) wgmma_rs_n32(d[i], a[s], (0x40000080ull << 32) | (dlo + i * 512 + (s >> 2) * 64 + (s & 3) * 2), s);
                    wg_commit();
                }
#pragma unroll
                for (int i = 0; i < 2; i++) {
                    if (i) wg_wait0(); else wg_wait1();
#pragma unroll
                    for (int k = 0; k < 16; k++) asm volatile("" : "+f"(d[i][k]) :: "memory");
                    sc[4 * i] = d[i][0] + d[i][6]; sc[4 * i + 1] = d[i][1] + d[i][7]; sc[4 * i + 2] = d[i][8] + d[i][14]; sc[4 * i + 3] = d[i][9] + d[i][15];
                    asm volatile("st.async.weak.shared::cluster.mbarrier::complete_tx::bytes.v4.f32 [%0], {%1, %2, %3, %4}, [%5];"
                                 :: "r"(xr + i * 1024), "f"(sc[4 * i]), "f"(sc[4 * i + 1]), "f"(sc[4 * i + 2]), "f"(sc[4 * i + 3]), "r"(bsr) : "memory");
                }
                if (u8 == 128) TRACE_Q(56 + (n < 6 ? n : -40));
                if (n >= 3) mbar_wait(BAR(EB_UNIT0 + n - 3), 0);
                dlo += n == 5 ? -5 * 2048 : 2048;
                fb += 32; xr ^= 512; bsr += 16;
                pin(fb); pin(xr); pin(bsr);
                mbar_wait(sf, 0);
                const float4 x = ldsf4(xl), y = ldsf4(xl + 1024);
                sc[0] += x.x; sc[1] += x.y; sc[2] += x.z; sc[3] += x.w; sc[4] += y.x; sc[5] += y.y; sc[6] += y.z; sc[7] += y.w;
                float pr[8];
#pragma unroll
                for (int i = 0; i < 8; i++) pr[i] = ex2(sc[i] - m);
                float mx = fmaxf(fmaxf(fmaxf(sc[0], sc[1]), fmaxf(sc[2], sc[3])), fmaxf(fmaxf(sc[4], sc[5]), fmaxf(sc[6], sc[7])));
                if (__builtin_expect(__any_sync(0xffffffffu, mx > m), 0)) {
                    mx = fmaxf(mx, shx(mx, 1));
                    mx = fmaxf(mx, shx(mx, 2));
                    const float mn = fmaxf(m, ceilf(mx * 0.0625f) * 16.f);
                    l *= ex2(m - mn);
                    m = mn;
#pragma unroll
                    for (int i = 0; i < 8; i++) pr[i] = ex2(sc[i] - m);
                }
                stsf(ma, m);
                asm volatile("st.shared.v4.u32 [%0], {%1, %2, %3, %4};" :: "r"(pa), "r"(pack2(pr[0], pr[1])), "r"(pack2(pr[2], pr[3])),
                             "r"(pack2(pr[4], pr[5])), "r"(pack2(pr[6], pr[7])) : "memory");
                __syncwarp();
                if (lane == 0) mbar_arrive(sf + (PF0 - SF0) * 8);
                l += ((pr[0] + pr[1]) + (pr[2] + pr[3])) + ((pr[4] + pr[5]) + (pr[6] + pr[7]));
                xl ^= 512; sf += 16; ma += 256; pa += (n == 2 || n == 5) ? -8192 : 4096;
            }
            l += shx(l, 1);
            l += shx(l, 2);
            float2* mlx = (float2*)(sm + SM_MX + 2048) + wq4 * 8 + g;
            if (v == 0) { *mlx = make_float2(m, l); bar_arrive(11, 256); }
            else {
                mbar_wait(BAR(JD), 0);
                bar_sync(11, 256);
                const float2 o = *mlx;
                const float mn = fmaxf(m, o.x);
                l = l * ex2(m - mn) + o.y * ex2(o.x - mn);
                if ((wq4 >> 1) == rk) st_x4(gs + (B_ML + wq4 * 8 + g) * 4096 + (t >> 1) * 1024 + (j >> 1) * 8 + (t & 1) * 4, encf(mn), encf(l), 1u, 1u);
            }
        }
        const int pi = j < NFF ? rk * 128 + w8 * 16 + (lane & 15) : ((j - J_RED) & 15) * 16 + (w8 & 1) * 8 + g;
        const uint32_t xw = *(const uint32_t*)(xin + 2 * pi);
        const uint32_t* pm = gs + near_off(B_MB, cls) + pi;
        {
            const uint32_t ab = sb + SM_U + B_WUV * 32768 + v * 4096 + a128;
            uint32_t pa = sb + SM_PB + wq4 * 320 + frag_off(64 * v + 32 * (g >> 2) + 16 * (t & 1) + 8 * (t >> 1) + 2 * (g & 3));
            uint32_t fa = sb + SM_PB + g * 320 + t * 16;
            const uint32_t* pe = gs + G_E1 + j * 8192 + (w8 >> 1) * 2048 + ((((cls >> 1) ^ (w8 >> 1)) & 1) << 10) + (((w8 & 1) * 16 + t) * 8 + g) * 4;
            uint32_t* p2 = gs + (B_E2 + (j >> 4)) * 4096 + (t >> 1) * 1024 + (j & 12) * 64 + w8 * 32 + (j & 3) * 8 + (g & 6) + (t & 1);
            pin(pa); pin(fa); pin(pe); pin(p2);
            const uint32_t mk = (g & 1) ? 0xffff0000u : 0x0000ffffu, m0 = (g & 2) ? 0u : mk, m1 = (g & 2) ? mk : 0u;
            uint4 pv[4];
            bool hv = false;
            bar_sync(3, 416);
            uint4 wa = lds128(sb + SM_W + (wq4 * 4 + t) * 16);
            uint32_t wb[8] = {wa.x & m0, wa.x & m1, wa.y & m0, wa.y & m1, wa.z & m0, wa.z & m1, wa.w & m0, wa.w & m1};
            pv[0] = pv[1] = pv[2] = pv[3] = make_uint4(0u, 0u, 0u, 0u);
            poll<512, E1_SLEEP, true>(pv, pe, [&]() {
                if (!hv) {
                    hv = __all_sync(0xffffffffu, mbar_test(BAR(IT_WUV + t), 0));
                    if (hv) load8<true>(a, [&](int s) { return ab + (s >> 1) * 8192 + (s & 1) * 2048; });
                }
            });
            if (lane == 0) TRACE_Q(48 + w8);
            if (u8 == 0) TRACE_Q(18);
            float lo, hi2;
            float2 inv;
#pragma unroll 1
            for (int pass = 0;; pass++) {
                float e[4][4];
#pragma unroll
                for (int i = 0; i < 4; i++) {
                    e[i][0] = e[i][1] = e[i][2] = e[i][3] = 0.f;
                    mma(e[i], pv[i].x, pv[i].y, pv[i].z, pv[i].w, wb[2 * i], wb[2 * i + 1]);
                }
                const float r0 = (t & 2) ? (e[0][2] + e[1][2]) + (e[2][2] + e[3][2]) : (e[0][0] + e[1][0]) + (e[2][0] + e[3][0]);
                const float r1 = (t & 2) ? (e[0][3] + e[1][3]) + (e[2][3] + e[3][3]) : (e[0][1] + e[1][1]) + (e[2][1] + e[3][1]);
                const uint32_t hi = pack2(r0, r1);
                sts32(pa, hi); sts32(pa + 1280, pack2(r0 - bflo(hi), r1 - bfhi(hi)));
                if (!hv) {
#pragma unroll 1
                    for (int i = 0; i < 4; i++) mbar_wait(BAR(IT_WUV + i), 0);
                    load8<true>(a, [&](int s) { return ab + (s >> 1) * 8192 + (s & 1) * 2048; });
                    hv = true;
                }
                bar_sync(1, 256);
                if (u8 == 0) TRACE(19);
                ldfrag(b, fa);
                mma8(c, a, b);
                mbar_wait(BAR(WR), 0);
                asm volatile("ld.shared.v2.f32 {%0, %1}, [%2];" : "=f"(inv.x), "=f"(inv.y) : "r"(sb + SM_FQ) : "memory");
                quad_pair(c[0] + c[1], c[2] + c[3], t, lo, hi2);
                if (__builtin_expect(__all_sync(0xffffffffu, pass || __float_as_uint(inv.y) == 0), 1)) break;
                wa = lds128(sb + SM_W2 + (wq4 * 4 + t) * 16);
                wb[0] = wa.x & m0; wb[1] = wa.x & m1; wb[2] = wa.y & m0; wb[3] = wa.y & m1; wb[4] = wa.z & m0; wb[5] = wa.z & m1; wb[6] = wa.w & m0; wb[7] = wa.w & m1;
                bar_sync(1, 256);
            }
            if (!(g & 1)) st_x1(p2, enc(pack2(lo * inv.x, hi2 * inv.x)));
            bar_arrive(4, 416);
            if (u8 == 0) TRACE(20);
        }
        if (j < NFF) {
            const uint32_t* p3 = gs + near_off(B_E3 + rk * 2 + v, cls) + wq4 * 256 + lane;
            uint32_t za = sb + SM_FZ + lb4 * 576 + frag_off(w8 * 32 + (lane & 15) * 2);
            uint32_t fa = sb + SM_FZ + (g & 3) * 576 + ((lane ^ j) & 16) * 16 + t * 16, ya = sb + SM_Y + u8 * 4;
            uint32_t mb[3];
            uint4 a2[8];
            poll<1024, MB_SLEEP>(mb, pm);
            const uint32_t kk = pack2(1.f + bflo(mb[2]), 1.f + bfhi(mb[2]));
            sts32(za + 2 * 576, lb4 ? mb[1] : kk);
            uint32_t e3[8] = {0u, 0u, 0u, 0u, 0u, 0u, 0u, 0u};
            uint32_t ra = peer_addr(sb + SM_RED + (rk * 2 + v) * 512 + ((wq4 & 1) * 16 + (t >> 1) * 8 + g) * 16 + (t & 1) * 8, wq4 >> 1), tbo = peer_addr(BAR(QB), wq4 >> 1);
            pin(za); pin(fa); pin(ya); pin(ra); pin(tbo);
            if (lane == 0) mbar_expect(BAR(QB), 256);
            const uint32_t gb = BAR(IT_X + v * 2), ab = sb + SM_U + (B_X + v) * 32768 + a128;
            bool early = false, early2 = false;
            auto ldw = [&]() {
                if (!early) {
                    early = __all_sync(0xffffffffu, mbar_test(gb, 0));
                    if (early) load8<true>(a, [&](int s) { return ab + s * 2048; });
                }
                if (!early2) {
                    early2 = __all_sync(0xffffffffu, mbar_test(gb + 8, 0));
                    if (early2) load8<true>(a2, [&](int s) { return ab + 16384 + s * 2048; });
                }
            };
            bar_sync(8, 384);
            poll<128, 0, true>(e3, p3, ldw);
            if (u8 == 0) TRACE(23);
            const float s0 = sumlo(e3), s1 = sumhi(e3);
            const float y0 = fmaf(bflo(mb[0]), s0 + shx(s0, 16), bflo(xw)), y1 = fmaf(bfhi(mb[0]), s1 + shx(s1, 16), bfhi(xw));
            stsf(ya, lb4 ? y1 : y0);
            const float z0 = y0 * bflo(kk), z1 = y1 * bfhi(kk);
            const uint32_t zh = pack2(z0, z1);
            sts32(za, lb4 ? pack2(z0 - bflo(zh), z1 - bfhi(zh)) : zh);
            bar_sync(7, 288);
            if (u8 == 0) TRACE(24);
            ldfrag(b, fa);
            if (!early) { mbar_wait(gb, 0); load8<true>(a, [&](int s) { return ab + s * 2048; }); }
            {
                float e[4][4];
#pragma unroll
                for (int s = 0; s < 16; s++) {
                    if (s == 8 && !early2) { mbar_wait(gb + 8, 0); load8<true>(a2, [&](int q) { return ab + 16384 + q * 2048; }); }
                    const uint4& x = s < 8 ? a[s] : a2[s & 7];
                    const uint4& y = b[(s >> 1) & 3];
                    float (&d)[4] = e[(s >> 3) * 2 + (s & 1)];
                    if (!(s & 6)) d[0] = d[1] = d[2] = d[3] = 0.f;
                    mma(d, x.x, x.y, x.z, x.w, (s & 1) ? y.z : y.x, (s & 1) ? y.w : y.y);
                }
                const bool hi = t >> 1;
                const float k0 = hi ? e[2][2] + e[3][2] : e[0][0] + e[1][0], k1 = hi ? e[2][3] + e[3][3] : e[0][1] + e[1][1];
                const float o0 = hi ? e[2][0] + e[3][0] : e[0][2] + e[1][2], o1 = hi ? e[2][1] + e[3][1] : e[0][3] + e[1][3];
                st_async2(ra, k0 + shx(o0, 2), k1 + shx(o1, 2), tbo);
            }
        } else if (j >= J_RED && j < J_END && w8 < 2) {
            uint32_t ga[1], e3[4];
            poll<0, MB_SLEEP>(ga, pm);
            bar_sync(8, 192);
            poll<64, 100>(e3, gs + near_off(B_E3 + (pi >> 6), cls) + (pi & 48) * 16 + t * 64 + (pi & 15));
            float y0 = (bflo(e3[0]) + bflo(e3[1])) + (bflo(e3[2]) + bflo(e3[3])), y1 = (bfhi(e3[0]) + bfhi(e3[1])) + (bfhi(e3[2]) + bfhi(e3[3]));
#pragma unroll
            for (int o = 1; o < 4; o <<= 1) { y0 += shx(y0, o); y1 += shx(y1, o); }
            const int col = g + (t & 1) * 8;
            y0 = __shfl_sync(0xffffffffu, (t & 1) ? fmaf(bfhi(ga[0]), y1, bfhi(xw)) : fmaf(bflo(ga[0]), y0, bflo(xw)), (col >> 1) * 4 + (col & 1));
            uint32_t gb = 0;
            auto ldg = [&]() { if (__all_sync(0xffffffffu, mbar_test(BAR(QB), 1))) gb = lds32(sb + SM_FV + 256 + w8 * 32 + (col >> 1) * 4); };
            uint16_t* po = (uint16_t*)out + (j - J_RED) * 32 + w8 * 16 + col;
            pin(po);
            uint32_t yv[NFF / 4];
            poll<256, 0>(yv, gs + near_off(B_E5 + j - J_RED, cls) + t * 16 + w8 * 8 + g, ldg);
            if (u8 == 0) TRACE(26);
            const uint32_t one = (g & 1) ? 0x3f800000u : 0x00003f80u;
            float e[4][4];
#pragma unroll
            for (int i = 0; i < 4; i++) {
                e[i][0] = e[i][1] = e[i][2] = e[i][3] = 0.f;
                mma(e[i], yv[4 * i], yv[4 * i + 1], i < 3 ? yv[(4 * i + 2) % (NFF / 4)] : 0u, i < 3 ? yv[(4 * i + 3) % (NFF / 4)] : 0u, one, one);
            }
            const float s = (t & 1) ? ((e[0][1] + e[0][3]) + (e[1][1] + e[1][3])) + ((e[2][1] + e[2][3]) + (e[3][1] + e[3][3]))
                                    : ((e[0][0] + e[0][2]) + (e[1][0] + e[1][2])) + ((e[2][0] + e[2][2]) + (e[3][0] + e[3][2]));
            if (__any_sync(0xffffffffu, !gb)) { mbar_wait(BAR(QB), 1); ldg(); }
            if (t < 2) *po = (uint16_t)pack2(fmaf((col & 1) ? bfhi(gb) : bflo(gb), s, y0), 0.f);
            if (u8 == 0) TRACE(27);
        }
    }
}

typedef CUresult (*EncFn)(CUtensorMap*, CUtensorMapDataType, cuuint32_t, void*, const cuuint64_t*, const cuuint64_t*,
                          const cuuint32_t*, const cuuint32_t*, CUtensorMapInterleave, CUtensorMapSwizzle,
                          CUtensorMapL2promotion, CUtensorMapFloatOOBfill);

void make_map(EncFn enc_fn, CUtensorMap* m, const void* p, cuuint64_t d0, cuuint64_t d1, cuuint64_t d2, cuuint64_t d3,
              cuuint64_t s1, cuuint64_t s2, cuuint64_t s3, cuuint32_t b0, cuuint32_t b1, cuuint32_t b2, cuuint32_t b3, CUtensorMapSwizzle sw) {
    const cuuint64_t dims[4] = {d0, d1, d2, d3}, strides[3] = {s1, s2, s3};
    const cuuint32_t box[4] = {b0, b1, b2, b3}, es[4] = {1, 1, 1, 1};
    enc_fn(m, CU_TENSOR_MAP_DATA_TYPE_BFLOAT16, 4, (void*)p, dims, strides, box, es,
           CU_TENSOR_MAP_INTERLEAVE_NONE, sw, PROMO, CU_TENSOR_MAP_FLOAT_OOB_FILL_NONE);
}

uint32_t* scratch = nullptr;

struct Tune { const char* win; const char* late; int tau, t_off; const char* tail[3][4]; };
Tune tune = {"66666666655555555555555555555555555533333",
             "00000000000000000000999999999999999999999", 322, -300,
             {{"VVVVOOOOguguDDDD", "zzzzzzzzzzzzzzzz", "8888999988887899", "eddd0efffaaab666"},
              {"VMVMVVOOOO", "zzzzzzzzzz", "8888889999", "288888iddd"},
              {"VVVVOOOOMM", "zzzzzzzzzz", "aaaaaaaa88", "6ggg0ghhkn"}}};
bool ready = false;

}

extern "C" void kernel_launch(void* const* d_in, const int* in_sizes, int n_in, void* d_out, int out_size) {
    (void)in_sizes; (void)n_in; (void)out_size;
    static Maps maps;
    static const void* cached[12] = {};
    bool same = ready;
    for (int i = 0; i < 12 && same; i++) same = cached[i] == d_in[i];
    if (!same) {
        void* fn = nullptr;
        cudaDriverEntryPointQueryResult qr;
        cudaGetDriverEntryPoint("cuTensorMapEncodeTiled", &fn, cudaEnableDefault, &qr);
        EncFn e = (EncFn)fn;
        const CUtensorMapSwizzle S128 = CU_TENSOR_MAP_SWIZZLE_128B;
        make_map(e, &maps.m[MP_WQ], d_in[2], 64, 512, 64, 1, 8192, 128, 8192, 64, 64, 1, 1, S128);
        make_map(e, &maps.m[MP_WUK], d_in[3], 64, 512, 64, 1, 8192, 128, 8192, 64, 64, 1, 1, S128);
        make_map(e, &maps.m[MP_CKV], d_in[1], 64, 8, 8, 4096, 1024, 128, 8192, 64, 8, 4, 2, S128);
        make_map(e, &maps.m[MP_MODB], d_in[11], 3072, 512, 1, 1, 6144, 6144, 6144, 64, 128, 1, 1, S128);
        make_map(e, &maps.m[MP_WUV], d_in[4], 64, 512, 64, 1, 8192, 128, 8192, 64, 32, 2, 1, S128);
        make_map(e, &maps.m[MP_WO], d_in[5], 512, 4096, 1, 1, 1024, 1024, 1024, 64, 64, 1, 1, S128);
        make_map(e, &maps.m[MP_GATE], d_in[7], 1792, 512, 1, 1, 3584, 3584, 3584, 64, 128, 1, 1, S128);
        make_map(e, &maps.m[MP_UP], d_in[8], 1792, 512, 1, 1, 3584, 3584, 3584, 64, 128, 1, 1, S128);
        make_map(e, &maps.m[MP_DOWN], d_in[9], 64, 1792, 8, 1, 1024, 128, 1024, 64, 32, 2, 1, S128);
        for (int r = 0; r < 3; r++) {
            int ids[58], cnt[128] = {}, tn = tune.t_off - (W0 - 1) * tune.tau;
            uint2* sc = maps.sched[r];
            auto dig = [](char ch) { return ch >= 'a' ? ch - 'a' + 10 : ch >= 'A' ? ch - 'A' + 36 : ch - '0'; };
            for (int i = 0; i < 58; i++) sc[i] = make_uint2(0u, 0u);
            for (int i = 0;; i++) {
                int id = i, buf, dep, w, wl;
                if (i < IT_WUV) {
                    const int u = (i - IT_CKV) >> 2;
                    buf = i < IT_CKV ? 4 + ((i - 1) >> 2) : u % 6;
                    dep = i < IT_CKV || u < 4 ? -1 : u < 6 ? EB_WQ + u - 4 : EB_UNIT0 + u - 6;
                    w = dig(tune.win[i]); wl = dig(tune.late[i]);
                    if (i) tn += tune.tau;
                } else {
                    const char ch = tune.tail[r][0][i - IT_WUV];
                    if (!ch) break;
                    buf = ch == 'V' ? B_WUV : ch == 'O' ? B_WO : ch == 'D' ? B_DN : ch == 'u' ? B_X + 1 : B_X;
                    id = (ch == 'V' ? IT_WUV : ch == 'O' ? IT_WO : ch == 'D' ? IT_DOWN : ch == 'u' ? IT_X + 2 : IT_X) + cnt[(int)ch]++;
                    dep = EB_UNIT0 + (buf < 2 ? buf + 6 : buf);
                    w = dig(tune.tail[r][1][i - IT_WUV]); wl = dig(tune.tail[r][2][i - IT_WUV]);
                    tn += 32 * dig(tune.tail[r][3][i - IT_WUV]);
                }
                if (id < IT_X || id >= IT_DOWN ? (id - 1) & 3 : (id - IT_X) & 1) dep = -1;
                ids[i] = id;
                auto back = [&](int d) { return i < d ? 0 : (ids[i - d] && ids[i - d] <= NCP ? 1 : ids[i - d]) + 1; };
                sc[i].x = id | (buf * 4 + (id < IT_X || id >= IT_DOWN ? (id - 1) & 3 : ((id - IT_X) & 1) * 2)) << 6 | (dep + 1) << 11 | (w > 32 ? NEVER + 1 : back(w)) << 18 | (wl ? back(wl) : 0) << 25;
                const int mp = id < IT_CKV ? MP_WQ + ((id - 1) >> 2) : id < IT_WUV ? MP_CKV : id < IT_WO ? MP_WUV : id < IT_X ? MP_WO
                             : id >= IT_DOWN ? MP_DOWN : r ? MP_MODB : MP_GATE + ((id - IT_X) >> 1);
                const int step = mp == MP_CKV ? id - IT_CKV : mp == MP_WUV ? (id - IT_WUV) * 2 : mp == MP_DOWN ? id - IT_DOWN : id < IT_X ? (id - 1) & 3 : ((id - IT_X) & 1) * 2;
                sc[i].y = (tn & 0xffff) | (mp & 15) << 16 | step << 20;
            }
        }
        cudaGetSymbolAddress((void**)&scratch, g_scratch);
        scratch = (uint32_t*)(((uintptr_t)scratch + (2u << 20) - 1) & ~(uintptr_t)((2u << 20) - 1));
        cudaFuncSetAttribute(fused_kernel, cudaFuncAttributeMaxDynamicSharedMemorySize, SM_TOTAL);
        for (int i = 0; i < 12; i++) cached[i] = d_in[i];
        ready = true;
    }
    const First f = {{(const uint8_t*)d_in[2], (const uint8_t*)d_in[11]}, {(const __nv_bfloat16*)d_in[0], (const __nv_bfloat16*)d_in[10]}};
    fused_kernel<<<NCTA, NTHREADS, SM_TOTAL>>>(f, (__nv_bfloat16*)d_out, scratch, maps);
}
```

```cpp
#include <cuda_runtime.h>
#include <cuda_bf16.h>
#include <cuda.h>
#include <stdint.h>
#include <limits.h>

namespace {

constexpr int NCTA = 128;
constexpr int NTHREADS = 512;
constexpr int NUNITS = 8;
constexpr int NFF = 56, J_RED = 104, J_END = 120;
constexpr uint32_t SPIN_LIMIT = 1u << 22;

#define PROMO CU_TENSOR_MAP_L2_PROMOTION_L2_64B
#define NEAR_CLK 390
#define E1_EARLY 50
#define STAG 300
#define NUMA 1
#define NPROBE 5
#define NCP 2
#define W0 4
#define RD_ITEM 15
#define JAN_SLEEP 100
#define RD_SLEEP 400
#define HA_DELAY 200
#define H_SLEEP 100
#define QA_DELAY 600
#define QA_SLEEP 200
#define ML_DELAY 300
#define E1_SLEEP 50
#define MB_SLEEP 100
constexpr int B_WUV = 2, B_WO = 3, B_X = 4  , B_DN = 0;

constexpr int SM_U = 0;
constexpr int SM_XA = 6 * 32768;
constexpr int SM_XB = SM_XA + 12288;
constexpr int SM_MX = SM_XB + 16384;
constexpr int SM_FZ = SM_XB + 8192;
constexpr int SM_PB = SM_XB;
constexpr int SM_Y = SM_XB + 12288;
constexpr int SM_RED = SM_XB + 4096;
constexpr int SM_FS = SM_XB + 20480;
constexpr int SM_FV = SM_FS + 1024;
constexpr int SM_QX = SM_XA + 8192;
constexpr int SM_FQ = SM_FV + 512;
constexpr int SM_CLS = SM_FQ + 128;
constexpr int SM_W = SM_FQ + 256;
constexpr int SM_W2 = SM_MX + 2304;
constexpr int SM_SCR = SM_XA + 9216;
constexpr int SM_TR = SM_XB + 19456;
constexpr int SM_BAR = SM_W + 256;
constexpr int SM_TOTAL = SM_BAR + 1024;
static_assert(SM_TOTAL <= 232448, "smem");

enum { IT_MODA = 0, IT_WQ = 1, IT_WUK = 5, IT_CKV = 9, IT_WUV = 41, IT_WO = 45, IT_X = 49  , IT_DOWN = 53, NITEMS = 57,
       NEVER = 63,
       SF0 = 64,
       PF0 = 80,
       EB_UNIT0 = 96, MBB = 103,
       EB_WQ = 104, EB_WUK, QT, QB, JD, WR };

enum { MP_WQ = 0, MP_WUK, MP_CKV, MP_WUV, MP_DOWN, MP_WO, MP_GATE, MP_UP, MP_MODB, NMAPS };
struct First { const uint8_t* w[2]; const __nv_bfloat16* v[2]; };
struct Maps { CUtensorMap m[NMAPS]; uint2 sched[3][58]; };

enum { B_HA = 0,
       B_MB = 6,
       B_RD = 7,
       B_E2 = 8,
       B_QA = 16,
       B_ML = 32,
       B_E5 = 64,
       B_E3 = 80,
       B_PR = 96,
       B_TR = 100 };
constexpr int G_E1 = 1 << 19;
constexpr int G_TR = B_TR * 4096;
__device__ __align__(1024) uint32_t g_scratch[(8 << 20) / 4];

#define TRACE(slot) do {} while (0)
#define TRACE_Q(slot) do {} while (0)
#define TRACE_GT(slot) do {} while (0)

__device__ __forceinline__ uint32_t s2u(const void* p) { return (uint32_t)__cvta_generic_to_shared(p); }
__device__ __forceinline__ void mbar_init(uint32_t b, int c) { asm volatile("mbarrier.init.shared::cta.b64 [%0], %1;" :: "r"(b), "r"(c) : "memory"); }
__device__ __forceinline__ void mbar_expect(uint32_t b, uint32_t bytes) { asm volatile("mbarrier.arrive.expect_tx.shared::cta.b64 _, [%0], %1;" :: "r"(b), "r"(bytes) : "memory"); }
__device__ __forceinline__ void mbar_arrive(uint32_t b) { asm volatile("mbarrier.arrive.shared::cta.b64 _, [%0];" :: "r"(b) : "memory"); }
__device__ __forceinline__ void mbar_wait(uint32_t b, uint32_t ph) {
    asm volatile("{\n.reg .pred p;\nW: mbarrier.try_wait.parity.shared::cta.b64 p, [%0], %1;\n@!p bra W;\n}" :: "r"(b), "r"(ph) : "memory");
}
__device__ __forceinline__ void mbar_waitb(uint32_t b, uint32_t ph) {
    asm volatile("{\n.reg .pred p;\n.reg .u32 n;\nmov.u32 n, 0;\n"
                 "W: mbarrier.try_wait.parity.shared::cta.b64 p, [%0], %1;\n@p bra D;\n"
                 "add.u32 n, n, 1;\nsetp.lt.u32 p, n, 0x100000;\n@p bra W;\ntrap;\nD:\n}" :: "r"(b), "r"(ph) : "memory");
}
__device__ __forceinline__ uint32_t mbar_test(uint32_t b, uint32_t ph) {
    uint32_t ok;
    asm volatile("{\n.reg .pred p;\nmbarrier.test_wait.parity.shared::cta.b64 p, [%1], %2;\nselp.u32 %0, 1, 0, p;\n}" : "=r"(ok) : "r"(b), "r"(ph) : "memory");
    return ok;
}
__device__ __forceinline__ void bar_sync(int id, int n) { asm volatile("bar.sync %0, %1;" :: "r"(id), "r"(n) : "memory"); }
__device__ __forceinline__ void bar_arrive(int id, int n) { asm volatile("bar.arrive %0, %1;" :: "r"(id), "r"(n) : "memory"); }
__device__ __forceinline__ uint32_t peer_addr(uint32_t a, uint32_t rank) { uint32_t r; asm("mapa.shared::cluster.u32 %0, %1, %2;" : "=r"(r) : "r"(a), "r"(rank)); return r; }
__device__ __forceinline__ void st_async2(uint32_t a, float x, float y, uint32_t bar) {
    asm volatile("st.async.weak.shared::cluster.mbarrier::complete_tx::bytes.v2.f32 [%0], {%1, %2}, [%3];" :: "r"(a), "f"(x), "f"(y), "r"(bar) : "memory");
}
__device__ __forceinline__ uint32_t gtime() { uint32_t t; asm volatile("mov.u32 %0, %%globaltimer_lo;" : "=r"(t)); return t; }
__device__ __forceinline__ void fence_gpu() { asm volatile("fence.acq_rel.gpu;" ::: "memory"); }

__device__ __forceinline__ uint32_t enc(uint32_t b) { uint32_t r; asm("max.u32 %0, %1, 1;" : "=r"(r) : "r"(b)); return r; }
__device__ __forceinline__ uint32_t encf(float f) { return enc(__float_as_uint(f)); }
__device__ __forceinline__ void st_x1(uint32_t* p, uint32_t v) { asm volatile("st.relaxed.gpu.global.u32 [%0], %1;" :: "l"(p), "r"(v) : "memory"); }
__device__ __forceinline__ void st_x4(void* p, uint32_t a, uint32_t b, uint32_t c, uint32_t d) {
    asm volatile("st.relaxed.gpu.global.v4.u32 [%0], {%1, %2, %3, %4};" :: "l"(p), "r"(a), "r"(b), "r"(c), "r"(d) : "memory");
}
__device__ __forceinline__ void st2_x1(uint32_t* p, uint32_t v) { st_x1(p, v); st_x1(p + 1024, v); }
__device__ __forceinline__ void st2_x4(uint32_t* p, uint32_t a, uint32_t b, uint32_t c, uint32_t d) { st_x4(p, a, b, c, d); st_x4(p + 1024, a, b, c, d); }
__device__ __forceinline__ int near_off(int b, uint32_t cls) { return b * 4096 + (((__popc(b & 0x2C) ^ cls) & 1) << 10); }
__device__ __forceinline__ void ld_x(uint32_t& v, const void* p) { asm volatile("ld.relaxed.gpu.global.u32 %0, [%1];" : "=r"(v) : "l"(p) : "memory"); }
__device__ __forceinline__ void ld_x(uint4& v, const void* p) {
    asm volatile("ld.relaxed.gpu.global.v4.u32 {%0, %1, %2, %3}, [%4];" : "=r"(v.x), "=r"(v.y), "=r"(v.z), "=r"(v.w) : "l"(p) : "memory");
}
__device__ __forceinline__ void ld_x(uint2& v, const void* p) { asm volatile("ld.relaxed.gpu.global.v2.u32 {%0, %1}, [%2];" : "=r"(v.x), "=r"(v.y) : "l"(p) : "memory"); }
__device__ __forceinline__ uint32_t minw(uint32_t v) { return v; }
__device__ __forceinline__ uint32_t minw(const uint2& v) { return min(v.x, v.y); }
__device__ __forceinline__ uint32_t minw(const uint4& v) { return min(__vimin3_u32(v.x, v.y, v.z), v.w); }
template <int N> __device__ __forceinline__ uint32_t mint(const uint32_t* m) {
    if constexpr (N == 1) return m[0];
    else if constexpr (N == 2) return min(m[0], m[1]);
    else return __vimin3_u32(mint<(N + 2) / 3>(m), mint<(N + 1) / 3>(m + (N + 2) / 3), mint<N / 3>(m + (N + 2) / 3 + (N + 1) / 3));
}

template <int STRIDE, int S4 = 4 * STRIDE, typename T, int N>
__device__ __forceinline__ void poll_start(T (&v)[N], const void* base) {
#pragma unroll
    for (int i = 0; i < N; i++) ld_x(v[i], (const uint8_t*)base + (i & 3) * STRIDE + (i >> 2) * S4);
}
struct Nop { __device__ void operator()() const {} };
template <int STRIDE, int SLEEP, bool STARTED = false, int S4 = 4 * STRIDE, typename T, int N, typename F = Nop>
__device__ __forceinline__ void poll(T (&v)[N], const void* base, F idle = F()) {
    if (!STARTED) { poll_start<STRIDE, S4>(v, base); idle(); }
#pragma unroll 1
    for (uint32_t it = 0;; it++) {
        uint32_t m[N];
#pragma unroll
        for (int i = 0; i < N; i++) m[i] = minw(v[i]);
        if (__all_sync(0xffffffffu, mint<N>(m) != 0)) break;
        if (SLEEP && it > 0) __nanosleep(SLEEP);
#pragma unroll
        for (int i = 0; i < N; i++) if (!m[i]) ld_x(v[i], (const uint8_t*)base + (i & 3) * STRIDE + (i >> 2) * S4);
        idle();
        if (it > SPIN_LIMIT) __trap();
    }
}

__device__ __forceinline__ float bflo(uint32_t w) { return __uint_as_float(w << 16); }
__device__ __forceinline__ float bfhi(uint32_t w) { return __uint_as_float(w & 0xffff0000u); }
__device__ __forceinline__ uint32_t pack2(float lo, float hi) {
    uint32_t r; asm("cvt.rn.bf16x2.f32 %0, %1, %2;" : "=r"(r) : "f"(hi), "f"(lo)); return r;
}
__device__ __forceinline__ float rbf(float x) { return __uint_as_float(pack2(0.f, x)); }
__device__ __forceinline__ float sumlo(const uint32_t (&v)[8]) { return ((bflo(v[0]) + bflo(v[1])) + (bflo(v[2]) + bflo(v[3]))) + ((bflo(v[4]) + bflo(v[5])) + (bflo(v[6]) + bflo(v[7]))); }
__device__ __forceinline__ float sumhi(const uint32_t (&v)[8]) { return ((bfhi(v[0]) + bfhi(v[1])) + (bfhi(v[2]) + bfhi(v[3]))) + ((bfhi(v[4]) + bfhi(v[5])) + (bfhi(v[6]) + bfhi(v[7]))); }
__device__ __forceinline__ float ex2(float x) { float r; asm("ex2.approx.ftz.f32 %0, %1;" : "=f"(r) : "f"(x)); return r; }
__device__ __forceinline__ float shx(float v, int m) { return __shfl_xor_sync(0xffffffffu, v, m); }
__device__ __forceinline__ uint4 lds128(uint32_t a) { uint4 v; asm volatile("ld.shared.v4.u32 {%0, %1, %2, %3}, [%4];" : "=r"(v.x), "=r"(v.y), "=r"(v.z), "=r"(v.w) : "r"(a) : "memory"); return v; }
__device__ __forceinline__ uint32_t lds32(uint32_t a) { uint32_t v; asm volatile("ld.shared.u32 %0, [%1];" : "=r"(v) : "r"(a) : "memory"); return v; }
__device__ __forceinline__ void sts32(uint32_t a, uint32_t v) { asm volatile("st.shared.u32 [%0], %1;" :: "r"(a), "r"(v) : "memory"); }
__device__ __forceinline__ void sts16(uint32_t a, uint32_t v) { asm volatile("st.shared.u16 [%0], %1;" :: "r"(a), "h"((uint16_t)v) : "memory"); }
__device__ __forceinline__ int frag_off(int k) { return (k >> 5) * 64 + ((k >> 1) & 3) * 16 + ((k >> 4) & 1) * 8 + ((k >> 3) & 1) * 4 + (k & 1) * 2; }

template <bool TRANS>
__device__ __forceinline__ uint4 ldsm(uint32_t a) {
    uint4 r;
    if (TRANS) asm volatile("ldmatrix.sync.aligned.m8n8.x4.trans.shared.b16 {%0, %1, %2, %3}, [%4];" : "=r"(r.x), "=r"(r.y), "=r"(r.z), "=r"(r.w) : "r"(a) : "memory");
    else asm volatile("ldmatrix.sync.aligned.m8n8.x4.shared.b16 {%0, %1, %2, %3}, [%4];" : "=r"(r.x), "=r"(r.y), "=r"(r.z), "=r"(r.w) : "r"(a) : "memory");
    return r;
}
__device__ __forceinline__ void mma(float (&c)[4], uint32_t a0, uint32_t a1, uint32_t a2, uint32_t a3, uint32_t b0, uint32_t b1) {
    asm volatile("mma.sync.aligned.m16n8k16.row.col.f32.bf16.bf16.f32 {%0,%1,%2,%3}, {%4,%5,%6,%7}, {%8,%9}, {%0,%1,%2,%3};"
                 : "+f"(c[0]), "+f"(c[1]), "+f"(c[2]), "+f"(c[3]) : "r"(a0), "r"(a1), "r"(a2), "r"(a3), "r"(b0), "r"(b1));
}
template <bool TRANS, typename F>
__device__ __forceinline__ void load8(uint4 (&a)[8], F addr) {
    __syncwarp();
#pragma unroll
    for (int s = 0; s < 8; s++) a[s] = ldsm<TRANS>(addr(s));
}
__device__ __forceinline__ void mma8(float (&c)[4], const uint4 (&a)[8], const uint4 (&b)[4]) {
    float e[4][4];
#pragma unroll
    for (int s = 0; s < 8; s++) {
        if (s < 4) e[s][0] = e[s][1] = e[s][2] = e[s][3] = 0.f;
        mma(e[s & 3], a[s].x, a[s].y, a[s].z, a[s].w, (s & 1) ? b[s >> 1].z : b[s >> 1].x, (s & 1) ? b[s >> 1].w : b[s >> 1].y);
    }
#pragma unroll
    for (int i = 0; i < 4; i++) c[i] = (e[0][i] + e[1][i]) + (e[2][i] + e[3][i]);
}
__device__ __forceinline__ void ldfrag(uint4 (&b)[4], uint32_t a) {
    asm volatile("ld.shared.v4.u32 {%0,%1,%2,%3}, [%16];\nld.shared.v4.u32 {%4,%5,%6,%7}, [%16+64];\n"
                 "ld.shared.v4.u32 {%8,%9,%10,%11}, [%16+128];\nld.shared.v4.u32 {%12,%13,%14,%15}, [%16+192];\n"
                 : "=r"(b[0].x), "=r"(b[0].y), "=r"(b[0].z), "=r"(b[0].w), "=r"(b[1].x), "=r"(b[1].y), "=r"(b[1].z), "=r"(b[1].w),
                   "=r"(b[2].x), "=r"(b[2].y), "=r"(b[2].z), "=r"(b[2].w), "=r"(b[3].x), "=r"(b[3].y), "=r"(b[3].z), "=r"(b[3].w) : "r"(a) : "memory");
}
__device__ __forceinline__ void quad_pair(float x, float y, int t, float& lo, float& hi) {
    const float k = ((t & 1) ? y : x) + shx((t & 1) ? x : y, 1);
    lo = k + shx(k, 2); hi = shx(k, 4) + shx(k, 6);
}
__device__ __forceinline__ void pin(uint32_t& x) { asm volatile("" : "+r"(x)); }
template <typename T> __device__ __forceinline__ void pin(T*& x) { asm volatile("" : "+l"(x)); }
__device__ __forceinline__ float4 ldsf4(uint32_t a) { const uint4 v = lds128(a); return make_float4(__uint_as_float(v.x), __uint_as_float(v.y), __uint_as_float(v.z), __uint_as_float(v.w)); }
__device__ __forceinline__ float sum4(const float4& f) { return (f.x + f.y) + (f.z + f.w); }
__device__ __forceinline__ void stsf(uint32_t a, float v) { sts32(a, __float_as_uint(v)); }

__device__ __forceinline__ void wg_fence() { asm volatile("wgmma.fence.sync.aligned;" ::: "memory"); }
__device__ __forceinline__ void wg_commit() { asm volatile("wgmma.commit_group.sync.aligned;" ::: "memory"); }
__device__ __forceinline__ void wg_wait1() { asm volatile("wgmma.wait_group.sync.aligned 1;" ::: "memory"); }
__device__ __forceinline__ void wg_wait0() { asm volatile("wgmma.wait_group.sync.aligned 0;" ::: "memory"); }
#define R8(o) "+f"(d[o]), "+f"(d[o + 1]), "+f"(d[o + 2]), "+f"(d[o + 3]), "+f"(d[o + 4]), "+f"(d[o + 5]), "+f"(d[o + 6]), "+f"(d[o + 7])
__device__ __forceinline__ void wgmma_rs_n32(float (&d)[16], const uint4& a, uint64_t db, int acc) {
    asm volatile("{\n.reg .pred p;\nsetp.ne.b32 p, %21, 0;\n"
        "wgmma.mma_async.sync.aligned.m64n32k16.f32.bf16.bf16 "
        "{%0,%1,%2,%3,%4,%5,%6,%7,%8,%9,%10,%11,%12,%13,%14,%15}, {%16,%17,%18,%19}, %20, p, 1, 1, 0;\n}"
        : R8(0), R8(8) : "r"(a.x), "r"(a.y), "r"(a.z), "r"(a.w), "l"(db), "r"(acc));
}
#define PV_LO "{%0,%1,%2,%3,%4,%5,%6,%7,%8,%9,%10,%11,%12,%13,%14,%15,%16,%17,%18,%19,%20,%21,%22,%23,%24,%25,%26,%27,%28,%29,%30,%31,%32,%33,%34,%35,%36,%37,%38,%39,%40,%41,%42,%43,%44,%45,%46,%47,%48,%49,%50,%51,%52,%53,%54,%55,%56,%57,%58,%59,%60,%61,%62,%63}, "
#define PV_HI "{%64,%65,%66,%67,%68,%69,%70,%71,%72,%73,%74,%75,%76,%77,%78,%79,%80,%81,%82,%83,%84,%85,%86,%87,%88,%89,%90,%91,%92,%93,%94,%95,%96,%97,%98,%99,%100,%101,%102,%103,%104,%105,%106,%107,%108,%109,%110,%111,%112,%113,%114,%115,%116,%117,%118,%119,%120,%121,%122,%123,%124,%125,%126,%127}, "
__device__ __forceinline__ void wgmma_pv(float (&d)[128], const uint4& a, uint32_t blo, int acc) {
    asm volatile("{\n.reg .pred p;\n.reg .b32 u0, u1, u2, u3, t;\n.reg .b64 d0, d1, d2, d3;\nsetp.ne.b32 p, %133, 0;\n"
        "mov.b64 d0, {%132, 0x40000100};\nadd.u32 t, %132, 512;\nmov.b64 d1, {t, 0x40000100};\n"
        "add.u32 t, %132, 128;\nmov.b64 d2, {t, 0x40000100};\nadd.u32 t, %132, 640;\nmov.b64 d3, {t, 0x40000100};\n"
        "wgmma.fence.sync.aligned;\n"
        "wgmma.mma_async.sync.aligned.m64n128k16.f32.bf16.bf16 " PV_LO "{%128, u0, %129, u1}, d0, p, 1, 1, 1;\n"
        "wgmma.mma_async.sync.aligned.m64n128k16.f32.bf16.bf16 " PV_LO "{%130, u2, %131, u3}, d1, 1, 1, 1, 1;\n"
        "wgmma.commit_group.sync.aligned;\n"
        "wgmma.mma_async.sync.aligned.m64n128k16.f32.bf16.bf16 " PV_HI "{%128, u0, %129, u1}, d2, p, 1, 1, 1;\n"
        "wgmma.mma_async.sync.aligned.m64n128k16.f32.bf16.bf16 " PV_HI "{%130, u2, %131, u3}, d3, 1, 1, 1, 1;\n"
        "wgmma.commit_group.sync.aligned;\n}"
        : R8(0), R8(8), R8(16), R8(24), R8(32), R8(40), R8(48), R8(56), R8(64), R8(72), R8(80), R8(88), R8(96), R8(104), R8(112), R8(120)
        : "r"(a.x), "r"(a.y), "r"(a.z), "r"(a.w), "r"(blo), "r"(acc) : "memory");
}

template <int NW>
__device__ __forceinline__ void ln_stats(float s, float q, float sh, float* scr, int w, int lane, int bar, float& mean_b, float& sd_b) {
#pragma unroll
    for (int o = 16; o; o >>= 1) { s += shx(s, o); q += shx(q, o); }
    constexpr float n = 512.f / NW;
    if (lane == 0) { scr[w] = sh + s * (1.f / n); scr[NW + w] = q - s * s * (1.f / n); }
    bar_sync(bar, NW * 32);
    float mu = 0.f, m2 = 0.f;
#pragma unroll
    for (int i = 0; i < NW; i++) { mu += scr[i]; m2 += scr[NW + i]; }
    mu *= 1.f / NW;
#pragma unroll
    for (int i = 0; i < NW; i++) { const float d = scr[i] - mu; m2 = fmaf(n * d, d, m2); }
    mean_b = rbf(mu);
    sd_b = rbf(sqrtf(rbf(rbf(fmaxf(m2, 0.f) * (1.f / 512.f)) + 1e-5f)));
}
__device__ __forceinline__ float ln_mod(float x, float mean_b, float sd_b, float c, float s) {
    return rbf(rbf(__fdividef(rbf(x - mean_b), sd_b)) * rbf(1.f + c)) + s;
}

__global__ void __cluster_dims__(2, 1, 1) __launch_bounds__(NTHREADS, 1)
fused_kernel(const __grid_constant__ First F, __nv_bfloat16* __restrict__ out, uint32_t* __restrict__ gs, const __grid_constant__ Maps M) {
    extern __shared__ __align__(1024) uint8_t sm[];
    const uint32_t sb = s2u(sm);
    const int tid = threadIdx.x, lane = tid & 31;
    const int j = blockIdx.x, rk = j & 1;
    const int g = lane >> 2, t = lane & 3;
    const int r8 = lane & 7, lb3 = (lane >> 3) & 1, lb4 = lane >> 4;
    uint64_t pol;
    asm("createpolicy.fractional.L2::evict_first.b64 %0, 1.0;" : "=l"(pol));
    {
        auto cpa = [&](uint32_t d, const uint8_t* s) {
            asm volatile("cp.async.cg.shared.global.L2::cache_hint.L2::128B [%0], [%1], 16, %2;" :: "r"(d), "l"(s), "l"(pol) : "memory");
        };
        const uint32_t ut = threadIdx.x, uj = blockIdx.x;
        const uint8_t* w = F.w[ut >= 128];
        if (ut < 128) {
            const uint32_t dq = (sb + ut * 16) ^ ((ut * 2) & 0x70);
            const uint8_t* sq = w + (uint32_t)(((uj & 1) * 256 + (ut >> 3)) * 8192 + (uj >> 1) * 128 + (ut & 7) * 16);
#pragma unroll
            for (int i = 0; i < 4 * NCP; i++) cpa(dq + 4 * 32768 + i * 2048, sq + i * 131072);
        } else if (ut < 384) {
            const uint32_t dm = (sb + ut * 16) ^ ((ut * 2) & 0x10);
            const uint8_t* sa = w + (uint32_t)(((uj >> 5) * 128 + (ut >> 1) - 64) * 6144 + (uj & 31) * 32 + (ut & 1) * 16);
            cpa(dm + SM_XA - 2048, sa); cpa(dm + SM_XA + 2048, sa + 1024);
        }
        else if (ut == 480 && uj < 64) asm volatile("prefetch.global.L2 [%0];" :: "l"(F.v[(uj >> 3) & 1] + (uj & 7) * 64));
    }
    const int warp = __shfl_sync(0xffffffffu, tid >> 5, 0);
    const __nv_bfloat16* const xin = F.v[0];
    uint32_t* const pl = gs + (warp < 2 ? (B_PR + (j >> 5)) * 4096 + (j & 31) * 32 : G_E1 + j * 8192) + (warp & 1) * 1024 + lane;
    if (warp < 4) st_x1(pl, 1u);
    auto BAR = [&](int i) -> uint32_t { return sb + SM_BAR + i * 8; };
    const uint32_t a16 = (r8 + 8 * lb4) * 32 + ((lb3 ^ (r8 >> 2)) * 16);
    const uint32_t a128 = (r8 + 8 * lb4) * 128 + ((((warp & 3) * 2 + lb3) ^ r8) * 16);
    auto ldcls = [&]() -> uint32_t { return *(const volatile uint32_t*)(sm + SM_CLS); };
    auto clear_head = [&]() {
        st2_x1(gs + (B_HA + ((j >> 4) & 1) * 2 + lb4) * 4096 + (j >> 5) * 256 + (j & 15) * 16 + (lane & 15), 0u);
        st2_x4(gs + (B_QA + rk * 8 + ((j >> 1) & 1) * 4 + (j >> 5)) * 4096 + g * 128 + ((j >> 2) & 7) * 16 + t * 4, 0u, 0u, 0u, 0u);
        if (lane < 8) st2_x1(gs + B_RD * 4096 + j * 8 + lane, 0u);
    };
    auto tma = [&](uint32_t dst, const CUtensorMap* mp, uint32_t bar, int c0, int c1, int c2, int c3) {
        asm volatile("{\n.reg .pred p;\nelect.sync _|p, 0xffffffff;\n"
                     "@p cp.async.bulk.tensor.4d.shared::cluster.global.mbarrier::complete_tx::bytes.L2::cache_hint [%0], [%1, {%3, %4, %5, %6}], [%2], %7;\n}"
                     :: "r"(dst), "l"(mp), "r"(bar), "r"(c0), "r"(c1), "r"(c2), "r"(c3), "l"(pol) : "memory");
    };
    if (warp <= 12 || warp == 15) {
        const int grp = warp == 12 ? 0 : warp == 15 ? 13 : warp + 1;
        const uint32_t cnt = grp < 10 ? 1 : grp < 13 ? 4 : 8;
        if (lane == 0) {
#pragma unroll
            for (int i = 0; i < 8; i++) mbar_init(BAR(grp * 8 + i), (i < 2 && grp == 0) ? (i ? 128 : 256) : cnt);
        }
        __syncwarp();
        if (grp < 10 && lane < 8 && (grp || lane > NCP)) mbar_expect(BAR(grp * 8 + lane), grp >= 8 ? 4096 : (uint32_t)(grp * 8 + lane - IT_X) < 4 ? 16384 : 8192);
        asm volatile("fence.mbarrier_init.release.cluster;" ::: "memory");
        __syncwarp();
        if (warp == 12) {
#pragma unroll
            for (int i = NCP + 1; i < W0; i++) tma(sb + (15 + i) * 8192, &M.m[MP_WQ], BAR(i), 0, rk * 256 + (i - 1) * 64, j >> 1, 0);
        }
    } else if (warp == 13) {
        if (lane < NMAPS) asm volatile("prefetch.tensormap [%0];" :: "l"(&M.m[lane]) : "memory");
    } else if (warp == 14) {
        clear_head();
    }
    __syncthreads();
    uint32_t in1 = 0, in2 = 0;
    if (warp < 4) { in1 = *(const uint32_t*)(xin + 2 * tid); in2 = *(const uint32_t*)(xin + 256 + 2 * tid); }
    else if (warp < 12) in1 = *(const uint32_t*)(F.v[1] + 2 * (tid - 128));
    if (warp < 12) asm volatile("cp.async.mbarrier.arrive.noinc.shared::cta.b64 [%0];" :: "r"(BAR(warp < 4)) : "memory");
    asm volatile("barrier.cluster.arrive.relaxed.aligned;" ::: "memory");

    if (warp >= 12) {
    asm volatile("setmaxnreg.dec.sync.aligned.u32 64;");
    if (warp == 12) {
        static_assert(W0 > NCP && W0 <= 5 && NCP >= 1 && NCP <= 4, "W0");
        const uint2* sched = M.sched[j < NFF ? 0 : j < J_RED ? 1 : 2];
        uint2 en = sched[W0];
        const uint32_t t0 = gtime();
        const uint32_t sp = __reduce_or_sync(0xffffffffu, sb);
        const int cx = (j >> 1) * 64 + (j < NFF ? 0 : 1024 - NFF * 32);
#pragma unroll 1
        for (int i = W0; en.x; i++) {
            uint32_t e = en.x, st = (en.y >> 20) * 64;
            const uint32_t tn = t0 + (int16_t)en.y, mp = (en.y >> 16) & 15;
            if (mp == MP_WUV || mp == MP_WUK) { st ^= (j >> 5) * (mp == MP_WUV ? 128 : 64); e ^= (j >> 5) << 6; }
            if (mp == MP_GATE || mp == MP_UP) st ^= (j & 16) * 8;
            if (mp == MP_DOWN) { st ^= (j & 3) * 64; e ^= (j & 3) << 6; }
            en = sched[i + 1];
            if (mp == MP_MODB && j >= J_END) break;
            uint32_t c0 = mp == MP_WO ? (j & 7) * 64 : mp > MP_WO ? cx : 0;
            uint32_t c1 = mp == MP_CKV ? 0 : mp == MP_DOWN ? j * 32 : st + (mp == MP_WUV ? (j & 3) * 32 : mp == MP_WO ? (j >> 3) * 256 : rk * 256);
            uint32_t c2 = mp < MP_CKV ? j >> 1 : mp == MP_CKV ? rk * 4 : mp == MP_WUV ? (j >> 2) * 2 : mp == MP_DOWN ? st >> 5 : 0;
            uint32_t c3 = mp == MP_CKV ? st * 2 + (j & ~1) : 0;
            uint32_t dst = sp + ((e << 7) & 0x3e000), bar = sp + SM_BAR + (e & 63) * 8;
            const uint32_t w0 = (e >> 8) & 0x3f8, w1 = (e >> 15) & 0x3f8, w2 = (e >> 22) & 0x3f8, bb = sp + SM_BAR - 8;
            const CUtensorMap* pm = &M.m[mp];
            pin(dst); pin(bar); pin(c0); pin(c1); pin(c2); pin(c3); pin(pm);
            if (w0) mbar_wait(bb + w0, 0);
            if (w2) {
                mbar_wait(bb + w2, 0);
                while (!__any_sync(0xffffffffu, mbar_test(bb + w1, 0) | ((int)(gtime() - tn) > 0))) {}
            } else if (w1) mbar_wait(bb + w1, 0);
            tma(dst, pm, bar, c0, c1, c2, c3);
        }
    } else if (warp == 13) {
#pragma unroll
        for (int i = 0; i < 2; i++) st_x4(gs + (B_ML + rk * 16 + i * 8 + g) * 4096 + (t >> 1) * 1024 + (j >> 1) * 8 + (t & 1) * 4, 0u, 0u, 0u, 0u);
        if (lane < 16) st2_x4(gs + (B_E2 + (j >> 4)) * 4096 + (j & 15) * 64 + lane * 4, 0u, 0u, 0u, 0u);
        st2_x1(gs + (B_E3 + (j >> 5)) * 4096 + (j & 31) * 32 + lane, 0u);
        if (lane < 8) st2_x1(gs + B_MB * 4096 + j * 8 + lane, 0u);
        if (j < NFF) {
#pragma unroll
            for (int i = 0; i < 2; i++) st2_x4(gs + (B_E5 + i * 8 + g) * 4096 + j * 16 + t * 4, 0u, 0u, 0u, 0u);
        }
        bar_sync(9, 64);
        const uint32_t cs = ldcls();
#pragma unroll 1
        for (int i = 0; i < 32; i++) {
            st_x4(gs + G_E1 + j * 8192 + (i >> 3) * 2048 + ((((cs >> 1) ^ (i >> 3)) & 1) << 10) + (i & 7) * 128 + lane * 4, 0u, 0u, 0u, 0u);
            __nanosleep(JAN_SLEEP);
        }
        fence_gpu();
        if (lane < 8) st2_x1(gs + B_RD * 4096 + j * 8 + lane, 1u + (cs >> 1));
        if (lane == 0) TRACE(41);
        uint32_t rd[4];
        mbar_wait(BAR(IT_CKV + RD_ITEM), 0);
        poll<1024, RD_SLEEP>(rd, gs + near_off(B_RD, cs) + lane * 8);
#pragma unroll
        for (int i = 0; i < 4; i++) {
            const uint32_t m = __ballot_sync(0xffffffffu, rd[i] == 2u);
            if (lane == 0) sts32(sb + SM_CLS + 16 + i * 4, m);
        }
        __syncwarp();
        if (lane < 8) mbar_arrive(BAR(JD));
        if (lane == 0) TRACE(42);
    } else if (warp == 14) {
        uint2 ml[2];
        mbar_waitb(BAR(JD), 0);
        const uint32_t cls = ldcls();
        mbar_waitb(BAR(PF0 + 2 * NUNITS - 1), 0);
        __nanosleep(ML_DELAY);
        const uint32_t* pl2 = gs + near_off(B_ML + (j >> 2), cls) + lane * 8;
        const uint32_t wa = sb + SM_W + lb4 * 64 + t * 16 + (g & 3) * 4;
        poll_start<1024>(ml, pl2);
        uint32_t w0 = 0, w1 = 0, redo = 0;
        bool first = true;
#pragma unroll 1
        for (uint32_t it = 0;; it++) {
            const bool p0 = minw(ml[0]) != 0, p1 = minw(ml[1]) != 0;
            const int n = __popc(__ballot_sync(0xffffffffu, p0)) + __popc(__ballot_sync(0xffffffffu, p1));
            const uint32_t x0 = ml[0].x, x1 = ml[1].x;
            if (n < 64) {
                if (!p0) ld_x(ml[0], pl2);
                if (!p1) ld_x(ml[1], pl2 + 256);
            }
            if (n == 64 || (first && n >= E1_EARLY)) {
                auto ord = [](int x) { return x ^ ((x >> 31) & 0x7fffffff); };
                const int o0 = ord(x0), o1 = ord(x1);
                const float mm = __int_as_float(ord(__reduce_max_sync(0xffffffffu, max(p0 ? o0 : INT_MIN, p1 ? o1 : INT_MIN))));
                const float lo = __int_as_float(ord(__reduce_min_sync(0xffffffffu, min(p0 ? o0 : INT_MAX, p1 ? o1 : INT_MAX))));
                const uint32_t v0 = pack2(ex2((p0 ? __uint_as_float(x0) : lo) - mm), 0.f), v1 = pack2(ex2((p1 ? __uint_as_float(x1) : lo) - mm), 0.f);
                redo = !first && __any_sync(0xffffffffu, v0 != w0 || v1 != w1);
                w0 = v0; w1 = v1;
                sts32(wa - redo * (SM_W - SM_W2), w0 * 0x10001u); sts32(wa - redo * (SM_W - SM_W2) + 128, w1 * 0x10001u);
                if (first) bar_arrive(3, 416);
                first = false;
                if (n == 64) break;
            }
            if (it > SPIN_LIMIT) __trap();
        }
        if (lane == 0) TRACE_Q(37);
        float L = bflo(w0) * __uint_as_float(ml[0].y) + bflo(w1) * __uint_as_float(ml[1].y);
#pragma unroll
        for (int o = 16; o; o >>= 1) L += shx(L, o);
        if (lane == 0) *(float2*)(sm + SM_FQ) = make_float2(__frcp_rn(L), __uint_as_float(redo));
        __syncwarp();
        if (lane < 8) mbar_arrive(BAR(WR));
        if (lane == 0) TRACE(10);
        bar_sync(4, 416);
        clear_head();
        if (j < NFF) {
            uint32_t ya = sb + SM_Y + lane * 16, sa = peer_addr(sb + SM_RED + 2048 + rk * 8, lane & 1), tb = peer_addr(BAR(MBB), lane & 1);
            pin(ya); pin(sa); pin(tb);
            bar_sync(7, 288);
            const float4 y0 = ldsf4(ya), y1 = ldsf4(ya + 512);
            float s = sum4(y0) + sum4(y1);
            float q = (fmaf(y0.x, y0.x, y0.y * y0.y) + fmaf(y0.z, y0.z, y0.w * y0.w)) + (fmaf(y1.x, y1.x, y1.y * y1.y) + fmaf(y1.z, y1.z, y1.w * y1.w));
#pragma unroll
            for (int o = 16; o; o >>= 1) { s += shx(s, o); q += shx(q, o); }
            if (lane < 2) st_async2(sa, s, q, tb);
        }
    } else if (warp == 15) {
        mbar_waitb(BAR(IT_X - 1), 0);
        if (j < J_END) mbar_waitb(BAR(j < NFF ? NITEMS - 1 : MBB), 0);
    }
    } else if (warp < 4) {
        float* scr = (float*)(sm + SM_SCR);
        uint32_t cls;
        {
            uint2 ha[8];
            uint32_t best = 0xffffffffu;
            sts32(sb + SM_SCR + 64 + warp * 4, best);
            const float sh = __shfl_sync(0xffffffffu, bflo(in1), 0);
            const float v0 = bflo(in1) - sh, v1 = bfhi(in1) - sh, v2 = bflo(in2) - sh, v3 = bfhi(in2) - sh;
            float mb, sd;
            ln_stats<4>((v0 + v1) + (v2 + v3), (v0 * v0 + v1 * v1) + (v2 * v2 + v3 * v3), sh, scr, warp, lane, 2, mb, sd);
            if (!rk) in2 = in1;
#pragma unroll 1
            for (int i = 0; i < NPROBE; i++) {
                uint32_t t0, t1, o;
                asm volatile("mov.u32 %0, %%clock;" : "=r"(t0));
                asm volatile("atom.relaxed.gpu.global.exch.b32 %0, [%1], %2;" : "=r"(o) : "l"(pl), "r"(2u + i) : "memory");
                asm volatile("{\n.reg .pred p;\nsetp.ne.u32 p, %1, 0x1234567;\nmov.u32 %0, 0;\n@p mov.u32 %0, %%clock;\n}" : "=r"(t1) : "r"(o));
                best = min(best, t1 - t0);
                sts32(sb + SM_SCR + 64 + warp * 4, best);
                if (__all_sync(0xffffffffu, min(best, lds32(sb + SM_SCR + 64 + (warp ^ 1) * 4)) < NEAR_CLK)) break;
            }
            bar_sync(2, 128);
            const uint4 lt = *(const uint4*)(scr + 16);
            cls = NUMA ? ((lt.y < lt.x) ^ (__popc((B_PR + (j >> 5)) & 0x2C) & 1)) | (lt.w < lt.z) << 1 : 0;
            if (warp == 0) { if (lane == 0) sts32(sb + SM_CLS, cls); bar_arrive(9, 64); }
            if (tid == 0) TRACE(38);
            asm volatile("barrier.cluster.wait.aligned;" ::: "memory");
            mbar_wait(BAR(IT_MODA), 0);
            if (HA_DELAY) __nanosleep(HA_DELAY);
            poll<1024, H_SLEEP, false, 16384>(ha, gs + near_off(B_HA + rk * 2, cls) + 2 * tid);
            auto rsum = [](uint32_t a, uint32_t b, uint32_t c, uint32_t d) { return rbf((__uint_as_float(a) + __uint_as_float(b)) + (__uint_as_float(c) + __uint_as_float(d))); };
            sts32(sb + SM_FV + frag_off(2 * tid),
                  pack2(ln_mod(bflo(in2), mb, sd, rsum(ha[4].x, ha[5].x, ha[6].x, ha[7].x), rsum(ha[0].x, ha[1].x, ha[2].x, ha[3].x)),
                        ln_mod(bfhi(in2), mb, sd, rsum(ha[4].y, ha[5].y, ha[6].y, ha[7].y), rsum(ha[0].y, ha[1].y, ha[2].y, ha[3].y))));
            bar_arrive(5, 384);
            mbar_wait(BAR(QB), 0);
            if (tid < 64) {
                const float* qx = (const float*)(sm + SM_QX) + tid;
                sts16(sb + SM_FQ + frag_off(tid), pack2((qx[0] + qx[64]) + (qx[128] + qx[192]), 0.f));
            }
            bar_arrive(6, 384);
        }
        asm volatile("setmaxnreg.inc.sync.aligned.u32 192;");
        float acc[128];
        float M = 0.f;
        uint32_t pa = sb + SM_XA + warp * 512 + lane * 16, ma = sb + SM_MX + (warp * 8 + g) * 4, pf = BAR(PF0);
        uint32_t blo = __reduce_or_sync(0xffffffffu, (((sb + SM_U) & 0x3FFFFu) >> 4) | 0x400000u);
        uint32_t* e1[4];
#pragma unroll
        for (int i = 0; i < 4; i++) e1[i] = gs + G_E1 + (warp * 8 + g) * 4 * 8192 + (rk * 2 + (j >> 6)) * 2048 + ((j >> 1) & 31) * 32 + t * 4;
#pragma unroll 1
        for (int h = 0; h < 2 * NUNITS; h++) {
            mbar_wait(pf, 0);
            const float m = __uint_as_float(lds32(ma));
            const uint4 pn = lds128(pa);
            wg_wait0();
#pragma unroll
            for (int i = 0; i < 128; i++) asm volatile("" : "+f"(acc[i]) :: "memory");
            if (h == 0) M = m;
            uint32_t b2 = 0x3f803f80u;
            if (__builtin_expect(__any_sync(0xffffffffu, m != M), 0)) {
                const float Mn = fmaxf(M, m), alpha = ex2(M - Mn), beta = ex2(m - Mn);
                M = Mn;
                b2 = pack2(beta, beta);
#pragma unroll
                for (int jj = 0; jj < 32; jj++) { acc[4 * jj] *= alpha; acc[4 * jj + 1] *= alpha; }
            }
            auto mul2 = [](uint32_t x, uint32_t y) { uint32_t r; asm("mul.rn.bf16x2 %0, %1, %2;" : "=r"(r) : "r"(x), "r"(y)); return r; };
            const uint4 p = make_uint4(mul2(pn.x, b2), mul2(pn.y, b2), mul2(pn.z, b2), mul2(pn.w, b2));
            if (tid == 0 && (h & 1)) TRACE_Q(48 + (h >> 1));
            wgmma_pv(acc, p, blo, h);
            if (lane == 0 && h > 0 && !(h & 1)) mbar_arrive(BAR(EB_UNIT0 + (h >> 1) - 1));
            blo += h == 11 ? -11 * 1024 : 1024;
            pa += (h == 5 || h == 11) ? -5 * 2048 : 2048;
            ma += 128; pf += 8;
            if (h == 2 * NUNITS - 3) {
                mbar_wait(BAR(JD), 0);
                const uint32_t hm = (*(const uint32_t*)(sm + SM_CLS + 16 + warp * 4) >> (g * 4)) ^ ((j >> 6) ? 15u : 0u);
#pragma unroll
                for (int i = 0; i < 4; i++) e1[i] += ((hm >> i) & 1) << 10;
            }
        }
#pragma unroll
        for (int vv = 0; vv < 2; vv++) {
            if (vv && M == 1.f) __trap();
            if (vv) wg_wait0(); else wg_wait1();
#pragma unroll
            for (int i = 0; i < 64; i++) asm volatile("" : "+f"(acc[vv * 64 + i]) :: "memory");
            if (tid == 0 && !vv) TRACE_Q(63);
#pragma unroll
            for (int i = 0; i < 4; i++) {
                const float* a = &acc[vv * 64 + i * 16];
                st_x4(e1[i] + i * 8192 + vv * 16, enc(pack2(a[0], a[1])), enc(pack2(a[4], a[5])), enc(pack2(a[8], a[9])), enc(pack2(a[12], a[13])));
            }
        }
        bar_arrive(3, 416);
        if (tid == 0) TRACE_Q(17);
#pragma unroll 1
        for (int pass = 0;; pass++) {
            if (j >= NFF && j < J_END && pass == (j >= J_RED)) {
                uint4 a[8], b[4];
                float c[4], e[4];
                const bool own = (warp >> 1) == rk;
                const uint32_t xa = sb + SM_FV + (warp & 1) * 64 + g * 8;
                if (lane == 0) mbar_expect(BAR(MBB), own ? 64 : 0);
#pragma unroll
                for (int i = 0; i < 2; i++) {
                    ldfrag(b, sb + SM_FS + rk * 512 + i * 256 + t * 16);
                    mbar_wait(BAR(IT_X + i), 0);
                    const uint32_t ab = sb + SM_U + B_X * 32768 + i * 16384 + a128;
                    load8<true>(a, [&](int s) { return ab + s * 2048; });
                    mma8(i ? e : c, a, b);
                }
                c[0] += e[0]; c[2] += e[2];
                if (!own) {
                    if (t == 0) st_async2(peer_addr(xa, rk ^ 1), c[0], c[2], peer_addr(BAR(MBB), rk ^ 1));
                } else {
                    mbar_wait(BAR(MBB), 0);
                    const float2 pp = *(const float2*)(sm + (xa - sb));
                    const float mine = t ? c[2] + pp.y : c[0] + pp.x, other = shx(mine, 4);
                    const uint32_t w = (warp & 1) * 8 + t * 4 + (g >> 1), val = enc(pack2(mine, other));
                    if (t < 2 && !(g & 1)) {
                        if (j < J_RED) st2_x1(gs + B_MB * 4096 + (j - NFF) * 16 + w, val);
                        else sts32(sb + SM_FV + 256 + w * 4, val);
                    }
                    __syncwarp();
                    if (j >= J_RED && lane < 4) mbar_arrive(BAR(QB));
                    if (lane == 0) TRACE(11);
                }
            }
            if (pass) break;
            uint4 a[8], a2[8];
            const uint32_t ab = sb + SM_U + B_WO * 32768 + a128;
            uint32_t* p3 = gs + (B_E3 + ((j >> 1) & 3)) * 4096 + (t >> 1) * 1024 + (rk * 2 + (warp >> 1)) * 256 + (j >> 3) * 16 + (warp & 1) * 8 + (t & 1) * 4 + (g >> 1);
            const uint32_t* pb = gs + near_off(B_E2 + (j >> 4), cls) + (((j >> 3) & 1) * 2 + lb4) * 256 + (lane & 15) * 2;
            pin(p3); pin(pb);
            uint2 bb[8];
#pragma unroll
            for (int i = 0; i < 8; i++) bb[i] = make_uint2(0u, 0u);
            bool h0 = false, h1 = false;
            auto idle = [&]() {
                if (!h0) {
                    h0 = __all_sync(0xffffffffu, mbar_test(BAR(IT_WO + (t & 1)), 0));
                    if (h0) load8<true>(a, [&](int s) { return ab + s * 2048; });
                }
                if (!h1) {
                    h1 = __all_sync(0xffffffffu, mbar_test(BAR(IT_WO + 2 + (t & 1)), 0));
                    if (h1) load8<true>(a2, [&](int s) { return ab + 16384 + s * 2048; });
                }
            };
            bar_sync(4, 416);
            idle();
            poll<128, 0, true>(bb, pb, idle);
            if (tid == 0) TRACE(21);
            float e[4][4];
#pragma unroll
            for (int s = 0; s < 16; s++) {
                if (s == 0 && !h0) { mbar_wait(BAR(IT_WO), 0); mbar_wait(BAR(IT_WO + 1), 0); load8<true>(a, [&](int q) { return ab + q * 2048; }); }
                if (s == 0 && !h1) { mbar_wait(BAR(IT_WO + 2), 0); mbar_wait(BAR(IT_WO + 3), 0); load8<true>(a2, [&](int q) { return ab + 16384 + q * 2048; }); }
                const int z = (s & 1) | (s & 2) << 2 | (s >> 2) << 1;
                const uint4& x = z < 8 ? a[z] : a2[z & 7];
                float (&d)[4] = e[(z >> 3) * 2 + (z & 1)];
                if (!(z & 6)) d[0] = d[1] = d[2] = d[3] = 0.f;
                mma(d, x.x, x.y, x.z, x.w, bb[z & 7].x, bb[z & 7].y);
            }
            float lo, hi;
            quad_pair((t & 2) ? (e[2][0] + e[3][0]) + (e[2][1] + e[3][1]) : (e[0][0] + e[1][0]) + (e[0][1] + e[1][1]),
                      (t & 2) ? (e[2][2] + e[3][2]) + (e[2][3] + e[3][3]) : (e[0][2] + e[1][2]) + (e[0][3] + e[1][3]), t, lo, hi);
            if (!(g & 1)) st_x1(p3, enc(pack2(lo, hi)));
            if (j < NFF) bar_arrive(8, 384); else if (j >= J_RED && j < J_END) bar_arrive(8, 192);
            if (tid == 0) TRACE(22);
        }
        if (j < NFF) {
            uint4 a[16];
            const uint32_t ad = sb + SM_U + B_DN * 32768 + warp * 8192 + (r8 + 8 * lb4) * 128 + (lb3 ^ r8) * 16;
            uint32_t rl = sb + SM_RED + lane * 16;
            uint32_t* p5 = gs + (B_E5 + warp * 4 + (t >> 1)) * 4096 + j * 16 + (t & 1) * 8 + g;
            pin(rl); pin(p5);
            if (lane == 0) mbar_expect(BAR(MBB), 4);
            auto ldd = [&]() {
#pragma unroll
                for (int s = 0; s < 16; s++) a[s] = ldsm<true>((ad ^ ((s & 3) * 32)) + (s >> 2) * 2048);
            };
            const uint32_t db = BAR(IT_DOWN + (warp ^ (j & 3)));
            mbar_wait(BAR(MBB), 0);
            const float4 st = ldsf4(sb + SM_RED + 2048);
            const bool hd = __all_sync(0xffffffffu, mbar_test(db, 0));
            if (hd) ldd();
            const float mu = (st.x + st.z) * (1.f / 512.f);
            float rstd;
            asm volatile("rsqrt.approx.ftz.f32 %0, %1;" : "=f"(rstd) : "f"(fmaxf(fmaf(-mu, mu, (st.y + st.w) * (1.f / 512.f)), 0.f) + 1e-5f));
            mbar_wait(BAR(QB), 1);
            if (tid == 0) TRACE(25);
            const float4 f0 = ldsf4(rl), f2 = ldsf4(rl + 1024), f1 = ldsf4(rl + 512), f3 = ldsf4(rl + 1536);
            const float gg = fmaf(rstd, fmaf(-mu, f0.z + f2.z, (f0.x + f0.y) + (f2.x + f2.y)), f0.w + f2.w);
            const float uu = fmaf(rstd, fmaf(-mu, f1.z + f3.z, (f1.x + f1.y) + (f3.x + f3.y)), f1.w + f3.w);
            const float hh = __fdividef(gg * uu, 1.f + ex2(-gg * fmaf(gg * gg, 0.10294324f, 2.3022082f)));
            uint32_t hb[4];
#pragma unroll
            for (int i = 0; i < 4; i++) hb[i] = pack2(__shfl_sync(0xffffffffu, hh, 2 * t + 8 * i), __shfl_sync(0xffffffffu, hh, 2 * t + 8 * i + 1));
            if (!hd) { mbar_wait(db, 0); ldd(); }
#pragma unroll
            for (int i = 0; i < 2; i++) {
                uint32_t res = 0;
#pragma unroll
                for (int k = 0; k < 4; k++) {
                    float c[4] = {0.f, 0.f, 0.f, 0.f};
                    const uint4 &x = a[i * 8 + k], &y = a[i * 8 + k + 4];
                    mma(c, x.x, x.y, x.z, x.w, hb[0], hb[1]);
                    mma(c, y.x, y.y, y.z, y.w, hb[2], hb[3]);
                    if (t == k) res = pack2(c[0], c[2]);
                }
                st2_x1(p5 + i * 8192, enc(res));
            }
            if (tid == 0) { TRACE(27); TRACE_GT(47); }
        }
    } else {
        const int u8 = tid - 128, w8 = warp - 4;
        const int v = w8 >> 2, wq4 = w8 & 3;
        {
            const float c0 = bflo(in1), c1 = bfhi(in1);
            sts32(sb + SM_FS + frag_off(2 * u8), pack2(__fdividef(c0, 1.f + __expf(-c0)), __fdividef(c1, 1.f + __expf(-c1))));
        }
        bar_sync(1, 256);
        asm volatile("barrier.cluster.wait.aligned;" ::: "memory");
        uint4 a[8], b[4]; float c[4];
        if (w8 < 2) {
            ldfrag(b, sb + SM_FS + (j >> 5) * 256 + t * 16);
            mbar_wait(BAR(IT_MODA), 0);
            if (u8 == 0) TRACE(12);
            const uint32_t ab = sb + SM_XA + w8 * 4096 + a16;
            load8<true>(a, [&](int s) { return ab + s * 512; });
            mma8(c, a, b);
            if (t < 2) st2_x1(gs + (B_HA + ((j >> 4) & 1) * 2 + w8) * 4096 + (j >> 5) * 256 + (j & 15) * 16 + t * 8 + g, encf(t ? c[2] : c[0]));
        }
        {
            mbar_wait(BAR(IT_WQ + 2 * v <= NCP ? 1 : IT_WQ + 2 * v), 0); mbar_wait(BAR(IT_WQ + 2 * v + 1 <= NCP ? 1 : IT_WQ + 2 * v + 1), 0);
            const uint32_t ab = sb + SM_U + 4 * 32768 + v * 16384 + a128;
            load8<true>(a, [&](int s) { return ab + s * 2048; });
            if (lane == 0) mbar_arrive(BAR(EB_WQ));
            bar_sync(5, 384);
            if (u8 == 0) TRACE(13);
            ldfrag(b, sb + SM_FV + v * 256 + t * 16);
            mma8(c, a, b);
            if (t < 2) {
                const float qv = t ? c[2] : c[0];
                const uint32_t qa_ = sb + SM_QX + ((rk * 2 + v) * 64 + wq4 * 16 + t * 8 + g) * 4;
                asm volatile("st.async.weak.shared::cluster.mbarrier::complete_tx::bytes.f32 [%0], %1, [%2];"
                             :: "r"(peer_addr(qa_, rk ^ 1)), "f"(qv), "r"(peer_addr(BAR(QB), rk ^ 1)) : "memory");
                sts32(qa_, __float_as_uint(qv));
            }
            __syncwarp();
            if (lane == 0) mbar_expect(BAR(QB), 64);
        }
        {
            mbar_wait(BAR(IT_WUK + (v ^ ((j >> 5) & 1))), 0); mbar_wait(BAR(IT_WUK + (v ^ ((j >> 5) & 1)) + 2), 0);
            const uint32_t ab = sb + SM_U + 5 * 32768 + (w8 * 16 + r8 + 8 * lb3) * 128;
            const uint32_t x16 = (lb4 ^ r8) * 16;
            load8<false>(a, [&](int s) { return ab + (s & 1) * 16384 + (x16 ^ ((s >> 1) * 32)); });
            bar_sync(6, 384);
            if (u8 == 0) TRACE(14);
            b[0] = lds128(sb + SM_FQ + t * 16); b[1] = lds128(sb + SM_FQ + 64 + t * 16);
            float e[4] = {0.f, 0.f, 0.f, 0.f};
            c[0] = c[1] = c[2] = c[3] = 0.f;
#pragma unroll
            for (int k = 0; k < 4; k++) {
                const uint32_t b0 = (k & 1) ? b[k >> 1].z : b[k >> 1].x, b1 = (k & 1) ? b[k >> 1].w : b[k >> 1].y;
                mma(c, a[2 * k].x, a[2 * k].y, a[2 * k].z, a[2 * k].w, b0, b1);
                mma(e, a[2 * k + 1].x, a[2 * k + 1].y, a[2 * k + 1].z, a[2 * k + 1].w, b0, b1);
            }
            const float mine = ((t & 1) ? ((t & 2) ? e[2] : e[0]) : ((t & 2) ? c[2] : c[0])) * 0.12751743f;
            const float other = shx(mine, 4);
            if (!(g & 1)) st2_x1(gs + (B_QA + rk * 8 + ((j >> 1) & 1) * 4 + (j >> 5)) * 4096 + w8 * 128 + ((j >> 2) & 7) * 16 + (g >> 1) * 4 + t, enc(pack2(mine, other)));
            if (u8 == 0) TRACE(15);
        }
        const uint32_t cls = ldcls();
        __nanosleep(QA_DELAY);
        {
            uint4 qb[8];
            const uint32_t* pq = gs + near_off(B_QA + rk * 8 + wq4, cls) + lane * 4;
            const uint32_t* pq2 = gs + near_off(B_QA + rk * 8 + 4 + wq4, cls) + lane * 4;
            if (lane == 0) {
                mbar_expect(BAR(QT), 4096);
                asm volatile("cp.async.bulk.shared::cluster.global.mbarrier::complete_tx::bytes [%0], [%1], 4096, [%2];"
                             :: "r"(sb + SM_U + 5 * 32768 + w8 * 4096), "l"(gs + near_off(B_QA + rk * 8 + w8, cls)), "r"(BAR(QT)) : "memory");
            }
            const uint32_t qs = sb + SM_U + 5 * 32768 + wq4 * 4096 + lane * 16;
            mbar_wait(BAR(QT), 0);
#pragma unroll
            for (int i = 0; i < 8; i++) { a[i] = lds128(qs + i * 512); qb[i] = lds128(qs + 16384 + i * 512); }
            poll<512, QA_SLEEP, true>(a, pq);
            poll<512, QA_SLEEP, true>(qb, pq2);
            if (lane == 0) mbar_arrive(BAR(EB_WUK));
            auto add2 = [](uint32_t x, uint32_t y) { uint32_t r; asm("add.rn.bf16x2 %0, %1, %2;" : "=r"(r) : "r"(x), "r"(y)); return r; };
#pragma unroll
            for (int i = 0; i < 8; i++) a[i] = make_uint4(add2(a[i].x, qb[i].x), add2(a[i].y, qb[i].y), add2(a[i].z, qb[i].z), add2(a[i].w, qb[i].w));
        }
        if (u8 == 0) TRACE(8);
        {
            float m = -INFINITY, l = 0.f;
            uint32_t xl = sb + SM_XB + w8 * 2048 + lane * 16, xr = peer_addr(xl, rk ^ 1), bsr = peer_addr(BAR(SF0 + v), rk ^ 1);
            uint32_t pa = sb + SM_XA + v * 2048 + wq4 * 512 + lane * 16, ma = sb + SM_MX + v * 128 + (wq4 * 8 + g) * 4;
            uint32_t fb = BAR(IT_CKV + v * 2), sf = BAR(SF0 + v);
            uint32_t dlo = __reduce_or_sync(0xffffffffu, (((sb + SM_U + v * 16384) & 0x3FFFFu) >> 4) | 0x10000u);
            if (STAG && v) __nanosleep(STAG);
#pragma unroll 1
            for (int n = 0; n < NUNITS; n++) {
                float d[2][16], sc[8];
#pragma unroll
                for (int i = 0; i < 2; i++) {
                    mbar_wait(fb + i * 8, 0);
                    wg_fence();
#pragma unroll
                    for (int s = 0; s < 8; s++) wgmma_rs_n32(d[i], a[s], (0x40000080ull << 32) | (dlo + i * 512 + (s >> 2) * 64 + (s & 3) * 2), s);
                    wg_commit();
                }
#pragma unroll
                for (int i = 0; i < 2; i++) {
                    if (i) wg_wait0(); else wg_wait1();
#pragma unroll
                    for (int k = 0; k < 16; k++) asm volatile("" : "+f"(d[i][k]) :: "memory");
                    sc[4 * i] = d[i][0] + d[i][6]; sc[4 * i + 1] = d[i][1] + d[i][7]; sc[4 * i + 2] = d[i][8] + d[i][14]; sc[4 * i + 3] = d[i][9] + d[i][15];
                    asm volatile("st.async.weak.shared::cluster.mbarrier::complete_tx::bytes.v4.f32 [%0], {%1, %2, %3, %4}, [%5];"
                                 :: "r"(xr + i * 1024), "f"(sc[4 * i]), "f"(sc[4 * i + 1]), "f"(sc[4 * i + 2]), "f"(sc[4 * i + 3]), "r"(bsr) : "memory");
                }
                if (u8 == 128) TRACE_Q(56 + (n < 6 ? n : -40));
                if (n >= 3) mbar_wait(BAR(EB_UNIT0 + n - 3), 0);
                dlo += n == 5 ? -5 * 2048 : 2048;
                fb += 32; xr ^= 512; bsr += 16;
                pin(fb); pin(xr); pin(bsr);
                mbar_wait(sf, 0);
                const float4 x = ldsf4(xl), y = ldsf4(xl + 1024);
                sc[0] += x.x; sc[1] += x.y; sc[2] += x.z; sc[3] += x.w; sc[4] += y.x; sc[5] += y.y; sc[6] += y.z; sc[7] += y.w;
                float pr[8];
#pragma unroll
                for (int i = 0; i < 8; i++) pr[i] = ex2(sc[i] - m);
                float mx = fmaxf(fmaxf(fmaxf(sc[0], sc[1]), fmaxf(sc[2], sc[3])), fmaxf(fmaxf(sc[4], sc[5]), fmaxf(sc[6], sc[7])));
                if (__builtin_expect(__any_sync(0xffffffffu, mx > m), 0)) {
                    mx = fmaxf(mx, shx(mx, 1));
                    mx = fmaxf(mx, shx(mx, 2));
                    const float mn = fmaxf(m, ceilf(mx * 0.0625f) * 16.f);
                    l *= ex2(m - mn);
                    m = mn;
#pragma unroll
                    for (int i = 0; i < 8; i++) pr[i] = ex2(sc[i] - m);
                }
                stsf(ma, m);
                asm volatile("st.shared.v4.u32 [%0], {%1, %2, %3, %4};" :: "r"(pa), "r"(pack2(pr[0], pr[1])), "r"(pack2(pr[2], pr[3])),
                             "r"(pack2(pr[4], pr[5])), "r"(pack2(pr[6], pr[7])) : "memory");
                __syncwarp();
                if (lane == 0) mbar_arrive(sf + (PF0 - SF0) * 8);
                l += ((pr[0] + pr[1]) + (pr[2] + pr[3])) + ((pr[4] + pr[5]) + (pr[6] + pr[7]));
                xl ^= 512; sf += 16; ma += 256; pa += (n == 2 || n == 5) ? -8192 : 4096;
            }
            l += shx(l, 1);
            l += shx(l, 2);
            float2* mlx = (float2*)(sm + SM_MX + 2048) + wq4 * 8 + g;
            if (v == 0) { *mlx = make_float2(m, l); bar_arrive(11, 256); }
            else {
                mbar_wait(BAR(JD), 0);
                bar_sync(11, 256);
                const float2 o = *mlx;
                const float mn = fmaxf(m, o.x);
                l = l * ex2(m - mn) + o.y * ex2(o.x - mn);
                if ((wq4 >> 1) == rk) st_x4(gs + (B_ML + wq4 * 8 + g) * 4096 + (t >> 1) * 1024 + (j >> 1) * 8 + (t & 1) * 4, encf(mn), encf(l), 1u, 1u);
            }
        }
        const int pi = j < NFF ? rk * 128 + w8 * 16 + (lane & 15) : ((j - J_RED) & 15) * 16 + (w8 & 1) * 8 + g;
        const uint32_t xw = *(const uint32_t*)(xin + 2 * pi);
        const uint32_t* pm = gs + near_off(B_MB, cls) + pi;
        {
            const uint32_t ab = sb + SM_U + B_WUV * 32768 + v * 4096 + a128;
            uint32_t pa = sb + SM_PB + wq4 * 320 + frag_off(64 * v + 32 * (g >> 2) + 16 * (t & 1) + 8 * (t >> 1) + 2 * (g & 3));
            uint32_t fa = sb + SM_PB + g * 320 + t * 16;
            const uint32_t* pe = gs + G_E1 + j * 8192 + (w8 >> 1) * 2048 + ((((cls >> 1) ^ (w8 >> 1)) & 1) << 10) + (((w8 & 1) * 16 + t) * 8 + g) * 4;
            uint32_t* p2 = gs + (B_E2 + (j >> 4)) * 4096 + (t >> 1) * 1024 + (j & 12) * 64 + w8 * 32 + (j & 3) * 8 + (g & 6) + (t & 1);
            pin(pa); pin(fa); pin(pe); pin(p2);
            const uint32_t mk = (g & 1) ? 0xffff0000u : 0x0000ffffu, m0 = (g & 2) ? 0u : mk, m1 = (g & 2) ? mk : 0u;
            uint4 pv[4];
            bool hv = false;
            bar_sync(3, 416);
            uint4 wa = lds128(sb + SM_W + (wq4 * 4 + t) * 16);
            uint32_t wb[8] = {wa.x & m0, wa.x & m1, wa.y & m0, wa.y & m1, wa.z & m0, wa.z & m1, wa.w & m0, wa.w & m1};
            pv[0] = pv[1] = pv[2] = pv[3] = make_uint4(0u, 0u, 0u, 0u);
            poll<512, E1_SLEEP, true>(pv, pe, [&]() {
                if (!hv) {
                    hv = __all_sync(0xffffffffu, mbar_test(BAR(IT_WUV + t), 0));
                    if (hv) load8<true>(a, [&](int s) { return ab + (s >> 1) * 8192 + (s & 1) * 2048; });
                }
            });
            if (lane == 0) TRACE_Q(48 + w8);
            if (u8 == 0) TRACE_Q(18);
            float lo, hi2;
            float2 inv;
#pragma unroll 1
            for (int pass = 0;; pass++) {
                float e[4][4];
#pragma unroll
                for (int i = 0; i < 4; i++) {
                    e[i][0] = e[i][1] = e[i][2] = e[i][3] = 0.f;
                    mma(e[i], pv[i].x, pv[i].y, pv[i].z, pv[i].w, wb[2 * i], wb[2 * i + 1]);
                }
                const float r0 = (t & 2) ? (e[0][2] + e[1][2]) + (e[2][2] + e[3][2]) : (e[0][0] + e[1][0]) + (e[2][0] + e[3][0]);
                const float r1 = (t & 2) ? (e[0][3] + e[1][3]) + (e[2][3] + e[3][3]) : (e[0][1] + e[1][1]) + (e[2][1] + e[3][1]);
                const uint32_t hi = pack2(r0, r1);
                sts32(pa, hi); sts32(pa + 1280, pack2(r0 - bflo(hi), r1 - bfhi(hi)));
                if (!hv) {
#pragma unroll 1
                    for (int i = 0; i < 4; i++) mbar_wait(BAR(IT_WUV + i), 0);
                    load8<true>(a, [&](int s) { return ab + (s >> 1) * 8192 + (s & 1) * 2048; });
                    hv = true;
                }
                bar_sync(1, 256);
                if (u8 == 0) TRACE(19);
                ldfrag(b, fa);
                mma8(c, a, b);
                mbar_wait(BAR(WR), 0);
                asm volatile("ld.shared.v2.f32 {%0, %1}, [%2];" : "=f"(inv.x), "=f"(inv.y) : "r"(sb + SM_FQ) : "memory");
                quad_pair(c[0] + c[1], c[2] + c[3], t, lo, hi2);
                if (__builtin_expect(__all_sync(0xffffffffu, pass || __float_as_uint(inv.y) == 0), 1)) break;
                wa = lds128(sb + SM_W2 + (wq4 * 4 + t) * 16);
                wb[0] = wa.x & m0; wb[1] = wa.x & m1; wb[2] = wa.y & m0; wb[3] = wa.y & m1; wb[4] = wa.z & m0; wb[5] = wa.z & m1; wb[6] = wa.w & m0; wb[7] = wa.w & m1;
                bar_sync(1, 256);
            }
            if (!(g & 1)) st_x1(p2, enc(pack2(lo * inv.x, hi2 * inv.x)));
            bar_arrive(4, 416);
            if (u8 == 0) TRACE(20);
        }
        if (j < NFF) {
            const uint32_t* p3 = gs + near_off(B_E3 + rk * 2 + v, cls) + wq4 * 256 + lane;
            uint32_t za = sb + SM_FZ + lb4 * 576 + frag_off(w8 * 32 + (lane & 15) * 2);
            uint32_t fa = sb + SM_FZ + (g & 3) * 576 + ((lane ^ j) & 16) * 16 + t * 16, ya = sb + SM_Y + u8 * 4;
            uint32_t mb[3];
            uint4 a2[8];
            poll<1024, MB_SLEEP>(mb, pm);
            const uint32_t kk = pack2(1.f + bflo(mb[2]), 1.f + bfhi(mb[2]));
            sts32(za + 2 * 576, lb4 ? mb[1] : kk);
            uint32_t e3[8] = {0u, 0u, 0u, 0u, 0u, 0u, 0u, 0u};
            uint32_t ra = peer_addr(sb + SM_RED + (rk * 2 + v) * 512 + ((wq4 & 1) * 16 + (t >> 1) * 8 + g) * 16 + (t & 1) * 8, wq4 >> 1), tbo = peer_addr(BAR(QB), wq4 >> 1);
            pin(za); pin(fa); pin(ya); pin(ra); pin(tbo);
            if (lane == 0) mbar_expect(BAR(QB), 256);
            const uint32_t gb = BAR(IT_X + v * 2), ab = sb + SM_U + (B_X + v) * 32768 + a128;
            bool early = false, early2 = false;
            auto ldw = [&]() {
                if (!early) {
                    early = __all_sync(0xffffffffu, mbar_test(gb, 0));
                    if (early) load8<true>(a, [&](int s) { return ab + s * 2048; });
                }
                if (!early2) {
                    early2 = __all_sync(0xffffffffu, mbar_test(gb + 8, 0));
                    if (early2) load8<true>(a2, [&](int s) { return ab + 16384 + s * 2048; });
                }
            };
            bar_sync(8, 384);
            poll<128, 0, true>(e3, p3, ldw);
            if (u8 == 0) TRACE(23);
            const float s0 = sumlo(e3), s1 = sumhi(e3);
            const float y0 = fmaf(bflo(mb[0]), s0 + shx(s0, 16), bflo(xw)), y1 = fmaf(bfhi(mb[0]), s1 + shx(s1, 16), bfhi(xw));
            stsf(ya, lb4 ? y1 : y0);
            const float z0 = y0 * bflo(kk), z1 = y1 * bfhi(kk);
            const uint32_t zh = pack2(z0, z1);
            sts32(za, lb4 ? pack2(z0 - bflo(zh), z1 - bfhi(zh)) : zh);
            bar_sync(7, 288);
            if (u8 == 0) TRACE(24);
            ldfrag(b, fa);
            if (!early) { mbar_wait(gb, 0); load8<true>(a, [&](int s) { return ab + s * 2048; }); }
            {
                float e[4][4];
#pragma unroll
                for (int s = 0; s < 16; s++) {
                    if (s == 8 && !early2) { mbar_wait(gb + 8, 0); load8<true>(a2, [&](int q) { return ab + 16384 + q * 2048; }); }
                    const uint4& x = s < 8 ? a[s] : a2[s & 7];
                    const uint4& y = b[(s >> 1) & 3];
                    float (&d)[4] = e[(s >> 3) * 2 + (s & 1)];
                    if (!(s & 6)) d[0] = d[1] = d[2] = d[3] = 0.f;
                    mma(d, x.x, x.y, x.z, x.w, (s & 1) ? y.z : y.x, (s & 1) ? y.w : y.y);
                }
                const bool hi = t >> 1;
                const float k0 = hi ? e[2][2] + e[3][2] : e[0][0] + e[1][0], k1 = hi ? e[2][3] + e[3][3] : e[0][1] + e[1][1];
                const float o0 = hi ? e[2][0] + e[3][0] : e[0][2] + e[1][2], o1 = hi ? e[2][1] + e[3][1] : e[0][3] + e[1][3];
                st_async2(ra, k0 + shx(o0, 2), k1 + shx(o1, 2), tbo);
            }
        } else if (j >= J_RED && j < J_END && w8 < 2) {
            uint32_t ga[1], e3[4];
            poll<0, MB_SLEEP>(ga, pm);
            bar_sync(8, 192);
            poll<64, 100>(e3, gs + near_off(B_E3 + (pi >> 6), cls) + (pi & 48) * 16 + t * 64 + (pi & 15));
            float y0 = (bflo(e3[0]) + bflo(e3[1])) + (bflo(e3[2]) + bflo(e3[3])), y1 = (bfhi(e3[0]) + bfhi(e3[1])) + (bfhi(e3[2]) + bfhi(e3[3]));
#pragma unroll
            for (int o = 1; o < 4; o <<= 1) { y0 += shx(y0, o); y1 += shx(y1, o); }
            const int col = g + (t & 1) * 8;
            y0 = __shfl_sync(0xffffffffu, (t & 1) ? fmaf(bfhi(ga[0]), y1, bfhi(xw)) : fmaf(bflo(ga[0]), y0, bflo(xw)), (col >> 1) * 4 + (col & 1));
            uint32_t gb = 0;
            auto ldg = [&]() { if (__all_sync(0xffffffffu, mbar_test(BAR(QB), 1))) gb = lds32(sb + SM_FV + 256 + w8 * 32 + (col >> 1) * 4); };
            uint16_t* po = (uint16_t*)out + (j - J_RED) * 32 + w8 * 16 + col;
            pin(po);
            uint32_t yv[NFF / 4];
            poll<256, 0>(yv, gs + near_off(B_E5 + j - J_RED, cls) + t * 16 + w8 * 8 + g, ldg);
            if (u8 == 0) TRACE(26);
            const uint32_t one = (g & 1) ? 0x3f800000u : 0x00003f80u;
            float e[4][4];
#pragma unroll
            for (int i = 0; i < 4; i++) {
                e[i][0] = e[i][1] = e[i][2] = e[i][3] = 0.f;
                mma(e[i], yv[4 * i], yv[4 * i + 1], i < 3 ? yv[(4 * i + 2) % (NFF / 4)] : 0u, i < 3 ? yv[(4 * i + 3) % (NFF / 4)] : 0u, one, one);
            }
            const float s = (t & 1) ? ((e[0][1] + e[0][3]) + (e[1][1] + e[1][3])) + ((e[2][1] + e[2][3]) + (e[3][1] + e[3][3]))
                                    : ((e[0][0] + e[0][2]) + (e[1][0] + e[1][2])) + ((e[2][0] + e[2][2]) + (e[3][0] + e[3][2]));
            if (__any_sync(0xffffffffu, !gb)) { mbar_wait(BAR(QB), 1); ldg(); }
            if (t < 2) *po = (uint16_t)pack2(fmaf((col & 1) ? bfhi(gb) : bflo(gb), s, y0), 0.f);
            if (u8 == 0) TRACE(27);
        }
    }
}

typedef CUresult (*EncFn)(CUtensorMap*, CUtensorMapDataType, cuuint32_t, void*, const cuuint64_t*, const cuuint64_t*,
                          const cuuint32_t*, const cuuint32_t*, CUtensorMapInterleave, CUtensorMapSwizzle,
                          CUtensorMapL2promotion, CUtensorMapFloatOOBfill);

void make_map(EncFn enc_fn, CUtensorMap* m, const void* p, cuuint64_t d0, cuuint64_t d1, cuuint64_t d2, cuuint64_t d3,
              cuuint64_t s1, cuuint64_t s2, cuuint64_t s3, cuuint32_t b0, cuuint32_t b1, cuuint32_t b2, cuuint32_t b3, CUtensorMapSwizzle sw) {
    const cuuint64_t dims[4] = {d0, d1, d2, d3}, strides[3] = {s1, s2, s3};
    const cuuint32_t box[4] = {b0, b1, b2, b3}, es[4] = {1, 1, 1, 1};
    enc_fn(m, CU_TENSOR_MAP_DATA_TYPE_BFLOAT16, 4, (void*)p, dims, strides, box, es,
           CU_TENSOR_MAP_INTERLEAVE_NONE, sw, PROMO, CU_TENSOR_MAP_FLOAT_OOB_FILL_NONE);
}

uint32_t* scratch = nullptr;

struct Tune { const char* win; const char* late; int tau, t_off; const char* tail[3][4]; };
Tune tune = {"66666666655555555555555555555555555533333",
             "00000000000000000000999999999999999999999", 320, -300,
             {{"VVVVOOOOguguDDDD", "zzzzzzzzzzzzzzzz", "888899998888789a", "ibbb0gjj7aaa3787"},
              {"VMVMVVOOOO", "zzzzzzzzzz", "8888889999", "588888kbbb"},
              {"VVVVOOOOMM", "zzzzzzzzzz", "aaaaaaaa88", "q8880cjjon"}}};
bool ready = false;

}

extern "C" void kernel_launch(void* const* d_in, const int* in_sizes, int n_in, void* d_out, int out_size) {
    (void)in_sizes; (void)n_in; (void)out_size;
    static Maps maps;
    static const void* cached[12] = {};
    bool same = ready;
    for (int i = 0; i < 12 && same; i++) same = cached[i] == d_in[i];
    if (!same) {
        void* fn = nullptr;
        cudaDriverEntryPointQueryResult qr;
        cudaGetDriverEntryPoint("cuTensorMapEncodeTiled", &fn, cudaEnableDefault, &qr);
        EncFn e = (EncFn)fn;
        const CUtensorMapSwizzle S128 = CU_TENSOR_MAP_SWIZZLE_128B;
        make_map(e, &maps.m[MP_WQ], d_in[2], 64, 512, 64, 1, 8192, 128, 8192, 64, 64, 1, 1, S128);
        make_map(e, &maps.m[MP_WUK], d_in[3], 64, 512, 64, 1, 8192, 128, 8192, 64, 64, 1, 1, S128);
        make_map(e, &maps.m[MP_CKV], d_in[1], 64, 8, 8, 4096, 1024, 128, 8192, 64, 8, 4, 2, S128);
        make_map(e, &maps.m[MP_MODB], d_in[11], 3072, 512, 1, 1, 6144, 6144, 6144, 64, 128, 1, 1, S128);
        make_map(e, &maps.m[MP_WUV], d_in[4], 64, 512, 64, 1, 8192, 128, 8192, 64, 32, 2, 1, S128);
        make_map(e, &maps.m[MP_WO], d_in[5], 512, 4096, 1, 1, 1024, 1024, 1024, 64, 64, 1, 1, S128);
        make_map(e, &maps.m[MP_GATE], d_in[7], 1792, 512, 1, 1, 3584, 3584, 3584, 64, 128, 1, 1, S128);
        make_map(e, &maps.m[MP_UP], d_in[8], 1792, 512, 1, 1, 3584, 3584, 3584, 64, 128, 1, 1, S128);
        make_map(e, &maps.m[MP_DOWN], d_in[9], 64, 1792, 8, 1, 1024, 128, 1024, 64, 32, 2, 1, S128);
        for (int r = 0; r < 3; r++) {
            int ids[58], cnt[128] = {}, tn = tune.t_off - (W0 - 1) * tune.tau;
            uint2* sc = maps.sched[r];
            auto dig = [](char ch) { return ch >= 'a' ? ch - 'a' + 10 : ch >= 'A' ? ch - 'A' + 36 : ch - '0'; };
            for (int i = 0; i < 58; i++) sc[i] = make_uint2(0u, 0u);
            for (int i = 0;; i++) {
                int id = i, buf, dep, w, wl;
                if (i < IT_WUV) {
                    const int u = (i - IT_CKV) >> 2;
                    buf = i < IT_CKV ? 4 + ((i - 1) >> 2) : u % 6;
                    dep = i < IT_CKV || u < 4 ? -1 : u < 6 ? EB_WQ + u - 4 : EB_UNIT0 + u - 6;
                    w = dig(tune.win[i]); wl = dig(tune.late[i]);
                    if (i) tn += tune.tau;
                } else {
                    const char ch = tune.tail[r][0][i - IT_WUV];
                    if (!ch) break;
                    buf = ch == 'V' ? B_WUV : ch == 'O' ? B_WO : ch == 'D' ? B_DN : ch == 'u' ? B_X + 1 : B_X;
                    id = (ch == 'V' ? IT_WUV : ch == 'O' ? IT_WO : ch == 'D' ? IT_DOWN : ch == 'u' ? IT_X + 2 : IT_X) + cnt[(int)ch]++;
                    dep = EB_UNIT0 + (buf < 2 ? buf + 6 : buf);
                    w = dig(tune.tail[r][1][i - IT_WUV]); wl = dig(tune.tail[r][2][i - IT_WUV]);
                    tn += 32 * dig(tune.tail[r][3][i - IT_WUV]);
                }
                if (id < IT_X || id >= IT_DOWN ? (id - 1) & 3 : (id - IT_X) & 1) dep = -1;
                ids[i] = id;
                auto back = [&](int d) { return i < d ? 0 : (ids[i - d] && ids[i - d] <= NCP ? 1 : ids[i - d]) + 1; };
                sc[i].x = id | (buf * 4 + (id < IT_X || id >= IT_DOWN ? (id - 1) & 3 : ((id - IT_X) & 1) * 2)) << 6 | (dep + 1) << 11 | (w > 32 ? NEVER + 1 : back(w)) << 18 | (wl ? back(wl) : 0) << 25;
                const int mp = id < IT_CKV ? MP_WQ + ((id - 1) >> 2) : id < IT_WUV ? MP_CKV : id < IT_WO ? MP_WUV : id < IT_X ? MP_WO
                             : id >= IT_DOWN ? MP_DOWN : r ? MP_MODB : MP_GATE + ((id - IT_X) >> 1);
                const int step = mp == MP_CKV ? id - IT_CKV : mp == MP_WUV ? (id - IT_WUV) * 2 : mp == MP_DOWN ? id - IT_DOWN : id < IT_X ? (id - 1) & 3 : ((id - IT_X) & 1) * 2;
                sc[i].y = (tn & 0xffff) | (mp & 15) << 16 | step << 20;
            }
        }
        cudaGetSymbolAddress((void**)&scratch, g_scratch);
        scratch = (uint32_t*)(((uintptr_t)scratch + (2u << 20) - 1) & ~(uintptr_t)((2u << 20) - 1));
        cudaFuncSetAttribute(fused_kernel, cudaFuncAttributeMaxDynamicSharedMemorySize, SM_TOTAL);
        for (int i = 0; i < 12; i++) cached[i] = d_in[i];
        ready = true;
    }
    const First f = {{(const uint8_t*)d_in[2], (const uint8_t*)d_in[11]}, {(const __nv_bfloat16*)d_in[0], (const __nv_bfloat16*)d_in[10]}};
    fused_kernel<<<NCTA, NTHREADS, SM_TOTAL>>>(f, (__nv_bfloat16*)d_out, scratch, maps);
}
```

```cpp
#include <cuda_runtime.h>
#include <cuda_bf16.h>
#include <cuda.h>
#include <stdint.h>
#include <limits.h>

namespace {

constexpr int NCTA = 128;
constexpr int NTHREADS = 512;
constexpr int NUNITS = 8;
constexpr int NFF = 56, J_RED = 104, J_END = 120;
constexpr uint32_t SPIN_LIMIT = 1u << 22;

#define PROMO CU_TENSOR_MAP_L2_PROMOTION_L2_64B
#define NEAR_CLK 390
#define E1_EARLY 50
#define STAG 300
#define NUMA 1
#define NPROBE 5
#define NCP 2
#define W0 4
#define RD_ITEM 15
#define JAN_SLEEP 100
#define RD_SLEEP 400
#define HA_DELAY 200
#define H_SLEEP 100
#define QA_DELAY 600
#define QA_SLEEP 200
#define ML_DELAY 300
#define E1_SLEEP 50
#define MB_SLEEP 100
constexpr int B_WUV = 2, B_WO = 3, B_X = 4  , B_DN = 0;

constexpr int SM_U = 0;
constexpr int SM_XA = 6 * 32768;
constexpr int SM_XB = SM_XA + 12288;
constexpr int SM_MX = SM_XB + 16384;
constexpr int SM_FZ = SM_XB + 8192;
constexpr int SM_PB = SM_XB;
constexpr int SM_Y = SM_XB + 12288;
constexpr int SM_RED = SM_XB + 4096;
constexpr int SM_FS = SM_XB + 20480;
constexpr int SM_FV = SM_FS + 1024;
constexpr int SM_QX = SM_XA + 8192;
constexpr int SM_FQ = SM_FV + 512;
constexpr int SM_CLS = SM_FQ + 128;
constexpr int SM_W = SM_FQ + 256;
constexpr int SM_W2 = SM_MX + 2304;
constexpr int SM_SCR = SM_XA + 9216;
constexpr int SM_TR = SM_XB + 19456;
constexpr int SM_BAR = SM_W + 256;
constexpr int SM_TOTAL = SM_BAR + 1024;
static_assert(SM_TOTAL <= 232448, "smem");

enum { IT_MODA = 0, IT_WQ = 1, IT_WUK = 5, IT_CKV = 9, IT_WUV = 41, IT_WO = 45, IT_X = 49  , IT_DOWN = 53, NITEMS = 57,
       NEVER = 63,
       SF0 = 64,
       PF0 = 80,
       EB_UNIT0 = 96, MBB = 103,
       EB_WQ = 104, EB_WUK, QT, QB, JD, WR };

enum { MP_WQ = 0, MP_WUK, MP_CKV, MP_WUV, MP_DOWN, MP_WO, MP_GATE, MP_UP, MP_MODB, NMAPS };
struct First { const uint8_t* w[2]; const __nv_bfloat16* v[2]; };
struct Maps { CUtensorMap m[NMAPS]; uint2 sched[3][58]; };

enum { B_HA = 0,
       B_MB = 6,
       B_RD = 7,
       B_E2 = 8,
       B_QA = 16,
       B_ML = 32,
       B_E5 = 64,
       B_E3 = 80,
       B_PR = 96,
       B_TR = 100 };
constexpr int G_E1 = 1 << 19;
constexpr int G_TR = B_TR * 4096;
__device__ __align__(1024) uint32_t g_scratch[(8 << 20) / 4];

#define TRACE(slot) do {} while (0)
#define TRACE_Q(slot) do {} while (0)
#define TRACE_GT(slot) do {} while (0)

__device__ __forceinline__ uint32_t s2u(const void* p) { return (uint32_t)__cvta_generic_to_shared(p); }
__device__ __forceinline__ void mbar_init(uint32_t b, int c) { asm volatile("mbarrier.init.shared::cta.b64 [%0], %1;" :: "r"(b), "r"(c) : "memory"); }
__device__ __forceinline__ void mbar_expect(uint32_t b, uint32_t bytes) { asm volatile("mbarrier.arrive.expect_tx.shared::cta.b64 _, [%0], %1;" :: "r"(b), "r"(bytes) : "memory"); }
__device__ __forceinline__ void mbar_arrive(uint32_t b) { asm volatile("mbarrier.arrive.shared::cta.b64 _, [%0];" :: "r"(b) : "memory"); }
__device__ __forceinline__ void mbar_wait(uint32_t b, uint32_t ph) {
    asm volatile("{\n.reg .pred p;\nW: mbarrier.try_wait.parity.shared::cta.b64 p, [%0], %1;\n@!p bra W;\n}" :: "r"(b), "r"(ph) : "memory");
}
__device__ __forceinline__ void mbar_waitb(uint32_t b, uint32_t ph) {
    asm volatile("{\n.reg .pred p;\n.reg .u32 n;\nmov.u32 n, 0;\n"
                 "W: mbarrier.try_wait.parity.shared::cta.b64 p, [%0], %1;\n@p bra D;\n"
                 "add.u32 n, n, 1;\nsetp.lt.u32 p, n, 0x100000;\n@p bra W;\ntrap;\nD:\n}" :: "r"(b), "r"(ph) : "memory");
}
__device__ __forceinline__ uint32_t mbar_test(uint32_t b, uint32_t ph) {
    uint32_t ok;
    asm volatile("{\n.reg .pred p;\nmbarrier.test_wait.parity.shared::cta.b64 p, [%1], %2;\nselp.u32 %0, 1, 0, p;\n}" : "=r"(ok) : "r"(b), "r"(ph) : "memory");
    return ok;
}
__device__ __forceinline__ void bar_sync(int id, int n) { asm volatile("bar.sync %0, %1;" :: "r"(id), "r"(n) : "memory"); }
__device__ __forceinline__ void bar_arrive(int id, int n) { asm volatile("bar.arrive %0, %1;" :: "r"(id), "r"(n) : "memory"); }
__device__ __forceinline__ uint32_t peer_addr(uint32_t a, uint32_t rank) { uint32_t r; asm("mapa.shared::cluster.u32 %0, %1, %2;" : "=r"(r) : "r"(a), "r"(rank)); return r; }
__device__ __forceinline__ void st_async2(uint32_t a, float x, float y, uint32_t bar) {
    asm volatile("st.async.weak.shared::cluster.mbarrier::complete_tx::bytes.v2.f32 [%0], {%1, %2}, [%3];" :: "r"(a), "f"(x), "f"(y), "r"(bar) : "memory");
}
__device__ __forceinline__ uint32_t gtime() { uint32_t t; asm volatile("mov.u32 %0, %%globaltimer_lo;" : "=r"(t)); return t; }
__device__ __forceinline__ void fence_gpu() { asm volatile("fence.acq_rel.gpu;" ::: "memory"); }

__device__ __forceinline__ uint32_t enc(uint32_t b) { uint32_t r; asm("max.u32 %0, %1, 1;" : "=r"(r) : "r"(b)); return r; }
__device__ __forceinline__ uint32_t encf(float f) { return enc(__float_as_uint(f)); }
__device__ __forceinline__ void st_x1(uint32_t* p, uint32_t v) { asm volatile("st.relaxed.gpu.global.u32 [%0], %1;" :: "l"(p), "r"(v) : "memory"); }
__device__ __forceinline__ void st_x4(void* p, uint32_t a, uint32_t b, uint32_t c, uint32_t d) {
    asm volatile("st.relaxed.gpu.global.v4.u32 [%0], {%1, %2, %3, %4};" :: "l"(p), "r"(a), "r"(b), "r"(c), "r"(d) : "memory");
}
__device__ __forceinline__ void st2_x1(uint32_t* p, uint32_t v) { st_x1(p, v); st_x1(p + 1024, v); }
__device__ __forceinline__ void st2_x4(uint32_t* p, uint32_t a, uint32_t b, uint32_t c, uint32_t d) { st_x4(p, a, b, c, d); st_x4(p + 1024, a, b, c, d); }
__device__ __forceinline__ int near_off(int b, uint32_t cls) { return b * 4096 + (((__popc(b & 0x2C) ^ cls) & 1) << 10); }
__device__ __forceinline__ void ld_x(uint32_t& v, const void* p) { asm volatile("ld.relaxed.gpu.global.u32 %0, [%1];" : "=r"(v) : "l"(p) : "memory"); }
__device__ __forceinline__ void ld_x(uint4& v, const void* p) {
    asm volatile("ld.relaxed.gpu.global.v4.u32 {%0, %1, %2, %3}, [%4];" : "=r"(v.x), "=r"(v.y), "=r"(v.z), "=r"(v.w) : "l"(p) : "memory");
}
__device__ __forceinline__ void ld_x(uint2& v, const void* p) { asm volatile("ld.relaxed.gpu.global.v2.u32 {%0, %1}, [%2];" : "=r"(v.x), "=r"(v.y) : "l"(p) : "memory"); }
__device__ __forceinline__ uint32_t minw(uint32_t v) { return v; }
__device__ __forceinline__ uint32_t minw(const uint2& v) { return min(v.x, v.y); }
__device__ __forceinline__ uint32_t minw(const uint4& v) { return min(__vimin3_u32(v.x, v.y, v.z), v.w); }
template <int N> __device__ __forceinline__ uint32_t mint(const uint32_t* m) {
    if constexpr (N == 1) return m[0];
    else if constexpr (N == 2) return min(m[0], m[1]);
    else return __vimin3_u32(mint<(N + 2) / 3>(m), mint<(N + 1) / 3>(m + (N + 2) / 3), mint<N / 3>(m + (N + 2) / 3 + (N + 1) / 3));
}

template <int STRIDE, int S4 = 4 * STRIDE, typename T, int N>
__device__ __forceinline__ void poll_start(T (&v)[N], const void* base) {
#pragma unroll
    for (int i = 0; i < N; i++) ld_x(v[i], (const uint8_t*)base + (i & 3) * STRIDE + (i >> 2) * S4);
}
struct Nop { __device__ void operator()() const {} };
template <int STRIDE, int SLEEP, bool STARTED = false, int S4 = 4 * STRIDE, typename T, int N, typename F = Nop>
__device__ __forceinline__ void poll(T (&v)[N], const void* base, F idle = F()) {
    if (!STARTED) { poll_start<STRIDE, S4>(v, base); idle(); }
#pragma unroll 1
    for (uint32_t it = 0;; it++) {
        uint32_t m[N];
#pragma unroll
        for (int i = 0; i < N; i++) m[i] = minw(v[i]);
        if (__all_sync(0xffffffffu, mint<N>(m) != 0)) break;
        if (SLEEP && it > 0) __nanosleep(SLEEP);
#pragma unroll
        for (int i = 0; i < N; i++) if (!m[i]) ld_x(v[i], (const uint8_t*)base + (i & 3) * STRIDE + (i >> 2) * S4);
        idle();
        if (it > SPIN_LIMIT) __trap();
    }
}

__device__ __forceinline__ float bflo(uint32_t w) { return __uint_as_float(w << 16); }
__device__ __forceinline__ float bfhi(uint32_t w) { return __uint_as_float(w & 0xffff0000u); }
__device__ __forceinline__ uint32_t pack2(float lo, float hi) {
    uint32_t r; asm("cvt.rn.bf16x2.f32 %0, %1, %2;" : "=r"(r) : "f"(hi), "f"(lo)); return r;
}
__device__ __forceinline__ float rbf(float x) { return __uint_as_float(pack2(0.f, x)); }
__device__ __forceinline__ float ex2(float x) { float r; asm("ex2.approx.ftz.f32 %0, %1;" : "=f"(r) : "f"(x)); return r; }
__device__ __forceinline__ float shx(float v, int m) { return __shfl_xor_sync(0xffffffffu, v, m); }
__device__ __forceinline__ uint4 lds128(uint32_t a) { uint4 v; asm volatile("ld.shared.v4.u32 {%0, %1, %2, %3}, [%4];" : "=r"(v.x), "=r"(v.y), "=r"(v.z), "=r"(v.w) : "r"(a) : "memory"); return v; }
__device__ __forceinline__ uint32_t lds32(uint32_t a) { uint32_t v; asm volatile("ld.shared.u32 %0, [%1];" : "=r"(v) : "r"(a) : "memory"); return v; }
__device__ __forceinline__ void sts32(uint32_t a, uint32_t v) { asm volatile("st.shared.u32 [%0], %1;" :: "r"(a), "r"(v) : "memory"); }
__device__ __forceinline__ void sts16(uint32_t a, uint32_t v) { asm volatile("st.shared.u16 [%0], %1;" :: "r"(a), "h"((uint16_t)v) : "memory"); }
__device__ __forceinline__ int frag_off(int k) { return (k >> 5) * 64 + ((k >> 1) & 3) * 16 + ((k >> 4) & 1) * 8 + ((k >> 3) & 1) * 4 + (k & 1) * 2; }

template <bool TRANS>
__device__ __forceinline__ uint4 ldsm(uint32_t a) {
    uint4 r;
    if (TRANS) asm volatile("ldmatrix.sync.aligned.m8n8.x4.trans.shared.b16 {%0, %1, %2, %3}, [%4];" : "=r"(r.x), "=r"(r.y), "=r"(r.z), "=r"(r.w) : "r"(a) : "memory");
    else asm volatile("ldmatrix.sync.aligned.m8n8.x4.shared.b16 {%0, %1, %2, %3}, [%4];" : "=r"(r.x), "=r"(r.y), "=r"(r.z), "=r"(r.w) : "r"(a) : "memory");
    return r;
}
__device__ __forceinline__ void mma(float (&c)[4], uint32_t a0, uint32_t a1, uint32_t a2, uint32_t a3, uint32_t b0, uint32_t b1) {
    asm volatile("mma.sync.aligned.m16n8k16.row.col.f32.bf16.bf16.f32 {%0,%1,%2,%3}, {%4,%5,%6,%7}, {%8,%9}, {%0,%1,%2,%3};"
                 : "+f"(c[0]), "+f"(c[1]), "+f"(c[2]), "+f"(c[3]) : "r"(a0), "r"(a1), "r"(a2), "r"(a3), "r"(b0), "r"(b1));
}
template <bool TRANS, typename F>
__device__ __forceinline__ void load8(uint4 (&a)[8], F addr) {
    __syncwarp();
#pragma unroll
    for (int s = 0; s < 8; s++) a[s] = ldsm<TRANS>(addr(s));
}
__device__ __forceinline__ void mma8(float (&c)[4], const uint4 (&a)[8], const uint4 (&b)[4]) {
    float e[4][4];
#pragma unroll
    for (int s = 0; s < 8; s++) {
        if (s < 4) e[s][0] = e[s][1] = e[s][2] = e[s][3] = 0.f;
        mma(e[s & 3], a[s].x, a[s].y, a[s].z, a[s].w, (s & 1) ? b[s >> 1].z : b[s >> 1].x, (s & 1) ? b[s >> 1].w : b[s >> 1].y);
    }
#pragma unroll
    for (int i = 0; i < 4; i++) c[i] = (e[0][i] + e[1][i]) + (e[2][i] + e[3][i]);
}
__device__ __forceinline__ void ldfrag(uint4 (&b)[4], uint32_t a) {
    asm volatile("ld.shared.v4.u32 {%0,%1,%2,%3}, [%16];\nld.shared.v4.u32 {%4,%5,%6,%7}, [%16+64];\n"
                 "ld.shared.v4.u32 {%8,%9,%10,%11}, [%16+128];\nld.shared.v4.u32 {%12,%13,%14,%15}, [%16+192];\n"
                 : "=r"(b[0].x), "=r"(b[0].y), "=r"(b[0].z), "=r"(b[0].w), "=r"(b[1].x), "=r"(b[1].y), "=r"(b[1].z), "=r"(b[1].w),
                   "=r"(b[2].x), "=r"(b[2].y), "=r"(b[2].z), "=r"(b[2].w), "=r"(b[3].x), "=r"(b[3].y), "=r"(b[3].z), "=r"(b[3].w) : "r"(a) : "memory");
}
__device__ __forceinline__ void quad_pair(float x, float y, int t, float& lo, float& hi) {
    const float k = ((t & 1) ? y : x) + shx((t & 1) ? x : y, 1);
    lo = k + shx(k, 2); hi = shx(k, 4) + shx(k, 6);
}
__device__ __forceinline__ void pin(uint32_t& x) { asm volatile("" : "+r"(x)); }
template <typename T> __device__ __forceinline__ void pin(T*& x) { asm volatile("" : "+l"(x)); }
__device__ __forceinline__ float4 ldsf4(uint32_t a) { const uint4 v = lds128(a); return make_float4(__uint_as_float(v.x), __uint_as_float(v.y), __uint_as_float(v.z), __uint_as_float(v.w)); }
__device__ __forceinline__ float sum4(const float4& f) { return (f.x + f.y) + (f.z + f.w); }
__device__ __forceinline__ void stsf(uint32_t a, float v) { sts32(a, __float_as_uint(v)); }

__device__ __forceinline__ void wg_fence() { asm volatile("wgmma.fence.sync.aligned;" ::: "memory"); }
__device__ __forceinline__ void wg_commit() { asm volatile("wgmma.commit_group.sync.aligned;" ::: "memory"); }
__device__ __forceinline__ void wg_wait1() { asm volatile("wgmma.wait_group.sync.aligned 1;" ::: "memory"); }
__device__ __forceinline__ void wg_wait0() { asm volatile("wgmma.wait_group.sync.aligned 0;" ::: "memory"); }
#define R8(o) "+f"(d[o]), "+f"(d[o + 1]), "+f"(d[o + 2]), "+f"(d[o + 3]), "+f"(d[o + 4]), "+f"(d[o + 5]), "+f"(d[o + 6]), "+f"(d[o + 7])
__device__ __forceinline__ void wgmma_rs_n32(float (&d)[16], const uint4& a, uint64_t db, int acc) {
    asm volatile("{\n.reg .pred p;\nsetp.ne.b32 p, %21, 0;\n"
        "wgmma.mma_async.sync.aligned.m64n32k16.f32.bf16.bf16 "
        "{%0,%1,%2,%3,%4,%5,%6,%7,%8,%9,%10,%11,%12,%13,%14,%15}, {%16,%17,%18,%19}, %20, p, 1, 1, 0;\n}"
        : R8(0), R8(8) : "r"(a.x), "r"(a.y), "r"(a.z), "r"(a.w), "l"(db), "r"(acc));
}
#define PV_LO "{%0,%1,%2,%3,%4,%5,%6,%7,%8,%9,%10,%11,%12,%13,%14,%15,%16,%17,%18,%19,%20,%21,%22,%23,%24,%25,%26,%27,%28,%29,%30,%31,%32,%33,%34,%35,%36,%37,%38,%39,%40,%41,%42,%43,%44,%45,%46,%47,%48,%49,%50,%51,%52,%53,%54,%55,%56,%57,%58,%59,%60,%61,%62,%63}, "
#define PV_HI "{%64,%65,%66,%67,%68,%69,%70,%71,%72,%73,%74,%75,%76,%77,%78,%79,%80,%81,%82,%83,%84,%85,%86,%87,%88,%89,%90,%91,%92,%93,%94,%95,%96,%97,%98,%99,%100,%101,%102,%103,%104,%105,%106,%107,%108,%109,%110,%111,%112,%113,%114,%115,%116,%117,%118,%119,%120,%121,%122,%123,%124,%125,%126,%127}, "
__device__ __forceinline__ void wgmma_pv(float (&d)[128], const uint4& a, uint32_t blo, int acc) {
    asm volatile("{\n.reg .pred p;\n.reg .b32 u0, u1, u2, u3, t;\n.reg .b64 d0, d1, d2, d3;\nsetp.ne.b32 p, %133, 0;\n"
        "mov.b64 d0, {%132, 0x40000100};\nadd.u32 t, %132, 512;\nmov.b64 d1, {t, 0x40000100};\n"
        "add.u32 t, %132, 128;\nmov.b64 d2, {t, 0x40000100};\nadd.u32 t, %132, 640;\nmov.b64 d3, {t, 0x40000100};\n"
        "wgmma.fence.sync.aligned;\n"
        "wgmma.mma_async.sync.aligned.m64n128k16.f32.bf16.bf16 " PV_LO "{%128, u0, %129, u1}, d0, p, 1, 1, 1;\n"
        "wgmma.mma_async.sync.aligned.m64n128k16.f32.bf16.bf16 " PV_LO "{%130, u2, %131, u3}, d1, 1, 1, 1, 1;\n"
        "wgmma.commit_group.sync.aligned;\n"
        "wgmma.mma_async.sync.aligned.m64n128k16.f32.bf16.bf16 " PV_HI "{%128, u0, %129, u1}, d2, p, 1, 1, 1;\n"
        "wgmma.mma_async.sync.aligned.m64n128k16.f32.bf16.bf16 " PV_HI "{%130, u2, %131, u3}, d3, 1, 1, 1, 1;\n"
        "wgmma.commit_group.sync.aligned;\n}"
        : R8(0), R8(8), R8(16), R8(24), R8(32), R8(40), R8(48), R8(56), R8(64), R8(72), R8(80), R8(88), R8(96), R8(104), R8(112), R8(120)
        : "r"(a.x), "r"(a.y), "r"(a.z), "r"(a.w), "r"(blo), "r"(acc) : "memory");
}

template <int NW>
__device__ __forceinline__ void ln_stats(float s, float q, float sh, float* scr, int w, int lane, int bar, float& mean_b, float& sd_b) {
#pragma unroll
    for (int o = 16; o; o >>= 1) { s += shx(s, o); q += shx(q, o); }
    constexpr float n = 512.f / NW;
    if (lane == 0) { scr[w] = sh + s * (1.f / n); scr[NW + w] = q - s * s * (1.f / n); }
    bar_sync(bar, NW * 32);
    float mu = 0.f, m2 = 0.f;
#pragma unroll
    for (int i = 0; i < NW; i++) { mu += scr[i]; m2 += scr[NW + i]; }
    mu *= 1.f / NW;
#pragma unroll
    for (int i = 0; i < NW; i++) { const float d = scr[i] - mu; m2 = fmaf(n * d, d, m2); }
    mean_b = rbf(mu);
    sd_b = rbf(sqrtf(rbf(rbf(fmaxf(m2, 0.f) * (1.f / 512.f)) + 1e-5f)));
}
__device__ __forceinline__ float ln_mod(float x, float mean_b, float sd_b, float c, float s) {
    return rbf(rbf(__fdividef(rbf(x - mean_b), sd_b)) * rbf(1.f + c)) + s;
}

__global__ void __cluster_dims__(2, 1, 1) __launch_bounds__(NTHREADS, 1)
fused_kernel(const __grid_constant__ First F, __nv_bfloat16* __restrict__ out, uint32_t* __restrict__ gs, const __grid_constant__ Maps M) {
    extern __shared__ __align__(1024) uint8_t sm[];
    const uint32_t sb = s2u(sm);
    const int tid = threadIdx.x, lane = tid & 31;
    const int j = blockIdx.x, rk = j & 1;
    const int g = lane >> 2, t = lane & 3;
    const int r8 = lane & 7, lb3 = (lane >> 3) & 1, lb4 = lane >> 4;
    uint64_t pol;
    asm("createpolicy.fractional.L2::evict_first.b64 %0, 1.0;" : "=l"(pol));
    {
        auto cpa = [&](uint32_t d, const uint8_t* s) {
            asm volatile("cp.async.cg.shared.global.L2::cache_hint.L2::128B [%0], [%1], 16, %2;" :: "r"(d), "l"(s), "l"(pol) : "memory");
        };
        const uint32_t ut = threadIdx.x, uj = blockIdx.x;
        const uint8_t* w = F.w[ut >= 128];
        if (ut < 128) {
            const uint32_t dq = (sb + ut * 16) ^ ((ut * 2) & 0x70);
            const uint8_t* sq = w + (uint32_t)(((uj & 1) * 256 + (ut >> 3)) * 8192 + (uj >> 1) * 128 + (ut & 7) * 16);
#pragma unroll
            for (int i = 0; i < 4 * NCP; i++) cpa(dq + 4 * 32768 + i * 2048, sq + i * 131072);
        } else if (ut < 384) {
            const uint32_t dm = (sb + ut * 16) ^ ((ut * 2) & 0x10);
            const uint8_t* sa = w + (uint32_t)(((uj >> 5) * 128 + (ut >> 1) - 64) * 6144 + (uj & 31) * 32 + (ut & 1) * 16);
            cpa(dm + SM_XA - 2048, sa); cpa(dm + SM_XA + 2048, sa + 1024);
        }
        else if (ut == 480 && uj < 64) asm volatile("prefetch.global.L2 [%0];" :: "l"(F.v[(uj >> 3) & 1] + (uj & 7) * 64));
    }
    const int warp = __shfl_sync(0xffffffffu, tid >> 5, 0);
    const __nv_bfloat16* const xin = F.v[0];
    uint32_t* const pl = gs + (warp < 2 ? (B_PR + (j >> 5)) * 4096 + (j & 31) * 32 : G_E1 + j * 8192) + (warp & 1) * 1024 + lane;
    if (warp < 4) st_x1(pl, 1u);
    auto BAR = [&](int i) -> uint32_t { return sb + SM_BAR + i * 8; };
    const uint32_t a16 = (r8 + 8 * lb4) * 32 + ((lb3 ^ (r8 >> 2)) * 16);
    const uint32_t a128 = (r8 + 8 * lb4) * 128 + ((((warp & 3) * 2 + lb3) ^ r8) * 16);
    auto ldcls = [&]() -> uint32_t { return *(const volatile uint32_t*)(sm + SM_CLS); };
    auto clear_head = [&]() {
        st2_x1(gs + (B_HA + ((j >> 4) & 1) * 2 + lb4) * 4096 + (j >> 5) * 256 + (j & 15) * 16 + (lane & 15), 0u);
        st2_x4(gs + (B_QA + rk * 8 + ((j >> 1) & 1) * 4 + (j >> 5)) * 4096 + g * 128 + ((j >> 2) & 7) * 16 + t * 4, 0u, 0u, 0u, 0u);
        if (lane < 8) st2_x1(gs + B_RD * 4096 + j * 8 + lane, 0u);
    };
    auto tma = [&](uint32_t dst, const CUtensorMap* mp, uint32_t bar, int c0, int c1, int c2, int c3) {
        asm volatile("{\n.reg .pred p;\nelect.sync _|p, 0xffffffff;\n"
                     "@p cp.async.bulk.tensor.4d.shared::cluster.global.mbarrier::complete_tx::bytes.L2::cache_hint [%0], [%1, {%3, %4, %5, %6}], [%2], %7;\n}"
                     :: "r"(dst), "l"(mp), "r"(bar), "r"(c0), "r"(c1), "r"(c2), "r"(c3), "l"(pol) : "memory");
    };
    if (warp <= 12 || warp == 15) {
        const int grp = warp == 12 ? 0 : warp == 15 ? 13 : warp + 1;
        const uint32_t cnt = grp < 10 ? 1 : grp < 13 ? 4 : 8;
        if (lane == 0) {
#pragma unroll
            for (int i = 0; i < 8; i++) mbar_init(BAR(grp * 8 + i), (i < 2 && grp == 0) ? (i ? 128 : 256) : cnt);
        }
        __syncwarp();
        if (grp < 10 && lane < 8 && (grp || lane > NCP)) mbar_expect(BAR(grp * 8 + lane), grp >= 8 ? 4096 : (uint32_t)(grp * 8 + lane - IT_X) < 4 ? 16384 : 8192);
        asm volatile("fence.mbarrier_init.release.cluster;" ::: "memory");
        __syncwarp();
        if (warp == 12) {
#pragma unroll
            for (int i = NCP + 1; i < W0; i++) tma(sb + (15 + i) * 8192, &M.m[MP_WQ], BAR(i), 0, rk * 256 + (i - 1) * 64, j >> 1, 0);
        }
    } else if (warp == 13) {
        if (lane < NMAPS) asm volatile("prefetch.tensormap [%0];" :: "l"(&M.m[lane]) : "memory");
    } else if (warp == 14) {
        clear_head();
    }
    __syncthreads();
    uint32_t in1 = 0, in2 = 0;
    if (warp < 4) { in1 = *(const uint32_t*)(xin + 2 * tid); in2 = *(const uint32_t*)(xin + 256 + 2 * tid); }
    else if (warp < 12) in1 = *(const uint32_t*)(F.v[1] + 2 * (tid - 128));
    if (warp < 12) asm volatile("cp.async.mbarrier.arrive.noinc.shared::cta.b64 [%0];" :: "r"(BAR(warp < 4)) : "memory");
    asm volatile("barrier.cluster.arrive.relaxed.aligned;" ::: "memory");

    if (warp >= 12) {
    asm volatile("setmaxnreg.dec.sync.aligned.u32 64;");
    if (warp == 12) {
        static_assert(W0 > NCP && W0 <= 5 && NCP >= 1 && NCP <= 4, "W0");
        const uint2* sched = M.sched[j < NFF ? 0 : j < J_RED ? 1 : 2];
        uint2 en = sched[W0];
        const uint32_t t0 = gtime();
        const uint32_t sp = __reduce_or_sync(0xffffffffu, sb);
        const int cx = (j >> 1) * 64 + (j < NFF ? 0 : 1024 - NFF * 32);
#pragma unroll 1
        for (int i = W0; en.x; i++) {
            uint32_t e = en.x, st = (en.y >> 20) * 64;
            const uint32_t tn = t0 + (int16_t)en.y, mp = (en.y >> 16) & 15;
            if (mp == MP_WUV || mp == MP_WUK) { st ^= (j >> 5) * (mp == MP_WUV ? 128 : 64); e ^= (j >> 5) << 6; }
            if (mp == MP_GATE || mp == MP_UP) st ^= (j & 16) * 8;
            if (mp == MP_DOWN) { st ^= (j & 3) * 64; e ^= (j & 3) << 6; }
            en = sched[i + 1];
            if (mp == MP_MODB && j >= J_END) break;
            uint32_t c0 = mp == MP_WO ? (j & 7) * 64 : mp > MP_WO ? cx : 0;
            uint32_t c1 = mp == MP_CKV ? 0 : mp == MP_DOWN ? j * 32 : st + (mp == MP_WUV ? (j & 3) * 32 : mp == MP_WO ? (j >> 3) * 256 : rk * 256);
            uint32_t c2 = mp < MP_CKV ? j >> 1 : mp == MP_CKV ? rk * 4 : mp == MP_WUV ? (j >> 2) * 2 : mp == MP_DOWN ? st >> 5 : 0;
            uint32_t c3 = mp == MP_CKV ? st * 2 + (j & ~1) : 0;
            uint32_t dst = sp + ((e << 7) & 0x3e000), bar = sp + SM_BAR + (e & 63) * 8;
            const uint32_t w0 = (e >> 8) & 0x3f8, w1 = (e >> 15) & 0x3f8, w2 = (e >> 22) & 0x3f8, bb = sp + SM_BAR - 8;
            const CUtensorMap* pm = &M.m[mp];
            pin(dst); pin(bar); pin(c0); pin(c1); pin(c2); pin(c3); pin(pm);
            if (w0) mbar_wait(bb + w0, 0);
            if (w2) {
                mbar_wait(bb + w2, 0);
                while (!__any_sync(0xffffffffu, mbar_test(bb + w1, 0) | ((int)(gtime() - tn) > 0))) {}
            } else if (w1) mbar_wait(bb + w1, 0);
            tma(dst, pm, bar, c0, c1, c2, c3);
        }
    } else if (warp == 13) {
#pragma unroll
        for (int i = 0; i < 2; i++) st_x4(gs + (B_ML + rk * 16 + i * 8 + g) * 4096 + (t >> 1) * 1024 + (j >> 1) * 8 + (t & 1) * 4, 0u, 0u, 0u, 0u);
        if (lane < 16) st2_x4(gs + (B_E2 + (j >> 4)) * 4096 + (j & 15) * 64 + lane * 4, 0u, 0u, 0u, 0u);
        st2_x1(gs + (B_E3 + (j >> 5)) * 4096 + (j & 31) * 32 + lane, 0u);
        if (lane < 8) st2_x1(gs + B_MB * 4096 + j * 8 + lane, 0u);
        if (j < NFF) {
#pragma unroll
            for (int i = 0; i < 2; i++) st2_x4(gs + (B_E5 + i * 8 + g) * 4096 + j * 16 + t * 4, 0u, 0u, 0u, 0u);
        }
        bar_sync(9, 64);
        const uint32_t cs = ldcls();
#pragma unroll 1
        for (int i = 0; i < 32; i++) {
            st_x4(gs + G_E1 + j * 8192 + (i >> 3) * 2048 + ((((cs >> 1) ^ (i >> 3)) & 1) << 10) + (i & 7) * 128 + lane * 4, 0u, 0u, 0u, 0u);
            __nanosleep(JAN_SLEEP);
        }
        fence_gpu();
        if (lane < 8) st2_x1(gs + B_RD * 4096 + j * 8 + lane, 1u + (cs >> 1));
        if (lane == 0) TRACE(41);
        uint32_t rd[4];
        mbar_wait(BAR(IT_CKV + RD_ITEM), 0);
        poll<1024, RD_SLEEP>(rd, gs + near_off(B_RD, cs) + lane * 8);
#pragma unroll
        for (int i = 0; i < 4; i++) {
            const uint32_t m = __ballot_sync(0xffffffffu, rd[i] == 2u);
            if (lane == 0) sts32(sb + SM_CLS + 16 + i * 4, m);
        }
        __syncwarp();
        if (lane < 8) mbar_arrive(BAR(JD));
        if (lane == 0) TRACE(42);
    } else if (warp == 14) {
        uint2 ml[2];
        mbar_waitb(BAR(JD), 0);
        const uint32_t cls = ldcls();
        mbar_waitb(BAR(PF0 + 2 * NUNITS - 1), 0);
        __nanosleep(ML_DELAY);
        const uint32_t* pl2 = gs + near_off(B_ML + (j >> 2), cls) + lane * 8;
        const uint32_t wa = sb + SM_W + lb4 * 64 + t * 16 + (g & 3) * 4;
        poll_start<1024>(ml, pl2);
        uint32_t w0 = 0, w1 = 0, redo = 0;
        bool first = true;
#pragma unroll 1
        for (uint32_t it = 0;; it++) {
            const bool p0 = minw(ml[0]) != 0, p1 = minw(ml[1]) != 0;
            const int n = __popc(__ballot_sync(0xffffffffu, p0)) + __popc(__ballot_sync(0xffffffffu, p1));
            const uint32_t x0 = ml[0].x, x1 = ml[1].x;
            if (n < 64) {
                if (!p0) ld_x(ml[0], pl2);
                if (!p1) ld_x(ml[1], pl2 + 256);
            }
            if (n == 64 || (first && n >= E1_EARLY)) {
                auto ord = [](int x) { return x ^ ((x >> 31) & 0x7fffffff); };
                const int o0 = ord(x0), o1 = ord(x1);
                const float mm = __int_as_float(ord(__reduce_max_sync(0xffffffffu, max(p0 ? o0 : INT_MIN, p1 ? o1 : INT_MIN))));
                const float lo = __int_as_float(ord(__reduce_min_sync(0xffffffffu, min(p0 ? o0 : INT_MAX, p1 ? o1 : INT_MAX))));
                const uint32_t v0 = pack2(ex2((p0 ? __uint_as_float(x0) : lo) - mm), 0.f), v1 = pack2(ex2((p1 ? __uint_as_float(x1) : lo) - mm), 0.f);
                redo = !first && __any_sync(0xffffffffu, v0 != w0 || v1 != w1);
                w0 = v0; w1 = v1;
                sts32(wa - redo * (SM_W - SM_W2), w0 * 0x10001u); sts32(wa - redo * (SM_W - SM_W2) + 128, w1 * 0x10001u);
                if (first) bar_arrive(3, 416);
                first = false;
                if (n == 64) break;
            }
            if (it > SPIN_LIMIT) __trap();
        }
        if (lane == 0) TRACE_Q(37);
        float L = bflo(w0) * __uint_as_float(ml[0].y) + bflo(w1) * __uint_as_float(ml[1].y);
#pragma unroll
        for (int o = 16; o; o >>= 1) L += shx(L, o);
        if (lane == 0) *(float2*)(sm + SM_FQ) = make_float2(__frcp_rn(L), __uint_as_float(redo));
        __syncwarp();
        if (lane < 8) mbar_arrive(BAR(WR));
        if (lane == 0) TRACE(10);
        bar_sync(4, 416);
        clear_head();
        if (j < NFF) {
            uint32_t ya = sb + SM_Y + lane * 16, sa = peer_addr(sb + SM_RED + 2048 + rk * 8, lane & 1), tb = peer_addr(BAR(MBB), lane & 1);
            pin(ya); pin(sa); pin(tb);
            bar_sync(7, 288);
            const float4 y0 = ldsf4(ya), y1 = ldsf4(ya + 512);
            float s = sum4(y0) + sum4(y1);
            float q = (fmaf(y0.x, y0.x, y0.y * y0.y) + fmaf(y0.z, y0.z, y0.w * y0.w)) + (fmaf(y1.x, y1.x, y1.y * y1.y) + fmaf(y1.z, y1.z, y1.w * y1.w));
#pragma unroll
            for (int o = 16; o; o >>= 1) { s += shx(s, o); q += shx(q, o); }
            if (lane < 2) st_async2(sa, s, q, tb);
        }
    } else if (warp == 15) {
        mbar_waitb(BAR(IT_X - 1), 0);
        if (j < J_END) mbar_waitb(BAR(j < NFF ? NITEMS - 1 : MBB), 0);
    }
    } else if (warp < 4) {
        float* scr = (float*)(sm + SM_SCR);
        uint32_t cls;
        {
            uint2 ha[8];
            uint32_t best = 0xffffffffu;
            sts32(sb + SM_SCR + 64 + warp * 4, best);
            const float sh = __shfl_sync(0xffffffffu, bflo(in1), 0);
            const float v0 = bflo(in1) - sh, v1 = bfhi(in1) - sh, v2 = bflo(in2) - sh, v3 = bfhi(in2) - sh;
            float mb, sd;
            ln_stats<4>((v0 + v1) + (v2 + v3), (v0 * v0 + v1 * v1) + (v2 * v2 + v3 * v3), sh, scr, warp, lane, 2, mb, sd);
            if (!rk) in2 = in1;
#pragma unroll 1
            for (int i = 0; i < NPROBE; i++) {
                uint32_t t0, t1, o;
                asm volatile("mov.u32 %0, %%clock;" : "=r"(t0));
                asm volatile("atom.relaxed.gpu.global.exch.b32 %0, [%1], %2;" : "=r"(o) : "l"(pl), "r"(2u + i) : "memory");
                asm volatile("{\n.reg .pred p;\nsetp.ne.u32 p, %1, 0x1234567;\nmov.u32 %0, 0;\n@p mov.u32 %0, %%clock;\n}" : "=r"(t1) : "r"(o));
                best = min(best, t1 - t0);
                sts32(sb + SM_SCR + 64 + warp * 4, best);
                if (__all_sync(0xffffffffu, min(best, lds32(sb + SM_SCR + 64 + (warp ^ 1) * 4)) < NEAR_CLK)) break;
            }
            bar_sync(2, 128);
            const uint4 lt = *(const uint4*)(scr + 16);
            cls = NUMA ? ((lt.y < lt.x) ^ (__popc((B_PR + (j >> 5)) & 0x2C) & 1)) | (lt.w < lt.z) << 1 : 0;
            if (warp == 0) { if (lane == 0) sts32(sb + SM_CLS, cls); bar_arrive(9, 64); }
            if (tid == 0) TRACE(38);
            asm volatile("barrier.cluster.wait.aligned;" ::: "memory");
            mbar_wait(BAR(IT_MODA), 0);
            if (HA_DELAY) __nanosleep(HA_DELAY);
            poll<1024, H_SLEEP, false, 16384>(ha, gs + near_off(B_HA + rk * 2, cls) + 2 * tid);
            auto rsum = [](uint32_t a, uint32_t b, uint32_t c, uint32_t d) { return rbf((__uint_as_float(a) + __uint_as_float(b)) + (__uint_as_float(c) + __uint_as_float(d))); };
            sts32(sb + SM_FV + frag_off(2 * tid),
                  pack2(ln_mod(bflo(in2), mb, sd, rsum(ha[4].x, ha[5].x, ha[6].x, ha[7].x), rsum(ha[0].x, ha[1].x, ha[2].x, ha[3].x)),
                        ln_mod(bfhi(in2), mb, sd, rsum(ha[4].y, ha[5].y, ha[6].y, ha[7].y), rsum(ha[0].y, ha[1].y, ha[2].y, ha[3].y))));
            bar_arrive(5, 384);
            mbar_wait(BAR(QB), 0);
            if (tid < 64) {
                const float* qx = (const float*)(sm + SM_QX) + tid;
                sts16(sb + SM_FQ + frag_off(tid), pack2((qx[0] + qx[64]) + (qx[128] + qx[192]), 0.f));
            }
            bar_arrive(6, 384);
        }
        asm volatile("setmaxnreg.inc.sync.aligned.u32 192;");
        float acc[128];
        float M = 0.f;
        uint32_t pa = sb + SM_XA + warp * 512 + lane * 16, ma = sb + SM_MX + (warp * 8 + g) * 4, pf = BAR(PF0);
        uint32_t blo = __reduce_or_sync(0xffffffffu, (((sb + SM_U) & 0x3FFFFu) >> 4) | 0x400000u);
        uint32_t* e1[4];
#pragma unroll
        for (int i = 0; i < 4; i++) e1[i] = gs + G_E1 + (warp * 8 + g) * 4 * 8192 + (rk * 2 + (j >> 6)) * 2048 + ((j >> 1) & 31) * 32 + t * 4;
#pragma unroll 1
        for (int h = 0; h < 2 * NUNITS; h++) {
            mbar_wait(pf, 0);
            const float m = __uint_as_float(lds32(ma));
            const uint4 pn = lds128(pa);
            wg_wait0();
#pragma unroll
            for (int i = 0; i < 128; i++) asm volatile("" : "+f"(acc[i]) :: "memory");
            if (h == 0) M = m;
            uint32_t b2 = 0x3f803f80u;
            if (__builtin_expect(__any_sync(0xffffffffu, m != M), 0)) {
                const float Mn = fmaxf(M, m), alpha = ex2(M - Mn), beta = ex2(m - Mn);
                M = Mn;
                b2 = pack2(beta, beta);
#pragma unroll
                for (int jj = 0; jj < 32; jj++) { acc[4 * jj] *= alpha; acc[4 * jj + 1] *= alpha; }
            }
            auto mul2 = [](uint32_t x, uint32_t y) { uint32_t r; asm("mul.rn.bf16x2 %0, %1, %2;" : "=r"(r) : "r"(x), "r"(y)); return r; };
            const uint4 p = make_uint4(mul2(pn.x, b2), mul2(pn.y, b2), mul2(pn.z, b2), mul2(pn.w, b2));
            if (tid == 0 && (h & 1)) TRACE_Q(48 + (h >> 1));
            wgmma_pv(acc, p, blo, h);
            if (lane == 0 && h > 0 && !(h & 1)) mbar_arrive(BAR(EB_UNIT0 + (h >> 1) - 1));
            blo += h == 11 ? -11 * 1024 : 1024;
            pa += (h == 5 || h == 11) ? -5 * 2048 : 2048;
            ma += 128; pf += 8;
            if (h == 2 * NUNITS - 3) {
                mbar_wait(BAR(JD), 0);
                const uint32_t hm = (*(const uint32_t*)(sm + SM_CLS + 16 + warp * 4) >> (g * 4)) ^ ((j >> 6) ? 15u : 0u);
#pragma unroll
                for (int i = 0; i < 4; i++) e1[i] += ((hm >> i) & 1) << 10;
            }
        }
#pragma unroll
        for (int vv = 0; vv < 2; vv++) {
            if (vv && M == 1.f) __trap();
            if (vv) wg_wait0(); else wg_wait1();
#pragma unroll
            for (int i = 0; i < 64; i++) asm volatile("" : "+f"(acc[vv * 64 + i]) :: "memory");
            if (tid == 0 && !vv) TRACE_Q(63);
#pragma unroll
            for (int i = 0; i < 4; i++) {
                const float* a = &acc[vv * 64 + i * 16];
                st_x4(e1[i] + i * 8192 + vv * 16, enc(pack2(a[0], a[1])), enc(pack2(a[4], a[5])), enc(pack2(a[8], a[9])), enc(pack2(a[12], a[13])));
            }
        }
        bar_arrive(3, 416);
        if (tid == 0) TRACE_Q(17);
#pragma unroll 1
        for (int pass = 0;; pass++) {
            if (j >= NFF && j < J_END && pass == (j >= J_RED)) {
                uint4 a[8], b[4];
                float c[4], e[4];
                const bool own = (warp >> 1) == rk;
                const uint32_t xa = sb + SM_FV + (warp & 1) * 64 + g * 8;
                if (lane == 0) mbar_expect(BAR(MBB), own ? 64 : 0);
#pragma unroll
                for (int i = 0; i < 2; i++) {
                    ldfrag(b, sb + SM_FS + rk * 512 + i * 256 + t * 16);
                    mbar_wait(BAR(IT_X + i), 0);
                    const uint32_t ab = sb + SM_U + B_X * 32768 + i * 16384 + a128;
                    load8<true>(a, [&](int s) { return ab + s * 2048; });
                    mma8(i ? e : c, a, b);
                }
                c[0] += e[0]; c[2] += e[2];
                if (!own) {
                    if (t == 0) st_async2(peer_addr(xa, rk ^ 1), c[0], c[2], peer_addr(BAR(MBB), rk ^ 1));
                } else {
                    mbar_wait(BAR(MBB), 0);
                    const float2 pp = *(const float2*)(sm + (xa - sb));
                    const float mine = t ? c[2] + pp.y : c[0] + pp.x, other = shx(mine, 4);
                    const uint32_t w = (warp & 1) * 8 + t * 4 + (g >> 1), val = enc(pack2(mine, other));
                    if (t < 2 && !(g & 1)) {
                        if (j < J_RED) st2_x1(gs + B_MB * 4096 + (j - NFF) * 16 + w, val);
                        else sts32(sb + SM_FV + 256 + w * 4, val);
                    }
                    __syncwarp();
                    if (j >= J_RED && lane < 4) mbar_arrive(BAR(QB));
                    if (lane == 0) TRACE(11);
                }
            }
            if (pass) break;
            uint4 a[8], a2[8];
            const uint32_t ab = sb + SM_U + B_WO * 32768 + a128;
            uint32_t* p3 = gs + (B_E3 + ((j >> 1) & 3)) * 4096 + (t >> 1) * 1024 + (rk * 2 + (warp >> 1)) * 256 + (j >> 3) * 16 + (warp & 1) * 8 + (t & 1) * 4 + (g >> 1);
            const uint32_t* pb = gs + near_off(B_E2 + (j >> 4), cls) + (((j >> 3) & 1) * 2 + lb4) * 256 + (lane & 15) * 2;
            pin(p3); pin(pb);
            uint2 bb[8];
            uint2 bq[2] = {make_uint2(0u, 0u), make_uint2(0u, 0u)};
            uint32_t xa = sb + SM_XA + lane * 16;
            pin(xa);
            bool h0 = false, h1 = false;
            auto idle = [&]() {
                if (!h0) {
                    h0 = __all_sync(0xffffffffu, mbar_test(BAR(IT_WO + (t & 1)), 0));
                    if (h0) load8<true>(a, [&](int s) { return ab + s * 2048; });
                }
                if (!h1) {
                    h1 = __all_sync(0xffffffffu, mbar_test(BAR(IT_WO + 2 + (t & 1)), 0));
                    if (h1) load8<true>(a2, [&](int s) { return ab + 16384 + s * 2048; });
                }
            };
            bar_sync(4, 416);
            idle();
            poll<128, 0, true>(bq, pb + warp * 64, idle);
            asm volatile("st.shared.v4.u32 [%0], {%1, %2, %3, %4};" :: "r"(xa + warp * 512), "r"(bq[0].x), "r"(bq[0].y), "r"(bq[1].x), "r"(bq[1].y) : "memory");
            bar_sync(2, 128);
#pragma unroll
            for (int i = 0; i < 4; i++) { const uint4 q = lds128(xa + i * 512); bb[2 * i] = make_uint2(q.x, q.y); bb[2 * i + 1] = make_uint2(q.z, q.w); }
            if (tid == 0) TRACE(21);
            float e[4][4];
#pragma unroll
            for (int s = 0; s < 16; s++) {
                if (s == 0 && !h0) { mbar_wait(BAR(IT_WO), 0); mbar_wait(BAR(IT_WO + 1), 0); load8<true>(a, [&](int q) { return ab + q * 2048; }); }
                if (s == 0 && !h1) { mbar_wait(BAR(IT_WO + 2), 0); mbar_wait(BAR(IT_WO + 3), 0); load8<true>(a2, [&](int q) { return ab + 16384 + q * 2048; }); }
                const int z = (s & 1) | (s & 2) << 2 | (s >> 2) << 1;
                const uint4& x = z < 8 ? a[z] : a2[z & 7];
                float (&d)[4] = e[(z >> 3) * 2 + (z & 1)];
                if (!(z & 6)) d[0] = d[1] = d[2] = d[3] = 0.f;
                mma(d, x.x, x.y, x.z, x.w, bb[z & 7].x, bb[z & 7].y);
            }
            float lo, hi;
            quad_pair((t & 2) ? (e[2][0] + e[3][0]) + (e[2][1] + e[3][1]) : (e[0][0] + e[1][0]) + (e[0][1] + e[1][1]),
                      (t & 2) ? (e[2][2] + e[3][2]) + (e[2][3] + e[3][3]) : (e[0][2] + e[1][2]) + (e[0][3] + e[1][3]), t, lo, hi);
            if (!(g & 1)) st_x1(p3, enc(pack2(lo, hi)));
            if (j < NFF) bar_arrive(8, 384); else if (j >= J_RED && j < J_END) bar_arrive(8, 192);
            if (tid == 0) TRACE(22);
        }
        if (j < NFF) {
            uint4 a[16];
            const uint32_t ad = sb + SM_U + B_DN * 32768 + warp * 8192 + (r8 + 8 * lb4) * 128 + (lb3 ^ r8) * 16;
            uint32_t rl = sb + SM_RED + lane * 16;
            uint32_t* p5 = gs + (B_E5 + warp * 4 + (t >> 1)) * 4096 + j * 16 + (t & 1) * 8 + g;
            pin(rl); pin(p5);
            if (lane == 0) mbar_expect(BAR(MBB), 4);
            auto ldd = [&]() {
#pragma unroll
                for (int s = 0; s < 16; s++) a[s] = ldsm<true>((ad ^ ((s & 3) * 32)) + (s >> 2) * 2048);
            };
            const uint32_t db = BAR(IT_DOWN + (warp ^ (j & 3)));
            mbar_wait(BAR(MBB), 0);
            const float4 st = ldsf4(sb + SM_RED + 2048);
            const bool hd = __all_sync(0xffffffffu, mbar_test(db, 0));
            if (hd) ldd();
            const float mu = (st.x + st.z) * (1.f / 512.f);
            float rstd;
            asm volatile("rsqrt.approx.ftz.f32 %0, %1;" : "=f"(rstd) : "f"(fmaxf(fmaf(-mu, mu, (st.y + st.w) * (1.f / 512.f)), 0.f) + 1e-5f));
            mbar_wait(BAR(QB), 1);
            if (tid == 0) TRACE(25);
            const float4 f0 = ldsf4(rl), f2 = ldsf4(rl + 1024), f1 = ldsf4(rl + 512), f3 = ldsf4(rl + 1536);
            const float gg = fmaf(rstd, fmaf(-mu, f0.z + f2.z, (f0.x + f0.y) + (f2.x + f2.y)), f0.w + f2.w);
            const float uu = fmaf(rstd, fmaf(-mu, f1.z + f3.z, (f1.x + f1.y) + (f3.x + f3.y)), f1.w + f3.w);
            const float hh = __fdividef(gg * uu, 1.f + ex2(-gg * fmaf(gg * gg, 0.10294324f, 2.3022082f)));
            uint32_t hb[4];
#pragma unroll
            for (int i = 0; i < 4; i++) hb[i] = pack2(__shfl_sync(0xffffffffu, hh, 2 * t + 8 * i), __shfl_sync(0xffffffffu, hh, 2 * t + 8 * i + 1));
            if (!hd) { mbar_wait(db, 0); ldd(); }
#pragma unroll
            for (int i = 0; i < 2; i++) {
                uint32_t res = 0;
#pragma unroll
                for (int k = 0; k < 4; k++) {
                    float c[4] = {0.f, 0.f, 0.f, 0.f};
                    const uint4 &x = a[i * 8 + k], &y = a[i * 8 + k + 4];
                    mma(c, x.x, x.y, x.z, x.w, hb[0], hb[1]);
                    mma(c, y.x, y.y, y.z, y.w, hb[2], hb[3]);
                    if (t == k) res = pack2(c[0], c[2]);
                }
                st2_x1(p5 + i * 8192, enc(res));
            }
            if (tid == 0) { TRACE(27); TRACE_GT(47); }
        }
    } else {
        const int u8 = tid - 128, w8 = warp - 4;
        const int v = w8 >> 2, wq4 = w8 & 3;
        {
            const float c0 = bflo(in1), c1 = bfhi(in1);
            sts32(sb + SM_FS + frag_off(2 * u8), pack2(__fdividef(c0, 1.f + __expf(-c0)), __fdividef(c1, 1.f + __expf(-c1))));
        }
        bar_sync(1, 256);
        asm volatile("barrier.cluster.wait.aligned;" ::: "memory");
        uint4 a[8], b[4]; float c[4];
        if (w8 < 2) {
            ldfrag(b, sb + SM_FS + (j >> 5) * 256 + t * 16);
            mbar_wait(BAR(IT_MODA), 0);
            if (u8 == 0) TRACE(12);
            const uint32_t ab = sb + SM_XA + w8 * 4096 + a16;
            load8<true>(a, [&](int s) { return ab + s * 512; });
            mma8(c, a, b);
            if (t < 2) st2_x1(gs + (B_HA + ((j >> 4) & 1) * 2 + w8) * 4096 + (j >> 5) * 256 + (j & 15) * 16 + t * 8 + g, encf(t ? c[2] : c[0]));
        }
        {
            mbar_wait(BAR(IT_WQ + 2 * v <= NCP ? 1 : IT_WQ + 2 * v), 0); mbar_wait(BAR(IT_WQ + 2 * v + 1 <= NCP ? 1 : IT_WQ + 2 * v + 1), 0);
            const uint32_t ab = sb + SM_U + 4 * 32768 + v * 16384 + a128;
            load8<true>(a, [&](int s) { return ab + s * 2048; });
            if (lane == 0) mbar_arrive(BAR(EB_WQ));
            bar_sync(5, 384);
            if (u8 == 0) TRACE(13);
            ldfrag(b, sb + SM_FV + v * 256 + t * 16);
            mma8(c, a, b);
            if (t < 2) {
                const float qv = t ? c[2] : c[0];
                const uint32_t qa_ = sb + SM_QX + ((rk * 2 + v) * 64 + wq4 * 16 + t * 8 + g) * 4;
                asm volatile("st.async.weak.shared::cluster.mbarrier::complete_tx::bytes.f32 [%0], %1, [%2];"
                             :: "r"(peer_addr(qa_, rk ^ 1)), "f"(qv), "r"(peer_addr(BAR(QB), rk ^ 1)) : "memory");
                sts32(qa_, __float_as_uint(qv));
            }
            __syncwarp();
            if (lane == 0) mbar_expect(BAR(QB), 64);
        }
        {
            mbar_wait(BAR(IT_WUK + (v ^ ((j >> 5) & 1))), 0); mbar_wait(BAR(IT_WUK + (v ^ ((j >> 5) & 1)) + 2), 0);
            const uint32_t ab = sb + SM_U + 5 * 32768 + (w8 * 16 + r8 + 8 * lb3) * 128;
            const uint32_t x16 = (lb4 ^ r8) * 16;
            load8<false>(a, [&](int s) { return ab + (s & 1) * 16384 + (x16 ^ ((s >> 1) * 32)); });
            bar_sync(6, 384);
            if (u8 == 0) TRACE(14);
            b[0] = lds128(sb + SM_FQ + t * 16); b[1] = lds128(sb + SM_FQ + 64 + t * 16);
            float e[4] = {0.f, 0.f, 0.f, 0.f};
            c[0] = c[1] = c[2] = c[3] = 0.f;
#pragma unroll
            for (int k = 0; k < 4; k++) {
                const uint32_t b0 = (k & 1) ? b[k >> 1].z : b[k >> 1].x, b1 = (k & 1) ? b[k >> 1].w : b[k >> 1].y;
                mma(c, a[2 * k].x, a[2 * k].y, a[2 * k].z, a[2 * k].w, b0, b1);
                mma(e, a[2 * k + 1].x, a[2 * k + 1].y, a[2 * k + 1].z, a[2 * k + 1].w, b0, b1);
            }
            const float mine = ((t & 1) ? ((t & 2) ? e[2] : e[0]) : ((t & 2) ? c[2] : c[0])) * 0.12751743f;
            const float other = shx(mine, 4);
            if (!(g & 1)) st2_x1(gs + (B_QA + rk * 8 + ((j >> 1) & 1) * 4 + (j >> 5)) * 4096 + w8 * 128 + ((j >> 2) & 7) * 16 + (g >> 1) * 4 + t, enc(pack2(mine, other)));
            if (u8 == 0) TRACE(15);
        }
        const uint32_t cls = ldcls();
        __nanosleep(QA_DELAY);
        {
            uint4 qb[8];
            const uint32_t* pq = gs + near_off(B_QA + rk * 8 + wq4, cls) + lane * 4;
            const uint32_t* pq2 = gs + near_off(B_QA + rk * 8 + 4 + wq4, cls) + lane * 4;
            if (lane == 0) {
                mbar_expect(BAR(QT), 4096);
                asm volatile("cp.async.bulk.shared::cluster.global.mbarrier::complete_tx::bytes [%0], [%1], 4096, [%2];"
                             :: "r"(sb + SM_U + 5 * 32768 + w8 * 4096), "l"(gs + near_off(B_QA + rk * 8 + w8, cls)), "r"(BAR(QT)) : "memory");
            }
            const uint32_t qs = sb + SM_U + 5 * 32768 + wq4 * 4096 + lane * 16;
            mbar_wait(BAR(QT), 0);
#pragma unroll
            for (int i = 0; i < 8; i++) { a[i] = lds128(qs + i * 512); qb[i] = lds128(qs + 16384 + i * 512); }
            poll<512, QA_SLEEP, true>(a, pq);
            poll<512, QA_SLEEP, true>(qb, pq2);
            if (lane == 0) mbar_arrive(BAR(EB_WUK));
            auto add2 = [](uint32_t x, uint32_t y) { uint32_t r; asm("add.rn.bf16x2 %0, %1, %2;" : "=r"(r) : "r"(x), "r"(y)); return r; };
#pragma unroll
            for (int i = 0; i < 8; i++) a[i] = make_uint4(add2(a[i].x, qb[i].x), add2(a[i].y, qb[i].y), add2(a[i].z, qb[i].z), add2(a[i].w, qb[i].w));
        }
        if (u8 == 0) TRACE(8);
        {
            float m = -INFINITY, l = 0.f;
            uint32_t xl = sb + SM_XB + w8 * 2048 + lane * 16, xr = peer_addr(xl, rk ^ 1), bsr = peer_addr(BAR(SF0 + v), rk ^ 1);
            uint32_t pa = sb + SM_XA + v * 2048 + wq4 * 512 + lane * 16, ma = sb + SM_MX + v * 128 + (wq4 * 8 + g) * 4;
            uint32_t fb = BAR(IT_CKV + v * 2), sf = BAR(SF0 + v);
            uint32_t dlo = __reduce_or_sync(0xffffffffu, (((sb + SM_U + v * 16384) & 0x3FFFFu) >> 4) | 0x10000u);
            if (STAG && v) __nanosleep(STAG);
#pragma unroll 1
            for (int n = 0; n < NUNITS; n++) {
                float d[2][16], sc[8];
#pragma unroll
                for (int i = 0; i < 2; i++) {
                    mbar_wait(fb + i * 8, 0);
                    wg_fence();
#pragma unroll
                    for (int s = 0; s < 8; s++) wgmma_rs_n32(d[i], a[s], (0x40000080ull << 32) | (dlo + i * 512 + (s >> 2) * 64 + (s & 3) * 2), s);
                    wg_commit();
                }
#pragma unroll
                for (int i = 0; i < 2; i++) {
                    if (i) wg_wait0(); else wg_wait1();
#pragma unroll
                    for (int k = 0; k < 16; k++) asm volatile("" : "+f"(d[i][k]) :: "memory");
                    sc[4 * i] = d[i][0] + d[i][6]; sc[4 * i + 1] = d[i][1] + d[i][7]; sc[4 * i + 2] = d[i][8] + d[i][14]; sc[4 * i + 3] = d[i][9] + d[i][15];
                    asm volatile("st.async.weak.shared::cluster.mbarrier::complete_tx::bytes.v4.f32 [%0], {%1, %2, %3, %4}, [%5];"
                                 :: "r"(xr + i * 1024), "f"(sc[4 * i]), "f"(sc[4 * i + 1]), "f"(sc[4 * i + 2]), "f"(sc[4 * i + 3]), "r"(bsr) : "memory");
                }
                if (u8 == 128) TRACE_Q(56 + (n < 6 ? n : -40));
                if (n >= 3) mbar_wait(BAR(EB_UNIT0 + n - 3), 0);
                dlo += n == 5 ? -5 * 2048 : 2048;
                fb += 32; xr ^= 512; bsr += 16;
                pin(fb); pin(xr); pin(bsr);
                mbar_wait(sf, 0);
                const float4 x = ldsf4(xl), y = ldsf4(xl + 1024);
                sc[0] += x.x; sc[1] += x.y; sc[2] += x.z; sc[3] += x.w; sc[4] += y.x; sc[5] += y.y; sc[6] += y.z; sc[7] += y.w;
                float pr[8];
#pragma unroll
                for (int i = 0; i < 8; i++) pr[i] = ex2(sc[i] - m);
                float mx = fmaxf(fmaxf(fmaxf(sc[0], sc[1]), fmaxf(sc[2], sc[3])), fmaxf(fmaxf(sc[4], sc[5]), fmaxf(sc[6], sc[7])));
                if (__builtin_expect(__any_sync(0xffffffffu, mx > m), 0)) {
                    mx = fmaxf(mx, shx(mx, 1));
                    mx = fmaxf(mx, shx(mx, 2));
                    const float mn = fmaxf(m, ceilf(mx * 0.0625f) * 16.f);
                    l *= ex2(m - mn);
                    m = mn;
#pragma unroll
                    for (int i = 0; i < 8; i++) pr[i] = ex2(sc[i] - m);
                }
                stsf(ma, m);
                asm volatile("st.shared.v4.u32 [%0], {%1, %2, %3, %4};" :: "r"(pa), "r"(pack2(pr[0], pr[1])), "r"(pack2(pr[2], pr[3])),
                             "r"(pack2(pr[4], pr[5])), "r"(pack2(pr[6], pr[7])) : "memory");
                __syncwarp();
                if (lane == 0) mbar_arrive(sf + (PF0 - SF0) * 8);
                l += ((pr[0] + pr[1]) + (pr[2] + pr[3])) + ((pr[4] + pr[5]) + (pr[6] + pr[7]));
                xl ^= 512; sf += 16; ma += 256; pa += (n == 2 || n == 5) ? -8192 : 4096;
            }
            l += shx(l, 1);
            l += shx(l, 2);
            float2* mlx = (float2*)(sm + SM_MX + 2048) + wq4 * 8 + g;
            if (v == 0) { *mlx = make_float2(m, l); bar_arrive(11, 256); }
            else {
                mbar_wait(BAR(JD), 0);
                bar_sync(11, 256);
                const float2 o = *mlx;
                const float mn = fmaxf(m, o.x);
                l = l * ex2(m - mn) + o.y * ex2(o.x - mn);
                if ((wq4 >> 1) == rk) st_x4(gs + (B_ML + wq4 * 8 + g) * 4096 + (t >> 1) * 1024 + (j >> 1) * 8 + (t & 1) * 4, encf(mn), encf(l), 1u, 1u);
            }
        }
        const int pi = j < NFF ? rk * 128 + w8 * 16 + (lane >> 1) : ((j - J_RED) & 15) * 16 + (w8 & 1) * 8 + g;
        const uint32_t xw = *(const uint32_t*)(xin + 2 * pi);
        const uint32_t one = (g & 1) ? 0x3f800000u : 0x00003f80u;
        const uint32_t* pm = gs + near_off(B_MB, cls) + pi;
        {
            const uint32_t ab = sb + SM_U + B_WUV * 32768 + v * 4096 + a128;
            uint32_t pa = sb + SM_PB + wq4 * 320 + frag_off(64 * v + 32 * (g >> 2) + 16 * (t & 1) + 8 * (t >> 1) + 2 * (g & 3));
            uint32_t fa = sb + SM_PB + g * 320 + t * 16;
            const uint32_t* pe = gs + G_E1 + j * 8192 + (w8 >> 1) * 2048 + ((((cls >> 1) ^ (w8 >> 1)) & 1) << 10) + (((w8 & 1) * 16 + t) * 8 + g) * 4;
            uint32_t* p2 = gs + (B_E2 + (j >> 4)) * 4096 + (t >> 1) * 1024 + (j & 12) * 64 + w8 * 32 + (j & 3) * 8 + (g & 6) + (t & 1);
            pin(pa); pin(fa); pin(pe); pin(p2);
            const uint32_t mk = (g & 1) ? 0xffff0000u : 0x0000ffffu, m0 = (g & 2) ? 0u : mk, m1 = (g & 2) ? mk : 0u;
            uint4 pv[4];
            bool hv = false;
            bar_sync(3, 416);
            uint4 wa = lds128(sb + SM_W + (wq4 * 4 + t) * 16);
            uint32_t wb[8] = {wa.x & m0, wa.x & m1, wa.y & m0, wa.y & m1, wa.z & m0, wa.z & m1, wa.w & m0, wa.w & m1};
            pv[0] = pv[1] = pv[2] = pv[3] = make_uint4(0u, 0u, 0u, 0u);
            poll<512, E1_SLEEP, true>(pv, pe, [&]() {
                if (!hv) {
                    hv = __all_sync(0xffffffffu, mbar_test(BAR(IT_WUV + t), 0));
                    if (hv) load8<true>(a, [&](int s) { return ab + (s >> 1) * 8192 + (s & 1) * 2048; });
                }
            });
            if (lane == 0) TRACE_Q(48 + w8);
            if (u8 == 0) TRACE_Q(18);
            float lo, hi2;
            float2 inv;
#pragma unroll 1
            for (int pass = 0;; pass++) {
                float e[4][4];
#pragma unroll
                for (int i = 0; i < 4; i++) {
                    e[i][0] = e[i][1] = e[i][2] = e[i][3] = 0.f;
                    mma(e[i], pv[i].x, pv[i].y, pv[i].z, pv[i].w, wb[2 * i], wb[2 * i + 1]);
                }
                const float r0 = (t & 2) ? (e[0][2] + e[1][2]) + (e[2][2] + e[3][2]) : (e[0][0] + e[1][0]) + (e[2][0] + e[3][0]);
                const float r1 = (t & 2) ? (e[0][3] + e[1][3]) + (e[2][3] + e[3][3]) : (e[0][1] + e[1][1]) + (e[2][1] + e[3][1]);
                const uint32_t hi = pack2(r0, r1);
                sts32(pa, hi); sts32(pa + 1280, pack2(r0 - bflo(hi), r1 - bfhi(hi)));
                if (!hv) {
#pragma unroll 1
                    for (int i = 0; i < 4; i++) mbar_wait(BAR(IT_WUV + i), 0);
                    load8<true>(a, [&](int s) { return ab + (s >> 1) * 8192 + (s & 1) * 2048; });
                    hv = true;
                }
                bar_sync(1, 256);
                if (u8 == 0) TRACE(19);
                ldfrag(b, fa);
                mma8(c, a, b);
                mbar_wait(BAR(WR), 0);
                asm volatile("ld.shared.v2.f32 {%0, %1}, [%2];" : "=f"(inv.x), "=f"(inv.y) : "r"(sb + SM_FQ) : "memory");
                quad_pair(c[0] + c[1], c[2] + c[3], t, lo, hi2);
                if (__builtin_expect(__all_sync(0xffffffffu, pass || __float_as_uint(inv.y) == 0), 1)) break;
                wa = lds128(sb + SM_W2 + (wq4 * 4 + t) * 16);
                wb[0] = wa.x & m0; wb[1] = wa.x & m1; wb[2] = wa.y & m0; wb[3] = wa.y & m1; wb[4] = wa.z & m0; wb[5] = wa.z & m1; wb[6] = wa.w & m0; wb[7] = wa.w & m1;
                bar_sync(1, 256);
            }
            if (!(g & 1)) st_x1(p2, enc(pack2(lo * inv.x, hi2 * inv.x)));
            bar_arrive(4, 416);
            if (u8 == 0) TRACE(20);
        }
        if (j < NFF) {
            const uint32_t* p3 = gs + near_off(B_E3 + rk * 2 + v, cls) + wq4 * 256 + t * 16 + g * 2;
            const int od = lane & 1;
            uint32_t za = sb + SM_FZ + od * 576 + frag_off(w8 * 32 + (lane & 30));
            uint32_t fa = sb + SM_FZ + (g & 3) * 576 + ((lane ^ j) & 16) * 16 + t * 16, ya = sb + SM_Y + u8 * 4;
            uint32_t mb[3];
            uint4 a2[8];
            poll<1024, MB_SLEEP>(mb, pm);
            const uint32_t kk = pack2(1.f + bflo(mb[2]), 1.f + bfhi(mb[2]));
            sts32(za + 2 * 576, od ? mb[1] : kk);
            uint2 e3[4] = {make_uint2(0u, 0u), make_uint2(0u, 0u), make_uint2(0u, 0u), make_uint2(0u, 0u)};
            uint32_t ra = peer_addr(sb + SM_RED + (rk * 2 + v) * 512 + ((wq4 & 1) * 16 + (t >> 1) * 8 + g) * 16 + (t & 1) * 8, wq4 >> 1), tbo = peer_addr(BAR(QB), wq4 >> 1);
            pin(za); pin(fa); pin(ya); pin(ra); pin(tbo);
            if (lane == 0) mbar_expect(BAR(QB), 256);
            const uint32_t gb = BAR(IT_X + v * 2), ab = sb + SM_U + (B_X + v) * 32768 + a128;
            bool early = false, early2 = false;
            auto ldw = [&]() {
                if (!early) {
                    early = __all_sync(0xffffffffu, mbar_test(gb, 0));
                    if (early) load8<true>(a, [&](int s) { return ab + s * 2048; });
                }
                if (!early2) {
                    early2 = __all_sync(0xffffffffu, mbar_test(gb + 8, 0));
                    if (early2) load8<true>(a2, [&](int s) { return ab + 16384 + s * 2048; });
                }
            };
            bar_sync(8, 384);
            poll<256, 0, true>(e3, p3, ldw);
            if (u8 == 0) TRACE(23);
            float s0[4] = {0.f, 0.f, 0.f, 0.f}, s1[4] = {0.f, 0.f, 0.f, 0.f};
            mma(s0, e3[0].x, e3[0].y, e3[1].x, e3[1].y, one, one); mma(s1, e3[2].x, e3[2].y, e3[3].x, e3[3].y, one, one);
            const float y0 = fmaf(bflo(mb[0]), (t & 2) ? s0[2] + s1[2] : s0[0] + s1[0], bflo(xw)), y1 = fmaf(bfhi(mb[0]), (t & 2) ? s0[3] + s1[3] : s0[1] + s1[1], bfhi(xw));
            stsf(ya, od ? y1 : y0);
            const float z0 = y0 * bflo(kk), z1 = y1 * bfhi(kk);
            const uint32_t zh = pack2(z0, z1);
            sts32(za, od ? pack2(z0 - bflo(zh), z1 - bfhi(zh)) : zh);
            bar_sync(7, 288);
            if (u8 == 0) TRACE(24);
            ldfrag(b, fa);
            if (!early) { mbar_wait(gb, 0); load8<true>(a, [&](int s) { return ab + s * 2048; }); }
            {
                float e[4][4];
#pragma unroll
                for (int s = 0; s < 16; s++) {
                    if (s == 8 && !early2) { mbar_wait(gb + 8, 0); load8<true>(a2, [&](int q) { return ab + 16384 + q * 2048; }); }
                    const uint4& x = s < 8 ? a[s] : a2[s & 7];
                    const uint4& y = b[(s >> 1) & 3];
                    float (&d)[4] = e[(s >> 3) * 2 + (s & 1)];
                    if (!(s & 6)) d[0] = d[1] = d[2] = d[3] = 0.f;
                    mma(d, x.x, x.y, x.z, x.w, (s & 1) ? y.z : y.x, (s & 1) ? y.w : y.y);
                }
                const bool hi = t >> 1;
                const float k0 = hi ? e[2][2] + e[3][2] : e[0][0] + e[1][0], k1 = hi ? e[2][3] + e[3][3] : e[0][1] + e[1][1];
                const float o0 = hi ? e[2][0] + e[3][0] : e[0][2] + e[1][2], o1 = hi ? e[2][1] + e[3][1] : e[0][3] + e[1][3];
                st_async2(ra, k0 + shx(o0, 2), k1 + shx(o1, 2), tbo);
            }
        } else if (j >= J_RED && j < J_END && w8 < 2) {
            uint32_t ga[1], e3[4];
            poll<0, MB_SLEEP>(ga, pm);
            bar_sync(8, 192);
            poll<64, 100>(e3, gs + near_off(B_E3 + (pi >> 6), cls) + (pi & 48) * 16 + t * 64 + (pi & 15));
            float y0 = (bflo(e3[0]) + bflo(e3[1])) + (bflo(e3[2]) + bflo(e3[3])), y1 = (bfhi(e3[0]) + bfhi(e3[1])) + (bfhi(e3[2]) + bfhi(e3[3]));
#pragma unroll
            for (int o = 1; o < 4; o <<= 1) { y0 += shx(y0, o); y1 += shx(y1, o); }
            const int col = g + (t & 1) * 8;
            y0 = __shfl_sync(0xffffffffu, (t & 1) ? fmaf(bfhi(ga[0]), y1, bfhi(xw)) : fmaf(bflo(ga[0]), y0, bflo(xw)), (col >> 1) * 4 + (col & 1));
            uint32_t gb = 0;
            auto ldg = [&]() { if (__all_sync(0xffffffffu, mbar_test(BAR(QB), 1))) gb = lds32(sb + SM_FV + 256 + w8 * 32 + (col >> 1) * 4); };
            uint16_t* po = (uint16_t*)out + (j - J_RED) * 32 + w8 * 16 + col;
            pin(po);
            uint32_t yv[NFF / 4];
            poll<256, 0>(yv, gs + near_off(B_E5 + j - J_RED, cls) + t * 16 + w8 * 8 + g, ldg);
            if (u8 == 0) TRACE(26);
            float e[4][4];
#pragma unroll
            for (int i = 0; i < 4; i++) {
                e[i][0] = e[i][1] = e[i][2] = e[i][3] = 0.f;
                mma(e[i], yv[4 * i], yv[4 * i + 1], i < 3 ? yv[(4 * i + 2) % (NFF / 4)] : 0u, i < 3 ? yv[(4 * i + 3) % (NFF / 4)] : 0u, one, one);
            }
            const float s = (t & 1) ? ((e[0][1] + e[0][3]) + (e[1][1] + e[1][3])) + ((e[2][1] + e[2][3]) + (e[3][1] + e[3][3]))
                                    : ((e[0][0] + e[0][2]) + (e[1][0] + e[1][2])) + ((e[2][0] + e[2][2]) + (e[3][0] + e[3][2]));
            if (__any_sync(0xffffffffu, !gb)) { mbar_wait(BAR(QB), 1); ldg(); }
            if (t < 2) *po = (uint16_t)pack2(fmaf((col & 1) ? bfhi(gb) : bflo(gb), s, y0), 0.f);
            if (u8 == 0) TRACE(27);
        }
    }
}

typedef CUresult (*EncFn)(CUtensorMap*, CUtensorMapDataType, cuuint32_t, void*, const cuuint64_t*, const cuuint64_t*,
                          const cuuint32_t*, const cuuint32_t*, CUtensorMapInterleave, CUtensorMapSwizzle,
                          CUtensorMapL2promotion, CUtensorMapFloatOOBfill);

void make_map(EncFn enc_fn, CUtensorMap* m, const void* p, cuuint64_t d0, cuuint64_t d1, cuuint64_t d2, cuuint64_t d3,
              cuuint64_t s1, cuuint64_t s2, cuuint64_t s3, cuuint32_t b0, cuuint32_t b1, cuuint32_t b2, cuuint32_t b3, CUtensorMapSwizzle sw) {
    const cuuint64_t dims[4] = {d0, d1, d2, d3}, strides[3] = {s1, s2, s3};
    const cuuint32_t box[4] = {b0, b1, b2, b3}, es[4] = {1, 1, 1, 1};
    enc_fn(m, CU_TENSOR_MAP_DATA_TYPE_BFLOAT16, 4, (void*)p, dims, strides, box, es,
           CU_TENSOR_MAP_INTERLEAVE_NONE, sw, PROMO, CU_TENSOR_MAP_FLOAT_OOB_FILL_NONE);
}

uint32_t* scratch = nullptr;

struct Tune { const char* win; const char* late; int tau, t_off; const char* tail[3][4]; };
Tune tune = {"66666666655555555555555555555555555533333",
             "00000000000000000000999999999999999999999", 320, -300,
             {{"VVVVOOOOguguDDDD", "zzzzzzzzzzzzzzzz", "888899998888789a", "ibbb0gjj7aaa3787"},
              {"VMVMVVOOOO", "zzzzzzzzzz", "8888889999", "588888kbbb"},
              {"VVVVOOOOMM", "zzzzzzzzzz", "aaaaaaaa88", "q8880cjjon"}}};
bool ready = false;

}

extern "C" void kernel_launch(void* const* d_in, const int* in_sizes, int n_in, void* d_out, int out_size) {
    (void)in_sizes; (void)n_in; (void)out_size;
    static Maps maps;
    static const void* cached[12] = {};
    bool same = ready;
    for (int i = 0; i < 12 && same; i++) same = cached[i] == d_in[i];
    if (!same) {
        void* fn = nullptr;
        cudaDriverEntryPointQueryResult qr;
        cudaGetDriverEntryPoint("cuTensorMapEncodeTiled", &fn, cudaEnableDefault, &qr);
        EncFn e = (EncFn)fn;
        const CUtensorMapSwizzle S128 = CU_TENSOR_MAP_SWIZZLE_128B;
        make_map(e, &maps.m[MP_WQ], d_in[2], 64, 512, 64, 1, 8192, 128, 8192, 64, 64, 1, 1, S128);
        make_map(e, &maps.m[MP_WUK], d_in[3], 64, 512, 64, 1, 8192, 128, 8192, 64, 64, 1, 1, S128);
        make_map(e, &maps.m[MP_CKV], d_in[1], 64, 8, 8, 4096, 1024, 128, 8192, 64, 8, 4, 2, S128);
        make_map(e, &maps.m[MP_MODB], d_in[11], 3072, 512, 1, 1, 6144, 6144, 6144, 64, 128, 1, 1, S128);
        make_map(e, &maps.m[MP_WUV], d_in[4], 64, 512, 64, 1, 8192, 128, 8192, 64, 32, 2, 1, S128);
        make_map(e, &maps.m[MP_WO], d_in[5], 512, 4096, 1, 1, 1024, 1024, 1024, 64, 64, 1, 1, S128);
        make_map(e, &maps.m[MP_GATE], d_in[7], 1792, 512, 1, 1, 3584, 3584, 3584, 64, 128, 1, 1, S128);
        make_map(e, &maps.m[MP_UP], d_in[8], 1792, 512, 1, 1, 3584, 3584, 3584, 64, 128, 1, 1, S128);
        make_map(e, &maps.m[MP_DOWN], d_in[9], 64, 1792, 8, 1, 1024, 128, 1024, 64, 32, 2, 1, S128);
        for (int r = 0; r < 3; r++) {
            int ids[58], cnt[128] = {}, tn = tune.t_off - (W0 - 1) * tune.tau;
            uint2* sc = maps.sched[r];
            auto dig = [](char ch) { return ch >= 'a' ? ch - 'a' + 10 : ch >= 'A' ? ch - 'A' + 36 : ch - '0'; };
            for (int i = 0; i < 58; i++) sc[i] = make_uint2(0u, 0u);
            for (int i = 0;; i++) {
                int id = i, buf, dep, w, wl;
                if (i < IT_WUV) {
                    const int u = (i - IT_CKV) >> 2;
                    buf = i < IT_CKV ? 4 + ((i - 1) >> 2) : u % 6;
                    dep = i < IT_CKV || u < 4 ? -1 : u < 6 ? EB_WQ + u - 4 : EB_UNIT0 + u - 6;
                    w = dig(tune.win[i]); wl = dig(tune.late[i]);
                    if (i) tn += tune.tau;
                } else {
                    const char ch = tune.tail[r][0][i - IT_WUV];
                    if (!ch) break;
                    buf = ch == 'V' ? B_WUV : ch == 'O' ? B_WO : ch == 'D' ? B_DN : ch == 'u' ? B_X + 1 : B_X;
                    id = (ch == 'V' ? IT_WUV : ch == 'O' ? IT_WO : ch == 'D' ? IT_DOWN : ch == 'u' ? IT_X + 2 : IT_X) + cnt[(int)ch]++;
                    dep = EB_UNIT0 + (buf < 2 ? buf + 6 : buf);
                    w = dig(tune.tail[r][1][i - IT_WUV]); wl = dig(tune.tail[r][2][i - IT_WUV]);
                    tn += 32 * dig(tune.tail[r][3][i - IT_WUV]);
                }
                if (id < IT_X || id >= IT_DOWN ? (id - 1) & 3 : (id - IT_X) & 1) dep = -1;
                ids[i] = id;
                auto back = [&](int d) { return i < d ? 0 : (ids[i - d] && ids[i - d] <= NCP ? 1 : ids[i - d]) + 1; };
                sc[i].x = id | (buf * 4 + (id < IT_X || id >= IT_DOWN ? (id - 1) & 3 : ((id - IT_X) & 1) * 2)) << 6 | (dep + 1) << 11 | (w > 32 ? NEVER + 1 : back(w)) << 18 | (wl ? back(wl) : 0) << 25;
                const int mp = id < IT_CKV ? MP_WQ + ((id - 1) >> 2) : id < IT_WUV ? MP_CKV : id < IT_WO ? MP_WUV : id < IT_X ? MP_WO
                             : id >= IT_DOWN ? MP_DOWN : r ? MP_MODB : MP_GATE + ((id - IT_X) >> 1);
                const int step = mp == MP_CKV ? id - IT_CKV : mp == MP_WUV ? (id - IT_WUV) * 2 : mp == MP_DOWN ? id - IT_DOWN : id < IT_X ? (id - 1) & 3 : ((id - IT_X) & 1) * 2;
                sc[i].y = (tn & 0xffff) | (mp & 15) << 16 | step << 20;
            }
        }
        cudaGetSymbolAddress((void**)&scratch, g_scratch);
        scratch = (uint32_t*)(((uintptr_t)scratch + (2u << 20) - 1) & ~(uintptr_t)((2u << 20) - 1));
        cudaFuncSetAttribute(fused_kernel, cudaFuncAttributeMaxDynamicSharedMemorySize, SM_TOTAL);
        for (int i = 0; i < 12; i++) cached[i] = d_in[i];
        ready = true;
    }
    const First f = {{(const uint8_t*)d_in[2], (const uint8_t*)d_in[11]}, {(const __nv_bfloat16*)d_in[0], (const __nv_bfloat16*)d_in[10]}};
    fused_kernel<<<NCTA, NTHREADS, SM_TOTAL>>>(f, (__nv_bfloat16*)d_out, scratch, maps);
}
```

```cpp
#include <cuda_runtime.h>
#include <cuda_bf16.h>
#include <cuda.h>
#include <stdint.h>
#include <limits.h>

namespace {

constexpr int NCTA = 128;
constexpr int NTHREADS = 512;
constexpr int NUNITS = 8;
constexpr int NFF = 56, J_RED = 104, J_END = 120;
constexpr uint32_t SPIN_LIMIT = 1u << 22;

#define PROMO CU_TENSOR_MAP_L2_PROMOTION_L2_64B
#define NEAR_CLK 390
#define E1_EARLY 50
#define STAG 300
#define NUMA 1
#define NPROBE 5
#define NCP 2
#define W0 4
#define RD_ITEM 15
#define JAN_SLEEP 100
#define RD_SLEEP 400
#define HA_DELAY 200
#define H_SLEEP 100
#define QA_DELAY 600
#define QA_SLEEP 200
#define ML_DELAY 300
#define E1_SLEEP 50
#define MB_SLEEP 100
constexpr int B_WUV = 2, B_WO = 3, B_X = 4  , B_DN = 0;

constexpr int SM_U = 0;
constexpr int SM_XA = 6 * 32768;
constexpr int SM_XB = SM_XA + 12288;
constexpr int SM_MX = SM_XB + 16384;
constexpr int SM_FZ = SM_XB + 8192;
constexpr int SM_PB = SM_XB;
constexpr int SM_Y = SM_XB + 12288;
constexpr int SM_RED = SM_XB + 4096;
constexpr int SM_FS = SM_XB + 20480;
constexpr int SM_FV = SM_FS + 1024;
constexpr int SM_QX = SM_XA + 8192;
constexpr int SM_FQ = SM_FV + 512;
constexpr int SM_CLS = SM_FQ + 128;
constexpr int SM_W = SM_FQ + 256;
constexpr int SM_W2 = SM_MX + 2304;
constexpr int SM_SCR = SM_XA + 9216;
constexpr int SM_TR = SM_XB + 19456;
constexpr int SM_BAR = SM_W + 256;
constexpr int SM_TOTAL = SM_BAR + 1024;
static_assert(SM_TOTAL <= 232448, "smem");

enum { IT_MODA = 0, IT_WQ = 1, IT_WUK = 5, IT_CKV = 9, IT_WUV = 41, IT_WO = 45, IT_X = 49  , IT_DOWN = 53, NITEMS = 57,
       NEVER = 63,
       SF0 = 64,
       PF0 = 80,
       EB_UNIT0 = 96, MBB = 103,
       EB_WQ = 104, EB_WUK, QT, QB, JD, WR };

enum { MP_WQ = 0, MP_WUK, MP_CKV, MP_WUV, MP_DOWN, MP_WO, MP_GATE, MP_UP, MP_MODB, NMAPS };
struct First { const uint8_t* w[2]; const __nv_bfloat16* v[2]; };
struct Maps { CUtensorMap m[NMAPS]; uint2 sched[3][58]; };

enum { B_HA = 0,
       B_MB = 6,
       B_RD = 7,
       B_E2 = 8,
       B_QA = 16,
       B_ML = 32,
       B_E5 = 64,
       B_E3 = 80,
       B_PR = 96,
       B_TR = 100 };
constexpr int G_E1 = 1 << 19;
constexpr int G_TR = B_TR * 4096;
__device__ __align__(1024) uint32_t g_scratch[(8 << 20) / 4];

#define TRACE(slot) do {} while (0)
#define TRACE_Q(slot) do {} while (0)
#define TRACE_GT(slot) do {} while (0)

__device__ __forceinline__ uint32_t s2u(const void* p) { return (uint32_t)__cvta_generic_to_shared(p); }
__device__ __forceinline__ void mbar_init(uint32_t b, int c) { asm volatile("mbarrier.init.shared::cta.b64 [%0], %1;" :: "r"(b), "r"(c) : "memory"); }
__device__ __forceinline__ void mbar_expect(uint32_t b, uint32_t bytes) { asm volatile("mbarrier.arrive.expect_tx.shared::cta.b64 _, [%0], %1;" :: "r"(b), "r"(bytes) : "memory"); }
__device__ __forceinline__ void mbar_arrive(uint32_t b) { asm volatile("mbarrier.arrive.shared::cta.b64 _, [%0];" :: "r"(b) : "memory"); }
__device__ __forceinline__ void mbar_wait(uint32_t b, uint32_t ph) {
    asm volatile("{\n.reg .pred p;\nW: mbarrier.try_wait.parity.shared::cta.b64 p, [%0], %1;\n@!p bra W;\n}" :: "r"(b), "r"(ph) : "memory");
}
__device__ __forceinline__ void mbar_waitb(uint32_t b, uint32_t ph) {
    asm volatile("{\n.reg .pred p;\n.reg .u32 n;\nmov.u32 n, 0;\n"
                 "W: mbarrier.try_wait.parity.shared::cta.b64 p, [%0], %1;\n@p bra D;\n"
                 "add.u32 n, n, 1;\nsetp.lt.u32 p, n, 0x100000;\n@p bra W;\ntrap;\nD:\n}" :: "r"(b), "r"(ph) : "memory");
}
__device__ __forceinline__ uint32_t mbar_test(uint32_t b, uint32_t ph) {
    uint32_t ok;
    asm volatile("{\n.reg .pred p;\nmbarrier.test_wait.parity.shared::cta.b64 p, [%1], %2;\nselp.u32 %0, 1, 0, p;\n}" : "=r"(ok) : "r"(b), "r"(ph) : "memory");
    return ok;
}
__device__ __forceinline__ void bar_sync(int id, int n) { asm volatile("bar.sync %0, %1;" :: "r"(id), "r"(n) : "memory"); }
__device__ __forceinline__ void bar_arrive(int id, int n) { asm volatile("bar.arrive %0, %1;" :: "r"(id), "r"(n) : "memory"); }
__device__ __forceinline__ uint32_t peer_addr(uint32_t a, uint32_t rank) { uint32_t r; asm("mapa.shared::cluster.u32 %0, %1, %2;" : "=r"(r) : "r"(a), "r"(rank)); return r; }
__device__ __forceinline__ void st_async2(uint32_t a, float x, float y, uint32_t bar) {
    asm volatile("st.async.weak.shared::cluster.mbarrier::complete_tx::bytes.v2.f32 [%0], {%1, %2}, [%3];" :: "r"(a), "f"(x), "f"(y), "r"(bar) : "memory");
}
__device__ __forceinline__ uint32_t gtime() { uint32_t t; asm volatile("mov.u32 %0, %%globaltimer_lo;" : "=r"(t)); return t; }
__device__ __forceinline__ void fence_gpu() { asm volatile("fence.acq_rel.gpu;" ::: "memory"); }

__device__ __forceinline__ uint32_t enc(uint32_t b) { uint32_t r; asm("max.u32 %0, %1, 1;" : "=r"(r) : "r"(b)); return r; }
__device__ __forceinline__ uint32_t encf(float f) { return enc(__float_as_uint(f)); }
__device__ __forceinline__ void st_x1(uint32_t* p, uint32_t v) { asm volatile("st.relaxed.gpu.global.u32 [%0], %1;" :: "l"(p), "r"(v) : "memory"); }
__device__ __forceinline__ void st_x4(void* p, uint32_t a, uint32_t b, uint32_t c, uint32_t d) {
    asm volatile("st.relaxed.gpu.global.v4.u32 [%0], {%1, %2, %3, %4};" :: "l"(p), "r"(a), "r"(b), "r"(c), "r"(d) : "memory");
}
__device__ __forceinline__ void st2_x1(uint32_t* p, uint32_t v) { st_x1(p, v); st_x1(p + 1024, v); }
__device__ __forceinline__ void st2_x4(uint32_t* p, uint32_t a, uint32_t b, uint32_t c, uint32_t d) { st_x4(p, a, b, c, d); st_x4(p + 1024, a, b, c, d); }
__device__ __forceinline__ int near_off(int b, uint32_t cls) { return b * 4096 + (((__popc(b & 0x2C) ^ cls) & 1) << 10); }
__device__ __forceinline__ void ld_x(uint32_t& v, const void* p) { asm volatile("ld.relaxed.gpu.global.u32 %0, [%1];" : "=r"(v) : "l"(p) : "memory"); }
__device__ __forceinline__ void ld_x(uint4& v, const void* p) {
    asm volatile("ld.relaxed.gpu.global.v4.u32 {%0, %1, %2, %3}, [%4];" : "=r"(v.x), "=r"(v.y), "=r"(v.z), "=r"(v.w) : "l"(p) : "memory");
}
__device__ __forceinline__ void ld_x(uint2& v, const void* p) { asm volatile("ld.relaxed.gpu.global.v2.u32 {%0, %1}, [%2];" : "=r"(v.x), "=r"(v.y) : "l"(p) : "memory"); }
__device__ __forceinline__ uint32_t minw(uint32_t v) { return v; }
__device__ __forceinline__ uint32_t minw(const uint2& v) { return min(v.x, v.y); }
__device__ __forceinline__ uint32_t minw(const uint4& v) { return min(__vimin3_u32(v.x, v.y, v.z), v.w); }
template <int N> __device__ __forceinline__ uint32_t mint(const uint32_t* m) {
    if constexpr (N == 1) return m[0];
    else if constexpr (N == 2) return min(m[0], m[1]);
    else return __vimin3_u32(mint<(N + 2) / 3>(m), mint<(N + 1) / 3>(m + (N + 2) / 3), mint<N / 3>(m + (N + 2) / 3 + (N + 1) / 3));
}

template <int STRIDE, int S4 = 4 * STRIDE, typename T, int N>
__device__ __forceinline__ void poll_start(T (&v)[N], const void* base) {
#pragma unroll
    for (int i = 0; i < N; i++) ld_x(v[i], (const uint8_t*)base + (i & 3) * STRIDE + (i >> 2) * S4);
}
struct Nop { __device__ void operator()() const {} };
template <int STRIDE, int SLEEP, bool STARTED = false, int S4 = 4 * STRIDE, typename T, int N, typename F = Nop, typename G = Nop>
__device__ __forceinline__ void poll(T (&v)[N], const void* base, F idle = F(), G ahead = G()) {
    if (!STARTED) { poll_start<STRIDE, S4>(v, base); idle(); }
#pragma unroll 1
    for (uint32_t it = 0;; it++) {
        uint32_t m[N];
        ahead();
#pragma unroll
        for (int i = 0; i < N; i++) m[i] = minw(v[i]);
        if (__all_sync(0xffffffffu, mint<N>(m) != 0)) break;
        if (SLEEP && it > 0) __nanosleep(SLEEP);
#pragma unroll
        for (int i = 0; i < N; i++) if (!m[i]) ld_x(v[i], (const uint8_t*)base + (i & 3) * STRIDE + (i >> 2) * S4);
        idle();
        if (it > SPIN_LIMIT) __trap();
    }
}

__device__ __forceinline__ float bflo(uint32_t w) { return __uint_as_float(w << 16); }
__device__ __forceinline__ float bfhi(uint32_t w) { return __uint_as_float(w & 0xffff0000u); }
__device__ __forceinline__ uint32_t pack2(float lo, float hi) {
    uint32_t r; asm("cvt.rn.bf16x2.f32 %0, %1, %2;" : "=r"(r) : "f"(hi), "f"(lo)); return r;
}
__device__ __forceinline__ float rbf(float x) { return __uint_as_float(pack2(0.f, x)); }
__device__ __forceinline__ float ex2(float x) { float r; asm("ex2.approx.ftz.f32 %0, %1;" : "=f"(r) : "f"(x)); return r; }
__device__ __forceinline__ float shx(float v, int m) { return __shfl_xor_sync(0xffffffffu, v, m); }
__device__ __forceinline__ uint4 lds128(uint32_t a) { uint4 v; asm volatile("ld.shared.v4.u32 {%0, %1, %2, %3}, [%4];" : "=r"(v.x), "=r"(v.y), "=r"(v.z), "=r"(v.w) : "r"(a) : "memory"); return v; }
__device__ __forceinline__ uint32_t lds32(uint32_t a) { uint32_t v; asm volatile("ld.shared.u32 %0, [%1];" : "=r"(v) : "r"(a) : "memory"); return v; }
__device__ __forceinline__ void sts32(uint32_t a, uint32_t v) { asm volatile("st.shared.u32 [%0], %1;" :: "r"(a), "r"(v) : "memory"); }
__device__ __forceinline__ void sts16(uint32_t a, uint32_t v) { asm volatile("st.shared.u16 [%0], %1;" :: "r"(a), "h"((uint16_t)v) : "memory"); }
__device__ __forceinline__ int frag_off(int k) { return (k >> 5) * 64 + ((k >> 1) & 3) * 16 + ((k >> 4) & 1) * 8 + ((k >> 3) & 1) * 4 + (k & 1) * 2; }

template <bool TRANS>
__device__ __forceinline__ uint4 ldsm(uint32_t a) {
    uint4 r;
    if (TRANS) asm volatile("ldmatrix.sync.aligned.m8n8.x4.trans.shared.b16 {%0, %1, %2, %3}, [%4];" : "=r"(r.x), "=r"(r.y), "=r"(r.z), "=r"(r.w) : "r"(a) : "memory");
    else asm volatile("ldmatrix.sync.aligned.m8n8.x4.shared.b16 {%0, %1, %2, %3}, [%4];" : "=r"(r.x), "=r"(r.y), "=r"(r.z), "=r"(r.w) : "r"(a) : "memory");
    return r;
}
__device__ __forceinline__ void mma(float (&c)[4], uint32_t a0, uint32_t a1, uint32_t a2, uint32_t a3, uint32_t b0, uint32_t b1) {
    asm volatile("mma.sync.aligned.m16n8k16.row.col.f32.bf16.bf16.f32 {%0,%1,%2,%3}, {%4,%5,%6,%7}, {%8,%9}, {%0,%1,%2,%3};"
                 : "+f"(c[0]), "+f"(c[1]), "+f"(c[2]), "+f"(c[3]) : "r"(a0), "r"(a1), "r"(a2), "r"(a3), "r"(b0), "r"(b1));
}
template <bool TRANS, typename F>
__device__ __forceinline__ void load8(uint4 (&a)[8], F addr) {
    __syncwarp();
#pragma unroll
    for (int s = 0; s < 8; s++) a[s] = ldsm<TRANS>(addr(s));
}
__device__ __forceinline__ void mma8(float (&c)[4], const uint4 (&a)[8], const uint4 (&b)[4]) {
    float e[4][4];
#pragma unroll
    for (int s = 0; s < 8; s++) {
        if (s < 4) e[s][0] = e[s][1] = e[s][2] = e[s][3] = 0.f;
        mma(e[s & 3], a[s].x, a[s].y, a[s].z, a[s].w, (s & 1) ? b[s >> 1].z : b[s >> 1].x, (s & 1) ? b[s >> 1].w : b[s >> 1].y);
    }
#pragma unroll
    for (int i = 0; i < 4; i++) c[i] = (e[0][i] + e[1][i]) + (e[2][i] + e[3][i]);
}
__device__ __forceinline__ void ldfrag(uint4 (&b)[4], uint32_t a) {
    asm volatile("ld.shared.v4.u32 {%0,%1,%2,%3}, [%16];\nld.shared.v4.u32 {%4,%5,%6,%7}, [%16+64];\n"
                 "ld.shared.v4.u32 {%8,%9,%10,%11}, [%16+128];\nld.shared.v4.u32 {%12,%13,%14,%15}, [%16+192];\n"
                 : "=r"(b[0].x), "=r"(b[0].y), "=r"(b[0].z), "=r"(b[0].w), "=r"(b[1].x), "=r"(b[1].y), "=r"(b[1].z), "=r"(b[1].w),
                   "=r"(b[2].x), "=r"(b[2].y), "=r"(b[2].z), "=r"(b[2].w), "=r"(b[3].x), "=r"(b[3].y), "=r"(b[3].z), "=r"(b[3].w) : "r"(a) : "memory");
}
__device__ __forceinline__ void quad_pair(float x, float y, int t, float& lo, float& hi) {
    const float k = ((t & 1) ? y : x) + shx((t & 1) ? x : y, 1);
    lo = k + shx(k, 2); hi = shx(k, 4) + shx(k, 6);
}
__device__ __forceinline__ void pin(uint32_t& x) { asm volatile("" : "+r"(x)); }
template <typename T> __device__ __forceinline__ void pin(T*& x) { asm volatile("" : "+l"(x)); }
__device__ __forceinline__ float4 ldsf4(uint32_t a) { const uint4 v = lds128(a); return make_float4(__uint_as_float(v.x), __uint_as_float(v.y), __uint_as_float(v.z), __uint_as_float(v.w)); }
__device__ __forceinline__ float sum4(const float4& f) { return (f.x + f.y) + (f.z + f.w); }
__device__ __forceinline__ void stsf(uint32_t a, float v) { sts32(a, __float_as_uint(v)); }

__device__ __forceinline__ void wg_fence() { asm volatile("wgmma.fence.sync.aligned;" ::: "memory"); }
__device__ __forceinline__ void wg_commit() { asm volatile("wgmma.commit_group.sync.aligned;" ::: "memory"); }
__device__ __forceinline__ void wg_wait1() { asm volatile("wgmma.wait_group.sync.aligned 1;" ::: "memory"); }
__device__ __forceinline__ void wg_wait0() { asm volatile("wgmma.wait_group.sync.aligned 0;" ::: "memory"); }
#define R8(o) "+f"(d[o]), "+f"(d[o + 1]), "+f"(d[o + 2]), "+f"(d[o + 3]), "+f"(d[o + 4]), "+f"(d[o + 5]), "+f"(d[o + 6]), "+f"(d[o + 7])
__device__ __forceinline__ void wgmma_rs_n32(float (&d)[16], const uint4& a, uint64_t db, int acc) {
    asm volatile("{\n.reg .pred p;\nsetp.ne.b32 p, %21, 0;\n"
        "wgmma.mma_async.sync.aligned.m64n32k16.f32.bf16.bf16 "
        "{%0,%1,%2,%3,%4,%5,%6,%7,%8,%9,%10,%11,%12,%13,%14,%15}, {%16,%17,%18,%19}, %20, p, 1, 1, 0;\n}"
        : R8(0), R8(8) : "r"(a.x), "r"(a.y), "r"(a.z), "r"(a.w), "l"(db), "r"(acc));
}
#define PV_LO "{%0,%1,%2,%3,%4,%5,%6,%7,%8,%9,%10,%11,%12,%13,%14,%15,%16,%17,%18,%19,%20,%21,%22,%23,%24,%25,%26,%27,%28,%29,%30,%31,%32,%33,%34,%35,%36,%37,%38,%39,%40,%41,%42,%43,%44,%45,%46,%47,%48,%49,%50,%51,%52,%53,%54,%55,%56,%57,%58,%59,%60,%61,%62,%63}, "
#define PV_HI "{%64,%65,%66,%67,%68,%69,%70,%71,%72,%73,%74,%75,%76,%77,%78,%79,%80,%81,%82,%83,%84,%85,%86,%87,%88,%89,%90,%91,%92,%93,%94,%95,%96,%97,%98,%99,%100,%101,%102,%103,%104,%105,%106,%107,%108,%109,%110,%111,%112,%113,%114,%115,%116,%117,%118,%119,%120,%121,%122,%123,%124,%125,%126,%127}, "
__device__ __forceinline__ void wgmma_pv(float (&d)[128], const uint4& a, uint32_t blo, int acc) {
    asm volatile("{\n.reg .pred p;\n.reg .b32 u0, u1, u2, u3, t;\n.reg .b64 d0, d1, d2, d3;\nsetp.ne.b32 p, %133, 0;\n"
        "mov.b64 d0, {%132, 0x40000100};\nadd.u32 t, %132, 512;\nmov.b64 d1, {t, 0x40000100};\n"
        "add.u32 t, %132, 128;\nmov.b64 d2, {t, 0x40000100};\nadd.u32 t, %132, 640;\nmov.b64 d3, {t, 0x40000100};\n"
        "wgmma.fence.sync.aligned;\n"
        "wgmma.mma_async.sync.aligned.m64n128k16.f32.bf16.bf16 " PV_LO "{%128, u0, %129, u1}, d0, p, 1, 1, 1;\n"
        "wgmma.mma_async.sync.aligned.m64n128k16.f32.bf16.bf16 " PV_LO "{%130, u2, %131, u3}, d1, 1, 1, 1, 1;\n"
        "wgmma.commit_group.sync.aligned;\n"
        "wgmma.mma_async.sync.aligned.m64n128k16.f32.bf16.bf16 " PV_HI "{%128, u0, %129, u1}, d2, p, 1, 1, 1;\n"
        "wgmma.mma_async.sync.aligned.m64n128k16.f32.bf16.bf16 " PV_HI "{%130, u2, %131, u3}, d3, 1, 1, 1, 1;\n"
        "wgmma.commit_group.sync.aligned;\n}"
        : R8(0), R8(8), R8(16), R8(24), R8(32), R8(40), R8(48), R8(56), R8(64), R8(72), R8(80), R8(88), R8(96), R8(104), R8(112), R8(120)
        : "r"(a.x), "r"(a.y), "r"(a.z), "r"(a.w), "r"(blo), "r"(acc) : "memory");
}

template <int NW>
__device__ __forceinline__ void ln_stats(float s, float q, float sh, float* scr, int w, int lane, int bar, float& mean_b, float& sd_b) {
#pragma unroll
    for (int o = 16; o; o >>= 1) { s += shx(s, o); q += shx(q, o); }
    constexpr float n = 512.f / NW;
    if (lane == 0) { scr[w] = sh + s * (1.f / n); scr[NW + w] = q - s * s * (1.f / n); }
    bar_sync(bar, NW * 32);
    float mu = 0.f, m2 = 0.f;
#pragma unroll
    for (int i = 0; i < NW; i++) { mu += scr[i]; m2 += scr[NW + i]; }
    mu *= 1.f / NW;
#pragma unroll
    for (int i = 0; i < NW; i++) { const float d = scr[i] - mu; m2 = fmaf(n * d, d, m2); }
    mean_b = rbf(mu);
    sd_b = rbf(sqrtf(rbf(rbf(fmaxf(m2, 0.f) * (1.f / 512.f)) + 1e-5f)));
}
__device__ __forceinline__ float ln_mod(float x, float mean_b, float sd_b, float c, float s) {
    return rbf(rbf(__fdividef(rbf(x - mean_b), sd_b)) * rbf(1.f + c)) + s;
}

__global__ void __cluster_dims__(2, 1, 1) __launch_bounds__(NTHREADS, 1)
fused_kernel(const __grid_constant__ First F, __nv_bfloat16* __restrict__ out, uint32_t* __restrict__ gs, const __grid_constant__ Maps M) {
    extern __shared__ __align__(1024) uint8_t sm[];
    const uint32_t sb = s2u(sm);
    const int tid = threadIdx.x, lane = tid & 31;
    const int j = blockIdx.x, rk = j & 1;
    const int g = lane >> 2, t = lane & 3;
    const int r8 = lane & 7, lb3 = (lane >> 3) & 1, lb4 = lane >> 4;
    uint64_t pol;
    asm("createpolicy.fractional.L2::evict_first.b64 %0, 1.0;" : "=l"(pol));
    {
        auto cpa = [&](uint32_t d, const uint8_t* s) {
            asm volatile("cp.async.cg.shared.global.L2::cache_hint.L2::128B [%0], [%1], 16, %2;" :: "r"(d), "l"(s), "l"(pol) : "memory");
        };
        const uint32_t ut = threadIdx.x, uj = blockIdx.x;
        const uint8_t* w = F.w[ut >= 128];
        if (ut < 128) {
            const uint32_t dq = (sb + ut * 16) ^ ((ut * 2) & 0x70);
            const uint8_t* sq = w + (uint32_t)(((uj & 1) * 256 + (ut >> 3)) * 8192 + (uj >> 1) * 128 + (ut & 7) * 16);
#pragma unroll
            for (int i = 0; i < 4 * NCP; i++) cpa(dq + 4 * 32768 + i * 2048, sq + i * 131072);
        } else if (ut < 384) {
            const uint32_t dm = (sb + ut * 16) ^ ((ut * 2) & 0x10);
            const uint8_t* sa = w + (uint32_t)(((uj >> 5) * 128 + (ut >> 1) - 64) * 6144 + (uj & 31) * 32 + (ut & 1) * 16);
            cpa(dm + SM_XA - 2048, sa); cpa(dm + SM_XA + 2048, sa + 1024);
        }
        else if (ut == 480 && uj < 64) asm volatile("prefetch.global.L2 [%0];" :: "l"(F.v[(uj >> 3) & 1] + (uj & 7) * 64));
    }
    const int warp = __shfl_sync(0xffffffffu, tid >> 5, 0);
    const __nv_bfloat16* const xin = F.v[0];
    uint32_t* const pl = gs + (warp < 2 ? (B_PR + (j >> 5)) * 4096 + (j & 31) * 32 : G_E1 + j * 8192) + (warp & 1) * 1024 + lane;
    if (warp < 4) st_x1(pl, 1u);
    auto BAR = [&](int i) -> uint32_t { return sb + SM_BAR + i * 8; };
    const uint32_t a16 = (r8 + 8 * lb4) * 32 + ((lb3 ^ (r8 >> 2)) * 16);
    const uint32_t a128 = (r8 + 8 * lb4) * 128 + ((((warp & 3) * 2 + lb3) ^ r8) * 16);
    auto ldcls = [&]() -> uint32_t { return *(const volatile uint32_t*)(sm + SM_CLS); };
    auto clear_head = [&]() {
        st2_x1(gs + (B_HA + ((j >> 4) & 1) * 2 + lb4) * 4096 + (j >> 5) * 256 + (j & 15) * 16 + (lane & 15), 0u);
        st2_x4(gs + (B_QA + rk * 8 + ((j >> 1) & 1) * 4 + (j >> 5)) * 4096 + g * 128 + ((j >> 2) & 7) * 16 + t * 4, 0u, 0u, 0u, 0u);
        if (lane < 8) st2_x1(gs + B_RD * 4096 + j * 8 + lane, 0u);
    };
    auto tma = [&](uint32_t dst, const CUtensorMap* mp, uint32_t bar, int c0, int c1, int c2, int c3) {
        asm volatile("{\n.reg .pred p;\nelect.sync _|p, 0xffffffff;\n"
                     "@p cp.async.bulk.tensor.4d.shared::cluster.global.mbarrier::complete_tx::bytes.L2::cache_hint [%0], [%1, {%3, %4, %5, %6}], [%2], %7;\n}"
                     :: "r"(dst), "l"(mp), "r"(bar), "r"(c0), "r"(c1), "r"(c2), "r"(c3), "l"(pol) : "memory");
    };
    if (warp <= 12 || warp == 15) {
        const int grp = warp == 12 ? 0 : warp == 15 ? 13 : warp + 1;
        const uint32_t cnt = grp < 10 ? 1 : grp < 13 ? 4 : 8;
        if (lane == 0) {
#pragma unroll
            for (int i = 0; i < 8; i++) mbar_init(BAR(grp * 8 + i), (i < 2 && grp == 0) ? (i ? 128 : 256) : cnt);
        }
        __syncwarp();
        if (grp < 10 && lane < 8 && (grp || lane > NCP)) mbar_expect(BAR(grp * 8 + lane), grp >= 8 ? 4096 : (uint32_t)(grp * 8 + lane - IT_X) < 4 ? 16384 : 8192);
        asm volatile("fence.mbarrier_init.release.cluster;" ::: "memory");
        __syncwarp();
        if (warp == 12) {
#pragma unroll
            for (int i = NCP + 1; i < W0; i++) tma(sb + (15 + i) * 8192, &M.m[MP_WQ], BAR(i), 0, rk * 256 + (i - 1) * 64, j >> 1, 0);
        }
    } else if (warp == 13) {
        if (lane < NMAPS) asm volatile("prefetch.tensormap [%0];" :: "l"(&M.m[lane]) : "memory");
    } else if (warp == 14) {
        clear_head();
    }
    __syncthreads();
    uint32_t in1 = 0, in2 = 0;
    if (warp < 4) { in1 = *(const uint32_t*)(xin + 2 * tid); in2 = *(const uint32_t*)(xin + 256 + 2 * tid); }
    else if (warp < 12) in1 = *(const uint32_t*)(F.v[1] + 2 * (tid - 128));
    if (warp < 12) asm volatile("cp.async.mbarrier.arrive.noinc.shared::cta.b64 [%0];" :: "r"(BAR(warp < 4)) : "memory");
    asm volatile("barrier.cluster.arrive.relaxed.aligned;" ::: "memory");

    if (warp >= 12) {
    asm volatile("setmaxnreg.dec.sync.aligned.u32 64;");
    if (warp == 12) {
        static_assert(W0 > NCP && W0 <= 5 && NCP >= 1 && NCP <= 4, "W0");
        const uint2* sched = M.sched[j < NFF ? 0 : j < J_RED ? 1 : 2];
        uint2 en = sched[W0];
        const uint32_t t0 = gtime();
        const uint32_t sp = __reduce_or_sync(0xffffffffu, sb);
        const int cx = (j >> 1) * 64 + (j < NFF ? 0 : 1024 - NFF * 32);
#pragma unroll 1
        for (int i = W0; en.x; i++) {
            uint32_t e = en.x, st = (en.y >> 20) * 64;
            const uint32_t tn = t0 + (int16_t)en.y, mp = (en.y >> 16) & 15;
            if (mp == MP_WUV || mp == MP_WUK) { st ^= (j >> 5) * (mp == MP_WUV ? 128 : 64); e ^= (j >> 5) << 6; }
            if (mp == MP_GATE || mp == MP_UP) st ^= (j & 16) * 8;
            if (mp == MP_DOWN) { st ^= (j & 3) * 64; e ^= (j & 3) << 6; }
            en = sched[i + 1];
            if (mp == MP_MODB && j >= J_END) break;
            uint32_t c0 = mp == MP_WO ? (j & 7) * 64 : mp > MP_WO ? cx : 0;
            uint32_t c1 = mp == MP_CKV ? 0 : mp == MP_DOWN ? j * 32 : st + (mp == MP_WUV ? (j & 3) * 32 : mp == MP_WO ? (j >> 3) * 256 : rk * 256);
            uint32_t c2 = mp < MP_CKV ? j >> 1 : mp == MP_CKV ? rk * 4 : mp == MP_WUV ? (j >> 2) * 2 : mp == MP_DOWN ? st >> 5 : 0;
            uint32_t c3 = mp == MP_CKV ? st * 2 + (j & ~1) : 0;
            uint32_t dst = sp + ((e << 7) & 0x3e000), bar = sp + SM_BAR + (e & 63) * 8;
            const uint32_t w0 = (e >> 8) & 0x3f8, w1 = (e >> 15) & 0x3f8, w2 = (e >> 22) & 0x3f8, bb = sp + SM_BAR - 8;
            const CUtensorMap* pm = &M.m[mp];
            pin(dst); pin(bar); pin(c0); pin(c1); pin(c2); pin(c3); pin(pm);
            if (w0) mbar_wait(bb + w0, 0);
            if (w2) {
                mbar_wait(bb + w2, 0);
                while (!__any_sync(0xffffffffu, mbar_test(bb + w1, 0) | ((int)(gtime() - tn) > 0))) {}
            } else if (w1) mbar_wait(bb + w1, 0);
            tma(dst, pm, bar, c0, c1, c2, c3);
        }
    } else if (warp == 13) {
#pragma unroll
        for (int i = 0; i < 2; i++) st_x4(gs + (B_ML + rk * 16 + i * 8 + g) * 4096 + (t >> 1) * 1024 + (j >> 1) * 8 + (t & 1) * 4, 0u, 0u, 0u, 0u);
        if (lane < 16) st2_x4(gs + (B_E2 + (j >> 4)) * 4096 + (j & 15) * 64 + lane * 4, 0u, 0u, 0u, 0u);
        st2_x1(gs + (B_E3 + (j >> 5)) * 4096 + (j & 31) * 32 + lane, 0u);
        if (lane < 8) st2_x1(gs + B_MB * 4096 + j * 8 + lane, 0u);
        if (j < NFF) {
#pragma unroll
            for (int i = 0; i < 2; i++) st2_x4(gs + (B_E5 + i * 8 + g) * 4096 + j * 16 + t * 4, 0u, 0u, 0u, 0u);
        }
        bar_sync(9, 64);
        const uint32_t cs = ldcls();
#pragma unroll 1
        for (int i = 0; i < 32; i++) {
            st_x4(gs + G_E1 + j * 8192 + (i >> 3) * 2048 + ((((cs >> 1) ^ (i >> 3)) & 1) << 10) + (i & 7) * 128 + lane * 4, 0u, 0u, 0u, 0u);
            __nanosleep(JAN_SLEEP);
        }
        fence_gpu();
        if (lane < 8) st2_x1(gs + B_RD * 4096 + j * 8 + lane, 1u + (cs >> 1));
        if (lane == 0) TRACE(41);
        uint32_t rd[4];
        mbar_wait(BAR(IT_CKV + RD_ITEM), 0);
        poll<1024, RD_SLEEP>(rd, gs + near_off(B_RD, cs) + lane * 8);
#pragma unroll
        for (int i = 0; i < 4; i++) {
            const uint32_t m = __ballot_sync(0xffffffffu, rd[i] == 2u);
            if (lane == 0) sts32(sb + SM_CLS + 16 + i * 4, m);
        }
        __syncwarp();
        if (lane < 8) mbar_arrive(BAR(JD));
        if (lane == 0) TRACE(42);
    } else if (warp == 14) {
        uint2 ml[2];
        mbar_waitb(BAR(JD), 0);
        const uint32_t cls = ldcls();
        mbar_waitb(BAR(PF0 + 2 * NUNITS - 1), 0);
        __nanosleep(ML_DELAY);
        const uint32_t* pl2 = gs + near_off(B_ML + (j >> 2), cls) + lane * 8;
        const uint32_t wa = sb + SM_W + lb4 * 64 + t * 16 + (g & 3) * 4;
        poll_start<1024>(ml, pl2);
        uint32_t w0 = 0, w1 = 0, redo = 0;
        bool first = true;
#pragma unroll 1
        for (uint32_t it = 0;; it++) {
            const bool p0 = minw(ml[0]) != 0, p1 = minw(ml[1]) != 0;
            const int n = __popc(__ballot_sync(0xffffffffu, p0)) + __popc(__ballot_sync(0xffffffffu, p1));
            const uint32_t x0 = ml[0].x, x1 = ml[1].x;
            if (n < 64) {
                if (!p0) ld_x(ml[0], pl2);
                if (!p1) ld_x(ml[1], pl2 + 256);
            }
            if (n == 64 || (first && n >= E1_EARLY)) {
                auto ord = [](int x) { return x ^ ((x >> 31) & 0x7fffffff); };
                const int o0 = ord(x0), o1 = ord(x1);
                const float mm = __int_as_float(ord(__reduce_max_sync(0xffffffffu, max(p0 ? o0 : INT_MIN, p1 ? o1 : INT_MIN))));
                const float lo = __int_as_float(ord(__reduce_min_sync(0xffffffffu, min(p0 ? o0 : INT_MAX, p1 ? o1 : INT_MAX))));
                const uint32_t v0 = pack2(ex2((p0 ? __uint_as_float(x0) : lo) - mm), 0.f), v1 = pack2(ex2((p1 ? __uint_as_float(x1) : lo) - mm), 0.f);
                redo = !first && __any_sync(0xffffffffu, v0 != w0 || v1 != w1);
                w0 = v0; w1 = v1;
                sts32(wa - redo * (SM_W - SM_W2), w0 * 0x10001u); sts32(wa - redo * (SM_W - SM_W2) + 128, w1 * 0x10001u);
                if (first) bar_arrive(3, 416);
                first = false;
                if (n == 64) break;
            }
            if (it > SPIN_LIMIT) __trap();
        }
        if (lane == 0) TRACE_Q(37);
        float L = bflo(w0) * __uint_as_float(ml[0].y) + bflo(w1) * __uint_as_float(ml[1].y);
#pragma unroll
        for (int o = 16; o; o >>= 1) L += shx(L, o);
        if (lane == 0) *(float2*)(sm + SM_FQ) = make_float2(__frcp_rn(L), __uint_as_float(redo));
        __syncwarp();
        if (lane < 8) mbar_arrive(BAR(WR));
        if (lane == 0) TRACE(10);
        bar_sync(4, 416);
        clear_head();
        if (j < NFF) {
            uint32_t ya = sb + SM_Y + lane * 16, sa = peer_addr(sb + SM_RED + 2048 + rk * 8, lane & 1), tb = peer_addr(BAR(MBB), lane & 1);
            pin(ya); pin(sa); pin(tb);
            bar_sync(7, 288);
            const float4 y0 = ldsf4(ya), y1 = ldsf4(ya + 512);
            float s = sum4(y0) + sum4(y1);
            float q = (fmaf(y0.x, y0.x, y0.y * y0.y) + fmaf(y0.z, y0.z, y0.w * y0.w)) + (fmaf(y1.x, y1.x, y1.y * y1.y) + fmaf(y1.z, y1.z, y1.w * y1.w));
#pragma unroll
            for (int o = 16; o; o >>= 1) { s += shx(s, o); q += shx(q, o); }
            if (lane < 2) st_async2(sa, s, q, tb);
        }
    } else if (warp == 15) {
        mbar_waitb(BAR(IT_X - 1), 0);
        if (j < J_END) mbar_waitb(BAR(j < NFF ? NITEMS - 1 : MBB), 0);
    }
    } else if (warp < 4) {
        float* scr = (float*)(sm + SM_SCR);
        uint32_t cls;
        {
            uint2 ha[8];
            uint32_t best = 0xffffffffu;
            sts32(sb + SM_SCR + 64 + warp * 4, best);
            const float sh = __shfl_sync(0xffffffffu, bflo(in1), 0);
            const float v0 = bflo(in1) - sh, v1 = bfhi(in1) - sh, v2 = bflo(in2) - sh, v3 = bfhi(in2) - sh;
            float mb, sd;
            ln_stats<4>((v0 + v1) + (v2 + v3), (v0 * v0 + v1 * v1) + (v2 * v2 + v3 * v3), sh, scr, warp, lane, 2, mb, sd);
            if (!rk) in2 = in1;
#pragma unroll 1
            for (int i = 0; i < NPROBE; i++) {
                uint32_t t0, t1, o;
                asm volatile("mov.u32 %0, %%clock;" : "=r"(t0));
                asm volatile("atom.relaxed.gpu.global.exch.b32 %0, [%1], %2;" : "=r"(o) : "l"(pl), "r"(2u + i) : "memory");
                asm volatile("{\n.reg .pred p;\nsetp.ne.u32 p, %1, 0x1234567;\nmov.u32 %0, 0;\n@p mov.u32 %0, %%clock;\n}" : "=r"(t1) : "r"(o));
                best = min(best, t1 - t0);
                sts32(sb + SM_SCR + 64 + warp * 4, best);
                if (__all_sync(0xffffffffu, min(best, lds32(sb + SM_SCR + 64 + (warp ^ 1) * 4)) < NEAR_CLK)) break;
            }
            bar_sync(2, 128);
            const uint4 lt = *(const uint4*)(scr + 16);
            cls = NUMA ? ((lt.y < lt.x) ^ (__popc((B_PR + (j >> 5)) & 0x2C) & 1)) | (lt.w < lt.z) << 1 : 0;
            if (warp == 0) { if (lane == 0) sts32(sb + SM_CLS, cls); bar_arrive(9, 64); }
            if (tid == 0) TRACE(38);
            asm volatile("barrier.cluster.wait.aligned;" ::: "memory");
            mbar_wait(BAR(IT_MODA), 0);
            if (HA_DELAY) __nanosleep(HA_DELAY);
            poll<1024, H_SLEEP, false, 16384>(ha, gs + near_off(B_HA + rk * 2, cls) + 2 * tid);
            auto rsum = [](uint32_t a, uint32_t b, uint32_t c, uint32_t d) { return rbf((__uint_as_float(a) + __uint_as_float(b)) + (__uint_as_float(c) + __uint_as_float(d))); };
            sts32(sb + SM_FV + frag_off(2 * tid),
                  pack2(ln_mod(bflo(in2), mb, sd, rsum(ha[4].x, ha[5].x, ha[6].x, ha[7].x), rsum(ha[0].x, ha[1].x, ha[2].x, ha[3].x)),
                        ln_mod(bfhi(in2), mb, sd, rsum(ha[4].y, ha[5].y, ha[6].y, ha[7].y), rsum(ha[0].y, ha[1].y, ha[2].y, ha[3].y))));
            bar_arrive(5, 384);
            mbar_wait(BAR(QB), 0);
            if (tid < 64) {
                const float* qx = (const float*)(sm + SM_QX) + tid;
                sts16(sb + SM_FQ + frag_off(tid), pack2((qx[0] + qx[64]) + (qx[128] + qx[192]), 0.f));
            }
            bar_arrive(6, 384);
        }
        asm volatile("setmaxnreg.inc.sync.aligned.u32 192;");
        float acc[128];
        float M = 0.f;
        uint32_t pa = sb + SM_XA + warp * 512 + lane * 16, ma = sb + SM_MX + (warp * 8 + g) * 4, pf = BAR(PF0);
        uint32_t blo = __reduce_or_sync(0xffffffffu, (((sb + SM_U) & 0x3FFFFu) >> 4) | 0x400000u);
        uint32_t* e1[4];
#pragma unroll
        for (int i = 0; i < 4; i++) e1[i] = gs + G_E1 + (warp * 8 + g) * 4 * 8192 + (rk * 2 + (j >> 6)) * 2048 + ((j >> 1) & 31) * 32 + t * 4;
#pragma unroll 1
        for (int h = 0; h < 2 * NUNITS; h++) {
            mbar_wait(pf, 0);
            const float m = __uint_as_float(lds32(ma));
            const uint4 pn = lds128(pa);
            wg_wait0();
#pragma unroll
            for (int i = 0; i < 128; i++) asm volatile("" : "+f"(acc[i]) :: "memory");
            if (h == 0) M = m;
            uint32_t b2 = 0x3f803f80u;
            if (__builtin_expect(__any_sync(0xffffffffu, m != M), 0)) {
                const float Mn = fmaxf(M, m), alpha = ex2(M - Mn), beta = ex2(m - Mn);
                M = Mn;
                b2 = pack2(beta, beta);
#pragma unroll
                for (int jj = 0; jj < 32; jj++) { acc[4 * jj] *= alpha; acc[4 * jj + 1] *= alpha; }
            }
            auto mul2 = [](uint32_t x, uint32_t y) { uint32_t r; asm("mul.rn.bf16x2 %0, %1, %2;" : "=r"(r) : "r"(x), "r"(y)); return r; };
            const uint4 p = make_uint4(mul2(pn.x, b2), mul2(pn.y, b2), mul2(pn.z, b2), mul2(pn.w, b2));
            if (tid == 0 && (h & 1)) TRACE_Q(48 + (h >> 1));
            wgmma_pv(acc, p, blo, h);
            if (lane == 0 && h > 0 && !(h & 1)) mbar_arrive(BAR(EB_UNIT0 + (h >> 1) - 1));
            blo += h == 11 ? -11 * 1024 : 1024;
            pa += (h == 5 || h == 11) ? -5 * 2048 : 2048;
            ma += 128; pf += 8;
            if (h == 2 * NUNITS - 3) {
                mbar_wait(BAR(JD), 0);
                const uint32_t hm = (*(const uint32_t*)(sm + SM_CLS + 16 + warp * 4) >> (g * 4)) ^ ((j >> 6) ? 15u : 0u);
#pragma unroll
                for (int i = 0; i < 4; i++) e1[i] += ((hm >> i) & 1) << 10;
            }
        }
#pragma unroll
        for (int vv = 0; vv < 2; vv++) {
            if (vv && M == 1.f) __trap();
            if (vv) wg_wait0(); else wg_wait1();
#pragma unroll
            for (int i = 0; i < 64; i++) asm volatile("" : "+f"(acc[vv * 64 + i]) :: "memory");
            if (tid == 0 && !vv) TRACE_Q(63);
#pragma unroll
            for (int i = 0; i < 4; i++) {
                const float* a = &acc[vv * 64 + i * 16];
                st_x4(e1[i] + i * 8192 + vv * 16, enc(pack2(a[0], a[1])), enc(pack2(a[4], a[5])), enc(pack2(a[8], a[9])), enc(pack2(a[12], a[13])));
            }
        }
        bar_arrive(3, 416);
        if (tid == 0) TRACE_Q(17);
#pragma unroll 1
        for (int pass = 0;; pass++) {
            if (j >= NFF && j < J_END && pass == (j >= J_RED)) {
                uint4 a[8], b[4];
                float c[4], e[4];
                const bool own = (warp >> 1) == rk;
                const uint32_t xa = sb + SM_FV + (warp & 1) * 64 + g * 8;
                if (lane == 0) mbar_expect(BAR(MBB), own ? 64 : 0);
#pragma unroll
                for (int i = 0; i < 2; i++) {
                    ldfrag(b, sb + SM_FS + rk * 512 + i * 256 + t * 16);
                    mbar_wait(BAR(IT_X + i), 0);
                    const uint32_t ab = sb + SM_U + B_X * 32768 + i * 16384 + a128;
                    load8<true>(a, [&](int s) { return ab + s * 2048; });
                    mma8(i ? e : c, a, b);
                }
                c[0] += e[0]; c[2] += e[2];
                if (!own) {
                    if (t == 0) st_async2(peer_addr(xa, rk ^ 1), c[0], c[2], peer_addr(BAR(MBB), rk ^ 1));
                } else {
                    mbar_wait(BAR(MBB), 0);
                    const float2 pp = *(const float2*)(sm + (xa - sb));
                    const float mine = t ? c[2] + pp.y : c[0] + pp.x, other = shx(mine, 4);
                    const uint32_t w = (warp & 1) * 8 + t * 4 + (g >> 1), val = enc(pack2(mine, other));
                    if (t < 2 && !(g & 1)) {
                        if (j < J_RED) st2_x1(gs + B_MB * 4096 + (j - NFF) * 16 + w, val);
                        else sts32(sb + SM_FV + 256 + w * 4, val);
                    }
                    __syncwarp();
                    if (j >= J_RED && lane < 4) mbar_arrive(BAR(QB));
                    if (lane == 0) TRACE(11);
                }
            }
            if (pass) break;
            uint4 a[8], a2[8];
            const uint32_t ab = sb + SM_U + B_WO * 32768 + a128;
            uint32_t* p3 = gs + (B_E3 + ((j >> 1) & 3)) * 4096 + (t >> 1) * 1024 + (rk * 2 + (warp >> 1)) * 256 + (j >> 3) * 16 + (warp & 1) * 8 + (t & 1) * 4 + (g >> 1);
            const uint32_t* pb = gs + near_off(B_E2 + (j >> 4), cls) + (((j >> 3) & 1) * 2 + lb4) * 256 + (lane & 15) * 2;
            pin(p3); pin(pb);
            uint2 bb[8];
            uint2 bq[2] = {make_uint2(0u, 0u), make_uint2(0u, 0u)};
            uint32_t xa = sb + SM_XA + lane * 16;
            pin(xa);
            bool h0 = false, h1 = false;
            auto idle = [&]() {
                if (!h0) {
                    h0 = __all_sync(0xffffffffu, mbar_test(BAR(IT_WO + (t & 1)), 0));
                    if (h0) load8<true>(a, [&](int s) { return ab + s * 2048; });
                }
                if (!h1) {
                    h1 = __all_sync(0xffffffffu, mbar_test(BAR(IT_WO + 2 + (t & 1)), 0));
                    if (h1) load8<true>(a2, [&](int s) { return ab + 16384 + s * 2048; });
                }
            };
            bar_sync(4, 416);
            idle();
            poll<128, 0, true>(bq, pb + warp * 64, idle);
            asm volatile("st.shared.v4.u32 [%0], {%1, %2, %3, %4};" :: "r"(xa + warp * 512), "r"(bq[0].x), "r"(bq[0].y), "r"(bq[1].x), "r"(bq[1].y) : "memory");
            bar_sync(2, 128);
#pragma unroll
            for (int i = 0; i < 4; i++) { const uint4 q = lds128(xa + i * 512); bb[2 * i] = make_uint2(q.x, q.y); bb[2 * i + 1] = make_uint2(q.z, q.w); }
            if (tid == 0) TRACE(21);
            float e[4][4];
#pragma unroll
            for (int s = 0; s < 16; s++) {
                if (s == 0 && !h0) { mbar_wait(BAR(IT_WO), 0); mbar_wait(BAR(IT_WO + 1), 0); load8<true>(a, [&](int q) { return ab + q * 2048; }); }
                if (s == 0 && !h1) { mbar_wait(BAR(IT_WO + 2), 0); mbar_wait(BAR(IT_WO + 3), 0); load8<true>(a2, [&](int q) { return ab + 16384 + q * 2048; }); }
                const int z = (s & 1) | (s & 2) << 2 | (s >> 2) << 1;
                const uint4& x = z < 8 ? a[z] : a2[z & 7];
                float (&d)[4] = e[(z >> 3) * 2 + (z & 1)];
                if (!(z & 6)) d[0] = d[1] = d[2] = d[3] = 0.f;
                mma(d, x.x, x.y, x.z, x.w, bb[z & 7].x, bb[z & 7].y);
            }
            float lo, hi;
            quad_pair((t & 2) ? (e[2][0] + e[3][0]) + (e[2][1] + e[3][1]) : (e[0][0] + e[1][0]) + (e[0][1] + e[1][1]),
                      (t & 2) ? (e[2][2] + e[3][2]) + (e[2][3] + e[3][3]) : (e[0][2] + e[1][2]) + (e[0][3] + e[1][3]), t, lo, hi);
            if (!(g & 1)) st_x1(p3, enc(pack2(lo, hi)));
            if (j < NFF) bar_arrive(8, 384); else if (j >= J_RED && j < J_END) bar_arrive(8, 192);
            if (tid == 0) TRACE(22);
        }
        if (j < NFF) {
            uint4 a[16];
            const uint32_t ad = sb + SM_U + B_DN * 32768 + warp * 8192 + (r8 + 8 * lb4) * 128 + (lb3 ^ r8) * 16;
            uint32_t rl = sb + SM_RED + lane * 16;
            uint32_t* p5 = gs + (B_E5 + warp * 4 + (t >> 1)) * 4096 + j * 16 + (t & 1) * 8 + g;
            pin(rl); pin(p5);
            if (lane == 0) mbar_expect(BAR(MBB), 4);
            auto ldd = [&]() {
#pragma unroll
                for (int s = 0; s < 16; s++) a[s] = ldsm<true>((ad ^ ((s & 3) * 32)) + (s >> 2) * 2048);
            };
            const uint32_t db = BAR(IT_DOWN + (warp ^ (j & 3)));
            mbar_wait(BAR(MBB), 0);
            const float4 st = ldsf4(sb + SM_RED + 2048);
            const bool hd = __all_sync(0xffffffffu, mbar_test(db, 0));
            if (hd) ldd();
            const float mu = (st.x + st.z) * (1.f / 512.f);
            float rstd;
            asm volatile("rsqrt.approx.ftz.f32 %0, %1;" : "=f"(rstd) : "f"(fmaxf(fmaf(-mu, mu, (st.y + st.w) * (1.f / 512.f)), 0.f) + 1e-5f));
            mbar_wait(BAR(QB), 1);
            if (tid == 0) TRACE(25);
            const float4 f0 = ldsf4(rl), f2 = ldsf4(rl + 1024), f1 = ldsf4(rl + 512), f3 = ldsf4(rl + 1536);
            const float gg = fmaf(rstd, fmaf(-mu, f0.z + f2.z, (f0.x + f0.y) + (f2.x + f2.y)), f0.w + f2.w);
            const float uu = fmaf(rstd, fmaf(-mu, f1.z + f3.z, (f1.x + f1.y) + (f3.x + f3.y)), f1.w + f3.w);
            const float hh = __fdividef(gg * uu, 1.f + ex2(-gg * fmaf(gg * gg, 0.10294324f, 2.3022082f)));
            uint32_t hb[4];
#pragma unroll
            for (int i = 0; i < 4; i++) hb[i] = pack2(__shfl_sync(0xffffffffu, hh, 2 * t + 8 * i), __shfl_sync(0xffffffffu, hh, 2 * t + 8 * i + 1));
            if (!hd) { mbar_wait(db, 0); ldd(); }
#pragma unroll
            for (int i = 0; i < 2; i++) {
                uint32_t res = 0;
#pragma unroll
                for (int k = 0; k < 4; k++) {
                    float c[4] = {0.f, 0.f, 0.f, 0.f};
                    const uint4 &x = a[i * 8 + k], &y = a[i * 8 + k + 4];
                    mma(c, x.x, x.y, x.z, x.w, hb[0], hb[1]);
                    mma(c, y.x, y.y, y.z, y.w, hb[2], hb[3]);
                    if (t == k) res = pack2(c[0], c[2]);
                }
                st2_x1(p5 + i * 8192, enc(res));
            }
            if (tid == 0) { TRACE(27); TRACE_GT(47); }
        }
    } else {
        const int u8 = tid - 128, w8 = warp - 4;
        const int v = w8 >> 2, wq4 = w8 & 3;
        {
            const float c0 = bflo(in1), c1 = bfhi(in1);
            sts32(sb + SM_FS + frag_off(2 * u8), pack2(__fdividef(c0, 1.f + __expf(-c0)), __fdividef(c1, 1.f + __expf(-c1))));
        }
        bar_sync(1, 256);
        asm volatile("barrier.cluster.wait.aligned;" ::: "memory");
        uint4 a[8], b[4]; float c[4];
        if (w8 < 2) {
            ldfrag(b, sb + SM_FS + (j >> 5) * 256 + t * 16);
            mbar_wait(BAR(IT_MODA), 0);
            if (u8 == 0) TRACE(12);
            const uint32_t ab = sb + SM_XA + w8 * 4096 + a16;
            load8<true>(a, [&](int s) { return ab + s * 512; });
            mma8(c, a, b);
            if (t < 2) st2_x1(gs + (B_HA + ((j >> 4) & 1) * 2 + w8) * 4096 + (j >> 5) * 256 + (j & 15) * 16 + t * 8 + g, encf(t ? c[2] : c[0]));
        }
        {
            mbar_wait(BAR(IT_WQ + 2 * v <= NCP ? 1 : IT_WQ + 2 * v), 0); mbar_wait(BAR(IT_WQ + 2 * v + 1 <= NCP ? 1 : IT_WQ + 2 * v + 1), 0);
            const uint32_t ab = sb + SM_U + 4 * 32768 + v * 16384 + a128;
            load8<true>(a, [&](int s) { return ab + s * 2048; });
            if (lane == 0) mbar_arrive(BAR(EB_WQ));
            bar_sync(5, 384);
            if (u8 == 0) TRACE(13);
            ldfrag(b, sb + SM_FV + v * 256 + t * 16);
            mma8(c, a, b);
            if (t < 2) {
                const float qv = t ? c[2] : c[0];
                const uint32_t qa_ = sb + SM_QX + ((rk * 2 + v) * 64 + wq4 * 16 + t * 8 + g) * 4;
                asm volatile("st.async.weak.shared::cluster.mbarrier::complete_tx::bytes.f32 [%0], %1, [%2];"
                             :: "r"(peer_addr(qa_, rk ^ 1)), "f"(qv), "r"(peer_addr(BAR(QB), rk ^ 1)) : "memory");
                sts32(qa_, __float_as_uint(qv));
            }
            __syncwarp();
            if (lane == 0) mbar_expect(BAR(QB), 64);
        }
        {
            mbar_wait(BAR(IT_WUK + (v ^ ((j >> 5) & 1))), 0); mbar_wait(BAR(IT_WUK + (v ^ ((j >> 5) & 1)) + 2), 0);
            const uint32_t ab = sb + SM_U + 5 * 32768 + (w8 * 16 + r8 + 8 * lb3) * 128;
            const uint32_t x16 = (lb4 ^ r8) * 16;
            load8<false>(a, [&](int s) { return ab + (s & 1) * 16384 + (x16 ^ ((s >> 1) * 32)); });
            bar_sync(6, 384);
            if (u8 == 0) TRACE(14);
            b[0] = lds128(sb + SM_FQ + t * 16); b[1] = lds128(sb + SM_FQ + 64 + t * 16);
            float e[4] = {0.f, 0.f, 0.f, 0.f};
            c[0] = c[1] = c[2] = c[3] = 0.f;
#pragma unroll
            for (int k = 0; k < 4; k++) {
                const uint32_t b0 = (k & 1) ? b[k >> 1].z : b[k >> 1].x, b1 = (k & 1) ? b[k >> 1].w : b[k >> 1].y;
                mma(c, a[2 * k].x, a[2 * k].y, a[2 * k].z, a[2 * k].w, b0, b1);
                mma(e, a[2 * k + 1].x, a[2 * k + 1].y, a[2 * k + 1].z, a[2 * k + 1].w, b0, b1);
            }
            const float mine = ((t & 1) ? ((t & 2) ? e[2] : e[0]) : ((t & 2) ? c[2] : c[0])) * 0.12751743f;
            const float other = shx(mine, 4);
            if (!(g & 1)) st2_x1(gs + (B_QA + rk * 8 + ((j >> 1) & 1) * 4 + (j >> 5)) * 4096 + w8 * 128 + ((j >> 2) & 7) * 16 + (g >> 1) * 4 + t, enc(pack2(mine, other)));
            if (u8 == 0) TRACE(15);
        }
        const uint32_t cls = ldcls();
        __nanosleep(QA_DELAY);
        {
            uint4 qb[8];
            const uint32_t* pq = gs + near_off(B_QA + rk * 8 + wq4, cls) + lane * 4;
            const uint32_t* pq2 = gs + near_off(B_QA + rk * 8 + 4 + wq4, cls) + lane * 4;
            if (lane == 0) {
                mbar_expect(BAR(QT), 4096);
                asm volatile("cp.async.bulk.shared::cluster.global.mbarrier::complete_tx::bytes [%0], [%1], 4096, [%2];"
                             :: "r"(sb + SM_U + 5 * 32768 + w8 * 4096), "l"(gs + near_off(B_QA + rk * 8 + w8, cls)), "r"(BAR(QT)) : "memory");
            }
            const uint32_t qs = sb + SM_U + 5 * 32768 + wq4 * 4096 + lane * 16;
            mbar_wait(BAR(QT), 0);
#pragma unroll
            for (int i = 0; i < 8; i++) { a[i] = lds128(qs + i * 512); qb[i] = lds128(qs + 16384 + i * 512); }
            poll<512, QA_SLEEP, true>(a, pq);
            poll<512, QA_SLEEP, true>(qb, pq2);
            if (lane == 0) mbar_arrive(BAR(EB_WUK));
            auto add2 = [](uint32_t x, uint32_t y) { uint32_t r; asm("add.rn.bf16x2 %0, %1, %2;" : "=r"(r) : "r"(x), "r"(y)); return r; };
#pragma unroll
            for (int i = 0; i < 8; i++) a[i] = make_uint4(add2(a[i].x, qb[i].x), add2(a[i].y, qb[i].y), add2(a[i].z, qb[i].z), add2(a[i].w, qb[i].w));
        }
        if (u8 == 0) TRACE(8);
        {
            float m = -INFINITY, l = 0.f;
            uint32_t xl = sb + SM_XB + w8 * 2048 + lane * 16, xr = peer_addr(xl, rk ^ 1), bsr = peer_addr(BAR(SF0 + v), rk ^ 1);
            uint32_t pa = sb + SM_XA + v * 2048 + wq4 * 512 + lane * 16, ma = sb + SM_MX + v * 128 + (wq4 * 8 + g) * 4;
            uint32_t fb = BAR(IT_CKV + v * 2), sf = BAR(SF0 + v);
            uint32_t dlo = __reduce_or_sync(0xffffffffu, (((sb + SM_U + v * 16384) & 0x3FFFFu) >> 4) | 0x10000u);
            if (STAG && v) __nanosleep(STAG);
#pragma unroll 1
            for (int n = 0; n < NUNITS; n++) {
                float d[2][16], sc[8];
#pragma unroll
                for (int i = 0; i < 2; i++) {
                    mbar_wait(fb + i * 8, 0);
                    wg_fence();
#pragma unroll
                    for (int s = 0; s < 8; s++) wgmma_rs_n32(d[i], a[s], (0x40000080ull << 32) | (dlo + i * 512 + (s >> 2) * 64 + (s & 3) * 2), s);
                    wg_commit();
                }
#pragma unroll
                for (int i = 0; i < 2; i++) {
                    if (i) wg_wait0(); else wg_wait1();
#pragma unroll
                    for (int k = 0; k < 16; k++) asm volatile("" : "+f"(d[i][k]) :: "memory");
                    sc[4 * i] = d[i][0] + d[i][6]; sc[4 * i + 1] = d[i][1] + d[i][7]; sc[4 * i + 2] = d[i][8] + d[i][14]; sc[4 * i + 3] = d[i][9] + d[i][15];
                    asm volatile("st.async.weak.shared::cluster.mbarrier::complete_tx::bytes.v4.f32 [%0], {%1, %2, %3, %4}, [%5];"
                                 :: "r"(xr + i * 1024), "f"(sc[4 * i]), "f"(sc[4 * i + 1]), "f"(sc[4 * i + 2]), "f"(sc[4 * i + 3]), "r"(bsr) : "memory");
                }
                if (u8 == 128) TRACE_Q(56 + (n < 6 ? n : -40));
                if (n >= 3) mbar_wait(BAR(EB_UNIT0 + n - 3), 0);
                dlo += n == 5 ? -5 * 2048 : 2048;
                fb += 32; xr ^= 512; bsr += 16;
                pin(fb); pin(xr); pin(bsr);
                mbar_wait(sf, 0);
                const float4 x = ldsf4(xl), y = ldsf4(xl + 1024);
                sc[0] += x.x; sc[1] += x.y; sc[2] += x.z; sc[3] += x.w; sc[4] += y.x; sc[5] += y.y; sc[6] += y.z; sc[7] += y.w;
                float pr[8];
#pragma unroll
                for (int i = 0; i < 8; i++) pr[i] = ex2(sc[i] - m);
                float mx = fmaxf(fmaxf(fmaxf(sc[0], sc[1]), fmaxf(sc[2], sc[3])), fmaxf(fmaxf(sc[4], sc[5]), fmaxf(sc[6], sc[7])));
                if (__builtin_expect(__any_sync(0xffffffffu, mx > m), 0)) {
                    mx = fmaxf(mx, shx(mx, 1));
                    mx = fmaxf(mx, shx(mx, 2));
                    const float mn = fmaxf(m, ceilf(mx * 0.0625f) * 16.f);
                    l *= ex2(m - mn);
                    m = mn;
#pragma unroll
                    for (int i = 0; i < 8; i++) pr[i] = ex2(sc[i] - m);
                }
                stsf(ma, m);
                asm volatile("st.shared.v4.u32 [%0], {%1, %2, %3, %4};" :: "r"(pa), "r"(pack2(pr[0], pr[1])), "r"(pack2(pr[2], pr[3])),
                             "r"(pack2(pr[4], pr[5])), "r"(pack2(pr[6], pr[7])) : "memory");
                __syncwarp();
                if (lane == 0) mbar_arrive(sf + (PF0 - SF0) * 8);
                l += ((pr[0] + pr[1]) + (pr[2] + pr[3])) + ((pr[4] + pr[5]) + (pr[6] + pr[7]));
                xl ^= 512; sf += 16; ma += 256; pa += (n == 2 || n == 5) ? -8192 : 4096;
            }
            l += shx(l, 1);
            l += shx(l, 2);
            float2* mlx = (float2*)(sm + SM_MX + 2048) + wq4 * 8 + g;
            if (v == 0) { *mlx = make_float2(m, l); bar_arrive(11, 256); }
            else {
                mbar_wait(BAR(JD), 0);
                bar_sync(11, 256);
                const float2 o = *mlx;
                const float mn = fmaxf(m, o.x);
                l = l * ex2(m - mn) + o.y * ex2(o.x - mn);
                if ((wq4 >> 1) == rk) st_x4(gs + (B_ML + wq4 * 8 + g) * 4096 + (t >> 1) * 1024 + (j >> 1) * 8 + (t & 1) * 4, encf(mn), encf(l), 1u, 1u);
            }
        }
        const int pi = j < NFF ? rk * 128 + w8 * 16 + (lane >> 1) : ((j - J_RED) & 15) * 16 + (w8 & 1) * 8 + g;
        const uint32_t xw = *(const uint32_t*)(xin + 2 * pi);
        const uint32_t one = (g & 1) ? 0x3f800000u : 0x00003f80u;
        const uint32_t* pm = gs + near_off(B_MB, cls) + pi;
        {
            const uint32_t ab = sb + SM_U + B_WUV * 32768 + v * 4096 + a128;
            uint32_t pa = sb + SM_PB + wq4 * 320 + frag_off(64 * v + 32 * (g >> 2) + 16 * (t & 1) + 8 * (t >> 1) + 2 * (g & 3));
            uint32_t fa = sb + SM_PB + g * 320 + t * 16;
            const uint32_t* pe = gs + G_E1 + j * 8192 + (w8 >> 1) * 2048 + ((((cls >> 1) ^ (w8 >> 1)) & 1) << 10) + (((w8 & 1) * 16 + t) * 8 + g) * 4;
            uint32_t* p2 = gs + (B_E2 + (j >> 4)) * 4096 + (t >> 1) * 1024 + (j & 12) * 64 + w8 * 32 + (j & 3) * 8 + (g & 6) + (t & 1);
            pin(pa); pin(fa); pin(pe); pin(p2);
            const uint32_t mk = (g & 1) ? 0xffff0000u : 0x0000ffffu, m0 = (g & 2) ? 0u : mk, m1 = (g & 2) ? mk : 0u;
            uint4 pv[4];
            bool hv = false;
            bar_sync(3, 416);
            uint4 wa = lds128(sb + SM_W + (wq4 * 4 + t) * 16);
            uint32_t wb[8] = {wa.x & m0, wa.x & m1, wa.y & m0, wa.y & m1, wa.z & m0, wa.z & m1, wa.w & m0, wa.w & m1};
            pv[0] = pv[1] = pv[2] = pv[3] = make_uint4(0u, 0u, 0u, 0u);
            float e[4][4];
            auto wsum = [&]() {
#pragma unroll
                for (int i = 0; i < 4; i++) {
                    e[i][0] = e[i][1] = e[i][2] = e[i][3] = 0.f;
                    mma(e[i], pv[i].x, pv[i].y, pv[i].z, pv[i].w, wb[2 * i], wb[2 * i + 1]);
                }
            };
            poll<512, E1_SLEEP, true>(pv, pe, [&]() {
                if (!hv) {
                    hv = __all_sync(0xffffffffu, mbar_test(BAR(IT_WUV + t), 0));
                    if (hv) load8<true>(a, [&](int s) { return ab + (s >> 1) * 8192 + (s & 1) * 2048; });
                }
            }, wsum);
            if (lane == 0) TRACE_Q(48 + w8);
            if (u8 == 0) TRACE_Q(18);
            float lo, hi2;
            float2 inv;
#pragma unroll 1
            for (int pass = 0;; pass++) {
                const float r0 = (t & 2) ? (e[0][2] + e[1][2]) + (e[2][2] + e[3][2]) : (e[0][0] + e[1][0]) + (e[2][0] + e[3][0]);
                const float r1 = (t & 2) ? (e[0][3] + e[1][3]) + (e[2][3] + e[3][3]) : (e[0][1] + e[1][1]) + (e[2][1] + e[3][1]);
                const uint32_t hi = pack2(r0, r1);
                sts32(pa, hi); sts32(pa + 1280, pack2(r0 - bflo(hi), r1 - bfhi(hi)));
                if (!hv) {
#pragma unroll 1
                    for (int i = 0; i < 4; i++) mbar_wait(BAR(IT_WUV + i), 0);
                    load8<true>(a, [&](int s) { return ab + (s >> 1) * 8192 + (s & 1) * 2048; });
                    hv = true;
                }
                bar_sync(1, 256);
                if (u8 == 0) TRACE(19);
                ldfrag(b, fa);
                mma8(c, a, b);
                mbar_wait(BAR(WR), 0);
                asm volatile("ld.shared.v2.f32 {%0, %1}, [%2];" : "=f"(inv.x), "=f"(inv.y) : "r"(sb + SM_FQ) : "memory");
                quad_pair(c[0] + c[1], c[2] + c[3], t, lo, hi2);
                if (__builtin_expect(__all_sync(0xffffffffu, pass || __float_as_uint(inv.y) == 0), 1)) break;
                wa = lds128(sb + SM_W2 + (wq4 * 4 + t) * 16);
                wb[0] = wa.x & m0; wb[1] = wa.x & m1; wb[2] = wa.y & m0; wb[3] = wa.y & m1; wb[4] = wa.z & m0; wb[5] = wa.z & m1; wb[6] = wa.w & m0; wb[7] = wa.w & m1;
                wsum();
                bar_sync(1, 256);
            }
            if (!(g & 1)) st_x1(p2, enc(pack2(lo * inv.x, hi2 * inv.x)));
            bar_arrive(4, 416);
            if (u8 == 0) TRACE(20);
        }
        if (j < NFF) {
            const uint32_t* p3 = gs + near_off(B_E3 + rk * 2 + v, cls) + wq4 * 256 + t * 16 + g * 2;
            const int od = lane & 1;
            uint32_t za = sb + SM_FZ + od * 576 + frag_off(w8 * 32 + (lane & 30));
            uint32_t fa = sb + SM_FZ + (g & 3) * 576 + ((lane ^ j) & 16) * 16 + t * 16, ya = sb + SM_Y + u8 * 4;
            uint32_t mb[3];
            uint4 a2[8];
            poll<1024, MB_SLEEP>(mb, pm);
            const uint32_t kk = pack2(1.f + bflo(mb[2]), 1.f + bfhi(mb[2]));
            sts32(za + 2 * 576, od ? mb[1] : kk);
            uint2 e3[4] = {make_uint2(0u, 0u), make_uint2(0u, 0u), make_uint2(0u, 0u), make_uint2(0u, 0u)};
            uint32_t ra = peer_addr(sb + SM_RED + (rk * 2 + v) * 512 + ((wq4 & 1) * 16 + (t >> 1) * 8 + g) * 16 + (t & 1) * 8, wq4 >> 1), tbo = peer_addr(BAR(QB), wq4 >> 1);
            pin(za); pin(fa); pin(ya); pin(ra); pin(tbo);
            if (lane == 0) mbar_expect(BAR(QB), 256);
            const uint32_t gb = BAR(IT_X + v * 2), ab = sb + SM_U + (B_X + v) * 32768 + a128;
            bool early = false, early2 = false;
            auto ldw = [&]() {
                if (!early) {
                    early = __all_sync(0xffffffffu, mbar_test(gb, 0));
                    if (early) load8<true>(a, [&](int s) { return ab + s * 2048; });
                }
                if (!early2) {
                    early2 = __all_sync(0xffffffffu, mbar_test(gb + 8, 0));
                    if (early2) load8<true>(a2, [&](int s) { return ab + 16384 + s * 2048; });
                }
            };
            bar_sync(8, 384);
            float s0[4], s1[4];
            auto sum = [&]() {
                s0[0] = s0[1] = s0[2] = s0[3] = s1[0] = s1[1] = s1[2] = s1[3] = 0.f;
                mma(s0, e3[0].x, e3[0].y, e3[1].x, e3[1].y, one, one); mma(s1, e3[2].x, e3[2].y, e3[3].x, e3[3].y, one, one);
            };
            poll<256, 0, true>(e3, p3, ldw, sum);
            if (u8 == 0) TRACE(23);
            const float y0 = fmaf(bflo(mb[0]), (t & 2) ? s0[2] + s1[2] : s0[0] + s1[0], bflo(xw)), y1 = fmaf(bfhi(mb[0]), (t & 2) ? s0[3] + s1[3] : s0[1] + s1[1], bfhi(xw));
            stsf(ya, od ? y1 : y0);
            const float z0 = y0 * bflo(kk), z1 = y1 * bfhi(kk);
            const uint32_t zh = pack2(z0, z1);
            sts32(za, od ? pack2(z0 - bflo(zh), z1 - bfhi(zh)) : zh);
            bar_sync(7, 288);
            if (u8 == 0) TRACE(24);
            ldfrag(b, fa);
            if (!early) { mbar_wait(gb, 0); load8<true>(a, [&](int s) { return ab + s * 2048; }); }
            {
                float e[4][4];
#pragma unroll
                for (int s = 0; s < 16; s++) {
                    if (s == 8 && !early2) { mbar_wait(gb + 8, 0); load8<true>(a2, [&](int q) { return ab + 16384 + q * 2048; }); }
                    const uint4& x = s < 8 ? a[s] : a2[s & 7];
                    const uint4& y = b[(s >> 1) & 3];
                    float (&d)[4] = e[(s >> 3) * 2 + (s & 1)];
                    if (!(s & 6)) d[0] = d[1] = d[2] = d[3] = 0.f;
                    mma(d, x.x, x.y, x.z, x.w, (s & 1) ? y.z : y.x, (s & 1) ? y.w : y.y);
                }
                const bool hi = t >> 1;
                const float k0 = hi ? e[2][2] + e[3][2] : e[0][0] + e[1][0], k1 = hi ? e[2][3] + e[3][3] : e[0][1] + e[1][1];
                const float o0 = hi ? e[2][0] + e[3][0] : e[0][2] + e[1][2], o1 = hi ? e[2][1] + e[3][1] : e[0][3] + e[1][3];
                st_async2(ra, k0 + shx(o0, 2), k1 + shx(o1, 2), tbo);
            }
        } else if (j >= J_RED && j < J_END && w8 < 2) {
            uint32_t ga[1], e3[4];
            poll<0, MB_SLEEP>(ga, pm);
            bar_sync(8, 192);
            poll<64, 100>(e3, gs + near_off(B_E3 + (pi >> 6), cls) + (pi & 48) * 16 + t * 64 + (pi & 15));
            float y0 = (bflo(e3[0]) + bflo(e3[1])) + (bflo(e3[2]) + bflo(e3[3])), y1 = (bfhi(e3[0]) + bfhi(e3[1])) + (bfhi(e3[2]) + bfhi(e3[3]));
#pragma unroll
            for (int o = 1; o < 4; o <<= 1) { y0 += shx(y0, o); y1 += shx(y1, o); }
            const int col = g + (t & 1) * 8;
            y0 = __shfl_sync(0xffffffffu, (t & 1) ? fmaf(bfhi(ga[0]), y1, bfhi(xw)) : fmaf(bflo(ga[0]), y0, bflo(xw)), (col >> 1) * 4 + (col & 1));
            float gb = 0.f;
            bool hg = false;
            auto ldg = [&]() {
                if (!hg && (hg = __all_sync(0xffffffffu, mbar_test(BAR(QB), 1)))) gb = __uint_as_float(lds32(sb + SM_FV + 256 + w8 * 32 + (col >> 1) * 4) << ((col & 1) ? 0 : 16) & 0xffff0000u);
            };
            uint16_t* po = (uint16_t*)out + (j - J_RED) * 32 + w8 * 16 + col;
            pin(po);
            uint32_t yv[NFF / 4];
            float e[4][4];
            auto sum = [&]() {
#pragma unroll
                for (int i = 0; i < 4; i++) {
                    e[i][0] = e[i][1] = e[i][2] = e[i][3] = 0.f;
                    mma(e[i], yv[4 * i], yv[4 * i + 1], i < 3 ? yv[(4 * i + 2) % (NFF / 4)] : 0u, i < 3 ? yv[(4 * i + 3) % (NFF / 4)] : 0u, one, one);
                }
            };
            poll<256, 0>(yv, gs + near_off(B_E5 + j - J_RED, cls) + t * 16 + w8 * 8 + g, ldg, sum);
            if (u8 == 0) TRACE(26);
            const float s = (t & 1) ? ((e[0][1] + e[0][3]) + (e[1][1] + e[1][3])) + ((e[2][1] + e[2][3]) + (e[3][1] + e[3][3]))
                                    : ((e[0][0] + e[0][2]) + (e[1][0] + e[1][2])) + ((e[2][0] + e[2][2]) + (e[3][0] + e[3][2]));
            if (!hg) { mbar_wait(BAR(QB), 1); ldg(); }
            if (t < 2) *po = (uint16_t)pack2(fmaf(gb, s, y0), 0.f);
            if (u8 == 0) TRACE(27);
        }
    }
}

typedef CUresult (*EncFn)(CUtensorMap*, CUtensorMapDataType, cuuint32_t, void*, const cuuint64_t*, const cuuint64_t*,
                          const cuuint32_t*, const cuuint32_t*, CUtensorMapInterleave, CUtensorMapSwizzle,
                          CUtensorMapL2promotion, CUtensorMapFloatOOBfill);

void make_map(EncFn enc_fn, CUtensorMap* m, const void* p, cuuint64_t d0, cuuint64_t d1, cuuint64_t d2, cuuint64_t d3,
              cuuint64_t s1, cuuint64_t s2, cuuint64_t s3, cuuint32_t b0, cuuint32_t b1, cuuint32_t b2, cuuint32_t b3, CUtensorMapSwizzle sw) {
    const cuuint64_t dims[4] = {d0, d1, d2, d3}, strides[3] = {s1, s2, s3};
    const cuuint32_t box[4] = {b0, b1, b2, b3}, es[4] = {1, 1, 1, 1};
    enc_fn(m, CU_TENSOR_MAP_DATA_TYPE_BFLOAT16, 4, (void*)p, dims, strides, box, es,
           CU_TENSOR_MAP_INTERLEAVE_NONE, sw, PROMO, CU_TENSOR_MAP_FLOAT_OOB_FILL_NONE);
}

uint32_t* scratch = nullptr;

struct Tune { const char* win; const char* late; int tau, t_off; const char* tail[3][4]; };
Tune tune = {"66666666655555555555555555555555555533333",
             "00000000000000000000999999999999999999999", 320, -300,
             {{"VVVVOOOOguguDDDD", "zzzzzzzzzzzzzzzz", "888899998888789a", "ibbb0gjj7aaa3787"},
              {"VMVMVVOOOO", "zzzzzzzzzz", "8888889999", "588888kbbb"},
              {"VVVVOOOOMM", "zzzzzzzzzz", "aaaaaaaa88", "q8880cjjon"}}};
bool ready = false;

}

extern "C" void kernel_launch(void* const* d_in, const int* in_sizes, int n_in, void* d_out, int out_size) {
    (void)in_sizes; (void)n_in; (void)out_size;
    static Maps maps;
    static const void* cached[12] = {};
    bool same = ready;
    for (int i = 0; i < 12 && same; i++) same = cached[i] == d_in[i];
    if (!same) {
        void* fn = nullptr;
        cudaDriverEntryPointQueryResult qr;
        cudaGetDriverEntryPoint("cuTensorMapEncodeTiled", &fn, cudaEnableDefault, &qr);
        EncFn e = (EncFn)fn;
        const CUtensorMapSwizzle S128 = CU_TENSOR_MAP_SWIZZLE_128B;
        make_map(e, &maps.m[MP_WQ], d_in[2], 64, 512, 64, 1, 8192, 128, 8192, 64, 64, 1, 1, S128);
        make_map(e, &maps.m[MP_WUK], d_in[3], 64, 512, 64, 1, 8192, 128, 8192, 64, 64, 1, 1, S128);
        make_map(e, &maps.m[MP_CKV], d_in[1], 64, 8, 8, 4096, 1024, 128, 8192, 64, 8, 4, 2, S128);
        make_map(e, &maps.m[MP_MODB], d_in[11], 3072, 512, 1, 1, 6144, 6144, 6144, 64, 128, 1, 1, S128);
        make_map(e, &maps.m[MP_WUV], d_in[4], 64, 512, 64, 1, 8192, 128, 8192, 64, 32, 2, 1, S128);
        make_map(e, &maps.m[MP_WO], d_in[5], 512, 4096, 1, 1, 1024, 1024, 1024, 64, 64, 1, 1, S128);
        make_map(e, &maps.m[MP_GATE], d_in[7], 1792, 512, 1, 1, 3584, 3584, 3584, 64, 128, 1, 1, S128);
        make_map(e, &maps.m[MP_UP], d_in[8], 1792, 512, 1, 1, 3584, 3584, 3584, 64, 128, 1, 1, S128);
        make_map(e, &maps.m[MP_DOWN], d_in[9], 64, 1792, 8, 1, 1024, 128, 1024, 64, 32, 2, 1, S128);
        for (int r = 0; r < 3; r++) {
            int ids[58], cnt[128] = {}, tn = tune.t_off - (W0 - 1) * tune.tau;
            uint2* sc = maps.sched[r];
            auto dig = [](char ch) { return ch >= 'a' ? ch - 'a' + 10 : ch >= 'A' ? ch - 'A' + 36 : ch - '0'; };
            for (int i = 0; i < 58; i++) sc[i] = make_uint2(0u, 0u);
            for (int i = 0;; i++) {
                int id = i, buf, dep, w, wl;
                if (i < IT_WUV) {
                    const int u = (i - IT_CKV) >> 2;
                    buf = i < IT_CKV ? 4 + ((i - 1) >> 2) : u % 6;
                    dep = i < IT_CKV || u < 4 ? -1 : u < 6 ? EB_WQ + u - 4 : EB_UNIT0 + u - 6;
                    w = dig(tune.win[i]); wl = dig(tune.late[i]);
                    if (i) tn += tune.tau;
                } else {
                    const char ch = tune.tail[r][0][i - IT_WUV];
                    if (!ch) break;
                    buf = ch == 'V' ? B_WUV : ch == 'O' ? B_WO : ch == 'D' ? B_DN : ch == 'u' ? B_X + 1 : B_X;
                    id = (ch == 'V' ? IT_WUV : ch == 'O' ? IT_WO : ch == 'D' ? IT_DOWN : ch == 'u' ? IT_X + 2 : IT_X) + cnt[(int)ch]++;
                    dep = EB_UNIT0 + (buf < 2 ? buf + 6 : buf);
                    w = dig(tune.tail[r][1][i - IT_WUV]); wl = dig(tune.tail[r][2][i - IT_WUV]);
                    tn += 32 * dig(tune.tail[r][3][i - IT_WUV]);
                }
                if (id < IT_X || id >= IT_DOWN ? (id - 1) & 3 : (id - IT_X) & 1) dep = -1;
                ids[i] = id;
                auto back = [&](int d) { return i < d ? 0 : (ids[i - d] && ids[i - d] <= NCP ? 1 : ids[i - d]) + 1; };
                sc[i].x = id | (buf * 4 + (id < IT_X || id >= IT_DOWN ? (id - 1) & 3 : ((id - IT_X) & 1) * 2)) << 6 | (dep + 1) << 11 | (w > 32 ? NEVER + 1 : back(w)) << 18 | (wl ? back(wl) : 0) << 25;
                const int mp = id < IT_CKV ? MP_WQ + ((id - 1) >> 2) : id < IT_WUV ? MP_CKV : id < IT_WO ? MP_WUV : id < IT_X ? MP_WO
                             : id >= IT_DOWN ? MP_DOWN : r ? MP_MODB : MP_GATE + ((id - IT_X) >> 1);
                const int step = mp == MP_CKV ? id - IT_CKV : mp == MP_WUV ? (id - IT_WUV) * 2 : mp == MP_DOWN ? id - IT_DOWN : id < IT_X ? (id - 1) & 3 : ((id - IT_X) & 1) * 2;
                sc[i].y = (tn & 0xffff) | (mp & 15) << 16 | step << 20;
            }
        }
        cudaGetSymbolAddress((void**)&scratch, g_scratch);
        scratch = (uint32_t*)(((uintptr_t)scratch + (2u << 20) - 1) & ~(uintptr_t)((2u << 20) - 1));
        cudaFuncSetAttribute(fused_kernel, cudaFuncAttributeMaxDynamicSharedMemorySize, SM_TOTAL);
        for (int i = 0; i < 12; i++) cached[i] = d_in[i];
        ready = true;
    }
    const First f = {{(const uint8_t*)d_in[2], (const uint8_t*)d_in[11]}, {(const __nv_bfloat16*)d_in[0], (const __nv_bfloat16*)d_in[10]}};
    fused_kernel<<<NCTA, NTHREADS, SM_TOTAL>>>(f, (__nv_bfloat16*)d_out, scratch, maps);
}
```

```cpp
#include <cuda_runtime.h>
#include <cuda_bf16.h>
#include <cuda.h>
#include <stdint.h>
#include <limits.h>

namespace {

constexpr int NCTA = 128;
constexpr int NTHREADS = 512;
constexpr int NUNITS = 8;
constexpr int NFF = 56, J_RED = 104, J_END = 120;
constexpr uint32_t SPIN_LIMIT = 1u << 22;

#define PROMO CU_TENSOR_MAP_L2_PROMOTION_L2_64B
#define NEAR_CLK 390
#define E1_EARLY 50
#define STAG 300
#define NUMA 1
#define NPROBE 5
#define NCP 2
#define W0 4
#define RD_ITEM 15
#define JAN_SLEEP 100
#define RD_SLEEP 400
#define HA_DELAY 200
#define H_SLEEP 100
#define QA_DELAY 600
#define QA_SLEEP 200
#define ML_DELAY 300
#define E1_SLEEP 50
#define MB_SLEEP 100
constexpr int B_WUV = 2, B_WO = 3, B_X = 4  , B_DN = 0;

constexpr int SM_U = 0;
constexpr int SM_XA = 6 * 32768;
constexpr int SM_XB = SM_XA + 12288;
constexpr int SM_MX = SM_XB + 16384;
constexpr int SM_FZ = SM_XB + 8192;
constexpr int SM_PB = SM_XB;
constexpr int SM_Y = SM_XB + 12288;
constexpr int SM_RED = SM_XB + 4096;
constexpr int SM_FS = SM_XB + 20480;
constexpr int SM_FV = SM_FS + 1024;
constexpr int SM_QX = SM_XA + 8192;
constexpr int SM_FQ = SM_FV + 512;
constexpr int SM_CLS = SM_FQ + 128;
constexpr int SM_W = SM_FQ + 256;
constexpr int SM_W2 = SM_MX + 2304;
constexpr int SM_SCR = SM_XA + 9216;
constexpr int SM_TR = SM_XB + 19456;
constexpr int SM_BAR = SM_W + 256;
constexpr int SM_TOTAL = SM_BAR + 1024;
static_assert(SM_TOTAL <= 232448, "smem");

enum { IT_MODA = 0, IT_WQ = 1, IT_WUK = 5, IT_CKV = 9, IT_WUV = 41, IT_WO = 45, IT_X = 49  , IT_DOWN = 53, NITEMS = 57,
       NEVER = 63,
       SF0 = 64,
       PF0 = 80,
       EB_UNIT0 = 96, MBB = 103,
       EB_WQ = 104, EB_WUK, QT, QB, JD, WR };

enum { MP_WQ = 0, MP_WUK, MP_CKV, MP_WUV, MP_DOWN, MP_WO, MP_GATE, MP_UP, MP_MODB, NMAPS };
struct First { const uint8_t* w[2]; const __nv_bfloat16* v[2]; };
struct Maps { CUtensorMap m[NMAPS]; uint2 sched[3][58]; };

enum { B_HA = 0,
       B_MB = 6,
       B_RD = 7,
       B_E2 = 8,
       B_QA = 16,
       B_ML = 32,
       B_E5 = 64,
       B_E3 = 80,
       B_PR = 96,
       B_TR = 100 };
constexpr int G_E1 = 1 << 19;
constexpr int G_TR = B_TR * 4096;
__device__ __align__(1024) uint32_t g_scratch[(8 << 20) / 4];

#define TRACE(slot) do {} while (0)
#define TRACE_Q(slot) do {} while (0)
#define TRACE_GT(slot) do {} while (0)

__device__ __forceinline__ uint32_t s2u(const void* p) { return (uint32_t)__cvta_generic_to_shared(p); }
__device__ __forceinline__ void mbar_init(uint32_t b, int c) { asm volatile("mbarrier.init.shared::cta.b64 [%0], %1;" :: "r"(b), "r"(c) : "memory"); }
__device__ __forceinline__ void mbar_expect(uint32_t b, uint32_t bytes) { asm volatile("mbarrier.arrive.expect_tx.shared::cta.b64 _, [%0], %1;" :: "r"(b), "r"(bytes) : "memory"); }
__device__ __forceinline__ void mbar_arrive(uint32_t b) { asm volatile("mbarrier.arrive.shared::cta.b64 _, [%0];" :: "r"(b) : "memory"); }
__device__ __forceinline__ void mbar_wait(uint32_t b, uint32_t ph) {
    asm volatile("{\n.reg .pred p;\nW: mbarrier.try_wait.parity.shared::cta.b64 p, [%0], %1;\n@!p bra W;\n}" :: "r"(b), "r"(ph) : "memory");
}
__device__ __forceinline__ void mbar_waitb(uint32_t b, uint32_t ph) {
    asm volatile("{\n.reg .pred p;\n.reg .u32 n;\nmov.u32 n, 0;\n"
                 "W: mbarrier.try_wait.parity.shared::cta.b64 p, [%0], %1;\n@p bra D;\n"
                 "add.u32 n, n, 1;\nsetp.lt.u32 p, n, 0x100000;\n@p bra W;\ntrap;\nD:\n}" :: "r"(b), "r"(ph) : "memory");
}
__device__ __forceinline__ uint32_t mbar_test(uint32_t b, uint32_t ph) {
    uint32_t ok;
    asm volatile("{\n.reg .pred p;\nmbarrier.test_wait.parity.shared::cta.b64 p, [%1], %2;\nselp.u32 %0, 1, 0, p;\n}" : "=r"(ok) : "r"(b), "r"(ph) : "memory");
    return ok;
}
__device__ __forceinline__ void bar_sync(int id, int n) { asm volatile("bar.sync %0, %1;" :: "r"(id), "r"(n) : "memory"); }
__device__ __forceinline__ void bar_arrive(int id, int n) { asm volatile("bar.arrive %0, %1;" :: "r"(id), "r"(n) : "memory"); }
__device__ __forceinline__ uint32_t peer_addr(uint32_t a, uint32_t rank) { uint32_t r; asm("mapa.shared::cluster.u32 %0, %1, %2;" : "=r"(r) : "r"(a), "r"(rank)); return r; }
__device__ __forceinline__ void st_async2(uint32_t a, float x, float y, uint32_t bar) {
    asm volatile("st.async.weak.shared::cluster.mbarrier::complete_tx::bytes.v2.f32 [%0], {%1, %2}, [%3];" :: "r"(a), "f"(x), "f"(y), "r"(bar) : "memory");
}
__device__ __forceinline__ uint32_t gtime() { uint32_t t; asm volatile("mov.u32 %0, %%globaltimer_lo;" : "=r"(t)); return t; }
__device__ __forceinline__ void fence_gpu() { asm volatile("fence.acq_rel.gpu;" ::: "memory"); }

__device__ __forceinline__ uint32_t enc(uint32_t b) { uint32_t r; asm("max.u32 %0, %1, 1;" : "=r"(r) : "r"(b)); return r; }
__device__ __forceinline__ uint32_t encf(float f) { return enc(__float_as_uint(f)); }
__device__ __forceinline__ void st_x1(uint32_t* p, uint32_t v) { asm volatile("st.relaxed.gpu.global.u32 [%0], %1;" :: "l"(p), "r"(v) : "memory"); }
__device__ __forceinline__ void st_x4(void* p, uint32_t a, uint32_t b, uint32_t c, uint32_t d) {
    asm volatile("st.relaxed.gpu.global.v4.u32 [%0], {%1, %2, %3, %4};" :: "l"(p), "r"(a), "r"(b), "r"(c), "r"(d) : "memory");
}
__device__ __forceinline__ void st2_x1(uint32_t* p, uint32_t v) { st_x1(p, v); st_x1(p + 1024, v); }
__device__ __forceinline__ void st2_x4(uint32_t* p, uint32_t a, uint32_t b, uint32_t c, uint32_t d) { st_x4(p, a, b, c, d); st_x4(p + 1024, a, b, c, d); }
__device__ __forceinline__ int near_off(int b, uint32_t cls) { return b * 4096 + (((__popc(b & 0x2C) ^ cls) & 1) << 10); }
__device__ __forceinline__ void ld_x(uint32_t& v, const void* p) { asm volatile("ld.relaxed.gpu.global.u32 %0, [%1];" : "=r"(v) : "l"(p) : "memory"); }
__device__ __forceinline__ void ld_x(uint4& v, const void* p) {
    asm volatile("ld.relaxed.gpu.global.v4.u32 {%0, %1, %2, %3}, [%4];" : "=r"(v.x), "=r"(v.y), "=r"(v.z), "=r"(v.w) : "l"(p) : "memory");
}
__device__ __forceinline__ void ld_x(uint2& v, const void* p) { asm volatile("ld.relaxed.gpu.global.v2.u32 {%0, %1}, [%2];" : "=r"(v.x), "=r"(v.y) : "l"(p) : "memory"); }
__device__ __forceinline__ uint32_t minw(uint32_t v) { return v; }
__device__ __forceinline__ uint32_t minw(const uint2& v) { return min(v.x, v.y); }
__device__ __forceinline__ uint32_t minw(const uint4& v) { return min(__vimin3_u32(v.x, v.y, v.z), v.w); }
template <int N> __device__ __forceinline__ uint32_t mint(const uint32_t* m) {
    if constexpr (N == 1) return m[0];
    else if constexpr (N == 2) return min(m[0], m[1]);
    else return __vimin3_u32(mint<(N + 2) / 3>(m), mint<(N + 1) / 3>(m + (N + 2) / 3), mint<N / 3>(m + (N + 2) / 3 + (N + 1) / 3));
}

template <int STRIDE, int S4 = 4 * STRIDE, typename T, int N>
__device__ __forceinline__ void poll_start(T (&v)[N], const void* base) {
#pragma unroll
    for (int i = 0; i < N; i++) ld_x(v[i], (const uint8_t*)base + (i & 3) * STRIDE + (i >> 2) * S4);
}
struct Nop { __device__ void operator()() const {} };
template <int STRIDE, int SLEEP, bool STARTED = false, int S4 = 4 * STRIDE, typename T, int N, typename F = Nop, typename G = Nop>
__device__ __forceinline__ void poll(T (&v)[N], const void* base, F idle = F(), G ahead = G()) {
    if (!STARTED) { poll_start<STRIDE, S4>(v, base); idle(); }
#pragma unroll 1
    for (uint32_t it = 0;; it++) {
        uint32_t m[N];
        ahead();
#pragma unroll
        for (int i = 0; i < N; i++) m[i] = minw(v[i]);
        if (__all_sync(0xffffffffu, mint<N>(m) != 0)) break;
        if (SLEEP && it > 0) __nanosleep(SLEEP);
#pragma unroll
        for (int i = 0; i < N; i++) if (!m[i]) ld_x(v[i], (const uint8_t*)base + (i & 3) * STRIDE + (i >> 2) * S4);
        idle();
        if (it > SPIN_LIMIT) __trap();
    }
}

__device__ __forceinline__ float bflo(uint32_t w) { return __uint_as_float(w << 16); }
__device__ __forceinline__ float bfhi(uint32_t w) { return __uint_as_float(w & 0xffff0000u); }
__device__ __forceinline__ uint32_t pack2(float lo, float hi) {
    uint32_t r; asm("cvt.rn.bf16x2.f32 %0, %1, %2;" : "=r"(r) : "f"(hi), "f"(lo)); return r;
}
__device__ __forceinline__ float rbf(float x) { return __uint_as_float(pack2(0.f, x)); }
__device__ __forceinline__ float ex2(float x) { float r; asm("ex2.approx.ftz.f32 %0, %1;" : "=f"(r) : "f"(x)); return r; }
__device__ __forceinline__ float shx(float v, int m) { return __shfl_xor_sync(0xffffffffu, v, m); }
__device__ __forceinline__ uint4 lds128(uint32_t a) { uint4 v; asm volatile("ld.shared.v4.u32 {%0, %1, %2, %3}, [%4];" : "=r"(v.x), "=r"(v.y), "=r"(v.z), "=r"(v.w) : "r"(a) : "memory"); return v; }
__device__ __forceinline__ uint32_t lds32(uint32_t a) { uint32_t v; asm volatile("ld.shared.u32 %0, [%1];" : "=r"(v) : "r"(a) : "memory"); return v; }
__device__ __forceinline__ void sts32(uint32_t a, uint32_t v) { asm volatile("st.shared.u32 [%0], %1;" :: "r"(a), "r"(v) : "memory"); }
__device__ __forceinline__ void sts16(uint32_t a, uint32_t v) { asm volatile("st.shared.u16 [%0], %1;" :: "r"(a), "h"((uint16_t)v) : "memory"); }
__device__ __forceinline__ int frag_off(int k) { return (k >> 5) * 64 + ((k >> 1) & 3) * 16 + ((k >> 4) & 1) * 8 + ((k >> 3) & 1) * 4 + (k & 1) * 2; }

template <bool TRANS>
__device__ __forceinline__ uint4 ldsm(uint32_t a) {
    uint4 r;
    if (TRANS) asm volatile("ldmatrix.sync.aligned.m8n8.x4.trans.shared.b16 {%0, %1, %2, %3}, [%4];" : "=r"(r.x), "=r"(r.y), "=r"(r.z), "=r"(r.w) : "r"(a) : "memory");
    else asm volatile("ldmatrix.sync.aligned.m8n8.x4.shared.b16 {%0, %1, %2, %3}, [%4];" : "=r"(r.x), "=r"(r.y), "=r"(r.z), "=r"(r.w) : "r"(a) : "memory");
    return r;
}
__device__ __forceinline__ void mma(float (&c)[4], uint32_t a0, uint32_t a1, uint32_t a2, uint32_t a3, uint32_t b0, uint32_t b1) {
    asm volatile("mma.sync.aligned.m16n8k16.row.col.f32.bf16.bf16.f32 {%0,%1,%2,%3}, {%4,%5,%6,%7}, {%8,%9}, {%0,%1,%2,%3};"
                 : "+f"(c[0]), "+f"(c[1]), "+f"(c[2]), "+f"(c[3]) : "r"(a0), "r"(a1), "r"(a2), "r"(a3), "r"(b0), "r"(b1));
}
template <bool TRANS, typename F>
__device__ __forceinline__ void load8(uint4 (&a)[8], F addr) {
    __syncwarp();
#pragma unroll
    for (int s = 0; s < 8; s++) a[s] = ldsm<TRANS>(addr(s));
}
__device__ __forceinline__ void mma8(float (&c)[4], const uint4 (&a)[8], const uint4 (&b)[4]) {
    float e[4][4];
#pragma unroll
    for (int s = 0; s < 8; s++) {
        if (s < 4) e[s][0] = e[s][1] = e[s][2] = e[s][3] = 0.f;
        mma(e[s & 3], a[s].x, a[s].y, a[s].z, a[s].w, (s & 1) ? b[s >> 1].z : b[s >> 1].x, (s & 1) ? b[s >> 1].w : b[s >> 1].y);
    }
#pragma unroll
    for (int i = 0; i < 4; i++) c[i] = (e[0][i] + e[1][i]) + (e[2][i] + e[3][i]);
}
__device__ __forceinline__ void ldfrag(uint4 (&b)[4], uint32_t a) {
    asm volatile("ld.shared.v4.u32 {%0,%1,%2,%3}, [%16];\nld.shared.v4.u32 {%4,%5,%6,%7}, [%16+64];\n"
                 "ld.shared.v4.u32 {%8,%9,%10,%11}, [%16+128];\nld.shared.v4.u32 {%12,%13,%14,%15}, [%16+192];\n"
                 : "=r"(b[0].x), "=r"(b[0].y), "=r"(b[0].z), "=r"(b[0].w), "=r"(b[1].x), "=r"(b[1].y), "=r"(b[1].z), "=r"(b[1].w),
                   "=r"(b[2].x), "=r"(b[2].y), "=r"(b[2].z), "=r"(b[2].w), "=r"(b[3].x), "=r"(b[3].y), "=r"(b[3].z), "=r"(b[3].w) : "r"(a) : "memory");
}
__device__ __forceinline__ void quad_pair(float x, float y, int t, float& lo, float& hi) {
    const float k = ((t & 1) ? y : x) + shx((t & 1) ? x : y, 1);
    lo = k + shx(k, 2); hi = shx(k, 4) + shx(k, 6);
}
__device__ __forceinline__ void pin(uint32_t& x) { asm volatile("" : "+r"(x)); }
template <typename T> __device__ __forceinline__ void pin(T*& x) { asm volatile("" : "+l"(x)); }
__device__ __forceinline__ float4 ldsf4(uint32_t a) { const uint4 v = lds128(a); return make_float4(__uint_as_float(v.x), __uint_as_float(v.y), __uint_as_float(v.z), __uint_as_float(v.w)); }
__device__ __forceinline__ float sum4(const float4& f) { return (f.x + f.y) + (f.z + f.w); }
__device__ __forceinline__ void stsf(uint32_t a, float v) { sts32(a, __float_as_uint(v)); }

__device__ __forceinline__ void wg_fence() { asm volatile("wgmma.fence.sync.aligned;" ::: "memory"); }
__device__ __forceinline__ void wg_commit() { asm volatile("wgmma.commit_group.sync.aligned;" ::: "memory"); }
__device__ __forceinline__ void wg_wait1() { asm volatile("wgmma.wait_group.sync.aligned 1;" ::: "memory"); }
__device__ __forceinline__ void wg_wait0() { asm volatile("wgmma.wait_group.sync.aligned 0;" ::: "memory"); }
#define R8(o) "+f"(d[o]), "+f"(d[o + 1]), "+f"(d[o + 2]), "+f"(d[o + 3]), "+f"(d[o + 4]), "+f"(d[o + 5]), "+f"(d[o + 6]), "+f"(d[o + 7])
__device__ __forceinline__ void wgmma_rs_n32(float (&d)[16], const uint4& a, uint64_t db, int acc) {
    asm volatile("{\n.reg .pred p;\nsetp.ne.b32 p, %21, 0;\n"
        "wgmma.mma_async.sync.aligned.m64n32k16.f32.bf16.bf16 "
        "{%0,%1,%2,%3,%4,%5,%6,%7,%8,%9,%10,%11,%12,%13,%14,%15}, {%16,%17,%18,%19}, %20, p, 1, 1, 0;\n}"
        : R8(0), R8(8) : "r"(a.x), "r"(a.y), "r"(a.z), "r"(a.w), "l"(db), "r"(acc));
}
#define PV_LO "{%0,%1,%2,%3,%4,%5,%6,%7,%8,%9,%10,%11,%12,%13,%14,%15,%16,%17,%18,%19,%20,%21,%22,%23,%24,%25,%26,%27,%28,%29,%30,%31,%32,%33,%34,%35,%36,%37,%38,%39,%40,%41,%42,%43,%44,%45,%46,%47,%48,%49,%50,%51,%52,%53,%54,%55,%56,%57,%58,%59,%60,%61,%62,%63}, "
#define PV_HI "{%64,%65,%66,%67,%68,%69,%70,%71,%72,%73,%74,%75,%76,%77,%78,%79,%80,%81,%82,%83,%84,%85,%86,%87,%88,%89,%90,%91,%92,%93,%94,%95,%96,%97,%98,%99,%100,%101,%102,%103,%104,%105,%106,%107,%108,%109,%110,%111,%112,%113,%114,%115,%116,%117,%118,%119,%120,%121,%122,%123,%124,%125,%126,%127}, "
__device__ __forceinline__ void wgmma_pv(float (&d)[128], const uint4& a, uint32_t blo, int acc) {
    asm volatile("{\n.reg .pred p;\n.reg .b32 u0, u1, u2, u3, t;\n.reg .b64 d0, d1, d2, d3;\nsetp.ne.b32 p, %133, 0;\n"
        "mov.b64 d0, {%132, 0x40000100};\nadd.u32 t, %132, 512;\nmov.b64 d1, {t, 0x40000100};\n"
        "add.u32 t, %132, 128;\nmov.b64 d2, {t, 0x40000100};\nadd.u32 t, %132, 640;\nmov.b64 d3, {t, 0x40000100};\n"
        "wgmma.fence.sync.aligned;\n"
        "wgmma.mma_async.sync.aligned.m64n128k16.f32.bf16.bf16 " PV_LO "{%128, u0, %129, u1}, d0, p, 1, 1, 1;\n"
        "wgmma.mma_async.sync.aligned.m64n128k16.f32.bf16.bf16 " PV_LO "{%130, u2, %131, u3}, d1, 1, 1, 1, 1;\n"
        "wgmma.commit_group.sync.aligned;\n"
        "wgmma.mma_async.sync.aligned.m64n128k16.f32.bf16.bf16 " PV_HI "{%128, u0, %129, u1}, d2, p, 1, 1, 1;\n"
        "wgmma.mma_async.sync.aligned.m64n128k16.f32.bf16.bf16 " PV_HI "{%130, u2, %131, u3}, d3, 1, 1, 1, 1;\n"
        "wgmma.commit_group.sync.aligned;\n}"
        : R8(0), R8(8), R8(16), R8(24), R8(32), R8(40), R8(48), R8(56), R8(64), R8(72), R8(80), R8(88), R8(96), R8(104), R8(112), R8(120)
        : "r"(a.x), "r"(a.y), "r"(a.z), "r"(a.w), "r"(blo), "r"(acc) : "memory");
}

template <int NW>
__device__ __forceinline__ void ln_stats(float s, float q, float sh, float* scr, int w, int lane, int bar, float& mean_b, float& sd_b) {
#pragma unroll
    for (int o = 16; o; o >>= 1) { s += shx(s, o); q += shx(q, o); }
    constexpr float n = 512.f / NW;
    if (lane == 0) { scr[w] = sh + s * (1.f / n); scr[NW + w] = q - s * s * (1.f / n); }
    bar_sync(bar, NW * 32);
    float mu = 0.f, m2 = 0.f;
#pragma unroll
    for (int i = 0; i < NW; i++) { mu += scr[i]; m2 += scr[NW + i]; }
    mu *= 1.f / NW;
#pragma unroll
    for (int i = 0; i < NW; i++) { const float d = scr[i] - mu; m2 = fmaf(n * d, d, m2); }
    mean_b = rbf(mu);
    sd_b = rbf(sqrtf(rbf(rbf(fmaxf(m2, 0.f) * (1.f / 512.f)) + 1e-5f)));
}
__device__ __forceinline__ float ln_mod(float x, float mean_b, float sd_b, float c, float s) {
    return rbf(rbf(__fdividef(rbf(x - mean_b), sd_b)) * rbf(1.f + c)) + s;
}

__global__ void __cluster_dims__(2, 1, 1) __launch_bounds__(NTHREADS, 1)
fused_kernel(const __grid_constant__ First F, __nv_bfloat16* __restrict__ out, uint32_t* __restrict__ gs, const __grid_constant__ Maps M) {
    extern __shared__ __align__(1024) uint8_t sm[];
    const uint32_t sb = s2u(sm);
    const int tid = threadIdx.x, lane = tid & 31;
    const int j = blockIdx.x, rk = j & 1;
    const int g = lane >> 2, t = lane & 3;
    const int r8 = lane & 7, lb3 = (lane >> 3) & 1, lb4 = lane >> 4;
    uint64_t pol;
    asm("createpolicy.fractional.L2::evict_first.b64 %0, 1.0;" : "=l"(pol));
    {
        auto cpa = [&](uint32_t d, const uint8_t* s) {
            asm volatile("cp.async.cg.shared.global.L2::cache_hint.L2::128B [%0], [%1], 16, %2;" :: "r"(d), "l"(s), "l"(pol) : "memory");
        };
        const uint32_t ut = threadIdx.x, uj = blockIdx.x;
        const uint8_t* w = F.w[ut >= 128];
        if (ut < 128) {
            const uint32_t dq = (sb + ut * 16) ^ ((ut * 2) & 0x70);
            const uint8_t* sq = w + (uint32_t)(((uj & 1) * 256 + (ut >> 3)) * 8192 + (uj >> 1) * 128 + (ut & 7) * 16);
#pragma unroll
            for (int i = 0; i < 4 * NCP; i++) cpa(dq + 4 * 32768 + i * 2048, sq + i * 131072);
        } else if (ut < 384) {
            const uint32_t dm = (sb + ut * 16) ^ ((ut * 2) & 0x10);
            const uint8_t* sa = w + (uint32_t)(((uj >> 5) * 128 + (ut >> 1) - 64) * 6144 + (uj & 31) * 32 + (ut & 1) * 16);
            cpa(dm + SM_XA - 2048, sa); cpa(dm + SM_XA + 2048, sa + 1024);
        }
        else if (ut == 480 && uj < 64) asm volatile("prefetch.global.L2 [%0];" :: "l"(F.v[(uj >> 3) & 1] + (uj & 7) * 64));
    }
    const int warp = __shfl_sync(0xffffffffu, tid >> 5, 0);
    const __nv_bfloat16* const xin = F.v[0];
    uint32_t* const pl = gs + (warp < 2 ? (B_PR + (j >> 5)) * 4096 + (j & 31) * 32 : G_E1 + j * 8192) + (warp & 1) * 1024 + lane;
    if (warp < 4) st_x1(pl, 1u);
    auto BAR = [&](int i) -> uint32_t { return sb + SM_BAR + i * 8; };
    const uint32_t a16 = (r8 + 8 * lb4) * 32 + ((lb3 ^ (r8 >> 2)) * 16);
    const uint32_t a128 = (r8 + 8 * lb4) * 128 + ((((warp & 3) * 2 + lb3) ^ r8) * 16);
    auto ldcls = [&]() -> uint32_t { return *(const volatile uint32_t*)(sm + SM_CLS); };
    auto clear_head = [&]() {
        st2_x1(gs + (B_HA + ((j >> 4) & 1) * 2 + lb4) * 4096 + (j >> 5) * 256 + (j & 15) * 16 + (lane & 15), 0u);
        st2_x4(gs + (B_QA + rk * 8 + ((j >> 1) & 1) * 4 + (j >> 5)) * 4096 + g * 128 + ((j >> 2) & 7) * 16 + t * 4, 0u, 0u, 0u, 0u);
        if (lane < 8) st2_x1(gs + B_RD * 4096 + j * 8 + lane, 0u);
    };
    auto tma = [&](uint32_t dst, const CUtensorMap* mp, uint32_t bar, int c0, int c1, int c2, int c3) {
        asm volatile("{\n.reg .pred p;\nelect.sync _|p, 0xffffffff;\n"
                     "@p cp.async.bulk.tensor.4d.shared::cluster.global.mbarrier::complete_tx::bytes.L2::cache_hint [%0], [%1, {%3, %4, %5, %6}], [%2], %7;\n}"
                     :: "r"(dst), "l"(mp), "r"(bar), "r"(c0), "r"(c1), "r"(c2), "r"(c3), "l"(pol) : "memory");
    };
    if (warp <= 12 || warp == 15) {
        const int grp = warp == 12 ? 0 : warp == 15 ? 13 : warp + 1;
        const uint32_t cnt = grp < 10 ? 1 : grp < 13 ? 4 : 8;
        if (lane == 0) {
#pragma unroll
            for (int i = 0; i < 8; i++) mbar_init(BAR(grp * 8 + i), (i < 2 && grp == 0) ? (i ? 128 : 256) : cnt);
        }
        __syncwarp();
        if (grp < 10 && lane < 8 && (grp || lane > NCP)) mbar_expect(BAR(grp * 8 + lane), grp >= 8 ? 4096 : (uint32_t)(grp * 8 + lane - IT_X) < 4 ? 16384 : 8192);
        asm volatile("fence.mbarrier_init.release.cluster;" ::: "memory");
        __syncwarp();
        if (warp == 12) {
#pragma unroll
            for (int i = NCP + 1; i < W0; i++) tma(sb + (15 + i) * 8192, &M.m[MP_WQ], BAR(i), 0, rk * 256 + (i - 1) * 64, j >> 1, 0);
        }
    } else if (warp == 13) {
        if (lane < NMAPS) asm volatile("prefetch.tensormap [%0];" :: "l"(&M.m[lane]) : "memory");
    } else if (warp == 14) {
        clear_head();
    }
    __syncthreads();
    uint32_t in1 = 0, in2 = 0;
    if (warp < 4) { in1 = *(const uint32_t*)(xin + 2 * tid); in2 = *(const uint32_t*)(xin + 256 + 2 * tid); }
    else if (warp < 12) in1 = *(const uint32_t*)(F.v[1] + 2 * (tid - 128));
    if (warp < 12) asm volatile("cp.async.mbarrier.arrive.noinc.shared::cta.b64 [%0];" :: "r"(BAR(warp < 4)) : "memory");
    asm volatile("barrier.cluster.arrive.relaxed.aligned;" ::: "memory");

    if (warp >= 12) {
    asm volatile("setmaxnreg.dec.sync.aligned.u32 64;");
    if (warp == 12) {
        static_assert(W0 > NCP && W0 <= 5 && NCP >= 1 && NCP <= 4, "W0");
        const uint2* sched = M.sched[j < NFF ? 0 : j < J_RED ? 1 : 2];
        uint2 en = sched[W0];
        const uint32_t t0 = gtime();
        const uint32_t sp = __reduce_or_sync(0xffffffffu, sb);
        const int cx = (j >> 1) * 64 + (j < NFF ? 0 : 1024 - NFF * 32);
#pragma unroll 1
        for (int i = W0; en.x; i++) {
            uint32_t e = en.x, st = (en.y >> 20) * 64;
            const uint32_t tn = t0 + (int16_t)en.y, mp = (en.y >> 16) & 15;
            if (mp == MP_WUV || mp == MP_WUK) { st ^= (j >> 5) * (mp == MP_WUV ? 128 : 64); e ^= (j >> 5) << 6; }
            if (mp == MP_GATE || mp == MP_UP) st ^= (j & 16) * 8;
            if (mp == MP_DOWN) { st ^= (j & 3) * 64; e ^= (j & 3) << 6; }
            en = sched[i + 1];
            if (mp == MP_MODB && j >= J_END) break;
            uint32_t c0 = mp == MP_WO ? (j & 7) * 64 : mp > MP_WO ? cx : 0;
            uint32_t c1 = mp == MP_CKV ? 0 : mp == MP_DOWN ? j * 32 : st + (mp == MP_WUV ? (j & 3) * 32 : mp == MP_WO ? (j >> 3) * 256 : rk * 256);
            uint32_t c2 = mp < MP_CKV ? j >> 1 : mp == MP_CKV ? rk * 4 : mp == MP_WUV ? (j >> 2) * 2 : mp == MP_DOWN ? st >> 5 : 0;
            uint32_t c3 = mp == MP_CKV ? st * 2 + (j & ~1) : 0;
            uint32_t dst = sp + ((e << 7) & 0x3e000), bar = sp + SM_BAR + (e & 63) * 8;
            const uint32_t w0 = (e >> 8) & 0x3f8, w1 = (e >> 15) & 0x3f8, w2 = (e >> 22) & 0x3f8, bb = sp + SM_BAR - 8;
            const CUtensorMap* pm = &M.m[mp];
            pin(dst); pin(bar); pin(c0); pin(c1); pin(c2); pin(c3); pin(pm);
            if (w0) mbar_wait(bb + w0, 0);
            if (w2) {
                mbar_wait(bb + w2, 0);
                while (!__any_sync(0xffffffffu, mbar_test(bb + w1, 0) | ((int)(gtime() - tn) > 0))) {}
            } else if (w1) mbar_wait(bb + w1, 0);
            tma(dst, pm, bar, c0, c1, c2, c3);
        }
    } else if (warp == 13) {
#pragma unroll
        for (int i = 0; i < 2; i++) st_x4(gs + (B_ML + rk * 16 + i * 8 + g) * 4096 + (t >> 1) * 1024 + (j >> 1) * 8 + (t & 1) * 4, 0u, 0u, 0u, 0u);
        if (lane < 16) st2_x4(gs + (B_E2 + (j >> 4)) * 4096 + (j & 15) * 64 + lane * 4, 0u, 0u, 0u, 0u);
        st2_x1(gs + (B_E3 + (j >> 5)) * 4096 + (j & 31) * 32 + lane, 0u);
        if (lane < 8) st2_x1(gs + B_MB * 4096 + j * 8 + lane, 0u);
        if (j < NFF) {
#pragma unroll
            for (int i = 0; i < 2; i++) st2_x4(gs + (B_E5 + i * 8 + g) * 4096 + j * 16 + t * 4, 0u, 0u, 0u, 0u);
        }
        bar_sync(9, 64);
        const uint32_t cs = ldcls();
#pragma unroll 1
        for (int i = 0; i < 32; i++) {
            st_x4(gs + G_E1 + j * 8192 + (i >> 3) * 2048 + ((((cs >> 1) ^ (i >> 3)) & 1) << 10) + (i & 7) * 128 + lane * 4, 0u, 0u, 0u, 0u);
            __nanosleep(JAN_SLEEP);
        }
        fence_gpu();
        if (lane < 8) st2_x1(gs + B_RD * 4096 + j * 8 + lane, 1u + (cs >> 1));
        if (lane == 0) TRACE(41);
        uint32_t rd[4];
        mbar_wait(BAR(IT_CKV + RD_ITEM), 0);
        poll<1024, RD_SLEEP>(rd, gs + near_off(B_RD, cs) + lane * 8);
#pragma unroll
        for (int i = 0; i < 4; i++) {
            const uint32_t m = __ballot_sync(0xffffffffu, rd[i] == 2u);
            if (lane == 0) sts32(sb + SM_CLS + 16 + i * 4, m);
        }
        __syncwarp();
        if (lane < 8) mbar_arrive(BAR(JD));
        if (lane == 0) TRACE(42);
    } else if (warp == 14) {
        uint2 ml[2];
        mbar_waitb(BAR(JD), 0);
        const uint32_t cls = ldcls();
        mbar_waitb(BAR(PF0 + 2 * NUNITS - 1), 0);
        __nanosleep(ML_DELAY);
        const uint32_t* pl2 = gs + near_off(B_ML + (j >> 2), cls) + lane * 8;
        const uint32_t wa = sb + SM_W + lb4 * 64 + t * 16 + (g & 3) * 4;
        poll_start<1024>(ml, pl2);
        uint32_t w0 = 0, w1 = 0, redo = 0;
        bool first = true;
#pragma unroll 1
        for (uint32_t it = 0;; it++) {
            const bool p0 = minw(ml[0]) != 0, p1 = minw(ml[1]) != 0;
            const int n = __popc(__ballot_sync(0xffffffffu, p0)) + __popc(__ballot_sync(0xffffffffu, p1));
            const uint32_t x0 = ml[0].x, x1 = ml[1].x;
            if (n < 64) {
                if (!p0) ld_x(ml[0], pl2);
                if (!p1) ld_x(ml[1], pl2 + 256);
            }
            if (n == 64 || (first && n >= E1_EARLY)) {
                auto ord = [](int x) { return x ^ ((x >> 31) & 0x7fffffff); };
                const int o0 = ord(x0), o1 = ord(x1);
                const float mm = __int_as_float(ord(__reduce_max_sync(0xffffffffu, max(p0 ? o0 : INT_MIN, p1 ? o1 : INT_MIN))));
                const float lo = __int_as_float(ord(__reduce_min_sync(0xffffffffu, min(p0 ? o0 : INT_MAX, p1 ? o1 : INT_MAX))));
                const uint32_t v0 = pack2(ex2((p0 ? __uint_as_float(x0) : lo) - mm), 0.f), v1 = pack2(ex2((p1 ? __uint_as_float(x1) : lo) - mm), 0.f);
                redo = !first && __any_sync(0xffffffffu, v0 != w0 || v1 != w1);
                w0 = v0; w1 = v1;
                sts32(wa - redo * (SM_W - SM_W2), w0 * 0x10001u); sts32(wa - redo * (SM_W - SM_W2) + 128, w1 * 0x10001u);
                if (first) bar_arrive(3, 416);
                first = false;
                if (n == 64) break;
            }
            if (it > SPIN_LIMIT) __trap();
        }
        if (lane == 0) TRACE_Q(37);
        float L = bflo(w0) * __uint_as_float(ml[0].y) + bflo(w1) * __uint_as_float(ml[1].y);
#pragma unroll
        for (int o = 16; o; o >>= 1) L += shx(L, o);
        if (lane == 0) *(float2*)(sm + SM_FQ) = make_float2(__frcp_rn(L), __uint_as_float(redo));
        __syncwarp();
        if (lane < 8) mbar_arrive(BAR(WR));
        if (lane == 0) TRACE(10);
        bar_sync(4, 416);
        clear_head();
        if (j < NFF) {
            uint32_t ya = sb + SM_Y + lane * 16, sa = peer_addr(sb + SM_RED + 2048 + rk * 8, lane & 1), tb = peer_addr(BAR(MBB), lane & 1);
            pin(ya); pin(sa); pin(tb);
            bar_sync(7, 288);
            const float4 y0 = ldsf4(ya), y1 = ldsf4(ya + 512);
            float s = sum4(y0) + sum4(y1);
            float q = (fmaf(y0.x, y0.x, y0.y * y0.y) + fmaf(y0.z, y0.z, y0.w * y0.w)) + (fmaf(y1.x, y1.x, y1.y * y1.y) + fmaf(y1.z, y1.z, y1.w * y1.w));
#pragma unroll
            for (int o = 16; o; o >>= 1) { s += shx(s, o); q += shx(q, o); }
            if (lane < 2) st_async2(sa, s, q, tb);
        }
    } else if (warp == 15) {
        mbar_waitb(BAR(IT_X - 1), 0);
        if (j < J_END) mbar_waitb(BAR(j < NFF ? NITEMS - 1 : MBB), 0);
    }
    } else if (warp < 4) {
        float* scr = (float*)(sm + SM_SCR);
        uint32_t cls;
        {
            uint2 ha[8];
            uint32_t best = 0xffffffffu;
            sts32(sb + SM_SCR + 64 + warp * 4, best);
            const float sh = __shfl_sync(0xffffffffu, bflo(in1), 0);
            const float v0 = bflo(in1) - sh, v1 = bfhi(in1) - sh, v2 = bflo(in2) - sh, v3 = bfhi(in2) - sh;
            float mb, sd;
            ln_stats<4>((v0 + v1) + (v2 + v3), (v0 * v0 + v1 * v1) + (v2 * v2 + v3 * v3), sh, scr, warp, lane, 2, mb, sd);
            if (!rk) in2 = in1;
#pragma unroll 1
            for (int i = 0; i < NPROBE; i++) {
                uint32_t t0, t1, o;
                asm volatile("mov.u32 %0, %%clock;" : "=r"(t0));
                asm volatile("atom.relaxed.gpu.global.exch.b32 %0, [%1], %2;" : "=r"(o) : "l"(pl), "r"(2u + i) : "memory");
                asm volatile("{\n.reg .pred p;\nsetp.ne.u32 p, %1, 0x1234567;\nmov.u32 %0, 0;\n@p mov.u32 %0, %%clock;\n}" : "=r"(t1) : "r"(o));
                best = min(best, t1 - t0);
                sts32(sb + SM_SCR + 64 + warp * 4, best);
                if (__all_sync(0xffffffffu, min(best, lds32(sb + SM_SCR + 64 + (warp ^ 1) * 4)) < NEAR_CLK)) break;
            }
            bar_sync(2, 128);
            const uint4 lt = *(const uint4*)(scr + 16);
            cls = NUMA ? ((lt.y < lt.x) ^ (__popc((B_PR + (j >> 5)) & 0x2C) & 1)) | (lt.w < lt.z) << 1 : 0;
            if (warp == 0) { if (lane == 0) sts32(sb + SM_CLS, cls); bar_arrive(9, 64); }
            if (tid == 0) TRACE(38);
            asm volatile("barrier.cluster.wait.aligned;" ::: "memory");
            mbar_wait(BAR(IT_MODA), 0);
            if (HA_DELAY) __nanosleep(HA_DELAY);
            poll<1024, H_SLEEP, false, 16384>(ha, gs + near_off(B_HA + rk * 2, cls) + 2 * tid);
            auto rsum = [](uint32_t a, uint32_t b, uint32_t c, uint32_t d) { return rbf((__uint_as_float(a) + __uint_as_float(b)) + (__uint_as_float(c) + __uint_as_float(d))); };
            sts32(sb + SM_FV + frag_off(2 * tid),
                  pack2(ln_mod(bflo(in2), mb, sd, rsum(ha[4].x, ha[5].x, ha[6].x, ha[7].x), rsum(ha[0].x, ha[1].x, ha[2].x, ha[3].x)),
                        ln_mod(bfhi(in2), mb, sd, rsum(ha[4].y, ha[5].y, ha[6].y, ha[7].y), rsum(ha[0].y, ha[1].y, ha[2].y, ha[3].y))));
            bar_arrive(5, 384);
            mbar_wait(BAR(QB), 0);
            if (tid < 64) {
                const float* qx = (const float*)(sm + SM_QX) + tid;
                sts16(sb + SM_FQ + frag_off(tid), pack2((qx[0] + qx[64]) + (qx[128] + qx[192]), 0.f));
            }
            bar_arrive(6, 384);
        }
        asm volatile("setmaxnreg.inc.sync.aligned.u32 192;");
        float acc[128];
        float M = 0.f;
        uint32_t pa = sb + SM_XA + warp * 512 + lane * 16, ma = sb + SM_MX + (warp * 8 + g) * 4, pf = BAR(PF0);
        uint32_t blo = __reduce_or_sync(0xffffffffu, (((sb + SM_U) & 0x3FFFFu) >> 4) | 0x400000u);
        uint32_t* e1[4];
#pragma unroll
        for (int i = 0; i < 4; i++) e1[i] = gs + G_E1 + (warp * 8 + g) * 4 * 8192 + (rk * 2 + (j >> 6)) * 2048 + ((j >> 1) & 31) * 32 + t * 4;
#pragma unroll 1
        for (int h = 0; h < 2 * NUNITS; h++) {
            mbar_wait(pf, 0);
            const float m = __uint_as_float(lds32(ma));
            const uint4 pn = lds128(pa);
            wg_wait0();
#pragma unroll
            for (int i = 0; i < 128; i++) asm volatile("" : "+f"(acc[i]) :: "memory");
            if (h == 0) M = m;
            uint32_t b2 = 0x3f803f80u;
            if (__builtin_expect(__any_sync(0xffffffffu, m != M), 0)) {
                const float Mn = fmaxf(M, m), alpha = ex2(M - Mn), beta = ex2(m - Mn);
                M = Mn;
                b2 = pack2(beta, beta);
#pragma unroll
                for (int jj = 0; jj < 32; jj++) { acc[4 * jj] *= alpha; acc[4 * jj + 1] *= alpha; }
            }
            auto mul2 = [](uint32_t x, uint32_t y) { uint32_t r; asm("mul.rn.bf16x2 %0, %1, %2;" : "=r"(r) : "r"(x), "r"(y)); return r; };
            const uint4 p = make_uint4(mul2(pn.x, b2), mul2(pn.y, b2), mul2(pn.z, b2), mul2(pn.w, b2));
            if (tid == 0 && (h & 1)) TRACE_Q(48 + (h >> 1));
            wgmma_pv(acc, p, blo, h);
            if (lane == 0 && h > 0 && !(h & 1)) mbar_arrive(BAR(EB_UNIT0 + (h >> 1) - 1));
            blo += h == 11 ? -11 * 1024 : 1024;
            pa += (h == 5 || h == 11) ? -5 * 2048 : 2048;
            ma += 128; pf += 8;
            if (h == 2 * NUNITS - 3) {
                mbar_wait(BAR(JD), 0);
                const uint32_t hm = (*(const uint32_t*)(sm + SM_CLS + 16 + warp * 4) >> (g * 4)) ^ ((j >> 6) ? 15u : 0u);
#pragma unroll
                for (int i = 0; i < 4; i++) e1[i] += ((hm >> i) & 1) << 10;
            }
        }
#pragma unroll
        for (int vv = 0; vv < 2; vv++) {
            if (vv && M == 1.f) __trap();
            if (vv) wg_wait0(); else wg_wait1();
#pragma unroll
            for (int i = 0; i < 64; i++) asm volatile("" : "+f"(acc[vv * 64 + i]) :: "memory");
            if (tid == 0 && !vv) TRACE_Q(63);
#pragma unroll
            for (int i = 0; i < 4; i++) {
                const float* a = &acc[vv * 64 + i * 16];
                st_x4(e1[i] + i * 8192 + vv * 16, enc(pack2(a[0], a[1])), enc(pack2(a[4], a[5])), enc(pack2(a[8], a[9])), enc(pack2(a[12], a[13])));
            }
        }
        bar_arrive(3, 416);
        if (tid == 0) TRACE_Q(17);
#pragma unroll 1
        for (int pass = 0;; pass++) {
            if (j >= NFF && j < J_END && pass == (j >= J_RED)) {
                uint4 a[8], b[4];
                float c[4], e[4];
                const bool own = (warp >> 1) == rk;
                const uint32_t xa = sb + SM_FV + (warp & 1) * 64 + g * 8;
                if (lane == 0) mbar_expect(BAR(MBB), own ? 64 : 0);
#pragma unroll
                for (int i = 0; i < 2; i++) {
                    ldfrag(b, sb + SM_FS + rk * 512 + i * 256 + t * 16);
                    mbar_wait(BAR(IT_X + i), 0);
                    const uint32_t ab = sb + SM_U + B_X * 32768 + i * 16384 + a128;
                    load8<true>(a, [&](int s) { return ab + s * 2048; });
                    mma8(i ? e : c, a, b);
                }
                c[0] += e[0]; c[2] += e[2];
                if (!own) {
                    if (t == 0) st_async2(peer_addr(xa, rk ^ 1), c[0], c[2], peer_addr(BAR(MBB), rk ^ 1));
                } else {
                    mbar_wait(BAR(MBB), 0);
                    const float2 pp = *(const float2*)(sm + (xa - sb));
                    const float mine = t ? c[2] + pp.y : c[0] + pp.x, other = shx(mine, 4);
                    const uint32_t w = (warp & 1) * 8 + t * 4 + (g >> 1), val = enc(pack2(mine, other));
                    if (t < 2 && !(g & 1)) {
                        if (j < J_RED) st2_x1(gs + B_MB * 4096 + (j - NFF) * 16 + w, val);
                        else sts32(sb + SM_FV + 256 + w * 4, val);
                    }
                    __syncwarp();
                    if (j >= J_RED && lane < 4) mbar_arrive(BAR(QB));
                    if (lane == 0) TRACE(11);
                }
            }
            if (pass) break;
            uint4 a[8], a2[8];
            const uint32_t ab = sb + SM_U + B_WO * 32768 + a128;
            uint32_t* p3 = gs + (B_E3 + ((j >> 1) & 3)) * 4096 + (t >> 1) * 1024 + (rk * 2 + (warp >> 1)) * 256 + (j >> 3) * 16 + (warp & 1) * 8 + (t & 1) * 4 + (g >> 1);
            const uint32_t* pb = gs + near_off(B_E2 + (j >> 4), cls) + (((j >> 3) & 1) * 2 + lb4) * 256 + (lane & 15) * 2;
            pin(p3); pin(pb);
            uint2 bb[8];
            uint2 bq[2] = {make_uint2(0u, 0u), make_uint2(0u, 0u)};
            uint32_t xa = sb + SM_XA + lane * 16;
            pin(xa);
            bool h0 = false, h1 = false;
            auto idle = [&]() {
                if (!h0) {
                    h0 = __all_sync(0xffffffffu, mbar_test(BAR(IT_WO + (t & 1)), 0));
                    if (h0) load8<true>(a, [&](int s) { return ab + s * 2048; });
                }
                if (!h1) {
                    h1 = __all_sync(0xffffffffu, mbar_test(BAR(IT_WO + 2 + (t & 1)), 0));
                    if (h1) load8<true>(a2, [&](int s) { return ab + 16384 + s * 2048; });
                }
            };
            bar_sync(4, 416);
            idle();
            poll<128, 0, true>(bq, pb + warp * 64, idle);
            asm volatile("st.shared.v4.u32 [%0], {%1, %2, %3, %4};" :: "r"(xa + warp * 512), "r"(bq[0].x), "r"(bq[0].y), "r"(bq[1].x), "r"(bq[1].y) : "memory");
            bar_sync(2, 128);
#pragma unroll
            for (int i = 0; i < 4; i++) { const uint4 q = lds128(xa + i * 512); bb[2 * i] = make_uint2(q.x, q.y); bb[2 * i + 1] = make_uint2(q.z, q.w); }
            if (tid == 0) TRACE(21);
            float e[4][4];
#pragma unroll
            for (int s = 0; s < 16; s++) {
                if (s == 0 && !h0) { mbar_wait(BAR(IT_WO), 0); mbar_wait(BAR(IT_WO + 1), 0); load8<true>(a, [&](int q) { return ab + q * 2048; }); }
                if (s == 0 && !h1) { mbar_wait(BAR(IT_WO + 2), 0); mbar_wait(BAR(IT_WO + 3), 0); load8<true>(a2, [&](int q) { return ab + 16384 + q * 2048; }); }
                const int z = (s & 1) | (s & 2) << 2 | (s >> 2) << 1;
                const uint4& x = z < 8 ? a[z] : a2[z & 7];
                float (&d)[4] = e[(z >> 3) * 2 + (z & 1)];
                if (!(z & 6)) d[0] = d[1] = d[2] = d[3] = 0.f;
                mma(d, x.x, x.y, x.z, x.w, bb[z & 7].x, bb[z & 7].y);
            }
            float lo, hi;
            quad_pair((t & 2) ? (e[2][0] + e[3][0]) + (e[2][1] + e[3][1]) : (e[0][0] + e[1][0]) + (e[0][1] + e[1][1]),
                      (t & 2) ? (e[2][2] + e[3][2]) + (e[2][3] + e[3][3]) : (e[0][2] + e[1][2]) + (e[0][3] + e[1][3]), t, lo, hi);
            if (!(g & 1)) st_x1(p3, enc(pack2(lo, hi)));
            if (j < NFF) bar_arrive(8, 384); else if (j >= J_RED && j < J_END) bar_arrive(8, 192);
            if (tid == 0) TRACE(22);
        }
        if (j < NFF) {
            uint4 a[16];
            const uint32_t ad = sb + SM_U + B_DN * 32768 + warp * 8192 + (r8 + 8 * lb4) * 128 + (lb3 ^ r8) * 16;
            uint32_t rl = sb + SM_RED + lane * 16;
            uint32_t* p5 = gs + (B_E5 + warp * 4 + (t >> 1)) * 4096 + j * 16 + (t & 1) * 8 + g;
            pin(rl); pin(p5);
            if (lane == 0) mbar_expect(BAR(MBB), 4);
            auto ldd = [&]() {
#pragma unroll
                for (int s = 0; s < 16; s++) a[s] = ldsm<true>((ad ^ ((s & 3) * 32)) + (s >> 2) * 2048);
            };
            const uint32_t db = BAR(IT_DOWN + (warp ^ (j & 3)));
            mbar_wait(BAR(MBB), 0);
            const float4 st = ldsf4(sb + SM_RED + 2048);
            const bool hd = __all_sync(0xffffffffu, mbar_test(db, 0));
            if (hd) ldd();
            const float mu = (st.x + st.z) * (1.f / 512.f);
            float rstd;
            asm volatile("rsqrt.approx.ftz.f32 %0, %1;" : "=f"(rstd) : "f"(fmaxf(fmaf(-mu, mu, (st.y + st.w) * (1.f / 512.f)), 0.f) + 1e-5f));
            mbar_wait(BAR(QB), 1);
            if (tid == 0) TRACE(25);
            const float4 f0 = ldsf4(rl), f2 = ldsf4(rl + 1024), f1 = ldsf4(rl + 512), f3 = ldsf4(rl + 1536);
            const float gg = fmaf(rstd, fmaf(-mu, f0.z + f2.z, (f0.x + f0.y) + (f2.x + f2.y)), f0.w + f2.w);
            const float uu = fmaf(rstd, fmaf(-mu, f1.z + f3.z, (f1.x + f1.y) + (f3.x + f3.y)), f1.w + f3.w);
            const float hh = __fdividef(gg * uu, 1.f + ex2(-gg * fmaf(gg * gg, 0.10294324f, 2.3022082f)));
            uint32_t hb[4];
#pragma unroll
            for (int i = 0; i < 4; i++) hb[i] = pack2(__shfl_sync(0xffffffffu, hh, 2 * t + 8 * i), __shfl_sync(0xffffffffu, hh, 2 * t + 8 * i + 1));
            if (!hd) { mbar_wait(db, 0); ldd(); }
#pragma unroll
            for (int i = 0; i < 2; i++) {
                uint32_t res = 0;
#pragma unroll
                for (int k = 0; k < 4; k++) {
                    float c[4] = {0.f, 0.f, 0.f, 0.f};
                    const uint4 &x = a[i * 8 + k], &y = a[i * 8 + k + 4];
                    mma(c, x.x, x.y, x.z, x.w, hb[0], hb[1]);
                    mma(c, y.x, y.y, y.z, y.w, hb[2], hb[3]);
                    if (t == k) res = pack2(c[0], c[2]);
                }
                st2_x1(p5 + i * 8192, enc(res));
            }
            if (tid == 0) { TRACE(27); TRACE_GT(47); }
        }
    } else {
        const int u8 = tid - 128, w8 = warp - 4;
        const int v = w8 >> 2, wq4 = w8 & 3;
        {
            const float c0 = bflo(in1), c1 = bfhi(in1);
            sts32(sb + SM_FS + frag_off(2 * u8), pack2(__fdividef(c0, 1.f + __expf(-c0)), __fdividef(c1, 1.f + __expf(-c1))));
        }
        bar_sync(1, 256);
        asm volatile("barrier.cluster.wait.aligned;" ::: "memory");
        uint4 a[8], b[4]; float c[4];
        if (w8 < 2) {
            ldfrag(b, sb + SM_FS + (j >> 5) * 256 + t * 16);
            mbar_wait(BAR(IT_MODA), 0);
            if (u8 == 0) TRACE(12);
            const uint32_t ab = sb + SM_XA + w8 * 4096 + a16;
            load8<true>(a, [&](int s) { return ab + s * 512; });
            mma8(c, a, b);
            if (t < 2) st2_x1(gs + (B_HA + ((j >> 4) & 1) * 2 + w8) * 4096 + (j >> 5) * 256 + (j & 15) * 16 + t * 8 + g, encf(t ? c[2] : c[0]));
        }
        {
            mbar_wait(BAR(IT_WQ + 2 * v <= NCP ? 1 : IT_WQ + 2 * v), 0); mbar_wait(BAR(IT_WQ + 2 * v + 1 <= NCP ? 1 : IT_WQ + 2 * v + 1), 0);
            const uint32_t ab = sb + SM_U + 4 * 32768 + v * 16384 + a128;
            load8<true>(a, [&](int s) { return ab + s * 2048; });
            if (lane == 0) mbar_arrive(BAR(EB_WQ));
            bar_sync(5, 384);
            if (u8 == 0) TRACE(13);
            ldfrag(b, sb + SM_FV + v * 256 + t * 16);
            mma8(c, a, b);
            if (t < 2) {
                const float qv = t ? c[2] : c[0];
                const uint32_t qa_ = sb + SM_QX + ((rk * 2 + v) * 64 + wq4 * 16 + t * 8 + g) * 4;
                asm volatile("st.async.weak.shared::cluster.mbarrier::complete_tx::bytes.f32 [%0], %1, [%2];"
                             :: "r"(peer_addr(qa_, rk ^ 1)), "f"(qv), "r"(peer_addr(BAR(QB), rk ^ 1)) : "memory");
                sts32(qa_, __float_as_uint(qv));
            }
            __syncwarp();
            if (lane == 0) mbar_expect(BAR(QB), 64);
        }
        {
            mbar_wait(BAR(IT_WUK + (v ^ ((j >> 5) & 1))), 0); mbar_wait(BAR(IT_WUK + (v ^ ((j >> 5) & 1)) + 2), 0);
            const uint32_t ab = sb + SM_U + 5 * 32768 + (w8 * 16 + r8 + 8 * lb3) * 128;
            const uint32_t x16 = (lb4 ^ r8) * 16;
            load8<false>(a, [&](int s) { return ab + (s & 1) * 16384 + (x16 ^ ((s >> 1) * 32)); });
            bar_sync(6, 384);
            if (u8 == 0) TRACE(14);
            b[0] = lds128(sb + SM_FQ + t * 16); b[1] = lds128(sb + SM_FQ + 64 + t * 16);
            float e[4] = {0.f, 0.f, 0.f, 0.f};
            c[0] = c[1] = c[2] = c[3] = 0.f;
#pragma unroll
            for (int k = 0; k < 4; k++) {
                const uint32_t b0 = (k & 1) ? b[k >> 1].z : b[k >> 1].x, b1 = (k & 1) ? b[k >> 1].w : b[k >> 1].y;
                mma(c, a[2 * k].x, a[2 * k].y, a[2 * k].z, a[2 * k].w, b0, b1);
                mma(e, a[2 * k + 1].x, a[2 * k + 1].y, a[2 * k + 1].z, a[2 * k + 1].w, b0, b1);
            }
            const float mine = ((t & 1) ? ((t & 2) ? e[2] : e[0]) : ((t & 2) ? c[2] : c[0])) * 0.12751743f;
            const float other = shx(mine, 4);
            if (!(g & 1)) st2_x1(gs + (B_QA + rk * 8 + ((j >> 1) & 1) * 4 + (j >> 5)) * 4096 + w8 * 128 + ((j >> 2) & 7) * 16 + (g >> 1) * 4 + t, enc(pack2(mine, other)));
            if (u8 == 0) TRACE(15);
        }
        const uint32_t cls = ldcls();
        __nanosleep(QA_DELAY);
        {
            uint4 qb[8];
            const uint32_t* pq = gs + near_off(B_QA + rk * 8 + wq4, cls) + lane * 4;
            const uint32_t* pq2 = gs + near_off(B_QA + rk * 8 + 4 + wq4, cls) + lane * 4;
            if (lane == 0) {
                mbar_expect(BAR(QT), 4096);
                asm volatile("cp.async.bulk.shared::cluster.global.mbarrier::complete_tx::bytes [%0], [%1], 4096, [%2];"
                             :: "r"(sb + SM_U + 5 * 32768 + w8 * 4096), "l"(gs + near_off(B_QA + rk * 8 + w8, cls)), "r"(BAR(QT)) : "memory");
            }
            const uint32_t qs = sb + SM_U + 5 * 32768 + wq4 * 4096 + lane * 16;
            mbar_wait(BAR(QT), 0);
#pragma unroll
            for (int i = 0; i < 8; i++) { a[i] = lds128(qs + i * 512); qb[i] = lds128(qs + 16384 + i * 512); }
            poll<512, QA_SLEEP, true>(a, pq);
            poll<512, QA_SLEEP, true>(qb, pq2);
            if (lane == 0) mbar_arrive(BAR(EB_WUK));
            auto add2 = [](uint32_t x, uint32_t y) { uint32_t r; asm("add.rn.bf16x2 %0, %1, %2;" : "=r"(r) : "r"(x), "r"(y)); return r; };
#pragma unroll
            for (int i = 0; i < 8; i++) a[i] = make_uint4(add2(a[i].x, qb[i].x), add2(a[i].y, qb[i].y), add2(a[i].z, qb[i].z), add2(a[i].w, qb[i].w));
        }
        if (u8 == 0) TRACE(8);
        {
            float m = -INFINITY, l = 0.f;
            uint32_t xl = sb + SM_XB + w8 * 2048 + lane * 16, xr = peer_addr(xl, rk ^ 1), bsr = peer_addr(BAR(SF0 + v), rk ^ 1);
            uint32_t pa = sb + SM_XA + v * 2048 + wq4 * 512 + lane * 16, ma = sb + SM_MX + v * 128 + (wq4 * 8 + g) * 4;
            uint32_t fb = BAR(IT_CKV + v * 2), sf = BAR(SF0 + v);
            uint32_t dlo = __reduce_or_sync(0xffffffffu, (((sb + SM_U + v * 16384) & 0x3FFFFu) >> 4) | 0x10000u);
            if (STAG && v) __nanosleep(STAG);
#pragma unroll 1
            for (int n = 0; n < NUNITS; n++) {
                float d[2][16], sc[8];
#pragma unroll
                for (int i = 0; i < 2; i++) {
                    mbar_wait(fb + i * 8, 0);
                    wg_fence();
#pragma unroll
                    for (int s = 0; s < 8; s++) wgmma_rs_n32(d[i], a[s], (0x40000080ull << 32) | (dlo + i * 512 + (s >> 2) * 64 + (s & 3) * 2), s);
                    wg_commit();
                }
#pragma unroll
                for (int i = 0; i < 2; i++) {
                    if (i) wg_wait0(); else wg_wait1();
#pragma unroll
                    for (int k = 0; k < 16; k++) asm volatile("" : "+f"(d[i][k]) :: "memory");
                    sc[4 * i] = d[i][0] + d[i][6]; sc[4 * i + 1] = d[i][1] + d[i][7]; sc[4 * i + 2] = d[i][8] + d[i][14]; sc[4 * i + 3] = d[i][9] + d[i][15];
                    asm volatile("st.async.weak.shared::cluster.mbarrier::complete_tx::bytes.v4.f32 [%0], {%1, %2, %3, %4}, [%5];"
                                 :: "r"(xr + i * 1024), "f"(sc[4 * i]), "f"(sc[4 * i + 1]), "f"(sc[4 * i + 2]), "f"(sc[4 * i + 3]), "r"(bsr) : "memory");
                }
                if (u8 == 128) TRACE_Q(56 + (n < 6 ? n : -40));
                if (n >= 3) mbar_wait(BAR(EB_UNIT0 + n - 3), 0);
                dlo += n == 5 ? -5 * 2048 : 2048;
                fb += 32; xr ^= 512; bsr += 16;
                pin(fb); pin(xr); pin(bsr);
                mbar_wait(sf, 0);
                const float4 x = ldsf4(xl), y = ldsf4(xl + 1024);
                sc[0] += x.x; sc[1] += x.y; sc[2] += x.z; sc[3] += x.w; sc[4] += y.x; sc[5] += y.y; sc[6] += y.z; sc[7] += y.w;
                float pr[8];
#pragma unroll
                for (int i = 0; i < 8; i++) pr[i] = ex2(sc[i] - m);
                float mx = fmaxf(fmaxf(fmaxf(sc[0], sc[1]), fmaxf(sc[2], sc[3])), fmaxf(fmaxf(sc[4], sc[5]), fmaxf(sc[6], sc[7])));
                if (__builtin_expect(__any_sync(0xffffffffu, mx > m), 0)) {
                    mx = fmaxf(mx, shx(mx, 1));
                    mx = fmaxf(mx, shx(mx, 2));
                    const float mn = fmaxf(m, ceilf(mx * 0.0625f) * 16.f);
                    l *= ex2(m - mn);
                    m = mn;
#pragma unroll
                    for (int i = 0; i < 8; i++) pr[i] = ex2(sc[i] - m);
                }
                stsf(ma, m);
                asm volatile("st.shared.v4.u32 [%0], {%1, %2, %3, %4};" :: "r"(pa), "r"(pack2(pr[0], pr[1])), "r"(pack2(pr[2], pr[3])),
                             "r"(pack2(pr[4], pr[5])), "r"(pack2(pr[6], pr[7])) : "memory");
                __syncwarp();
                if (lane == 0) mbar_arrive(sf + (PF0 - SF0) * 8);
                l += ((pr[0] + pr[1]) + (pr[2] + pr[3])) + ((pr[4] + pr[5]) + (pr[6] + pr[7]));
                xl ^= 512; sf += 16; ma += 256; pa += (n == 2 || n == 5) ? -8192 : 4096;
            }
            l += shx(l, 1);
            l += shx(l, 2);
            float2* mlx = (float2*)(sm + SM_MX + 2048) + wq4 * 8 + g;
            if (v == 0) { *mlx = make_float2(m, l); bar_arrive(11, 256); }
            else {
                mbar_wait(BAR(JD), 0);
                bar_sync(11, 256);
                const float2 o = *mlx;
                const float mn = fmaxf(m, o.x);
                l = l * ex2(m - mn) + o.y * ex2(o.x - mn);
                if ((wq4 >> 1) == rk) st_x4(gs + (B_ML + wq4 * 8 + g) * 4096 + (t >> 1) * 1024 + (j >> 1) * 8 + (t & 1) * 4, encf(mn), encf(l), 1u, 1u);
            }
        }
        const int pi = j < NFF ? rk * 128 + w8 * 16 + (lane >> 1) : ((j - J_RED) & 15) * 16 + (w8 & 1) * 8 + g;
        const uint32_t xw = *(const uint32_t*)(xin + 2 * pi);
        const uint32_t one = (g & 1) ? 0x3f800000u : 0x00003f80u;
        const uint32_t* pm = gs + near_off(B_MB, cls) + pi;
        {
            const uint32_t ab = sb + SM_U + B_WUV * 32768 + v * 4096 + a128;
            uint32_t pa = sb + SM_PB + wq4 * 320 + frag_off(64 * v + 32 * (g >> 2) + 16 * (t & 1) + 8 * (t >> 1) + 2 * (g & 3));
            uint32_t fa = sb + SM_PB + g * 320 + t * 16;
            const uint32_t* pe = gs + G_E1 + j * 8192 + (w8 >> 1) * 2048 + ((((cls >> 1) ^ (w8 >> 1)) & 1) << 10) + (((w8 & 1) * 16 + t) * 8 + g) * 4;
            uint32_t* p2 = gs + (B_E2 + (j >> 4)) * 4096 + (t >> 1) * 1024 + (j & 12) * 64 + w8 * 32 + (j & 3) * 8 + (g & 6) + (t & 1);
            pin(pa); pin(fa); pin(pe); pin(p2);
            const uint32_t mk = (g & 1) ? 0xffff0000u : 0x0000ffffu, m0 = (g & 2) ? 0u : mk, m1 = (g & 2) ? mk : 0u;
            uint4 pv[4];
            bool hv = false;
            bar_sync(3, 416);
            uint4 wa = lds128(sb + SM_W + (wq4 * 4 + t) * 16);
            uint32_t wb[8] = {wa.x & m0, wa.x & m1, wa.y & m0, wa.y & m1, wa.z & m0, wa.z & m1, wa.w & m0, wa.w & m1};
            pv[0] = pv[1] = pv[2] = pv[3] = make_uint4(0u, 0u, 0u, 0u);
            float e[4][4];
            auto wsum = [&]() {
#pragma unroll
                for (int i = 0; i < 4; i++) {
                    e[i][0] = e[i][1] = e[i][2] = e[i][3] = 0.f;
                    mma(e[i], pv[i].x, pv[i].y, pv[i].z, pv[i].w, wb[2 * i], wb[2 * i + 1]);
                }
            };
            poll<512, E1_SLEEP, true>(pv, pe, [&]() {
                if (!hv) {
                    hv = __all_sync(0xffffffffu, mbar_test(BAR(IT_WUV + t), 0));
                    if (hv) load8<true>(a, [&](int s) { return ab + (s >> 1) * 8192 + (s & 1) * 2048; });
                }
            }, wsum);
            if (lane == 0) TRACE_Q(48 + w8);
            if (u8 == 0) TRACE_Q(18);
            float lo, hi2;
            float2 inv;
#pragma unroll 1
            for (int pass = 0;; pass++) {
                const float r0 = (t & 2) ? (e[0][2] + e[1][2]) + (e[2][2] + e[3][2]) : (e[0][0] + e[1][0]) + (e[2][0] + e[3][0]);
                const float r1 = (t & 2) ? (e[0][3] + e[1][3]) + (e[2][3] + e[3][3]) : (e[0][1] + e[1][1]) + (e[2][1] + e[3][1]);
                const uint32_t hi = pack2(r0, r1);
                sts32(pa, hi); sts32(pa + 1280, pack2(r0 - bflo(hi), r1 - bfhi(hi)));
                if (!hv) {
#pragma unroll 1
                    for (int i = 0; i < 4; i++) mbar_wait(BAR(IT_WUV + i), 0);
                    load8<true>(a, [&](int s) { return ab + (s >> 1) * 8192 + (s & 1) * 2048; });
                    hv = true;
                }
                bar_sync(1, 256);
                if (u8 == 0) TRACE(19);
                ldfrag(b, fa);
                mma8(c, a, b);
                mbar_wait(BAR(WR), 0);
                asm volatile("ld.shared.v2.f32 {%0, %1}, [%2];" : "=f"(inv.x), "=f"(inv.y) : "r"(sb + SM_FQ) : "memory");
                quad_pair(c[0] + c[1], c[2] + c[3], t, lo, hi2);
                if (__builtin_expect(__all_sync(0xffffffffu, pass || __float_as_uint(inv.y) == 0), 1)) break;
                wa = lds128(sb + SM_W2 + (wq4 * 4 + t) * 16);
                wb[0] = wa.x & m0; wb[1] = wa.x & m1; wb[2] = wa.y & m0; wb[3] = wa.y & m1; wb[4] = wa.z & m0; wb[5] = wa.z & m1; wb[6] = wa.w & m0; wb[7] = wa.w & m1;
                wsum();
                bar_sync(1, 256);
            }
            if (!(g & 1)) st_x1(p2, enc(pack2(lo * inv.x, hi2 * inv.x)));
            bar_arrive(4, 416);
            if (u8 == 0) TRACE(20);
        }
        if (j < NFF) {
            const uint32_t* p3 = gs + near_off(B_E3 + rk * 2 + v, cls) + wq4 * 256 + t * 16 + g * 2;
            const int od = lane & 1;
            uint32_t za = sb + SM_FZ + od * 576 + frag_off(w8 * 32 + (lane & 30));
            uint32_t fa = sb + SM_FZ + (g & 3) * 576 + ((lane ^ j) & 16) * 16 + t * 16, ya = sb + SM_Y + u8 * 4;
            uint32_t mb[3];
            uint4 a2[8];
            poll<1024, MB_SLEEP>(mb, pm);
            const uint32_t kk = pack2(1.f + bflo(mb[2]), 1.f + bfhi(mb[2]));
            sts32(za + 2 * 576, od ? mb[1] : kk);
            uint2 e3[4] = {make_uint2(0u, 0u), make_uint2(0u, 0u), make_uint2(0u, 0u), make_uint2(0u, 0u)};
            uint32_t ra = peer_addr(sb + SM_RED + (rk * 2 + v) * 512 + ((wq4 & 1) * 16 + (t >> 1) * 8 + g) * 16 + (t & 1) * 8, wq4 >> 1), tbo = peer_addr(BAR(QB), wq4 >> 1);
            pin(za); pin(fa); pin(ya); pin(ra); pin(tbo);
            if (lane == 0) mbar_expect(BAR(QB), 256);
            const uint32_t gb = BAR(IT_X + v * 2), ab = sb + SM_U + (B_X + v) * 32768 + a128;
            bool early = false, early2 = false;
            auto ldw = [&]() {
                if (!early) {
                    early = __all_sync(0xffffffffu, mbar_test(gb, 0));
                    if (early) load8<true>(a, [&](int s) { return ab + s * 2048; });
                }
                if (!early2) {
                    early2 = __all_sync(0xffffffffu, mbar_test(gb + 8, 0));
                    if (early2) load8<true>(a2, [&](int s) { return ab + 16384 + s * 2048; });
                }
            };
            bar_sync(8, 384);
            float s0[4], s1[4];
            auto sum = [&]() {
                s0[0] = s0[1] = s0[2] = s0[3] = s1[0] = s1[1] = s1[2] = s1[3] = 0.f;
                mma(s0, e3[0].x, e3[0].y, e3[1].x, e3[1].y, one, one); mma(s1, e3[2].x, e3[2].y, e3[3].x, e3[3].y, one, one);
            };
            poll<256, 0, true>(e3, p3, ldw, sum);
            if (u8 == 0) TRACE(23);
            const float y0 = fmaf(bflo(mb[0]), (t & 2) ? s0[2] + s1[2] : s0[0] + s1[0], bflo(xw)), y1 = fmaf(bfhi(mb[0]), (t & 2) ? s0[3] + s1[3] : s0[1] + s1[1], bfhi(xw));
            stsf(ya, od ? y1 : y0);
            const float z0 = y0 * bflo(kk), z1 = y1 * bfhi(kk);
            const uint32_t zh = pack2(z0, z1);
            sts32(za, od ? pack2(z0 - bflo(zh), z1 - bfhi(zh)) : zh);
            bar_sync(7, 288);
            if (u8 == 0) TRACE(24);
            ldfrag(b, fa);
            if (!early) { mbar_wait(gb, 0); load8<true>(a, [&](int s) { return ab + s * 2048; }); }
            {
                float e[4][4];
#pragma unroll
                for (int s = 0; s < 16; s++) {
                    if (s == 8 && !early2) { mbar_wait(gb + 8, 0); load8<true>(a2, [&](int q) { return ab + 16384 + q * 2048; }); }
                    const uint4& x = s < 8 ? a[s] : a2[s & 7];
                    const uint4& y = b[(s >> 1) & 3];
                    float (&d)[4] = e[(s >> 3) * 2 + (s & 1)];
                    if (!(s & 6)) d[0] = d[1] = d[2] = d[3] = 0.f;
                    mma(d, x.x, x.y, x.z, x.w, (s & 1) ? y.z : y.x, (s & 1) ? y.w : y.y);
                }
                const bool hi = t >> 1;
                const float k0 = hi ? e[2][2] + e[3][2] : e[0][0] + e[1][0], k1 = hi ? e[2][3] + e[3][3] : e[0][1] + e[1][1];
                const float o0 = hi ? e[2][0] + e[3][0] : e[0][2] + e[1][2], o1 = hi ? e[2][1] + e[3][1] : e[0][3] + e[1][3];
                st_async2(ra, k0 + shx(o0, 2), k1 + shx(o1, 2), tbo);
            }
        } else if (j >= J_RED && j < J_END && w8 < 2) {
            uint32_t ga[1], e3[4];
            poll<0, MB_SLEEP>(ga, pm);
            bar_sync(8, 192);
            poll<64, 100>(e3, gs + near_off(B_E3 + (pi >> 6), cls) + (pi & 48) * 16 + t * 64 + (pi & 15));
            float y0 = (bflo(e3[0]) + bflo(e3[1])) + (bflo(e3[2]) + bflo(e3[3])), y1 = (bfhi(e3[0]) + bfhi(e3[1])) + (bfhi(e3[2]) + bfhi(e3[3]));
#pragma unroll
            for (int o = 1; o < 4; o <<= 1) { y0 += shx(y0, o); y1 += shx(y1, o); }
            const int col = g + (t & 1) * 8;
            y0 = __shfl_sync(0xffffffffu, (t & 1) ? fmaf(bfhi(ga[0]), y1, bfhi(xw)) : fmaf(bflo(ga[0]), y0, bflo(xw)), (col >> 1) * 4 + (col & 1));
            uint16_t* po = (uint16_t*)out + (j - J_RED) * 32 + w8 * 16 + col;
            const uint32_t* pe = gs + near_off(B_E5 + j - J_RED, cls) + t * 16 + w8 * 8 + g;
            pin(po);
            const uint32_t sel = (g & 2) ? 0x3f800000u : 0x00003f80u;
            uint32_t yv[NFF / 4 + 1];
            float e[4][4], gb = 0.f;
#pragma unroll
            for (int i = 0; i <= NFF / 4; i++) yv[i] = 0u;
#pragma unroll 1
            for (uint32_t it = 0;; it++) {
#pragma unroll
                for (int i = 0; i < NFF / 4; i++) if (!yv[i]) ld_x(yv[i], pe + i * 64);
                if (__all_sync(0xffffffffu, !yv[NFF / 4] && mbar_test(BAR(QB), 1))) {
                    yv[NFF / 4] = lds32(sb + SM_FV + 256 + w8 * 32 + (col >> 1) * 4);
                    gb = (col & 1) ? bfhi(yv[NFF / 4]) : bflo(yv[NFF / 4]);
                }
                if (it > SPIN_LIMIT) __trap();
#pragma unroll
                for (int i = 0; i < 4; i++) {
                    e[i][0] = e[i][1] = e[i][2] = e[i][3] = 0.f;
                    mma(e[i], yv[4 * i], yv[4 * i + 1], i < 3 ? yv[(4 * i + 2) % (NFF / 4)] : 0u, i < 3 ? yv[(4 * i + 3) % (NFF / 4)] : 0u, sel, sel);
                }
                if (__all_sync(0xffffffffu, mint<NFF / 4 + 1>(yv) != 0)) break;
            }
            if (u8 == 0) TRACE(26);
            const float s = ((e[0][0] + e[0][2]) + (e[1][0] + e[1][2])) + ((e[2][0] + e[2][2]) + (e[3][0] + e[3][2]));
            asm volatile("{\n.reg .pred p;\nsetp.lt.u32 p, %2, 2;\n@p st.global.u16 [%0], %1;\n}" :: "l"(po), "h"((uint16_t)pack2(fmaf(gb, s, y0), 0.f)), "r"(t) : "memory");
            asm volatile("{\n.reg .pred p;\nsetp.eq.f32 p, %0, 0f7F7FFFFF;\n@p nanosleep.u32 0;\n}" :: "f"(((e[0][1] + e[0][3]) + (e[1][1] + e[1][3])) + ((e[2][1] + e[2][3]) + (e[3][1] + e[3][3]))));
            if (u8 == 0) TRACE(27);
        }
    }
}

typedef CUresult (*EncFn)(CUtensorMap*, CUtensorMapDataType, cuuint32_t, void*, const cuuint64_t*, const cuuint64_t*,
                          const cuuint32_t*, const cuuint32_t*, CUtensorMapInterleave, CUtensorMapSwizzle,
                          CUtensorMapL2promotion, CUtensorMapFloatOOBfill);

void make_map(EncFn enc_fn, CUtensorMap* m, const void* p, cuuint64_t d0, cuuint64_t d1, cuuint64_t d2, cuuint64_t d3,
              cuuint64_t s1, cuuint64_t s2, cuuint64_t s3, cuuint32_t b0, cuuint32_t b1, cuuint32_t b2, cuuint32_t b3, CUtensorMapSwizzle sw) {
    const cuuint64_t dims[4] = {d0, d1, d2, d3}, strides[3] = {s1, s2, s3};
    const cuuint32_t box[4] = {b0, b1, b2, b3}, es[4] = {1, 1, 1, 1};
    enc_fn(m, CU_TENSOR_MAP_DATA_TYPE_BFLOAT16, 4, (void*)p, dims, strides, box, es,
           CU_TENSOR_MAP_INTERLEAVE_NONE, sw, PROMO, CU_TENSOR_MAP_FLOAT_OOB_FILL_NONE);
}

uint32_t* scratch = nullptr;

struct Tune { const char* win; const char* late; int tau, t_off; const char* tail[3][4]; };
Tune tune = {"66666666655555555555555555555555555533333",
             "00000000000000000000999999999999999999999", 320, -300,
             {{"VVVVOOOOguguDDDD", "zzzzzzzzzzzzzzzz", "888899998888789a", "ibbb0gjj7aaa3787"},
              {"VMVMVVOOOO", "zzzzzzzzzz", "8888889999", "588888kbbb"},
              {"VVVVOOOOMM", "zzzzzzzzzz", "aaaaaaaa88", "q8880cjjon"}}};
bool ready = false;

}

extern "C" void kernel_launch(void* const* d_in, const int* in_sizes, int n_in, void* d_out, int out_size) {
    (void)in_sizes; (void)n_in; (void)out_size;
    static Maps maps;
    static const void* cached[12] = {};
    bool same = ready;
    for (int i = 0; i < 12 && same; i++) same = cached[i] == d_in[i];
    if (!same) {
        void* fn = nullptr;
        cudaDriverEntryPointQueryResult qr;
        cudaGetDriverEntryPoint("cuTensorMapEncodeTiled", &fn, cudaEnableDefault, &qr);
        EncFn e = (EncFn)fn;
        const CUtensorMapSwizzle S128 = CU_TENSOR_MAP_SWIZZLE_128B;
        make_map(e, &maps.m[MP_WQ], d_in[2], 64, 512, 64, 1, 8192, 128, 8192, 64, 64, 1, 1, S128);
        make_map(e, &maps.m[MP_WUK], d_in[3], 64, 512, 64, 1, 8192, 128, 8192, 64, 64, 1, 1, S128);
        make_map(e, &maps.m[MP_CKV], d_in[1], 64, 8, 8, 4096, 1024, 128, 8192, 64, 8, 4, 2, S128);
        make_map(e, &maps.m[MP_MODB], d_in[11], 3072, 512, 1, 1, 6144, 6144, 6144, 64, 128, 1, 1, S128);
        make_map(e, &maps.m[MP_WUV], d_in[4], 64, 512, 64, 1, 8192, 128, 8192, 64, 32, 2, 1, S128);
        make_map(e, &maps.m[MP_WO], d_in[5], 512, 4096, 1, 1, 1024, 1024, 1024, 64, 64, 1, 1, S128);
        make_map(e, &maps.m[MP_GATE], d_in[7], 1792, 512, 1, 1, 3584, 3584, 3584, 64, 128, 1, 1, S128);
        make_map(e, &maps.m[MP_UP], d_in[8], 1792, 512, 1, 1, 3584, 3584, 3584, 64, 128, 1, 1, S128);
        make_map(e, &maps.m[MP_DOWN], d_in[9], 64, 1792, 8, 1, 1024, 128, 1024, 64, 32, 2, 1, S128);
        for (int r = 0; r < 3; r++) {
            int ids[58], cnt[128] = {}, tn = tune.t_off - (W0 - 1) * tune.tau;
            uint2* sc = maps.sched[r];
            auto dig = [](char ch) { return ch >= 'a' ? ch - 'a' + 10 : ch >= 'A' ? ch - 'A' + 36 : ch - '0'; };
            for (int i = 0; i < 58; i++) sc[i] = make_uint2(0u, 0u);
            for (int i = 0;; i++) {
                int id = i, buf, dep, w, wl;
                if (i < IT_WUV) {
                    const int u = (i - IT_CKV) >> 2;
                    buf = i < IT_CKV ? 4 + ((i - 1) >> 2) : u % 6;
                    dep = i < IT_CKV || u < 4 ? -1 : u < 6 ? EB_WQ + u - 4 : EB_UNIT0 + u - 6;
                    w = dig(tune.win[i]); wl = dig(tune.late[i]);
                    if (i) tn += tune.tau;
                } else {
                    const char ch = tune.tail[r][0][i - IT_WUV];
                    if (!ch) break;
                    buf = ch == 'V' ? B_WUV : ch == 'O' ? B_WO : ch == 'D' ? B_DN : ch == 'u' ? B_X + 1 : B_X;
                    id = (ch == 'V' ? IT_WUV : ch == 'O' ? IT_WO : ch == 'D' ? IT_DOWN : ch == 'u' ? IT_X + 2 : IT_X) + cnt[(int)ch]++;
                    dep = EB_UNIT0 + (buf < 2 ? buf + 6 : buf);
                    w = dig(tune.tail[r][1][i - IT_WUV]); wl = dig(tune.tail[r][2][i - IT_WUV]);
                    tn += 32 * dig(tune.tail[r][3][i - IT_WUV]);
                }
                if (id < IT_X || id >= IT_DOWN ? (id - 1) & 3 : (id - IT_X) & 1) dep = -1;
                ids[i] = id;
                auto back = [&](int d) { return i < d ? 0 : (ids[i - d] && ids[i - d] <= NCP ? 1 : ids[i - d]) + 1; };
                sc[i].x = id | (buf * 4 + (id < IT_X || id >= IT_DOWN ? (id - 1) & 3 : ((id - IT_X) & 1) * 2)) << 6 | (dep + 1) << 11 | (w > 32 ? NEVER + 1 : back(w)) << 18 | (wl ? back(wl) : 0) << 25;
                const int mp = id < IT_CKV ? MP_WQ + ((id - 1) >> 2) : id < IT_WUV ? MP_CKV : id < IT_WO ? MP_WUV : id < IT_X ? MP_WO
                             : id >= IT_DOWN ? MP_DOWN : r ? MP_MODB : MP_GATE + ((id - IT_X) >> 1);
                const int step = mp == MP_CKV ? id - IT_CKV : mp == MP_WUV ? (id - IT_WUV) * 2 : mp == MP_DOWN ? id - IT_DOWN : id < IT_X ? (id - 1) & 3 : ((id - IT_X) & 1) * 2;
                sc[i].y = (tn & 0xffff) | (mp & 15) << 16 | step << 20;
            }
        }
        cudaGetSymbolAddress((void**)&scratch, g_scratch);
        scratch = (uint32_t*)(((uintptr_t)scratch + (2u << 20) - 1) & ~(uintptr_t)((2u << 20) - 1));
        cudaFuncSetAttribute(fused_kernel, cudaFuncAttributeMaxDynamicSharedMemorySize, SM_TOTAL);
        for (int i = 0; i < 12; i++) cached[i] = d_in[i];
        ready = true;
    }
    const First f = {{(const uint8_t*)d_in[2], (const uint8_t*)d_in[11]}, {(const __nv_bfloat16*)d_in[0], (const __nv_bfloat16*)d_in[10]}};
    fused_kernel<<<NCTA, NTHREADS, SM_TOTAL>>>(f, (__nv_bfloat16*)d_out, scratch, maps);
}
```

```cpp
#include <cuda_runtime.h>
#include <cuda_bf16.h>
#include <cuda.h>
#include <stdint.h>
#include <limits.h>

namespace {

constexpr int NCTA = 128;
constexpr int NTHREADS = 512;
constexpr int NUNITS = 8;
constexpr int NFF = 56, J_RED = 104, J_END = 120;
constexpr uint32_t SPIN_LIMIT = 1u << 22;

#define PROMO CU_TENSOR_MAP_L2_PROMOTION_L2_64B
#define NEAR_CLK 390
#define E1_EARLY 50
#define STAG 300
#define NUMA 1
#define NPROBE 5
#define NCP 2
#define W0 4
#define RD_ITEM 15
#define JAN_SLEEP 100
#define RD_SLEEP 400
#define HA_DELAY 200
#define H_SLEEP 100
#define QA_DELAY 600
#define QA_SLEEP 200
#define ML_DELAY 300
#define E1_SLEEP 50
#define MB_SLEEP 100
constexpr int B_WUV = 2, B_WO = 3, B_X = 4  , B_DN = 0;

constexpr int SM_U = 0;
constexpr int SM_XA = 6 * 32768;
constexpr int SM_XB = SM_XA + 12288;
constexpr int SM_MX = SM_XB + 16384;
constexpr int SM_FZ = SM_XB + 8192;
constexpr int SM_PB = SM_XB;
constexpr int SM_Y = SM_XB + 12288;
constexpr int SM_RED = SM_XB + 4096;
constexpr int SM_FS = SM_XB + 20480;
constexpr int SM_FV = SM_FS + 1024;
constexpr int SM_QX = SM_XA + 8192;
constexpr int SM_FQ = SM_FV + 512;
constexpr int SM_CLS = SM_FQ + 128;
constexpr int SM_W = SM_FQ + 256;
constexpr int SM_W2 = SM_MX + 2304;
constexpr int SM_SCR = SM_XA + 9216;
constexpr int SM_TR = SM_XB + 19456;
constexpr int SM_BAR = SM_W + 256;
constexpr int SM_TOTAL = SM_BAR + 1024;
static_assert(SM_TOTAL <= 232448, "smem");

enum { IT_MODA = 0, IT_WQ = 1, IT_WUK = 5, IT_CKV = 9, IT_WUV = 41, IT_WO = 45, IT_X = 49  , IT_DOWN = 53, NITEMS = 57,
       NEVER = 63,
       SF0 = 64,
       PF0 = 80,
       EB_UNIT0 = 96, MBB = 103,
       EB_WQ = 104, EB_WUK, QT, QB, JD, WR };

enum { MP_WQ = 0, MP_WUK, MP_CKV, MP_WUV, MP_DOWN, MP_WO, MP_GATE, MP_UP, MP_MODB, NMAPS };
struct First { const uint8_t* w[2]; const __nv_bfloat16* v[2]; };
struct Maps { CUtensorMap m[NMAPS]; uint2 sched[3][58]; };

enum { B_HA = 0,
       B_MB = 6,
       B_RD = 7,
       B_E2 = 8,
       B_QA = 16,
       B_ML = 32,
       B_E5 = 64,
       B_E3 = 80,
       B_PR = 96,
       B_TR = 100 };
constexpr int G_E1 = 1 << 19;
constexpr int G_TR = B_TR * 4096;
__device__ __align__(1024) uint32_t g_scratch[(8 << 20) / 4];

#define TRACE(slot) do {} while (0)
#define TRACE_Q(slot) do {} while (0)
#define TRACE_GT(slot) do {} while (0)

__device__ __forceinline__ uint32_t s2u(const void* p) { return (uint32_t)__cvta_generic_to_shared(p); }
__device__ __forceinline__ void mbar_init(uint32_t b, int c) { asm volatile("mbarrier.init.shared::cta.b64 [%0], %1;" :: "r"(b), "r"(c) : "memory"); }
__device__ __forceinline__ void mbar_expect(uint32_t b, uint32_t bytes) { asm volatile("mbarrier.arrive.expect_tx.shared::cta.b64 _, [%0], %1;" :: "r"(b), "r"(bytes) : "memory"); }
__device__ __forceinline__ void mbar_arrive(uint32_t b) { asm volatile("mbarrier.arrive.shared::cta.b64 _, [%0];" :: "r"(b) : "memory"); }
__device__ __forceinline__ void mbar_wait(uint32_t b, uint32_t ph) {
    asm volatile("{\n.reg .pred p;\nW: mbarrier.try_wait.parity.shared::cta.b64 p, [%0], %1;\n@!p bra W;\n}" :: "r"(b), "r"(ph) : "memory");
}
__device__ __forceinline__ void mbar_waitb(uint32_t b, uint32_t ph) {
    asm volatile("{\n.reg .pred p;\n.reg .u32 n;\nmov.u32 n, 0;\n"
                 "W: mbarrier.try_wait.parity.shared::cta.b64 p, [%0], %1;\n@p bra D;\n"
                 "add.u32 n, n, 1;\nsetp.lt.u32 p, n, 0x100000;\n@p bra W;\ntrap;\nD:\n}" :: "r"(b), "r"(ph) : "memory");
}
__device__ __forceinline__ uint32_t mbar_test(uint32_t b, uint32_t ph) {
    uint32_t ok;
    asm volatile("{\n.reg .pred p;\nmbarrier.test_wait.parity.shared::cta.b64 p, [%1], %2;\nselp.u32 %0, 1, 0, p;\n}" : "=r"(ok) : "r"(b), "r"(ph) : "memory");
    return ok;
}
__device__ __forceinline__ void bar_sync(int id, int n) { asm volatile("bar.sync %0, %1;" :: "r"(id), "r"(n) : "memory"); }
__device__ __forceinline__ void bar_arrive(int id, int n) { asm volatile("bar.arrive %0, %1;" :: "r"(id), "r"(n) : "memory"); }
__device__ __forceinline__ uint32_t peer_addr(uint32_t a, uint32_t rank) { uint32_t r; asm("mapa.shared::cluster.u32 %0, %1, %2;" : "=r"(r) : "r"(a), "r"(rank)); return r; }
__device__ __forceinline__ void st_async2(uint32_t a, float x, float y, uint32_t bar) {
    asm volatile("st.async.weak.shared::cluster.mbarrier::complete_tx::bytes.v2.f32 [%0], {%1, %2}, [%3];" :: "r"(a), "f"(x), "f"(y), "r"(bar) : "memory");
}
__device__ __forceinline__ uint32_t gtime() { uint32_t t; asm volatile("mov.u32 %0, %%globaltimer_lo;" : "=r"(t)); return t; }
__device__ __forceinline__ void fence_gpu() { asm volatile("fence.acq_rel.gpu;" ::: "memory"); }

__device__ __forceinline__ uint32_t enc(uint32_t b) { uint32_t r; asm("max.u32 %0, %1, 1;" : "=r"(r) : "r"(b)); return r; }
__device__ __forceinline__ uint32_t encf(float f) { return enc(__float_as_uint(f)); }
__device__ __forceinline__ void st_x1(uint32_t* p, uint32_t v) { asm volatile("st.relaxed.gpu.global.u32 [%0], %1;" :: "l"(p), "r"(v) : "memory"); }
__device__ __forceinline__ void st_x4(void* p, uint32_t a, uint32_t b, uint32_t c, uint32_t d) {
    asm volatile("st.relaxed.gpu.global.v4.u32 [%0], {%1, %2, %3, %4};" :: "l"(p), "r"(a), "r"(b), "r"(c), "r"(d) : "memory");
}
__device__ __forceinline__ void st2_x1(uint32_t* p, uint32_t v) { st_x1(p, v); st_x1(p + 1024, v); }
__device__ __forceinline__ void st2_x4(uint32_t* p, uint32_t a, uint32_t b, uint32_t c, uint32_t d) { st_x4(p, a, b, c, d); st_x4(p + 1024, a, b, c, d); }
__device__ __forceinline__ int near_off(int b, uint32_t cls) { return b * 4096 + (((__popc(b & 0x2C) ^ cls) & 1) << 10); }
__device__ __forceinline__ void ld_x(uint32_t& v, const void* p) { asm volatile("ld.relaxed.gpu.global.u32 %0, [%1];" : "=r"(v) : "l"(p) : "memory"); }
__device__ __forceinline__ void ld_x(uint4& v, const void* p) {
    asm volatile("ld.relaxed.gpu.global.v4.u32 {%0, %1, %2, %3}, [%4];" : "=r"(v.x), "=r"(v.y), "=r"(v.z), "=r"(v.w) : "l"(p) : "memory");
}
__device__ __forceinline__ void ld_x(uint2& v, const void* p) { asm volatile("ld.relaxed.gpu.global.v2.u32 {%0, %1}, [%2];" : "=r"(v.x), "=r"(v.y) : "l"(p) : "memory"); }
__device__ __forceinline__ uint32_t minw(uint32_t v) { return v; }
__device__ __forceinline__ uint32_t minw(const uint2& v) { return min(v.x, v.y); }
__device__ __forceinline__ uint32_t minw(const uint4& v) { return min(__vimin3_u32(v.x, v.y, v.z), v.w); }
template <int N> __device__ __forceinline__ uint32_t mint(const uint32_t* m) {
    if constexpr (N == 1) return m[0];
    else if constexpr (N == 2) return min(m[0], m[1]);
    else return __vimin3_u32(mint<(N + 2) / 3>(m), mint<(N + 1) / 3>(m + (N + 2) / 3), mint<N / 3>(m + (N + 2) / 3 + (N + 1) / 3));
}

template <int STRIDE, int S4 = 4 * STRIDE, typename T, int N>
__device__ __forceinline__ void poll_start(T (&v)[N], const void* base) {
#pragma unroll
    for (int i = 0; i < N; i++) ld_x(v[i], (const uint8_t*)base + (i & 3) * STRIDE + (i >> 2) * S4);
}
struct Nop { __device__ void operator()() const {} };
template <int STRIDE, int SLEEP, bool STARTED = false, int S4 = 4 * STRIDE, typename T, int N, typename F = Nop, typename G = Nop>
__device__ __forceinline__ void poll(T (&v)[N], const void* base, F idle = F(), G ahead = G()) {
    if (!STARTED) { poll_start<STRIDE, S4>(v, base); idle(); }
#pragma unroll 1
    for (uint32_t it = 0;; it++) {
        uint32_t m[N];
        ahead();
#pragma unroll
        for (int i = 0; i < N; i++) m[i] = minw(v[i]);
        if (__all_sync(0xffffffffu, mint<N>(m) != 0)) break;
        if (SLEEP && it > 0) __nanosleep(SLEEP);
#pragma unroll
        for (int i = 0; i < N; i++) if (!m[i]) ld_x(v[i], (const uint8_t*)base + (i & 3) * STRIDE + (i >> 2) * S4);
        idle();
        if (it > SPIN_LIMIT) __trap();
    }
}

__device__ __forceinline__ float bflo(uint32_t w) { return __uint_as_float(w << 16); }
__device__ __forceinline__ float bfhi(uint32_t w) { return __uint_as_float(w & 0xffff0000u); }
__device__ __forceinline__ uint32_t pack2(float lo, float hi) {
    uint32_t r; asm("cvt.rn.bf16x2.f32 %0, %1, %2;" : "=r"(r) : "f"(hi), "f"(lo)); return r;
}
__device__ __forceinline__ float rbf(float x) { return __uint_as_float(pack2(0.f, x)); }
__device__ __forceinline__ float ex2(float x) { float r; asm("ex2.approx.ftz.f32 %0, %1;" : "=f"(r) : "f"(x)); return r; }
__device__ __forceinline__ float shx(float v, int m) { return __shfl_xor_sync(0xffffffffu, v, m); }
__device__ __forceinline__ uint4 lds128(uint32_t a) { uint4 v; asm volatile("ld.shared.v4.u32 {%0, %1, %2, %3}, [%4];" : "=r"(v.x), "=r"(v.y), "=r"(v.z), "=r"(v.w) : "r"(a) : "memory"); return v; }
__device__ __forceinline__ uint32_t lds32(uint32_t a) { uint32_t v; asm volatile("ld.shared.u32 %0, [%1];" : "=r"(v) : "r"(a) : "memory"); return v; }
__device__ __forceinline__ void sts32(uint32_t a, uint32_t v) { asm volatile("st.shared.u32 [%0], %1;" :: "r"(a), "r"(v) : "memory"); }
__device__ __forceinline__ void sts16(uint32_t a, uint32_t v) { asm volatile("st.shared.u16 [%0], %1;" :: "r"(a), "h"((uint16_t)v) : "memory"); }
__device__ __forceinline__ int frag_off(int k) { return (k >> 5) * 64 + ((k >> 1) & 3) * 16 + ((k >> 4) & 1) * 8 + ((k >> 3) & 1) * 4 + (k & 1) * 2; }

template <bool TRANS>
__device__ __forceinline__ uint4 ldsm(uint32_t a) {
    uint4 r;
    if (TRANS) asm volatile("ldmatrix.sync.aligned.m8n8.x4.trans.shared.b16 {%0, %1, %2, %3}, [%4];" : "=r"(r.x), "=r"(r.y), "=r"(r.z), "=r"(r.w) : "r"(a) : "memory");
    else asm volatile("ldmatrix.sync.aligned.m8n8.x4.shared.b16 {%0, %1, %2, %3}, [%4];" : "=r"(r.x), "=r"(r.y), "=r"(r.z), "=r"(r.w) : "r"(a) : "memory");
    return r;
}
__device__ __forceinline__ void mma(float (&c)[4], uint32_t a0, uint32_t a1, uint32_t a2, uint32_t a3, uint32_t b0, uint32_t b1) {
    asm volatile("mma.sync.aligned.m16n8k16.row.col.f32.bf16.bf16.f32 {%0,%1,%2,%3}, {%4,%5,%6,%7}, {%8,%9}, {%0,%1,%2,%3};"
                 : "+f"(c[0]), "+f"(c[1]), "+f"(c[2]), "+f"(c[3]) : "r"(a0), "r"(a1), "r"(a2), "r"(a3), "r"(b0), "r"(b1));
}
template <bool TRANS, typename F>
__device__ __forceinline__ void load8(uint4 (&a)[8], F addr) {
    __syncwarp();
#pragma unroll
    for (int s = 0; s < 8; s++) a[s] = ldsm<TRANS>(addr(s));
}
__device__ __forceinline__ void mma8(float (&c)[4], const uint4 (&a)[8], const uint4 (&b)[4]) {
    float e[4][4];
#pragma unroll
    for (int s = 0; s < 8; s++) {
        if (s < 4) e[s][0] = e[s][1] = e[s][2] = e[s][3] = 0.f;
        mma(e[s & 3], a[s].x, a[s].y, a[s].z, a[s].w, (s & 1) ? b[s >> 1].z : b[s >> 1].x, (s & 1) ? b[s >> 1].w : b[s >> 1].y);
    }
#pragma unroll
    for (int i = 0; i < 4; i++) c[i] = (e[0][i] + e[1][i]) + (e[2][i] + e[3][i]);
}
__device__ __forceinline__ void ldfrag(uint4 (&b)[4], uint32_t a) {
    asm volatile("ld.shared.v4.u32 {%0,%1,%2,%3}, [%16];\nld.shared.v4.u32 {%4,%5,%6,%7}, [%16+64];\n"
                 "ld.shared.v4.u32 {%8,%9,%10,%11}, [%16+128];\nld.shared.v4.u32 {%12,%13,%14,%15}, [%16+192];\n"
                 : "=r"(b[0].x), "=r"(b[0].y), "=r"(b[0].z), "=r"(b[0].w), "=r"(b[1].x), "=r"(b[1].y), "=r"(b[1].z), "=r"(b[1].w),
                   "=r"(b[2].x), "=r"(b[2].y), "=r"(b[2].z), "=r"(b[2].w), "=r"(b[3].x), "=r"(b[3].y), "=r"(b[3].z), "=r"(b[3].w) : "r"(a) : "memory");
}
__device__ __forceinline__ void quad_pair(float x, float y, int t, float& lo, float& hi) {
    const float k = ((t & 1) ? y : x) + shx((t & 1) ? x : y, 1);
    lo = k + shx(k, 2); hi = shx(k, 4) + shx(k, 6);
}
__device__ __forceinline__ void pin(uint32_t& x) { asm volatile("" : "+r"(x)); }
template <typename T> __device__ __forceinline__ void pin(T*& x) { asm volatile("" : "+l"(x)); }
__device__ __forceinline__ float4 ldsf4(uint32_t a) { const uint4 v = lds128(a); return make_float4(__uint_as_float(v.x), __uint_as_float(v.y), __uint_as_float(v.z), __uint_as_float(v.w)); }
__device__ __forceinline__ float sum4(const float4& f) { return (f.x + f.y) + (f.z + f.w); }
__device__ __forceinline__ void stsf(uint32_t a, float v) { sts32(a, __float_as_uint(v)); }

__device__ __forceinline__ void wg_fence() { asm volatile("wgmma.fence.sync.aligned;" ::: "memory"); }
__device__ __forceinline__ void wg_commit() { asm volatile("wgmma.commit_group.sync.aligned;" ::: "memory"); }
__device__ __forceinline__ void wg_wait1() { asm volatile("wgmma.wait_group.sync.aligned 1;" ::: "memory"); }
__device__ __forceinline__ void wg_wait0() { asm volatile("wgmma.wait_group.sync.aligned 0;" ::: "memory"); }
#define R8(o) "+f"(d[o]), "+f"(d[o + 1]), "+f"(d[o + 2]), "+f"(d[o + 3]), "+f"(d[o + 4]), "+f"(d[o + 5]), "+f"(d[o + 6]), "+f"(d[o + 7])
__device__ __forceinline__ void wgmma_rs_n32(float (&d)[16], const uint4& a, uint64_t db, int acc) {
    asm volatile("{\n.reg .pred p;\nsetp.ne.b32 p, %21, 0;\n"
        "wgmma.mma_async.sync.aligned.m64n32k16.f32.bf16.bf16 "
        "{%0,%1,%2,%3,%4,%5,%6,%7,%8,%9,%10,%11,%12,%13,%14,%15}, {%16,%17,%18,%19}, %20, p, 1, 1, 0;\n}"
        : R8(0), R8(8) : "r"(a.x), "r"(a.y), "r"(a.z), "r"(a.w), "l"(db), "r"(acc));
}
#define PV_LO "{%0,%1,%2,%3,%4,%5,%6,%7,%8,%9,%10,%11,%12,%13,%14,%15,%16,%17,%18,%19,%20,%21,%22,%23,%24,%25,%26,%27,%28,%29,%30,%31,%32,%33,%34,%35,%36,%37,%38,%39,%40,%41,%42,%43,%44,%45,%46,%47,%48,%49,%50,%51,%52,%53,%54,%55,%56,%57,%58,%59,%60,%61,%62,%63}, "
#define PV_HI "{%64,%65,%66,%67,%68,%69,%70,%71,%72,%73,%74,%75,%76,%77,%78,%79,%80,%81,%82,%83,%84,%85,%86,%87,%88,%89,%90,%91,%92,%93,%94,%95,%96,%97,%98,%99,%100,%101,%102,%103,%104,%105,%106,%107,%108,%109,%110,%111,%112,%113,%114,%115,%116,%117,%118,%119,%120,%121,%122,%123,%124,%125,%126,%127}, "
__device__ __forceinline__ void wgmma_pv(float (&d)[128], const uint4& a, uint32_t blo, int acc) {
    asm volatile("{\n.reg .pred p;\n.reg .b32 u0, u1, u2, u3, t;\n.reg .b64 d0, d1, d2, d3;\nsetp.ne.b32 p, %133, 0;\n"
        "mov.b64 d0, {%132, 0x40000100};\nadd.u32 t, %132, 512;\nmov.b64 d1, {t, 0x40000100};\n"
        "add.u32 t, %132, 128;\nmov.b64 d2, {t, 0x40000100};\nadd.u32 t, %132, 640;\nmov.b64 d3, {t, 0x40000100};\n"
        "wgmma.fence.sync.aligned;\n"
        "wgmma.mma_async.sync.aligned.m64n128k16.f32.bf16.bf16 " PV_LO "{%128, u0, %129, u1}, d0, p, 1, 1, 1;\n"
        "wgmma.mma_async.sync.aligned.m64n128k16.f32.bf16.bf16 " PV_LO "{%130, u2, %131, u3}, d1, 1, 1, 1, 1;\n"
        "wgmma.commit_group.sync.aligned;\n"
        "wgmma.mma_async.sync.aligned.m64n128k16.f32.bf16.bf16 " PV_HI "{%128, u0, %129, u1}, d2, p, 1, 1, 1;\n"
        "wgmma.mma_async.sync.aligned.m64n128k16.f32.bf16.bf16 " PV_HI "{%130, u2, %131, u3}, d3, 1, 1, 1, 1;\n"
        "wgmma.commit_group.sync.aligned;\n}"
        : R8(0), R8(8), R8(16), R8(24), R8(32), R8(40), R8(48), R8(56), R8(64), R8(72), R8(80), R8(88), R8(96), R8(104), R8(112), R8(120)
        : "r"(a.x), "r"(a.y), "r"(a.z), "r"(a.w), "r"(blo), "r"(acc) : "memory");
}

template <int NW>
__device__ __forceinline__ void ln_stats(float s, float q, float sh, float* scr, int w, int lane, int bar, float& mean_b, float& sd_b) {
#pragma unroll
    for (int o = 16; o; o >>= 1) { s += shx(s, o); q += shx(q, o); }
    constexpr float n = 512.f / NW;
    if (lane == 0) { scr[w] = sh + s * (1.f / n); scr[NW + w] = q - s * s * (1.f / n); }
    bar_sync(bar, NW * 32);
    float mu = 0.f, m2 = 0.f;
#pragma unroll
    for (int i = 0; i < NW; i++) { mu += scr[i]; m2 += scr[NW + i]; }
    mu *= 1.f / NW;
#pragma unroll
    for (int i = 0; i < NW; i++) { const float d = scr[i] - mu; m2 = fmaf(n * d, d, m2); }
    mean_b = rbf(mu);
    sd_b = rbf(sqrtf(rbf(rbf(fmaxf(m2, 0.f) * (1.f / 512.f)) + 1e-5f)));
}
__device__ __forceinline__ float ln_mod(float x, float mean_b, float sd_b, float c, float s) {
    return rbf(rbf(__fdividef(rbf(x - mean_b), sd_b)) * rbf(1.f + c)) + s;
}

__global__ void __cluster_dims__(2, 1, 1) __launch_bounds__(NTHREADS, 1)
fused_kernel(const __grid_constant__ First F, __nv_bfloat16* __restrict__ out, uint32_t* __restrict__ gs, const __grid_constant__ Maps M) {
    extern __shared__ __align__(1024) uint8_t sm[];
    const uint32_t sb = s2u(sm);
    const int tid = threadIdx.x, lane = tid & 31;
    const int j = blockIdx.x, rk = j & 1;
    const int g = lane >> 2, t = lane & 3;
    const int r8 = lane & 7, lb3 = (lane >> 3) & 1, lb4 = lane >> 4;
    uint64_t pol;
    asm("createpolicy.fractional.L2::evict_first.b64 %0, 1.0;" : "=l"(pol));
    {
        auto cpa = [&](uint32_t d, const uint8_t* s) {
            asm volatile("cp.async.cg.shared.global.L2::cache_hint.L2::128B [%0], [%1], 16, %2;" :: "r"(d), "l"(s), "l"(pol) : "memory");
        };
        const uint32_t ut = threadIdx.x, uj = blockIdx.x;
        const uint8_t* w = F.w[ut >= 128];
        if (ut < 128) {
            const uint32_t dq = (sb + ut * 16) ^ ((ut * 2) & 0x70);
            const uint8_t* sq = w + (uint32_t)(((uj & 1) * 256 + (ut >> 3)) * 8192 + (uj >> 1) * 128 + (ut & 7) * 16);
#pragma unroll
            for (int i = 0; i < 4 * NCP; i++) cpa(dq + 4 * 32768 + i * 2048, sq + i * 131072);
        } else if (ut < 384) {
            const uint32_t dm = (sb + ut * 16) ^ ((ut * 2) & 0x10);
            const uint8_t* sa = w + (uint32_t)(((uj >> 5) * 128 + (ut >> 1) - 64) * 6144 + (uj & 31) * 32 + (ut & 1) * 16);
            cpa(dm + SM_XA - 2048, sa); cpa(dm + SM_XA + 2048, sa + 1024);
        }
        else if (ut == 480 && uj < 64) asm volatile("prefetch.global.L2 [%0];" :: "l"(F.v[(uj >> 3) & 1] + (uj & 7) * 64));
    }
    const int warp = __shfl_sync(0xffffffffu, tid >> 5, 0);
    const __nv_bfloat16* const xin = F.v[0];
    uint32_t* const pl = gs + (warp < 2 ? (B_PR + (j >> 5)) * 4096 + (j & 31) * 32 : G_E1 + j * 8192) + (warp & 1) * 1024 + lane;
    if (warp < 4) st_x1(pl, 1u);
    auto BAR = [&](int i) -> uint32_t { return sb + SM_BAR + i * 8; };
    const uint32_t a16 = (r8 + 8 * lb4) * 32 + ((lb3 ^ (r8 >> 2)) * 16);
    const uint32_t a128 = (r8 + 8 * lb4) * 128 + ((((warp & 3) * 2 + lb3) ^ r8) * 16);
    auto ldcls = [&]() -> uint32_t { return *(const volatile uint32_t*)(sm + SM_CLS); };
    auto clear_head = [&]() {
        st2_x1(gs + (B_HA + ((j >> 4) & 1) * 2 + lb4) * 4096 + (j >> 5) * 256 + (j & 15) * 16 + (lane & 15), 0u);
        st2_x4(gs + (B_QA + rk * 8 + ((j >> 1) & 1) * 4 + (j >> 5)) * 4096 + g * 128 + ((j >> 2) & 7) * 16 + t * 4, 0u, 0u, 0u, 0u);
        if (lane < 8) st2_x1(gs + B_RD * 4096 + j * 8 + lane, 0u);
    };
    auto tma = [&](uint32_t dst, const CUtensorMap* mp, uint32_t bar, int c0, int c1, int c2, int c3) {
        asm volatile("{\n.reg .pred p;\nelect.sync _|p, 0xffffffff;\n"
                     "@p cp.async.bulk.tensor.4d.shared::cluster.global.mbarrier::complete_tx::bytes.L2::cache_hint [%0], [%1, {%3, %4, %5, %6}], [%2], %7;\n}"
                     :: "r"(dst), "l"(mp), "r"(bar), "r"(c0), "r"(c1), "r"(c2), "r"(c3), "l"(pol) : "memory");
    };
    if (warp <= 12 || warp == 15) {
        const int grp = warp == 12 ? 0 : warp == 15 ? 13 : warp + 1;
        const uint32_t cnt = grp < 10 ? 1 : grp < 13 ? 4 : 8;
        if (lane == 0) {
#pragma unroll
            for (int i = 0; i < 8; i++) mbar_init(BAR(grp * 8 + i), (i < 2 && grp == 0) ? (i ? 128 : 256) : cnt);
        }
        __syncwarp();
        if (grp < 10 && lane < 8 && (grp || lane > NCP)) mbar_expect(BAR(grp * 8 + lane), grp >= 8 ? 4096 : (uint32_t)(grp * 8 + lane - IT_X) < 4 ? 16384 : 8192);
        asm volatile("fence.mbarrier_init.release.cluster;" ::: "memory");
        __syncwarp();
        if (warp == 12) {
#pragma unroll
            for (int i = NCP + 1; i < W0; i++) tma(sb + (15 + i) * 8192, &M.m[MP_WQ], BAR(i), 0, rk * 256 + (i - 1) * 64, j >> 1, 0);
        }
    } else if (warp == 13) {
        if (lane < NMAPS) asm volatile("prefetch.tensormap [%0];" :: "l"(&M.m[lane]) : "memory");
    } else if (warp == 14) {
        clear_head();
    }
    __syncthreads();
    uint32_t in1 = 0, in2 = 0;
    if (warp < 4) { in1 = *(const uint32_t*)(xin + 2 * tid); in2 = *(const uint32_t*)(xin + 256 + 2 * tid); }
    else if (warp < 12) in1 = *(const uint32_t*)(F.v[1] + 2 * (tid - 128));
    if (warp < 12) asm volatile("cp.async.mbarrier.arrive.noinc.shared::cta.b64 [%0];" :: "r"(BAR(warp < 4)) : "memory");
    asm volatile("barrier.cluster.arrive.relaxed.aligned;" ::: "memory");

    if (warp >= 12) {
    asm volatile("setmaxnreg.dec.sync.aligned.u32 64;");
    if (warp == 12) {
        static_assert(W0 > NCP && W0 <= 5 && NCP >= 1 && NCP <= 4, "W0");
        const uint2* sched = M.sched[j < NFF ? 0 : j < J_RED ? 1 : 2];
        uint2 en = sched[W0];
        const uint32_t t0 = gtime();
        const uint32_t sp = __reduce_or_sync(0xffffffffu, sb);
        const int cx = (j >> 1) * 64 + (j < NFF ? 0 : 1024 - NFF * 32);
#pragma unroll 1
        for (int i = W0; en.x; i++) {
            uint32_t e = en.x, st = (en.y >> 20) * 64;
            const uint32_t tn = t0 + (int16_t)en.y, mp = (en.y >> 16) & 15;
            if (mp == MP_WUV || mp == MP_WUK) { st ^= (j >> 5) * (mp == MP_WUV ? 128 : 64); e ^= (j >> 5) << 6; }
            if (mp == MP_GATE || mp == MP_UP) st ^= (j & 16) * 8;
            if (mp == MP_DOWN) { st ^= (j & 3) * 64; e ^= (j & 3) << 6; }
            en = sched[i + 1];
            if (mp == MP_MODB && j >= J_END) break;
            uint32_t c0 = mp == MP_WO ? (j & 7) * 64 : mp > MP_WO ? cx : 0;
            uint32_t c1 = mp == MP_CKV ? 0 : mp == MP_DOWN ? j * 32 : st + (mp == MP_WUV ? (j & 3) * 32 : mp == MP_WO ? (j >> 3) * 256 : rk * 256);
            uint32_t c2 = mp < MP_CKV ? j >> 1 : mp == MP_CKV ? rk * 4 : mp == MP_WUV ? (j >> 2) * 2 : mp == MP_DOWN ? st >> 5 : 0;
            uint32_t c3 = mp == MP_CKV ? st * 2 + (j & ~1) : 0;
            uint32_t dst = sp + ((e << 7) & 0x3e000), bar = sp + SM_BAR + (e & 63) * 8;
            const uint32_t w0 = (e >> 8) & 0x3f8, w1 = (e >> 15) & 0x3f8, w2 = (e >> 22) & 0x3f8, bb = sp + SM_BAR - 8;
            const CUtensorMap* pm = &M.m[mp];
            pin(dst); pin(bar); pin(c0); pin(c1); pin(c2); pin(c3); pin(pm);
            if (w0) mbar_wait(bb + w0, 0);
            if (w2) {
                mbar_wait(bb + w2, 0);
                while (!__any_sync(0xffffffffu, mbar_test(bb + w1, 0) | ((int)(gtime() - tn) > 0))) {}
            } else if (w1) mbar_wait(bb + w1, 0);
            tma(dst, pm, bar, c0, c1, c2, c3);
        }
    } else if (warp == 13) {
#pragma unroll
        for (int i = 0; i < 2; i++) st_x4(gs + (B_ML + rk * 16 + i * 8 + g) * 4096 + (t >> 1) * 1024 + (j >> 1) * 8 + (t & 1) * 4, 0u, 0u, 0u, 0u);
        if (lane < 16) st2_x4(gs + (B_E2 + (j >> 4)) * 4096 + (j & 15) * 64 + lane * 4, 0u, 0u, 0u, 0u);
        st2_x1(gs + (B_E3 + (j >> 5)) * 4096 + (j & 31) * 32 + lane, 0u);
        if (lane < 8) st2_x1(gs + B_MB * 4096 + j * 8 + lane, 0u);
        if (j < NFF) {
#pragma unroll
            for (int i = 0; i < 2; i++) st2_x4(gs + (B_E5 + i * 8 + g) * 4096 + j * 16 + t * 4, 0u, 0u, 0u, 0u);
        }
        bar_sync(9, 64);
        const uint32_t cs = ldcls();
#pragma unroll 1
        for (int i = 0; i < 32; i++) {
            st_x4(gs + G_E1 + j * 8192 + (i >> 3) * 2048 + ((((cs >> 1) ^ (i >> 3)) & 1) << 10) + (i & 7) * 128 + lane * 4, 0u, 0u, 0u, 0u);
            __nanosleep(JAN_SLEEP);
        }
        fence_gpu();
        if (lane < 8) st2_x1(gs + B_RD * 4096 + j * 8 + lane, 1u + (cs >> 1));
        if (lane == 0) TRACE(41);
        uint32_t rd[4];
        mbar_wait(BAR(IT_CKV + RD_ITEM), 0);
        poll<1024, RD_SLEEP>(rd, gs + near_off(B_RD, cs) + lane * 8);
#pragma unroll
        for (int i = 0; i < 4; i++) {
            const uint32_t m = __ballot_sync(0xffffffffu, rd[i] == 2u);
            if (lane == 0) sts32(sb + SM_CLS + 16 + i * 4, m);
        }
        __syncwarp();
        if (lane < 8) mbar_arrive(BAR(JD));
        if (lane == 0) TRACE(42);
    } else if (warp == 14) {
        uint2 ml[2];
        mbar_waitb(BAR(JD), 0);
        const uint32_t cls = ldcls();
        mbar_waitb(BAR(PF0 + 2 * NUNITS - 1), 0);
        __nanosleep(ML_DELAY);
        const uint32_t* pl2 = gs + near_off(B_ML + (j >> 2), cls) + lane * 8;
        const uint32_t wa = sb + SM_W + lb4 * 64 + t * 16 + (g & 3) * 4;
        poll_start<1024>(ml, pl2);
        uint32_t w0 = 0, w1 = 0, redo = 0;
        bool first = true;
#pragma unroll 1
        for (uint32_t it = 0;; it++) {
            const bool p0 = minw(ml[0]) != 0, p1 = minw(ml[1]) != 0;
            const int n = __popc(__ballot_sync(0xffffffffu, p0)) + __popc(__ballot_sync(0xffffffffu, p1));
            const uint32_t x0 = ml[0].x, x1 = ml[1].x;
            if (n < 64) {
                if (!p0) ld_x(ml[0], pl2);
                if (!p1) ld_x(ml[1], pl2 + 256);
            }
            if (n == 64 || (first && n >= E1_EARLY)) {
                auto ord = [](int x) { return x ^ ((x >> 31) & 0x7fffffff); };
                const int o0 = ord(x0), o1 = ord(x1);
                const float mm = __int_as_float(ord(__reduce_max_sync(0xffffffffu, max(p0 ? o0 : INT_MIN, p1 ? o1 : INT_MIN))));
                const float lo = __int_as_float(ord(__reduce_min_sync(0xffffffffu, min(p0 ? o0 : INT_MAX, p1 ? o1 : INT_MAX))));
                const uint32_t v0 = pack2(ex2((p0 ? __uint_as_float(x0) : lo) - mm), 0.f), v1 = pack2(ex2((p1 ? __uint_as_float(x1) : lo) - mm), 0.f);
                redo = !first && __any_sync(0xffffffffu, v0 != w0 || v1 != w1);
                w0 = v0; w1 = v1;
                sts32(wa - redo * (SM_W - SM_W2), w0 * 0x10001u); sts32(wa - redo * (SM_W - SM_W2) + 128, w1 * 0x10001u);
                if (first) bar_arrive(3, 416);
                first = false;
                if (n == 64) break;
            }
            if (it > SPIN_LIMIT) __trap();
        }
        if (lane == 0) TRACE_Q(37);
        float L = bflo(w0) * __uint_as_float(ml[0].y) + bflo(w1) * __uint_as_float(ml[1].y);
#pragma unroll
        for (int o = 16; o; o >>= 1) L += shx(L, o);
        if (lane == 0) *(float2*)(sm + SM_FQ) = make_float2(__frcp_rn(L), __uint_as_float(redo));
        __syncwarp();
        if (lane < 8) mbar_arrive(BAR(WR));
        if (lane == 0) TRACE(10);
        bar_sync(4, 416);
        clear_head();
        if (j < NFF) {
            uint32_t ya = sb + SM_Y + lane * 16, sa = peer_addr(sb + SM_RED + 2048 + rk * 8, lane & 1), tb = peer_addr(BAR(MBB), lane & 1);
            pin(ya); pin(sa); pin(tb);
            bar_sync(7, 288);
            const float4 y0 = ldsf4(ya), y1 = ldsf4(ya + 512);
            float s = sum4(y0) + sum4(y1);
            float q = (fmaf(y0.x, y0.x, y0.y * y0.y) + fmaf(y0.z, y0.z, y0.w * y0.w)) + (fmaf(y1.x, y1.x, y1.y * y1.y) + fmaf(y1.z, y1.z, y1.w * y1.w));
#pragma unroll
            for (int o = 16; o; o >>= 1) { s += shx(s, o); q += shx(q, o); }
            if (lane < 2) st_async2(sa, s, q, tb);
        }
    } else if (warp == 15) {
        mbar_waitb(BAR(IT_X - 1), 0);
        if (j < J_END) mbar_waitb(BAR(j < NFF ? NITEMS - 1 : MBB), 0);
    }
    } else if (warp < 4) {
        float* scr = (float*)(sm + SM_SCR);
        uint32_t cls;
        {
            uint2 ha[8];
            uint32_t best = 0xffffffffu;
            sts32(sb + SM_SCR + 64 + warp * 4, best);
            const float sh = __shfl_sync(0xffffffffu, bflo(in1), 0);
            const float v0 = bflo(in1) - sh, v1 = bfhi(in1) - sh, v2 = bflo(in2) - sh, v3 = bfhi(in2) - sh;
            float mb, sd;
            ln_stats<4>((v0 + v1) + (v2 + v3), (v0 * v0 + v1 * v1) + (v2 * v2 + v3 * v3), sh, scr, warp, lane, 2, mb, sd);
            if (!rk) in2 = in1;
#pragma unroll 1
            for (int i = 0; i < NPROBE; i++) {
                uint32_t t0, t1, o;
                asm volatile("mov.u32 %0, %%clock;" : "=r"(t0));
                asm volatile("atom.relaxed.gpu.global.exch.b32 %0, [%1], %2;" : "=r"(o) : "l"(pl), "r"(2u + i) : "memory");
                asm volatile("{\n.reg .pred p;\nsetp.ne.u32 p, %1, 0x1234567;\nmov.u32 %0, 0;\n@p mov.u32 %0, %%clock;\n}" : "=r"(t1) : "r"(o));
                best = min(best, t1 - t0);
                sts32(sb + SM_SCR + 64 + warp * 4, best);
                if (__all_sync(0xffffffffu, min(best, lds32(sb + SM_SCR + 64 + (warp ^ 1) * 4)) < NEAR_CLK)) break;
            }
            bar_sync(2, 128);
            const uint4 lt = *(const uint4*)(scr + 16);
            cls = NUMA ? ((lt.y < lt.x) ^ (__popc((B_PR + (j >> 5)) & 0x2C) & 1)) | (lt.w < lt.z) << 1 : 0;
            if (warp == 0) { if (lane == 0) sts32(sb + SM_CLS, cls); bar_arrive(9, 64); }
            if (tid == 0) TRACE(38);
            asm volatile("barrier.cluster.wait.aligned;" ::: "memory");
            mbar_wait(BAR(IT_MODA), 0);
            if (HA_DELAY) __nanosleep(HA_DELAY);
            poll<1024, H_SLEEP, false, 16384>(ha, gs + near_off(B_HA + rk * 2, cls) + 2 * tid);
            auto rsum = [](uint32_t a, uint32_t b, uint32_t c, uint32_t d) { return rbf((__uint_as_float(a) + __uint_as_float(b)) + (__uint_as_float(c) + __uint_as_float(d))); };
            sts32(sb + SM_FV + frag_off(2 * tid),
                  pack2(ln_mod(bflo(in2), mb, sd, rsum(ha[4].x, ha[5].x, ha[6].x, ha[7].x), rsum(ha[0].x, ha[1].x, ha[2].x, ha[3].x)),
                        ln_mod(bfhi(in2), mb, sd, rsum(ha[4].y, ha[5].y, ha[6].y, ha[7].y), rsum(ha[0].y, ha[1].y, ha[2].y, ha[3].y))));
            bar_arrive(5, 384);
            mbar_wait(BAR(QB), 0);
            if (tid < 64) {
                const float* qx = (const float*)(sm + SM_QX) + tid;
                sts16(sb + SM_FQ + frag_off(tid), pack2((qx[0] + qx[64]) + (qx[128] + qx[192]), 0.f));
            }
            bar_arrive(6, 384);
        }
        asm volatile("setmaxnreg.inc.sync.aligned.u32 192;");
        float acc[128];
        float M = 0.f;
        uint32_t pa = sb + SM_XA + warp * 512 + lane * 16, ma = sb + SM_MX + (warp * 8 + g) * 4, pf = BAR(PF0);
        uint32_t blo = __reduce_or_sync(0xffffffffu, (((sb + SM_U) & 0x3FFFFu) >> 4) | 0x400000u);
        uint32_t* e1[4];
#pragma unroll
        for (int i = 0; i < 4; i++) e1[i] = gs + G_E1 + (warp * 8 + g) * 4 * 8192 + (rk * 2 + (j >> 6)) * 2048 + ((j >> 1) & 31) * 32 + t * 4;
#pragma unroll 1
        for (int h = 0; h < 2 * NUNITS; h++) {
            mbar_wait(pf, 0);
            const float m = __uint_as_float(lds32(ma));
            const uint4 pn = lds128(pa);
            wg_wait0();
#pragma unroll
            for (int i = 0; i < 128; i++) asm volatile("" : "+f"(acc[i]) :: "memory");
            if (h == 0) M = m;
            uint32_t b2 = 0x3f803f80u;
            if (__builtin_expect(__any_sync(0xffffffffu, m != M), 0)) {
                const float Mn = fmaxf(M, m), alpha = ex2(M - Mn), beta = ex2(m - Mn);
                M = Mn;
                b2 = pack2(beta, beta);
#pragma unroll
                for (int jj = 0; jj < 32; jj++) { acc[4 * jj] *= alpha; acc[4 * jj + 1] *= alpha; }
            }
            auto mul2 = [](uint32_t x, uint32_t y) { uint32_t r; asm("mul.rn.bf16x2 %0, %1, %2;" : "=r"(r) : "r"(x), "r"(y)); return r; };
            const uint4 p = make_uint4(mul2(pn.x, b2), mul2(pn.y, b2), mul2(pn.z, b2), mul2(pn.w, b2));
            if (tid == 0 && (h & 1)) TRACE_Q(48 + (h >> 1));
            wgmma_pv(acc, p, blo, h);
            if (lane == 0 && h > 0 && !(h & 1)) mbar_arrive(BAR(EB_UNIT0 + (h >> 1) - 1));
            blo += h == 11 ? -11 * 1024 : 1024;
            pa += (h == 5 || h == 11) ? -5 * 2048 : 2048;
            ma += 128; pf += 8;
            if (h == 2 * NUNITS - 3) {
                mbar_wait(BAR(JD), 0);
                const uint32_t hm = (*(const uint32_t*)(sm + SM_CLS + 16 + warp * 4) >> (g * 4)) ^ ((j >> 6) ? 15u : 0u);
#pragma unroll
                for (int i = 0; i < 4; i++) e1[i] += ((hm >> i) & 1) << 10;
            }
        }
#pragma unroll
        for (int vv = 0; vv < 2; vv++) {
            if (vv && M == 1.f) __trap();
            if (vv) wg_wait0(); else wg_wait1();
#pragma unroll
            for (int i = 0; i < 64; i++) asm volatile("" : "+f"(acc[vv * 64 + i]) :: "memory");
            if (tid == 0 && !vv) TRACE_Q(63);
#pragma unroll
            for (int i = 0; i < 4; i++) {
                const float* a = &acc[vv * 64 + i * 16];
                st_x4(e1[i] + i * 8192 + vv * 16, enc(pack2(a[0], a[1])), enc(pack2(a[4], a[5])), enc(pack2(a[8], a[9])), enc(pack2(a[12], a[13])));
            }
        }
        bar_arrive(3, 416);
        if (tid == 0) TRACE_Q(17);
#pragma unroll 1
        for (int pass = 0;; pass++) {
            if (j >= NFF && j < J_END && pass == (j >= J_RED)) {
                uint4 a[8], b[4];
                float c[4], e[4];
                const bool own = (warp >> 1) == rk;
                const uint32_t xa = sb + SM_FV + (warp & 1) * 64 + g * 8;
                if (lane == 0) mbar_expect(BAR(MBB), own ? 64 : 0);
#pragma unroll
                for (int i = 0; i < 2; i++) {
                    ldfrag(b, sb + SM_FS + rk * 512 + i * 256 + t * 16);
                    mbar_wait(BAR(IT_X + i), 0);
                    const uint32_t ab = sb + SM_U + B_X * 32768 + i * 16384 + a128;
                    load8<true>(a, [&](int s) { return ab + s * 2048; });
                    mma8(i ? e : c, a, b);
                }
                c[0] += e[0]; c[2] += e[2];
                if (!own) {
                    if (t == 0) st_async2(peer_addr(xa, rk ^ 1), c[0], c[2], peer_addr(BAR(MBB), rk ^ 1));
                } else {
                    mbar_wait(BAR(MBB), 0);
                    const float2 pp = *(const float2*)(sm + (xa - sb));
                    const float mine = t ? c[2] + pp.y : c[0] + pp.x, other = shx(mine, 4);
                    const uint32_t w = (warp & 1) * 8 + t * 4 + (g >> 1), val = enc(pack2(mine, other));
                    if (t < 2 && !(g & 1)) {
                        if (j < J_RED) st2_x1(gs + B_MB * 4096 + (j - NFF) * 16 + w, val);
                        else sts32(sb + SM_FV + 256 + w * 4, val);
                    }
                    __syncwarp();
                    if (j >= J_RED && lane < 4) mbar_arrive(BAR(QB));
                    if (lane == 0) TRACE(11);
                }
            }
            if (pass) break;
            uint4 a[8], a2[8];
            const uint32_t ab = sb + SM_U + B_WO * 32768 + a128;
            uint32_t* p3 = gs + (B_E3 + ((j >> 1) & 3)) * 4096 + (t >> 1) * 1024 + (rk * 2 + (warp >> 1)) * 256 + (j >> 3) * 16 + (warp & 1) * 8 + (t & 1) * 4 + (g >> 1);
            const uint32_t* pb = gs + near_off(B_E2 + (j >> 4), cls) + (((j >> 3) & 1) * 2 + lb4) * 256 + (lane & 15) * 2;
            pin(p3); pin(pb);
            uint2 bb[8];
            uint2 bq[2] = {make_uint2(0u, 0u), make_uint2(0u, 0u)};
            uint32_t xa = sb + SM_XA + lane * 16;
            pin(xa);
            bool h0 = false, h1 = false;
            auto idle = [&]() {
                if (!h0) {
                    h0 = __all_sync(0xffffffffu, mbar_test(BAR(IT_WO + (t & 1)), 0));
                    if (h0) load8<true>(a, [&](int s) { return ab + s * 2048; });
                }
                if (!h1) {
                    h1 = __all_sync(0xffffffffu, mbar_test(BAR(IT_WO + 2 + (t & 1)), 0));
                    if (h1) load8<true>(a2, [&](int s) { return ab + 16384 + s * 2048; });
                }
            };
            bar_sync(4, 416);
            idle();
            poll<128, 0, true>(bq, pb + warp * 64, idle);
            asm volatile("st.shared.v4.u32 [%0], {%1, %2, %3, %4};" :: "r"(xa + warp * 512), "r"(bq[0].x), "r"(bq[0].y), "r"(bq[1].x), "r"(bq[1].y) : "memory");
            bar_sync(2, 128);
#pragma unroll
            for (int i = 0; i < 4; i++) { const uint4 q = lds128(xa + i * 512); bb[2 * i] = make_uint2(q.x, q.y); bb[2 * i + 1] = make_uint2(q.z, q.w); }
            if (tid == 0) TRACE(21);
            float e[4][4];
#pragma unroll
            for (int s = 0; s < 16; s++) {
                if (s == 0 && !h0) { mbar_wait(BAR(IT_WO), 0); mbar_wait(BAR(IT_WO + 1), 0); load8<true>(a, [&](int q) { return ab + q * 2048; }); }
                if (s == 0 && !h1) { mbar_wait(BAR(IT_WO + 2), 0); mbar_wait(BAR(IT_WO + 3), 0); load8<true>(a2, [&](int q) { return ab + 16384 + q * 2048; }); }
                const int z = (s & 1) | (s & 2) << 2 | (s >> 2) << 1;
                const uint4& x = z < 8 ? a[z] : a2[z & 7];
                float (&d)[4] = e[(z >> 3) * 2 + (z & 1)];
                if (!(z & 6)) d[0] = d[1] = d[2] = d[3] = 0.f;
                mma(d, x.x, x.y, x.z, x.w, bb[z & 7].x, bb[z & 7].y);
            }
            float lo, hi;
            quad_pair((t & 2) ? (e[2][0] + e[3][0]) + (e[2][1] + e[3][1]) : (e[0][0] + e[1][0]) + (e[0][1] + e[1][1]),
                      (t & 2) ? (e[2][2] + e[3][2]) + (e[2][3] + e[3][3]) : (e[0][2] + e[1][2]) + (e[0][3] + e[1][3]), t, lo, hi);
            if (!(g & 1)) st_x1(p3, enc(pack2(lo, hi)));
            if (j < NFF) bar_arrive(8, 384); else if (j >= J_RED && j < J_END) bar_arrive(8, 192);
            if (tid == 0) TRACE(22);
        }
        if (j < NFF) {
            uint4 a[16];
            const uint32_t ad = sb + SM_U + B_DN * 32768 + warp * 8192 + (r8 + 8 * lb4) * 128 + (lb3 ^ r8) * 16;
            uint32_t rl = sb + SM_RED + lane * 16;
            uint32_t* p5 = gs + (B_E5 + warp * 4 + (t >> 1)) * 4096 + j * 16 + (t & 1) * 8 + g;
            pin(rl); pin(p5);
            if (lane == 0) mbar_expect(BAR(MBB), 4);
            auto ldd = [&]() {
#pragma unroll
                for (int s = 0; s < 16; s++) a[s] = ldsm<true>((ad ^ ((s & 3) * 32)) + (s >> 2) * 2048);
            };
            const uint32_t db = BAR(IT_DOWN + (warp ^ (j & 3)));
            mbar_wait(BAR(MBB), 0);
            const float4 st = ldsf4(sb + SM_RED + 2048);
            const bool hd = __all_sync(0xffffffffu, mbar_test(db, 0));
            if (hd) ldd();
            const float mu = (st.x + st.z) * (1.f / 512.f);
            float rstd;
            asm volatile("rsqrt.approx.ftz.f32 %0, %1;" : "=f"(rstd) : "f"(fmaxf(fmaf(-mu, mu, (st.y + st.w) * (1.f / 512.f)), 0.f) + 1e-5f));
            mbar_wait(BAR(QB), 1);
            if (tid == 0) TRACE(25);
            const float4 f0 = ldsf4(rl), f2 = ldsf4(rl + 1024), f1 = ldsf4(rl + 512), f3 = ldsf4(rl + 1536);
            const float gg = fmaf(rstd, fmaf(-mu, f0.z + f2.z, (f0.x + f0.y) + (f2.x + f2.y)), f0.w + f2.w);
            const float uu = fmaf(rstd, fmaf(-mu, f1.z + f3.z, (f1.x + f1.y) + (f3.x + f3.y)), f1.w + f3.w);
            const float hh = __fdividef(gg * uu, 1.f + ex2(-gg * fmaf(gg * gg, 0.10294324f, 2.3022082f)));
            uint32_t hb[4];
#pragma unroll
            for (int i = 0; i < 4; i++) hb[i] = pack2(__shfl_sync(0xffffffffu, hh, 2 * t + 8 * i), __shfl_sync(0xffffffffu, hh, 2 * t + 8 * i + 1));
            if (!hd) { mbar_wait(db, 0); ldd(); }
#pragma unroll
            for (int i = 0; i < 2; i++) {
                uint32_t res = 0;
#pragma unroll
                for (int k = 0; k < 4; k++) {
                    float c[4] = {0.f, 0.f, 0.f, 0.f};
                    const uint4 &x = a[i * 8 + k], &y = a[i * 8 + k + 4];
                    mma(c, x.x, x.y, x.z, x.w, hb[0], hb[1]);
                    mma(c, y.x, y.y, y.z, y.w, hb[2], hb[3]);
                    if (t == k) res = pack2(c[0], c[2]);
                }
                st2_x1(p5 + i * 8192, enc(res));
            }
            if (tid == 0) { TRACE(27); TRACE_GT(47); }
        }
    } else {
        const int u8 = tid - 128, w8 = warp - 4;
        const int v = w8 >> 2, wq4 = w8 & 3;
        {
            const float c0 = bflo(in1), c1 = bfhi(in1);
            sts32(sb + SM_FS + frag_off(2 * u8), pack2(__fdividef(c0, 1.f + __expf(-c0)), __fdividef(c1, 1.f + __expf(-c1))));
        }
        bar_sync(1, 256);
        asm volatile("barrier.cluster.wait.aligned;" ::: "memory");
        uint4 a[8], b[4]; float c[4];
        if (w8 < 2) {
            ldfrag(b, sb + SM_FS + (j >> 5) * 256 + t * 16);
            mbar_wait(BAR(IT_MODA), 0);
            if (u8 == 0) TRACE(12);
            const uint32_t ab = sb + SM_XA + w8 * 4096 + a16;
            load8<true>(a, [&](int s) { return ab + s * 512; });
            mma8(c, a, b);
            if (t < 2) st2_x1(gs + (B_HA + ((j >> 4) & 1) * 2 + w8) * 4096 + (j >> 5) * 256 + (j & 15) * 16 + t * 8 + g, encf(t ? c[2] : c[0]));
        }
        {
            mbar_wait(BAR(IT_WQ + 2 * v <= NCP ? 1 : IT_WQ + 2 * v), 0); mbar_wait(BAR(IT_WQ + 2 * v + 1 <= NCP ? 1 : IT_WQ + 2 * v + 1), 0);
            const uint32_t ab = sb + SM_U + 4 * 32768 + v * 16384 + a128;
            load8<true>(a, [&](int s) { return ab + s * 2048; });
            if (lane == 0) mbar_arrive(BAR(EB_WQ));
            bar_sync(5, 384);
            if (u8 == 0) TRACE(13);
            ldfrag(b, sb + SM_FV + v * 256 + t * 16);
            mma8(c, a, b);
            if (t < 2) {
                const float qv = t ? c[2] : c[0];
                const uint32_t qa_ = sb + SM_QX + ((rk * 2 + v) * 64 + wq4 * 16 + t * 8 + g) * 4;
                asm volatile("st.async.weak.shared::cluster.mbarrier::complete_tx::bytes.f32 [%0], %1, [%2];"
                             :: "r"(peer_addr(qa_, rk ^ 1)), "f"(qv), "r"(peer_addr(BAR(QB), rk ^ 1)) : "memory");
                sts32(qa_, __float_as_uint(qv));
            }
            __syncwarp();
            if (lane == 0) mbar_expect(BAR(QB), 64);
        }
        {
            mbar_wait(BAR(IT_WUK + (v ^ ((j >> 5) & 1))), 0); mbar_wait(BAR(IT_WUK + (v ^ ((j >> 5) & 1)) + 2), 0);
            const uint32_t ab = sb + SM_U + 5 * 32768 + (w8 * 16 + r8 + 8 * lb3) * 128;
            const uint32_t x16 = (lb4 ^ r8) * 16;
            load8<false>(a, [&](int s) { return ab + (s & 1) * 16384 + (x16 ^ ((s >> 1) * 32)); });
            bar_sync(6, 384);
            if (u8 == 0) TRACE(14);
            b[0] = lds128(sb + SM_FQ + t * 16); b[1] = lds128(sb + SM_FQ + 64 + t * 16);
            float e[4] = {0.f, 0.f, 0.f, 0.f};
            c[0] = c[1] = c[2] = c[3] = 0.f;
#pragma unroll
            for (int k = 0; k < 4; k++) {
                const uint32_t b0 = (k & 1) ? b[k >> 1].z : b[k >> 1].x, b1 = (k & 1) ? b[k >> 1].w : b[k >> 1].y;
                mma(c, a[2 * k].x, a[2 * k].y, a[2 * k].z, a[2 * k].w, b0, b1);
                mma(e, a[2 * k + 1].x, a[2 * k + 1].y, a[2 * k + 1].z, a[2 * k + 1].w, b0, b1);
            }
            const float mine = ((t & 1) ? ((t & 2) ? e[2] : e[0]) : ((t & 2) ? c[2] : c[0])) * 0.12751743f;
            const float other = shx(mine, 4);
            if (!(g & 1)) st2_x1(gs + (B_QA + rk * 8 + ((j >> 1) & 1) * 4 + (j >> 5)) * 4096 + w8 * 128 + ((j >> 2) & 7) * 16 + (g >> 1) * 4 + t, enc(pack2(mine, other)));
            if (u8 == 0) TRACE(15);
        }
        const uint32_t cls = ldcls();
        __nanosleep(QA_DELAY);
        {
            uint4 qb[8];
            const uint32_t* pq = gs + near_off(B_QA + rk * 8 + wq4, cls) + lane * 4;
            const uint32_t* pq2 = gs + near_off(B_QA + rk * 8 + 4 + wq4, cls) + lane * 4;
            if (lane == 0) {
                mbar_expect(BAR(QT), 4096);
                asm volatile("cp.async.bulk.shared::cluster.global.mbarrier::complete_tx::bytes [%0], [%1], 4096, [%2];"
                             :: "r"(sb + SM_U + 5 * 32768 + w8 * 4096), "l"(gs + near_off(B_QA + rk * 8 + w8, cls)), "r"(BAR(QT)) : "memory");
            }
            const uint32_t qs = sb + SM_U + 5 * 32768 + wq4 * 4096 + lane * 16;
            mbar_wait(BAR(QT), 0);
#pragma unroll
            for (int i = 0; i < 8; i++) { a[i] = lds128(qs + i * 512); qb[i] = lds128(qs + 16384 + i * 512); }
            poll<512, QA_SLEEP, true>(a, pq);
            poll<512, QA_SLEEP, true>(qb, pq2);
            if (lane == 0) mbar_arrive(BAR(EB_WUK));
            auto add2 = [](uint32_t x, uint32_t y) { uint32_t r; asm("add.rn.bf16x2 %0, %1, %2;" : "=r"(r) : "r"(x), "r"(y)); return r; };
#pragma unroll
            for (int i = 0; i < 8; i++) a[i] = make_uint4(add2(a[i].x, qb[i].x), add2(a[i].y, qb[i].y), add2(a[i].z, qb[i].z), add2(a[i].w, qb[i].w));
        }
        if (u8 == 0) TRACE(8);
        {
            float m = -INFINITY, l = 0.f;
            uint32_t xl = sb + SM_XB + w8 * 2048 + lane * 16, xr = peer_addr(xl, rk ^ 1), bsr = peer_addr(BAR(SF0 + v), rk ^ 1);
            uint32_t pa = sb + SM_XA + v * 2048 + wq4 * 512 + lane * 16, ma = sb + SM_MX + v * 128 + (wq4 * 8 + g) * 4;
            uint32_t fb = BAR(IT_CKV + v * 2), sf = BAR(SF0 + v);
            uint32_t dlo = __reduce_or_sync(0xffffffffu, (((sb + SM_U + v * 16384) & 0x3FFFFu) >> 4) | 0x10000u);
            if (STAG && v) __nanosleep(STAG);
#pragma unroll 1
            for (int n = 0; n < NUNITS; n++) {
                float d[2][16], sc[8];
#pragma unroll
                for (int i = 0; i < 2; i++) {
                    mbar_wait(fb + i * 8, 0);
                    wg_fence();
#pragma unroll
                    for (int s = 0; s < 8; s++) wgmma_rs_n32(d[i], a[s], (0x40000080ull << 32) | (dlo + i * 512 + (s >> 2) * 64 + (s & 3) * 2), s);
                    wg_commit();
                }
#pragma unroll
                for (int i = 0; i < 2; i++) {
                    if (i) wg_wait0(); else wg_wait1();
#pragma unroll
                    for (int k = 0; k < 16; k++) asm volatile("" : "+f"(d[i][k]) :: "memory");
                    sc[4 * i] = d[i][0] + d[i][6]; sc[4 * i + 1] = d[i][1] + d[i][7]; sc[4 * i + 2] = d[i][8] + d[i][14]; sc[4 * i + 3] = d[i][9] + d[i][15];
                    asm volatile("st.async.weak.shared::cluster.mbarrier::complete_tx::bytes.v4.f32 [%0], {%1, %2, %3, %4}, [%5];"
                                 :: "r"(xr + i * 1024), "f"(sc[4 * i]), "f"(sc[4 * i + 1]), "f"(sc[4 * i + 2]), "f"(sc[4 * i + 3]), "r"(bsr) : "memory");
                }
                if (u8 == 128) TRACE_Q(56 + (n < 6 ? n : -40));
                if (n >= 3) mbar_wait(BAR(EB_UNIT0 + n - 3), 0);
                dlo += n == 5 ? -5 * 2048 : 2048;
                fb += 32; xr ^= 512; bsr += 16;
                pin(fb); pin(xr); pin(bsr);
                mbar_wait(sf, 0);
                const float4 x = ldsf4(xl), y = ldsf4(xl + 1024);
                sc[0] += x.x; sc[1] += x.y; sc[2] += x.z; sc[3] += x.w; sc[4] += y.x; sc[5] += y.y; sc[6] += y.z; sc[7] += y.w;
                float pr[8];
#pragma unroll
                for (int i = 0; i < 8; i++) pr[i] = ex2(sc[i] - m);
                float mx = fmaxf(fmaxf(fmaxf(sc[0], sc[1]), fmaxf(sc[2], sc[3])), fmaxf(fmaxf(sc[4], sc[5]), fmaxf(sc[6], sc[7])));
                if (__builtin_expect(__any_sync(0xffffffffu, mx > m), 0)) {
                    mx = fmaxf(mx, shx(mx, 1));
                    mx = fmaxf(mx, shx(mx, 2));
                    const float mn = fmaxf(m, ceilf(mx * 0.0625f) * 16.f);
                    l *= ex2(m - mn);
                    m = mn;
#pragma unroll
                    for (int i = 0; i < 8; i++) pr[i] = ex2(sc[i] - m);
                }
                stsf(ma, m);
                asm volatile("st.shared.v4.u32 [%0], {%1, %2, %3, %4};" :: "r"(pa), "r"(pack2(pr[0], pr[1])), "r"(pack2(pr[2], pr[3])),
                             "r"(pack2(pr[4], pr[5])), "r"(pack2(pr[6], pr[7])) : "memory");
                __syncwarp();
                if (lane == 0) mbar_arrive(sf + (PF0 - SF0) * 8);
                l += ((pr[0] + pr[1]) + (pr[2] + pr[3])) + ((pr[4] + pr[5]) + (pr[6] + pr[7]));
                xl ^= 512; sf += 16; ma += 256; pa += (n == 2 || n == 5) ? -8192 : 4096;
            }
            l += shx(l, 1);
            l += shx(l, 2);
            float2* mlx = (float2*)(sm + SM_MX + 2048) + wq4 * 8 + g;
            if (v == 0) { *mlx = make_float2(m, l); bar_arrive(11, 256); }
            else {
                mbar_wait(BAR(JD), 0);
                bar_sync(11, 256);
                const float2 o = *mlx;
                const float mn = fmaxf(m, o.x);
                l = l * ex2(m - mn) + o.y * ex2(o.x - mn);
                if ((wq4 >> 1) == rk) st_x4(gs + (B_ML + wq4 * 8 + g) * 4096 + (t >> 1) * 1024 + (j >> 1) * 8 + (t & 1) * 4, encf(mn), encf(l), 1u, 1u);
            }
        }
        const int pi = j < NFF ? rk * 128 + w8 * 16 + (lane >> 1) : ((j - J_RED) & 15) * 16 + (w8 & 1) * 8 + g;
        const uint32_t xw = *(const uint32_t*)(xin + 2 * pi);
        const uint32_t one = (g & 1) ? 0x3f800000u : 0x00003f80u;
        const uint32_t* pm = gs + near_off(B_MB, cls) + pi;
        {
            const uint32_t ab = sb + SM_U + B_WUV * 32768 + v * 4096 + a128;
            uint32_t pa = sb + SM_PB + wq4 * 320 + frag_off(64 * v + 32 * (g >> 2) + 16 * (t & 1) + 8 * (t >> 1) + 2 * (g & 3));
            uint32_t fa = sb + SM_PB + g * 320 + t * 16;
            const uint32_t* pe = gs + G_E1 + j * 8192 + (w8 >> 1) * 2048 + ((((cls >> 1) ^ (w8 >> 1)) & 1) << 10) + (((w8 & 1) * 16 + t) * 8 + g) * 4;
            uint32_t* p2 = gs + (B_E2 + (j >> 4)) * 4096 + (t >> 1) * 1024 + (j & 12) * 64 + w8 * 32 + (j & 3) * 8 + (g & 6) + (t & 1);
            pin(pa); pin(fa); pin(pe); pin(p2);
            const uint32_t mk = (g & 1) ? 0xffff0000u : 0x0000ffffu, m0 = (g & 2) ? 0u : mk, m1 = (g & 2) ? mk : 0u;
            uint4 pv[4];
            bool hv = false;
            bar_sync(3, 416);
            uint4 wa = lds128(sb + SM_W + (wq4 * 4 + t) * 16);
            uint32_t wb[8] = {wa.x & m0, wa.x & m1, wa.y & m0, wa.y & m1, wa.z & m0, wa.z & m1, wa.w & m0, wa.w & m1};
            pv[0] = pv[1] = pv[2] = pv[3] = make_uint4(0u, 0u, 0u, 0u);
            float e[4][4];
            auto wsum = [&]() {
#pragma unroll
                for (int i = 0; i < 4; i++) {
                    e[i][0] = e[i][1] = e[i][2] = e[i][3] = 0.f;
                    mma(e[i], pv[i].x, pv[i].y, pv[i].z, pv[i].w, wb[2 * i], wb[2 * i + 1]);
                }
            };
            poll<512, E1_SLEEP, true>(pv, pe, [&]() {
                if (!hv) {
                    hv = __all_sync(0xffffffffu, mbar_test(BAR(IT_WUV + t), 0));
                    if (hv) load8<true>(a, [&](int s) { return ab + (s >> 1) * 8192 + (s & 1) * 2048; });
                }
            }, wsum);
            if (lane == 0) TRACE_Q(48 + w8);
            if (u8 == 0) TRACE_Q(18);
            float lo, hi2;
            float2 inv;
#pragma unroll 1
            for (int pass = 0;; pass++) {
                const float r0 = (t & 2) ? (e[0][2] + e[1][2]) + (e[2][2] + e[3][2]) : (e[0][0] + e[1][0]) + (e[2][0] + e[3][0]);
                const float r1 = (t & 2) ? (e[0][3] + e[1][3]) + (e[2][3] + e[3][3]) : (e[0][1] + e[1][1]) + (e[2][1] + e[3][1]);
                const uint32_t hi = pack2(r0, r1);
                sts32(pa, hi); sts32(pa + 1280, pack2(r0 - bflo(hi), r1 - bfhi(hi)));
                if (!hv) {
#pragma unroll 1
                    for (int i = 0; i < 4; i++) mbar_wait(BAR(IT_WUV + i), 0);
                    load8<true>(a, [&](int s) { return ab + (s >> 1) * 8192 + (s & 1) * 2048; });
                    hv = true;
                }
                bar_sync(1, 256);
                if (u8 == 0) TRACE(19);
                ldfrag(b, fa);
                mma8(c, a, b);
                mbar_wait(BAR(WR), 0);
                asm volatile("ld.shared.v2.f32 {%0, %1}, [%2];" : "=f"(inv.x), "=f"(inv.y) : "r"(sb + SM_FQ) : "memory");
                quad_pair(c[0] + c[1], c[2] + c[3], t, lo, hi2);
                if (__builtin_expect(__all_sync(0xffffffffu, pass || __float_as_uint(inv.y) == 0), 1)) break;
                wa = lds128(sb + SM_W2 + (wq4 * 4 + t) * 16);
                wb[0] = wa.x & m0; wb[1] = wa.x & m1; wb[2] = wa.y & m0; wb[3] = wa.y & m1; wb[4] = wa.z & m0; wb[5] = wa.z & m1; wb[6] = wa.w & m0; wb[7] = wa.w & m1;
                wsum();
                bar_sync(1, 256);
            }
            if (!(g & 1)) st_x1(p2, enc(pack2(lo * inv.x, hi2 * inv.x)));
            bar_arrive(4, 416);
            if (u8 == 0) TRACE(20);
        }
        if (j < NFF) {
            const uint32_t* p3 = gs + near_off(B_E3 + rk * 2 + v, cls) + wq4 * 256 + t * 16 + g * 2;
            const int od = lane & 1;
            uint32_t za = sb + SM_FZ + od * 576 + frag_off(w8 * 32 + (lane & 30));
            uint32_t fa = sb + SM_FZ + (g & 3) * 576 + ((lane ^ j) & 16) * 16 + t * 16, ya = sb + SM_Y + u8 * 4;
            uint32_t mb[3];
            uint4 a2[8];
            poll<1024, MB_SLEEP>(mb, pm);
            const uint32_t kk = pack2(1.f + bflo(mb[2]), 1.f + bfhi(mb[2]));
            sts32(za + 2 * 576, od ? mb[1] : kk);
            uint2 e3[4] = {make_uint2(0u, 0u), make_uint2(0u, 0u), make_uint2(0u, 0u), make_uint2(0u, 0u)};
            uint32_t ra = peer_addr(sb + SM_RED + (rk * 2 + v) * 512 + ((wq4 & 1) * 16 + (t >> 1) * 8 + g) * 16 + (t & 1) * 8, wq4 >> 1), tbo = peer_addr(BAR(QB), wq4 >> 1);
            pin(za); pin(fa); pin(ya); pin(ra); pin(tbo);
            if (lane == 0) mbar_expect(BAR(QB), 256);
            const uint32_t gb = BAR(IT_X + v * 2), ab = sb + SM_U + (B_X + v) * 32768 + a128;
            bool early = false, early2 = false;
            auto ldw = [&]() {
                if (!early) {
                    early = __all_sync(0xffffffffu, mbar_test(gb, 0));
                    if (early) load8<true>(a, [&](int s) { return ab + s * 2048; });
                }
                if (!early2) {
                    early2 = __all_sync(0xffffffffu, mbar_test(gb + 8, 0));
                    if (early2) load8<true>(a2, [&](int s) { return ab + 16384 + s * 2048; });
                }
            };
            bar_sync(8, 384);
            float s0[4], s1[4];
            auto sum = [&]() {
                s0[0] = s0[1] = s0[2] = s0[3] = s1[0] = s1[1] = s1[2] = s1[3] = 0.f;
                mma(s0, e3[0].x, e3[0].y, e3[1].x, e3[1].y, one, one); mma(s1, e3[2].x, e3[2].y, e3[3].x, e3[3].y, one, one);
            };
            poll<256, 0, true>(e3, p3, ldw, sum);
            if (u8 == 0) TRACE(23);
            const float y0 = fmaf(bflo(mb[0]), (t & 2) ? s0[2] + s1[2] : s0[0] + s1[0], bflo(xw)), y1 = fmaf(bfhi(mb[0]), (t & 2) ? s0[3] + s1[3] : s0[1] + s1[1], bfhi(xw));
            stsf(ya, od ? y1 : y0);
            const float z0 = y0 * bflo(kk), z1 = y1 * bfhi(kk);
            const uint32_t zh = pack2(z0, z1);
            sts32(za, od ? pack2(z0 - bflo(zh), z1 - bfhi(zh)) : zh);
            bar_sync(7, 288);
            if (u8 == 0) TRACE(24);
            ldfrag(b, fa);
            if (!early) { mbar_wait(gb, 0); load8<true>(a, [&](int s) { return ab + s * 2048; }); }
            {
                float e[4][4];
#pragma unroll
                for (int s = 0; s < 16; s++) {
                    if (s == 8 && !early2) { mbar_wait(gb + 8, 0); load8<true>(a2, [&](int q) { return ab + 16384 + q * 2048; }); }
                    const uint4& x = s < 8 ? a[s] : a2[s & 7];
                    const uint4& y = b[(s >> 1) & 3];
                    float (&d)[4] = e[(s >> 3) * 2 + (s & 1)];
                    if (!(s & 6)) d[0] = d[1] = d[2] = d[3] = 0.f;
                    mma(d, x.x, x.y, x.z, x.w, (s & 1) ? y.z : y.x, (s & 1) ? y.w : y.y);
                }
                const bool hi = t >> 1;
                const float k0 = hi ? e[2][2] + e[3][2] : e[0][0] + e[1][0], k1 = hi ? e[2][3] + e[3][3] : e[0][1] + e[1][1];
                const float o0 = hi ? e[2][0] + e[3][0] : e[0][2] + e[1][2], o1 = hi ? e[2][1] + e[3][1] : e[0][3] + e[1][3];
                st_async2(ra, k0 + shx(o0, 2), k1 + shx(o1, 2), tbo);
            }
        } else if (j >= J_RED && j < J_END && w8 < 2) {
            uint32_t ga[1], e3[4];
            poll<0, MB_SLEEP>(ga, pm);
            bar_sync(8, 192);
            poll<64, 100>(e3, gs + near_off(B_E3 + (pi >> 6), cls) + (pi & 48) * 16 + t * 64 + (pi & 15));
            float y0 = (bflo(e3[0]) + bflo(e3[1])) + (bflo(e3[2]) + bflo(e3[3])), y1 = (bfhi(e3[0]) + bfhi(e3[1])) + (bfhi(e3[2]) + bfhi(e3[3]));
#pragma unroll
            for (int o = 1; o < 4; o <<= 1) { y0 += shx(y0, o); y1 += shx(y1, o); }
            const int col = g + (t & 1) * 8;
            y0 = __shfl_sync(0xffffffffu, (t & 1) ? fmaf(bfhi(ga[0]), y1, bfhi(xw)) : fmaf(bflo(ga[0]), y0, bflo(xw)), (col >> 1) * 4 + (col & 1));
            uint16_t* po = (uint16_t*)out + (j - J_RED) * 32 + w8 * 16 + col;
            const uint32_t* pe = gs + near_off(B_E5 + j - J_RED, cls) + t * 16 + w8 * 8 + g;
            pin(po);
            const uint32_t sel = (g & 2) ? 0x3f800000u : 0x00003f80u;
            uint32_t yv[NFF / 4 + 1];
            float e[4][4], gb = 0.f;
#pragma unroll
            for (int i = 0; i <= NFF / 4; i++) yv[i] = 0u;
#pragma unroll 1
            for (uint32_t it = 0;; it++) {
#pragma unroll
                for (int i = 0; i < NFF / 4; i++) if (!yv[i]) ld_x(yv[i], pe + i * 64);
                if (__all_sync(0xffffffffu, !yv[NFF / 4] && mbar_test(BAR(QB), 1))) {
                    yv[NFF / 4] = lds32(sb + SM_FV + 256 + w8 * 32 + (col >> 1) * 4);
                    gb = (col & 1) ? bfhi(yv[NFF / 4]) : bflo(yv[NFF / 4]);
                }
                if (it > SPIN_LIMIT) __trap();
#pragma unroll
                for (int i = 0; i < 4; i++) {
                    e[i][0] = e[i][1] = e[i][2] = e[i][3] = 0.f;
                    mma(e[i], yv[4 * i], yv[4 * i + 1], i < 3 ? yv[(4 * i + 2) % (NFF / 4)] : 0u, i < 3 ? yv[(4 * i + 3) % (NFF / 4)] : 0u, sel, sel);
                }
                if (__all_sync(0xffffffffu, mint<NFF / 4 + 1>(yv) != 0)) break;
            }
            if (u8 == 0) TRACE(26);
            const float s = ((e[0][0] + e[0][2]) + (e[1][0] + e[1][2])) + ((e[2][0] + e[2][2]) + (e[3][0] + e[3][2]));
            asm volatile("{\n.reg .pred p;\nsetp.lt.u32 p, %2, 2;\n@p st.global.u16 [%0], %1;\n}" :: "l"(po), "h"((uint16_t)pack2(fmaf(gb, s, y0), 0.f)), "r"(t) : "memory");
            asm volatile("{\n.reg .pred p;\nsetp.eq.f32 p, %0, 0f7F7FFFFF;\n@p nanosleep.u32 0;\n}" :: "f"(((e[0][1] + e[0][3]) + (e[1][1] + e[1][3])) + ((e[2][1] + e[2][3]) + (e[3][1] + e[3][3]))));
            if (u8 == 0) TRACE(27);
        }
    }
}

typedef CUresult (*EncFn)(CUtensorMap*, CUtensorMapDataType, cuuint32_t, void*, const cuuint64_t*, const cuuint64_t*,
                          const cuuint32_t*, const cuuint32_t*, CUtensorMapInterleave, CUtensorMapSwizzle,
                          CUtensorMapL2promotion, CUtensorMapFloatOOBfill);

void make_map(EncFn enc_fn, CUtensorMap* m, const void* p, cuuint64_t d0, cuuint64_t d1, cuuint64_t d2, cuuint64_t d3,
              cuuint64_t s1, cuuint64_t s2, cuuint64_t s3, cuuint32_t b0, cuuint32_t b1, cuuint32_t b2, cuuint32_t b3, CUtensorMapSwizzle sw) {
    const cuuint64_t dims[4] = {d0, d1, d2, d3}, strides[3] = {s1, s2, s3};
    const cuuint32_t box[4] = {b0, b1, b2, b3}, es[4] = {1, 1, 1, 1};
    enc_fn(m, CU_TENSOR_MAP_DATA_TYPE_BFLOAT16, 4, (void*)p, dims, strides, box, es,
           CU_TENSOR_MAP_INTERLEAVE_NONE, sw, PROMO, CU_TENSOR_MAP_FLOAT_OOB_FILL_NONE);
}

uint32_t* scratch = nullptr;

struct Tune { const char* win; const char* late; int tau, t_off; const char* tail[3][4]; };
Tune tune = {"77777777755555555555555555555555555555544",
             "00000000000000888888888888888888888888888", 320, -300,
             {{"VVVVOOOOguguDDDD", "zzzzzzzzzzzzzzzz", "7777aaaaaaaa6789", "ibbb5fffbaaa3999"},
              {"VMVMVVOOOO", "zzzzzzzzzz", "9999999999", "899999cbbb"},
              {"VVVVOOOOMM", "zzzzzzzzzz", "aaaaaaaa88", "m222fhhhox"}}};
bool ready = false;

}

extern "C" void kernel_launch(void* const* d_in, const int* in_sizes, int n_in, void* d_out, int out_size) {
    (void)in_sizes; (void)n_in; (void)out_size;
    static Maps maps;
    static const void* cached[12] = {};
    bool same = ready;
    for (int i = 0; i < 12 && same; i++) same = cached[i] == d_in[i];
    if (!same) {
        void* fn = nullptr;
        cudaDriverEntryPointQueryResult qr;
        cudaGetDriverEntryPoint("cuTensorMapEncodeTiled", &fn, cudaEnableDefault, &qr);
        EncFn e = (EncFn)fn;
        const CUtensorMapSwizzle S128 = CU_TENSOR_MAP_SWIZZLE_128B;
        make_map(e, &maps.m[MP_WQ], d_in[2], 64, 512, 64, 1, 8192, 128, 8192, 64, 64, 1, 1, S128);
        make_map(e, &maps.m[MP_WUK], d_in[3], 64, 512, 64, 1, 8192, 128, 8192, 64, 64, 1, 1, S128);
        make_map(e, &maps.m[MP_CKV], d_in[1], 64, 8, 8, 4096, 1024, 128, 8192, 64, 8, 4, 2, S128);
        make_map(e, &maps.m[MP_MODB], d_in[11], 3072, 512, 1, 1, 6144, 6144, 6144, 64, 128, 1, 1, S128);
        make_map(e, &maps.m[MP_WUV], d_in[4], 64, 512, 64, 1, 8192, 128, 8192, 64, 32, 2, 1, S128);
        make_map(e, &maps.m[MP_WO], d_in[5], 512, 4096, 1, 1, 1024, 1024, 1024, 64, 64, 1, 1, S128);
        make_map(e, &maps.m[MP_GATE], d_in[7], 1792, 512, 1, 1, 3584, 3584, 3584, 64, 128, 1, 1, S128);
        make_map(e, &maps.m[MP_UP], d_in[8], 1792, 512, 1, 1, 3584, 3584, 3584, 64, 128, 1, 1, S128);
        make_map(e, &maps.m[MP_DOWN], d_in[9], 64, 1792, 8, 1, 1024, 128, 1024, 64, 32, 2, 1, S128);
        for (int r = 0; r < 3; r++) {
            int ids[58], cnt[128] = {}, tn = tune.t_off - (W0 - 1) * tune.tau;
            uint2* sc = maps.sched[r];
            auto dig = [](char ch) { return ch >= 'a' ? ch - 'a' + 10 : ch >= 'A' ? ch - 'A' + 36 : ch - '0'; };
            for (int i = 0; i < 58; i++) sc[i] = make_uint2(0u, 0u);
            for (int i = 0;; i++) {
                int id = i, buf, dep, w, wl;
                if (i < IT_WUV) {
                    const int u = (i - IT_CKV) >> 2;
                    buf = i < IT_CKV ? 4 + ((i - 1) >> 2) : u % 6;
                    dep = i < IT_CKV || u < 4 ? -1 : u < 6 ? EB_WQ + u - 4 : EB_UNIT0 + u - 6;
                    w = dig(tune.win[i]); wl = dig(tune.late[i]);
                    if (i) tn += tune.tau;
                } else {
                    const char ch = tune.tail[r][0][i - IT_WUV];
                    if (!ch) break;
                    buf = ch == 'V' ? B_WUV : ch == 'O' ? B_WO : ch == 'D' ? B_DN : ch == 'u' ? B_X + 1 : B_X;
                    id = (ch == 'V' ? IT_WUV : ch == 'O' ? IT_WO : ch == 'D' ? IT_DOWN : ch == 'u' ? IT_X + 2 : IT_X) + cnt[(int)ch]++;
                    dep = EB_UNIT0 + (buf < 2 ? buf + 6 : buf);
                    w = dig(tune.tail[r][1][i - IT_WUV]); wl = dig(tune.tail[r][2][i - IT_WUV]);
                    tn += 32 * dig(tune.tail[r][3][i - IT_WUV]);
                }
                if (id < IT_X || id >= IT_DOWN ? (id - 1) & 3 : (id - IT_X) & 1) dep = -1;
                ids[i] = id;
                auto back = [&](int d) { return i < d ? 0 : (ids[i - d] && ids[i - d] <= NCP ? 1 : ids[i - d]) + 1; };
                sc[i].x = id | (buf * 4 + (id < IT_X || id >= IT_DOWN ? (id - 1) & 3 : ((id - IT_X) & 1) * 2)) << 6 | (dep + 1) << 11 | (w > 32 ? NEVER + 1 : back(w)) << 18 | (wl ? back(wl) : 0) << 25;
                const int mp = id < IT_CKV ? MP_WQ + ((id - 1) >> 2) : id < IT_WUV ? MP_CKV : id < IT_WO ? MP_WUV : id < IT_X ? MP_WO
                             : id >= IT_DOWN ? MP_DOWN : r ? MP_MODB : MP_GATE + ((id - IT_X) >> 1);
                const int step = mp == MP_CKV ? id - IT_CKV : mp == MP_WUV ? (id - IT_WUV) * 2 : mp == MP_DOWN ? id - IT_DOWN : id < IT_X ? (id - 1) & 3 : ((id - IT_X) & 1) * 2;
                sc[i].y = (tn & 0xffff) | (mp & 15) << 16 | step << 20;
            }
        }
        cudaGetSymbolAddress((void**)&scratch, g_scratch);
        scratch = (uint32_t*)(((uintptr_t)scratch + (2u << 20) - 1) & ~(uintptr_t)((2u << 20) - 1));
        cudaFuncSetAttribute(fused_kernel, cudaFuncAttributeMaxDynamicSharedMemorySize, SM_TOTAL);
        for (int i = 0; i < 12; i++) cached[i] = d_in[i];
        ready = true;
    }
    const First f = {{(const uint8_t*)d_in[2], (const uint8_t*)d_in[11]}, {(const __nv_bfloat16*)d_in[0], (const __nv_bfloat16*)d_in[10]}};
    fused_kernel<<<NCTA, NTHREADS, SM_TOTAL>>>(f, (__nv_bfloat16*)d_out, scratch, maps);
}
```

```cpp
#include <cuda_runtime.h>
#include <cuda_bf16.h>
#include <cuda.h>
#include <stdint.h>
#include <limits.h>

namespace {

constexpr int NCTA = 128;
constexpr int NTHREADS = 512;
constexpr int NUNITS = 8;
constexpr int NFF = 56, J_RED = 104, J_END = 120;
constexpr uint32_t SPIN_LIMIT = 1u << 22;

#define PROMO CU_TENSOR_MAP_L2_PROMOTION_L2_64B
#define NEAR_CLK 390
#define E1_EARLY 50
#define STAG 300
#define NUMA 1
#define NPROBE 5
#define NCP 2
#define W0 4
#define RD_ITEM 15
#define JAN_SLEEP 100
#define RD_SLEEP 400
#define HA_DELAY 200
#define H_SLEEP 100
#define QA_DELAY 600
#define QA_SLEEP 200
#define ML_DELAY 300
#define E1_SLEEP 50
#define MB_SLEEP 100
constexpr int B_WUV = 2, B_WO = 3, B_X = 4  , B_DN = 0;

constexpr int SM_U = 0;
constexpr int SM_XA = 6 * 32768;
constexpr int SM_XB = SM_XA + 12288;
constexpr int SM_MX = SM_XB + 16384;
constexpr int SM_FZ = SM_XB + 8192;
constexpr int SM_PB = SM_XB;
constexpr int SM_Y = SM_XB + 12288;
constexpr int SM_RED = SM_XB + 4096;
constexpr int SM_FS = SM_XB + 20480;
constexpr int SM_FV = SM_FS + 1024;
constexpr int SM_QX = SM_XA + 8192;
constexpr int SM_FQ = SM_FV + 512;
constexpr int SM_CLS = SM_FQ + 128;
constexpr int SM_W = SM_FQ + 256;
constexpr int SM_W2 = SM_MX + 2304;
constexpr int SM_SCR = SM_XA + 9216;
constexpr int SM_TR = SM_XB + 19456;
constexpr int SM_BAR = SM_W + 256;
constexpr int SM_TOTAL = SM_BAR + 1024;
static_assert(SM_TOTAL <= 232448, "smem");

enum { IT_MODA = 0, IT_WQ = 1, IT_WUK = 5, IT_CKV = 9, IT_WUV = 41, IT_WO = 45, IT_X = 49  , IT_DOWN = 53, NITEMS = 57,
       NEVER = 63,
       SF0 = 64,
       PF0 = 80,
       EB_UNIT0 = 96, MBB = 103,
       EB_WQ = 104, EB_WUK, QT, QB, JD, WR };

enum { MP_WQ = 0, MP_WUK, MP_CKV, MP_WUV, MP_DOWN, MP_WO, MP_GATE, MP_UP, MP_MODB, NMAPS };
struct First { const uint8_t* w[2]; const __nv_bfloat16* v[2]; };
struct Maps { CUtensorMap m[NMAPS]; uint2 sched[3][58]; };

enum { B_HA = 0,
       B_MB = 6,
       B_RD = 7,
       B_E2 = 8,
       B_QA = 16,
       B_ML = 32,
       B_E5 = 64,
       B_E3 = 80,
       B_PR = 96,
       B_TR = 100 };
constexpr int G_E1 = 1 << 19;
constexpr int G_TR = B_TR * 4096;
__device__ __align__(1024) uint32_t g_scratch[(8 << 20) / 4];

#define TRACE(slot) do {} while (0)
#define TRACE_Q(slot) do {} while (0)
#define TRACE_GT(slot) do {} while (0)

__device__ __forceinline__ uint32_t s2u(const void* p) { return (uint32_t)__cvta_generic_to_shared(p); }
__device__ __forceinline__ void mbar_init(uint32_t b, int c) { asm volatile("mbarrier.init.shared::cta.b64 [%0], %1;" :: "r"(b), "r"(c) : "memory"); }
__device__ __forceinline__ void mbar_expect(uint32_t b, uint32_t bytes) { asm volatile("mbarrier.arrive.expect_tx.shared::cta.b64 _, [%0], %1;" :: "r"(b), "r"(bytes) : "memory"); }
__device__ __forceinline__ void mbar_arrive(uint32_t b) { asm volatile("mbarrier.arrive.shared::cta.b64 _, [%0];" :: "r"(b) : "memory"); }
__device__ __forceinline__ void mbar_wait(uint32_t b, uint32_t ph) {
    asm volatile("{\n.reg .pred p;\nW: mbarrier.try_wait.parity.shared::cta.b64 p, [%0], %1;\n@!p bra W;\n}" :: "r"(b), "r"(ph) : "memory");
}
__device__ __forceinline__ void mbar_waitb(uint32_t b, uint32_t ph) {
    asm volatile("{\n.reg .pred p;\n.reg .u32 n;\nmov.u32 n, 0;\n"
                 "W: mbarrier.try_wait.parity.shared::cta.b64 p, [%0], %1;\n@p bra D;\n"
                 "add.u32 n, n, 1;\nsetp.lt.u32 p, n, 0x100000;\n@p bra W;\ntrap;\nD:\n}" :: "r"(b), "r"(ph) : "memory");
}
__device__ __forceinline__ uint32_t mbar_test(uint32_t b, uint32_t ph) {
    uint32_t ok;
    asm volatile("{\n.reg .pred p;\nmbarrier.test_wait.parity.shared::cta.b64 p, [%1], %2;\nselp.u32 %0, 1, 0, p;\n}" : "=r"(ok) : "r"(b), "r"(ph) : "memory");
    return ok;
}
__device__ __forceinline__ void bar_sync(int id, int n) { asm volatile("bar.sync %0, %1;" :: "r"(id), "r"(n) : "memory"); }
__device__ __forceinline__ void bar_arrive(int id, int n) { asm volatile("bar.arrive %0, %1;" :: "r"(id), "r"(n) : "memory"); }
__device__ __forceinline__ uint32_t peer_addr(uint32_t a, uint32_t rank) { uint32_t r; asm("mapa.shared::cluster.u32 %0, %1, %2;" : "=r"(r) : "r"(a), "r"(rank)); return r; }
__device__ __forceinline__ void st_async2(uint32_t a, float x, float y, uint32_t bar) {
    asm volatile("st.async.weak.shared::cluster.mbarrier::complete_tx::bytes.v2.f32 [%0], {%1, %2}, [%3];" :: "r"(a), "f"(x), "f"(y), "r"(bar) : "memory");
}
__device__ __forceinline__ uint32_t gtime() { uint32_t t; asm volatile("mov.u32 %0, %%globaltimer_lo;" : "=r"(t)); return t; }
__device__ __forceinline__ void fence_gpu() { asm volatile("fence.acq_rel.gpu;" ::: "memory"); }

__device__ __forceinline__ uint32_t enc(uint32_t b) { uint32_t r; asm("max.u32 %0, %1, 1;" : "=r"(r) : "r"(b)); return r; }
__device__ __forceinline__ uint32_t encf(float f) { return enc(__float_as_uint(f)); }
__device__ __forceinline__ void st_x1(uint32_t* p, uint32_t v) { asm volatile("st.relaxed.gpu.global.u32 [%0], %1;" :: "l"(p), "r"(v) : "memory"); }
__device__ __forceinline__ void st_x4(void* p, uint32_t a, uint32_t b, uint32_t c, uint32_t d) {
    asm volatile("st.relaxed.gpu.global.v4.u32 [%0], {%1, %2, %3, %4};" :: "l"(p), "r"(a), "r"(b), "r"(c), "r"(d) : "memory");
}
__device__ __forceinline__ void st2_x1(uint32_t* p, uint32_t v) { st_x1(p, v); st_x1(p + 1024, v); }
__device__ __forceinline__ void st2_x4(uint32_t* p, uint32_t a, uint32_t b, uint32_t c, uint32_t d) { st_x4(p, a, b, c, d); st_x4(p + 1024, a, b, c, d); }
__device__ __forceinline__ int near_off(int b, uint32_t cls) { return b * 4096 + (((__popc(b & 0x2C) ^ cls) & 1) << 10); }
__device__ __forceinline__ void ld_x(uint32_t& v, const void* p) { asm volatile("ld.relaxed.gpu.global.u32 %0, [%1];" : "=r"(v) : "l"(p) : "memory"); }
__device__ __forceinline__ void ld_x(uint4& v, const void* p) {
    asm volatile("ld.relaxed.gpu.global.v4.u32 {%0, %1, %2, %3}, [%4];" : "=r"(v.x), "=r"(v.y), "=r"(v.z), "=r"(v.w) : "l"(p) : "memory");
}
__device__ __forceinline__ void ld_x(uint2& v, const void* p) { asm volatile("ld.relaxed.gpu.global.v2.u32 {%0, %1}, [%2];" : "=r"(v.x), "=r"(v.y) : "l"(p) : "memory"); }
__device__ __forceinline__ uint32_t minw(uint32_t v) { return v; }
__device__ __forceinline__ uint32_t minw(const uint2& v) { return min(v.x, v.y); }
__device__ __forceinline__ uint32_t minw(const uint4& v) { return min(__vimin3_u32(v.x, v.y, v.z), v.w); }
template <int N> __device__ __forceinline__ uint32_t mint(const uint32_t* m) {
    if constexpr (N == 1) return m[0];
    else if constexpr (N == 2) return min(m[0], m[1]);
    else return __vimin3_u32(mint<(N + 2) / 3>(m), mint<(N + 1) / 3>(m + (N + 2) / 3), mint<N / 3>(m + (N + 2) / 3 + (N + 1) / 3));
}

template <int STRIDE, int S4 = 4 * STRIDE, typename T, int N>
__device__ __forceinline__ void poll_start(T (&v)[N], const void* base) {
#pragma unroll
    for (int i = 0; i < N; i++) ld_x(v[i], (const uint8_t*)base + (i & 3) * STRIDE + (i >> 2) * S4);
}
struct Nop { __device__ void operator()() const {} };
template <int STRIDE, int SLEEP, bool STARTED = false, int S4 = 4 * STRIDE, typename T, int N, typename F = Nop, typename G = Nop>
__device__ __forceinline__ void poll(T (&v)[N], const void* base, F idle = F(), G ahead = G()) {
    if (!STARTED) { poll_start<STRIDE, S4>(v, base); idle(); }
#pragma unroll 1
    for (uint32_t it = 0;; it++) {
        uint32_t m[N];
        ahead();
#pragma unroll
        for (int i = 0; i < N; i++) m[i] = minw(v[i]);
        if (__all_sync(0xffffffffu, mint<N>(m) != 0)) break;
        if (SLEEP && it > 0) __nanosleep(SLEEP);
#pragma unroll
        for (int i = 0; i < N; i++) if (!m[i]) ld_x(v[i], (const uint8_t*)base + (i & 3) * STRIDE + (i >> 2) * S4);
        idle();
        if (it > SPIN_LIMIT) __trap();
    }
}

__device__ __forceinline__ float bflo(uint32_t w) { return __uint_as_float(w << 16); }
__device__ __forceinline__ float bfhi(uint32_t w) { return __uint_as_float(w & 0xffff0000u); }
__device__ __forceinline__ uint32_t pack2(float lo, float hi) {
    uint32_t r; asm("cvt.rn.bf16x2.f32 %0, %1, %2;" : "=r"(r) : "f"(hi), "f"(lo)); return r;
}
__device__ __forceinline__ float rbf(float x) { return __uint_as_float(pack2(0.f, x)); }
__device__ __forceinline__ float ex2(float x) { float r; asm("ex2.approx.ftz.f32 %0, %1;" : "=f"(r) : "f"(x)); return r; }
__device__ __forceinline__ float shx(float v, int m) { return __shfl_xor_sync(0xffffffffu, v, m); }
__device__ __forceinline__ uint4 lds128(uint32_t a) { uint4 v; asm volatile("ld.shared.v4.u32 {%0, %1, %2, %3}, [%4];" : "=r"(v.x), "=r"(v.y), "=r"(v.z), "=r"(v.w) : "r"(a) : "memory"); return v; }
__device__ __forceinline__ uint32_t lds32(uint32_t a) { uint32_t v; asm volatile("ld.shared.u32 %0, [%1];" : "=r"(v) : "r"(a) : "memory"); return v; }
__device__ __forceinline__ void sts32(uint32_t a, uint32_t v) { asm volatile("st.shared.u32 [%0], %1;" :: "r"(a), "r"(v) : "memory"); }
__device__ __forceinline__ void sts16(uint32_t a, uint32_t v) { asm volatile("st.shared.u16 [%0], %1;" :: "r"(a), "h"((uint16_t)v) : "memory"); }
__device__ __forceinline__ int frag_off(int k) { return (k >> 5) * 64 + ((k >> 1) & 3) * 16 + ((k >> 4) & 1) * 8 + ((k >> 3) & 1) * 4 + (k & 1) * 2; }

template <bool TRANS>
__device__ __forceinline__ uint4 ldsm(uint32_t a) {
    uint4 r;
    if (TRANS) asm volatile("ldmatrix.sync.aligned.m8n8.x4.trans.shared.b16 {%0, %1, %2, %3}, [%4];" : "=r"(r.x), "=r"(r.y), "=r"(r.z), "=r"(r.w) : "r"(a) : "memory");
    else asm volatile("ldmatrix.sync.aligned.m8n8.x4.shared.b16 {%0, %1, %2, %3}, [%4];" : "=r"(r.x), "=r"(r.y), "=r"(r.z), "=r"(r.w) : "r"(a) : "memory");
    return r;
}
__device__ __forceinline__ void mma(float (&c)[4], uint32_t a0, uint32_t a1, uint32_t a2, uint32_t a3, uint32_t b0, uint32_t b1) {
    asm volatile("mma.sync.aligned.m16n8k16.row.col.f32.bf16.bf16.f32 {%0,%1,%2,%3}, {%4,%5,%6,%7}, {%8,%9}, {%0,%1,%2,%3};"
                 : "+f"(c[0]), "+f"(c[1]), "+f"(c[2]), "+f"(c[3]) : "r"(a0), "r"(a1), "r"(a2), "r"(a3), "r"(b0), "r"(b1));
}
template <bool TRANS, typename F>
__device__ __forceinline__ void load8(uint4 (&a)[8], F addr) {
    __syncwarp();
#pragma unroll
    for (int s = 0; s < 8; s++) a[s] = ldsm<TRANS>(addr(s));
}
__device__ __forceinline__ void mma8(float (&c)[4], const uint4 (&a)[8], const uint4 (&b)[4]) {
    float e[4][4];
#pragma unroll
    for (int s = 0; s < 8; s++) {
        if (s < 4) e[s][0] = e[s][1] = e[s][2] = e[s][3] = 0.f;
        mma(e[s & 3], a[s].x, a[s].y, a[s].z, a[s].w, (s & 1) ? b[s >> 1].z : b[s >> 1].x, (s & 1) ? b[s >> 1].w : b[s >> 1].y);
    }
#pragma unroll
    for (int i = 0; i < 4; i++) c[i] = (e[0][i] + e[1][i]) + (e[2][i] + e[3][i]);
}
__device__ __forceinline__ void ldfrag(uint4 (&b)[4], uint32_t a) {
    asm volatile("ld.shared.v4.u32 {%0,%1,%2,%3}, [%16];\nld.shared.v4.u32 {%4,%5,%6,%7}, [%16+64];\n"
                 "ld.shared.v4.u32 {%8,%9,%10,%11}, [%16+128];\nld.shared.v4.u32 {%12,%13,%14,%15}, [%16+192];\n"
                 : "=r"(b[0].x), "=r"(b[0].y), "=r"(b[0].z), "=r"(b[0].w), "=r"(b[1].x), "=r"(b[1].y), "=r"(b[1].z), "=r"(b[1].w),
                   "=r"(b[2].x), "=r"(b[2].y), "=r"(b[2].z), "=r"(b[2].w), "=r"(b[3].x), "=r"(b[3].y), "=r"(b[3].z), "=r"(b[3].w) : "r"(a) : "memory");
}
__device__ __forceinline__ void quad_pair(float x, float y, int t, float& lo, float& hi) {
    const float k = ((t & 1) ? y : x) + shx((t & 1) ? x : y, 1);
    lo = k + shx(k, 2); hi = shx(k, 4) + shx(k, 6);
}
__device__ __forceinline__ void pin(uint32_t& x) { asm volatile("" : "+r"(x)); }
template <typename T> __device__ __forceinline__ void pin(T*& x) { asm volatile("" : "+l"(x)); }
__device__ __forceinline__ float4 ldsf4(uint32_t a) { const uint4 v = lds128(a); return make_float4(__uint_as_float(v.x), __uint_as_float(v.y), __uint_as_float(v.z), __uint_as_float(v.w)); }
__device__ __forceinline__ float sum4(const float4& f) { return (f.x + f.y) + (f.z + f.w); }
__device__ __forceinline__ void stsf(uint32_t a, float v) { sts32(a, __float_as_uint(v)); }

__device__ __forceinline__ void wg_fence() { asm volatile("wgmma.fence.sync.aligned;" ::: "memory"); }
__device__ __forceinline__ void wg_commit() { asm volatile("wgmma.commit_group.sync.aligned;" ::: "memory"); }
__device__ __forceinline__ void wg_wait1() { asm volatile("wgmma.wait_group.sync.aligned 1;" ::: "memory"); }
__device__ __forceinline__ void wg_wait0() { asm volatile("wgmma.wait_group.sync.aligned 0;" ::: "memory"); }
#define R8(o) "+f"(d[o]), "+f"(d[o + 1]), "+f"(d[o + 2]), "+f"(d[o + 3]), "+f"(d[o + 4]), "+f"(d[o + 5]), "+f"(d[o + 6]), "+f"(d[o + 7])
__device__ __forceinline__ void wgmma_rs_n32(float (&d)[16], const uint4& a, uint64_t db, int acc) {
    asm volatile("{\n.reg .pred p;\nsetp.ne.b32 p, %21, 0;\n"
        "wgmma.mma_async.sync.aligned.m64n32k16.f32.bf16.bf16 "
        "{%0,%1,%2,%3,%4,%5,%6,%7,%8,%9,%10,%11,%12,%13,%14,%15}, {%16,%17,%18,%19}, %20, p, 1, 1, 0;\n}"
        : R8(0), R8(8) : "r"(a.x), "r"(a.y), "r"(a.z), "r"(a.w), "l"(db), "r"(acc));
}
#define PV_LO "{%0,%1,%2,%3,%4,%5,%6,%7,%8,%9,%10,%11,%12,%13,%14,%15,%16,%17,%18,%19,%20,%21,%22,%23,%24,%25,%26,%27,%28,%29,%30,%31,%32,%33,%34,%35,%36,%37,%38,%39,%40,%41,%42,%43,%44,%45,%46,%47,%48,%49,%50,%51,%52,%53,%54,%55,%56,%57,%58,%59,%60,%61,%62,%63}, "
#define PV_HI "{%64,%65,%66,%67,%68,%69,%70,%71,%72,%73,%74,%75,%76,%77,%78,%79,%80,%81,%82,%83,%84,%85,%86,%87,%88,%89,%90,%91,%92,%93,%94,%95,%96,%97,%98,%99,%100,%101,%102,%103,%104,%105,%106,%107,%108,%109,%110,%111,%112,%113,%114,%115,%116,%117,%118,%119,%120,%121,%122,%123,%124,%125,%126,%127}, "
__device__ __forceinline__ void wgmma_pv(float (&d)[128], const uint4& a, uint32_t blo, int acc) {
    asm volatile("{\n.reg .pred p;\n.reg .b32 u0, u1, u2, u3, t;\n.reg .b64 d0, d1, d2, d3;\nsetp.ne.b32 p, %133, 0;\n"
        "mov.b64 d0, {%132, 0x40000100};\nadd.u32 t, %132, 512;\nmov.b64 d1, {t, 0x40000100};\n"
        "add.u32 t, %132, 128;\nmov.b64 d2, {t, 0x40000100};\nadd.u32 t, %132, 640;\nmov.b64 d3, {t, 0x40000100};\n"
        "wgmma.fence.sync.aligned;\n"
        "wgmma.mma_async.sync.aligned.m64n128k16.f32.bf16.bf16 " PV_LO "{%128, u0, %129, u1}, d0, p, 1, 1, 1;\n"
        "wgmma.mma_async.sync.aligned.m64n128k16.f32.bf16.bf16 " PV_LO "{%130, u2, %131, u3}, d1, 1, 1, 1, 1;\n"
        "wgmma.commit_group.sync.aligned;\n"
        "wgmma.mma_async.sync.aligned.m64n128k16.f32.bf16.bf16 " PV_HI "{%128, u0, %129, u1}, d2, p, 1, 1, 1;\n"
        "wgmma.mma_async.sync.aligned.m64n128k16.f32.bf16.bf16 " PV_HI "{%130, u2, %131, u3}, d3, 1, 1, 1, 1;\n"
        "wgmma.commit_group.sync.aligned;\n}"
        : R8(0), R8(8), R8(16), R8(24), R8(32), R8(40), R8(48), R8(56), R8(64), R8(72), R8(80), R8(88), R8(96), R8(104), R8(112), R8(120)
        : "r"(a.x), "r"(a.y), "r"(a.z), "r"(a.w), "r"(blo), "r"(acc) : "memory");
}

template <int NW>
__device__ __forceinline__ void ln_stats(float s, float q, float sh, float* scr, int w, int lane, int bar, float& mean_b, float& sd_b) {
#pragma unroll
    for (int o = 16; o; o >>= 1) { s += shx(s, o); q += shx(q, o); }
    constexpr float n = 512.f / NW;
    if (lane == 0) { scr[w] = sh + s * (1.f / n); scr[NW + w] = q - s * s * (1.f / n); }
    bar_sync(bar, NW * 32);
    float mu = 0.f, m2 = 0.f;
#pragma unroll
    for (int i = 0; i < NW; i++) { mu += scr[i]; m2 += scr[NW + i]; }
    mu *= 1.f / NW;
#pragma unroll
    for (int i = 0; i < NW; i++) { const float d = scr[i] - mu; m2 = fmaf(n * d, d, m2); }
    mean_b = rbf(mu);
    sd_b = rbf(sqrtf(rbf(rbf(fmaxf(m2, 0.f) * (1.f / 512.f)) + 1e-5f)));
}
__device__ __forceinline__ float ln_mod(float x, float mean_b, float sd_b, float c, float s) {
    return rbf(rbf(__fdividef(rbf(x - mean_b), sd_b)) * rbf(1.f + c)) + s;
}

__global__ void __cluster_dims__(2, 1, 1) __launch_bounds__(NTHREADS, 1)
fused_kernel(const __grid_constant__ First F, __nv_bfloat16* __restrict__ out, uint32_t* __restrict__ gs, const __grid_constant__ Maps M) {
    extern __shared__ __align__(1024) uint8_t sm[];
    const uint32_t sb = s2u(sm);
    const int tid = threadIdx.x, lane = tid & 31;
    const int j = blockIdx.x, rk = j & 1;
    const int g = lane >> 2, t = lane & 3;
    const int r8 = lane & 7, lb3 = (lane >> 3) & 1, lb4 = lane >> 4;
    uint64_t pol;
    asm("createpolicy.fractional.L2::evict_first.b64 %0, 1.0;" : "=l"(pol));
    {
        auto cpa = [&](uint32_t d, const uint8_t* s) {
            asm volatile("cp.async.cg.shared.global.L2::cache_hint.L2::128B [%0], [%1], 16, %2;" :: "r"(d), "l"(s), "l"(pol) : "memory");
        };
        const uint32_t ut = threadIdx.x, uj = blockIdx.x;
        const uint8_t* w = F.w[ut >= 128];
        if (ut < 128) {
            const uint32_t dq = (sb + ut * 16) ^ ((ut * 2) & 0x70);
            const uint8_t* sq = w + (uint32_t)(((uj & 1) * 256 + (ut >> 3)) * 8192 + (uj >> 1) * 128 + (ut & 7) * 16);
#pragma unroll
            for (int i = 0; i < 4 * NCP; i++) cpa(dq + 4 * 32768 + i * 2048, sq + i * 131072);
        } else if (ut < 384) {
            const uint32_t dm = (sb + ut * 16) ^ ((ut * 2) & 0x10);
            const uint8_t* sa = w + (uint32_t)(((uj >> 5) * 128 + (ut >> 1) - 64) * 6144 + (uj & 31) * 32 + (ut & 1) * 16);
            cpa(dm + SM_XA - 2048, sa); cpa(dm + SM_XA + 2048, sa + 1024);
        }
        else if (ut == 480 && uj < 64) asm volatile("prefetch.global.L2 [%0];" :: "l"(F.v[(uj >> 3) & 1] + (uj & 7) * 64));
    }
    const int warp = __shfl_sync(0xffffffffu, tid >> 5, 0);
    const __nv_bfloat16* const xin = F.v[0];
    uint32_t* const pl = gs + (warp < 2 ? (B_PR + (j >> 5)) * 4096 + (j & 31) * 32 : G_E1 + j * 8192) + (warp & 1) * 1024 + lane;
    if (warp < 4) st_x1(pl, 1u);
    auto BAR = [&](int i) -> uint32_t { return sb + SM_BAR + i * 8; };
    const uint32_t a16 = (r8 + 8 * lb4) * 32 + ((lb3 ^ (r8 >> 2)) * 16);
    const uint32_t a128 = (r8 + 8 * lb4) * 128 + ((((warp & 3) * 2 + lb3) ^ r8) * 16);
    auto ldcls = [&]() -> uint32_t { return *(const volatile uint32_t*)(sm + SM_CLS); };
    auto clear_head = [&]() {
        st2_x1(gs + (B_HA + ((j >> 4) & 1) * 2 + lb4) * 4096 + (j >> 5) * 256 + (j & 15) * 16 + (lane & 15), 0u);
        st2_x4(gs + (B_QA + rk * 8 + ((j >> 1) & 1) * 4 + (j >> 5)) * 4096 + g * 128 + ((j >> 2) & 7) * 16 + t * 4, 0u, 0u, 0u, 0u);
        if (lane < 8) st2_x1(gs + B_RD * 4096 + j * 8 + lane, 0u);
    };
    auto tma = [&](uint32_t dst, const CUtensorMap* mp, uint32_t bar, int c0, int c1, int c2, int c3) {
        asm volatile("{\n.reg .pred p;\nelect.sync _|p, 0xffffffff;\n"
                     "@p cp.async.bulk.tensor.4d.shared::cluster.global.mbarrier::complete_tx::bytes.L2::cache_hint [%0], [%1, {%3, %4, %5, %6}], [%2], %7;\n}"
                     :: "r"(dst), "l"(mp), "r"(bar), "r"(c0), "r"(c1), "r"(c2), "r"(c3), "l"(pol) : "memory");
    };
    if (warp <= 12 || warp == 15) {
        const int grp = warp == 12 ? 0 : warp == 15 ? 13 : warp + 1;
        const uint32_t cnt = grp < 10 ? 1 : grp < 13 ? 4 : 8;
        if (lane == 0) {
#pragma unroll
            for (int i = 0; i < 8; i++) mbar_init(BAR(grp * 8 + i), (i < 2 && grp == 0) ? (i ? 128 : 256) : cnt);
        }
        __syncwarp();
        if (grp < 10 && lane < 8 && (grp || lane > NCP)) mbar_expect(BAR(grp * 8 + lane), grp >= 8 ? 4096 : (uint32_t)(grp * 8 + lane - IT_X) < 4 ? 16384 : 8192);
        asm volatile("fence.mbarrier_init.release.cluster;" ::: "memory");
        __syncwarp();
        if (warp == 12) {
#pragma unroll
            for (int i = NCP + 1; i < W0; i++) tma(sb + (15 + i) * 8192, &M.m[MP_WQ], BAR(i), 0, rk * 256 + (i - 1) * 64, j >> 1, 0);
        }
    } else if (warp == 13) {
        if (lane < NMAPS) asm volatile("prefetch.tensormap [%0];" :: "l"(&M.m[lane]) : "memory");
    } else if (warp == 14) {
        clear_head();
    }
    __syncthreads();
    uint32_t in1 = 0, in2 = 0;
    if (warp < 4) { in1 = *(const uint32_t*)(xin + 2 * tid); in2 = *(const uint32_t*)(xin + 256 + 2 * tid); }
    else if (warp < 12) in1 = *(const uint32_t*)(F.v[1] + 2 * (tid - 128));
    if (warp < 12) asm volatile("cp.async.mbarrier.arrive.noinc.shared::cta.b64 [%0];" :: "r"(BAR(warp < 4)) : "memory");
    asm volatile("barrier.cluster.arrive.relaxed.aligned;" ::: "memory");

    if (warp >= 12) {
    asm volatile("setmaxnreg.dec.sync.aligned.u32 64;");
    if (warp == 12) {
        static_assert(W0 > NCP && W0 <= 5 && NCP >= 1 && NCP <= 4, "W0");
        const uint2* sched = M.sched[j < NFF ? 0 : j < J_RED ? 1 : 2];
        uint2 en = sched[W0];
        const uint32_t t0 = gtime();
        const uint32_t sp = __reduce_or_sync(0xffffffffu, sb);
        const int cx = (j >> 1) * 64 + (j < NFF ? 0 : 1024 - NFF * 32);
#pragma unroll 1
        for (int i = W0; en.x; i++) {
            uint32_t e = en.x, st = (en.y >> 20) * 64;
            const uint32_t tn = t0 + (int16_t)en.y, mp = (en.y >> 16) & 15;
            if (mp == MP_WUV || mp == MP_WUK) { st ^= (j >> 5) * (mp == MP_WUV ? 128 : 64); e ^= (j >> 5) << 6; }
            if (mp == MP_GATE || mp == MP_UP) st ^= (j & 16) * 8;
            if (mp == MP_DOWN) { st ^= (j & 3) * 64; e ^= (j & 3) << 6; }
            en = sched[i + 1];
            if (mp == MP_MODB && j >= J_END) break;
            uint32_t c0 = mp == MP_WO ? (j & 7) * 64 : mp > MP_WO ? cx : 0;
            uint32_t c1 = mp == MP_CKV ? 0 : mp == MP_DOWN ? j * 32 : st + (mp == MP_WUV ? (j & 3) * 32 : mp == MP_WO ? (j >> 3) * 256 : rk * 256);
            uint32_t c2 = mp < MP_CKV ? j >> 1 : mp == MP_CKV ? rk * 4 : mp == MP_WUV ? (j >> 2) * 2 : mp == MP_DOWN ? st >> 5 : 0;
            uint32_t c3 = mp == MP_CKV ? st * 2 + (j & ~1) : 0;
            uint32_t dst = sp + ((e << 7) & 0x3e000), bar = sp + SM_BAR + (e & 63) * 8;
            const uint32_t w0 = (e >> 8) & 0x3f8, w1 = (e >> 15) & 0x3f8, w2 = (e >> 22) & 0x3f8, bb = sp + SM_BAR - 8;
            const CUtensorMap* pm = &M.m[mp];
            pin(dst); pin(bar); pin(c0); pin(c1); pin(c2); pin(c3); pin(pm);
            if (w0) mbar_wait(bb + w0, 0);
            if (w2) {
                mbar_wait(bb + w2, 0);
                while (!__any_sync(0xffffffffu, mbar_test(bb + w1, 0) | ((int)(gtime() - tn) > 0))) {}
            } else if (w1) mbar_wait(bb + w1, 0);
            tma(dst, pm, bar, c0, c1, c2, c3);
        }
    } else if (warp == 13) {
#pragma unroll
        for (int i = 0; i < 2; i++) st_x4(gs + (B_ML + rk * 16 + i * 8 + g) * 4096 + (t >> 1) * 1024 + (j >> 1) * 8 + (t & 1) * 4, 0u, 0u, 0u, 0u);
        if (lane < 16) st2_x4(gs + (B_E2 + (j >> 4)) * 4096 + (j & 15) * 64 + lane * 4, 0u, 0u, 0u, 0u);
        st2_x1(gs + (B_E3 + (j >> 5)) * 4096 + (j & 31) * 32 + lane, 0u);
        if (lane < 8) st2_x1(gs + B_MB * 4096 + j * 8 + lane, 0u);
        if (j < NFF) {
#pragma unroll
            for (int i = 0; i < 2; i++) st2_x4(gs + (B_E5 + i * 8 + g) * 4096 + j * 16 + t * 4, 0u, 0u, 0u, 0u);
        }
        bar_sync(9, 64);
        const uint32_t cs = ldcls();
#pragma unroll 1
        for (int i = 0; i < 32; i++) {
            st_x4(gs + G_E1 + j * 8192 + (i >> 3) * 2048 + ((((cs >> 1) ^ (i >> 3)) & 1) << 10) + (i & 7) * 128 + lane * 4, 0u, 0u, 0u, 0u);
            __nanosleep(JAN_SLEEP);
        }
        fence_gpu();
        if (lane < 8) st2_x1(gs + B_RD * 4096 + j * 8 + lane, 1u + (cs >> 1));
        if (lane == 0) TRACE(41);
        uint32_t rd[4];
        mbar_wait(BAR(IT_CKV + RD_ITEM), 0);
        poll<1024, RD_SLEEP>(rd, gs + near_off(B_RD, cs) + lane * 8);
#pragma unroll
        for (int i = 0; i < 4; i++) {
            const uint32_t m = __ballot_sync(0xffffffffu, rd[i] == 2u);
            if (lane == 0) sts32(sb + SM_CLS + 16 + i * 4, m);
        }
        __syncwarp();
        if (lane < 8) mbar_arrive(BAR(JD));
        if (lane == 0) TRACE(42);
    } else if (warp == 14) {
        uint2 ml[2];
        mbar_waitb(BAR(JD), 0);
        const uint32_t cls = ldcls();
        mbar_waitb(BAR(PF0 + 2 * NUNITS - 1), 0);
        __nanosleep(ML_DELAY);
        const uint32_t* pl2 = gs + near_off(B_ML + (j >> 2), cls) + lane * 8;
        const uint32_t wa = sb + SM_W + lb4 * 64 + t * 16 + (g & 3) * 4;
        poll_start<1024>(ml, pl2);
        uint32_t w0 = 0, w1 = 0, redo = 0;
        bool first = true;
#pragma unroll 1
        for (uint32_t it = 0;; it++) {
            const bool p0 = minw(ml[0]) != 0, p1 = minw(ml[1]) != 0;
            const int n = __popc(__ballot_sync(0xffffffffu, p0)) + __popc(__ballot_sync(0xffffffffu, p1));
            const uint32_t x0 = ml[0].x, x1 = ml[1].x;
            if (n < 64) {
                if (!p0) ld_x(ml[0], pl2);
                if (!p1) ld_x(ml[1], pl2 + 256);
            }
            if (n == 64 || (first && n >= E1_EARLY)) {
                auto ord = [](int x) { return x ^ ((x >> 31) & 0x7fffffff); };
                const int o0 = ord(x0), o1 = ord(x1);
                const float mm = __int_as_float(ord(__reduce_max_sync(0xffffffffu, max(p0 ? o0 : INT_MIN, p1 ? o1 : INT_MIN))));
                const float lo = __int_as_float(ord(__reduce_min_sync(0xffffffffu, min(p0 ? o0 : INT_MAX, p1 ? o1 : INT_MAX))));
                const uint32_t v0 = pack2(ex2((p0 ? __uint_as_float(x0) : lo) - mm), 0.f), v1 = pack2(ex2((p1 ? __uint_as_float(x1) : lo) - mm), 0.f);
                redo = !first && __any_sync(0xffffffffu, v0 != w0 || v1 != w1);
                w0 = v0; w1 = v1;
                sts32(wa - redo * (SM_W - SM_W2), w0 * 0x10001u); sts32(wa - redo * (SM_W - SM_W2) + 128, w1 * 0x10001u);
                if (first) bar_arrive(3, 416);
                first = false;
                if (n == 64) break;
            }
            if (it > SPIN_LIMIT) __trap();
        }
        if (lane == 0) TRACE_Q(37);
        float L = bflo(w0) * __uint_as_float(ml[0].y) + bflo(w1) * __uint_as_float(ml[1].y);
#pragma unroll
        for (int o = 16; o; o >>= 1) L += shx(L, o);
        if (lane == 0) *(float2*)(sm + SM_FQ) = make_float2(__frcp_rn(L), __uint_as_float(redo));
        __syncwarp();
        if (lane < 8) mbar_arrive(BAR(WR));
        if (lane == 0) TRACE(10);
        bar_sync(4, 416);
        clear_head();
        if (j < NFF) {
            uint32_t ya = sb + SM_Y + lane * 16, sa = peer_addr(sb + SM_RED + 2048 + rk * 8, lane & 1), tb = peer_addr(BAR(MBB), lane & 1);
            pin(ya); pin(sa); pin(tb);
            bar_sync(7, 288);
            const float4 y0 = ldsf4(ya), y1 = ldsf4(ya + 512);
            float s = sum4(y0) + sum4(y1);
            float q = (fmaf(y0.x, y0.x, y0.y * y0.y) + fmaf(y0.z, y0.z, y0.w * y0.w)) + (fmaf(y1.x, y1.x, y1.y * y1.y) + fmaf(y1.z, y1.z, y1.w * y1.w));
#pragma unroll
            for (int o = 16; o; o >>= 1) { s += shx(s, o); q += shx(q, o); }
            if (lane < 2) st_async2(sa, s, q, tb);
        }
    } else if (warp == 15) {
        mbar_waitb(BAR(IT_X - 1), 0);
        if (j < J_END) mbar_waitb(BAR(j < NFF ? NITEMS - 1 : MBB), 0);
    }
    } else if (warp < 4) {
        float* scr = (float*)(sm + SM_SCR);
        uint32_t cls;
        {
            uint2 ha[8];
            uint32_t best = 0xffffffffu;
            sts32(sb + SM_SCR + 64 + warp * 4, best);
            const float sh = __shfl_sync(0xffffffffu, bflo(in1), 0);
            const float v0 = bflo(in1) - sh, v1 = bfhi(in1) - sh, v2 = bflo(in2) - sh, v3 = bfhi(in2) - sh;
            float mb, sd;
            ln_stats<4>((v0 + v1) + (v2 + v3), (v0 * v0 + v1 * v1) + (v2 * v2 + v3 * v3), sh, scr, warp, lane, 2, mb, sd);
            if (!rk) in2 = in1;
#pragma unroll 1
            for (int i = 0; i < NPROBE; i++) {
                uint32_t t0, t1, o;
                asm volatile("mov.u32 %0, %%clock;" : "=r"(t0));
                asm volatile("atom.relaxed.gpu.global.exch.b32 %0, [%1], %2;" : "=r"(o) : "l"(pl), "r"(2u + i) : "memory");
                asm volatile("{\n.reg .pred p;\nsetp.ne.u32 p, %1, 0x1234567;\nmov.u32 %0, 0;\n@p mov.u32 %0, %%clock;\n}" : "=r"(t1) : "r"(o));
                best = min(best, t1 - t0);
                sts32(sb + SM_SCR + 64 + warp * 4, best);
                if (__all_sync(0xffffffffu, min(best, lds32(sb + SM_SCR + 64 + (warp ^ 1) * 4)) < NEAR_CLK)) break;
            }
            bar_sync(2, 128);
            const uint4 lt = *(const uint4*)(scr + 16);
            cls = NUMA ? ((lt.y < lt.x) ^ (__popc((B_PR + (j >> 5)) & 0x2C) & 1)) | (lt.w < lt.z) << 1 : 0;
            if (warp == 0) { if (lane == 0) sts32(sb + SM_CLS, cls); bar_arrive(9, 64); }
            if (tid == 0) TRACE(38);
            asm volatile("barrier.cluster.wait.aligned;" ::: "memory");
            mbar_wait(BAR(IT_MODA), 0);
            if (HA_DELAY) __nanosleep(HA_DELAY);
            poll<1024, H_SLEEP, false, 16384>(ha, gs + near_off(B_HA + rk * 2, cls) + 2 * tid);
            auto rsum = [](uint32_t a, uint32_t b, uint32_t c, uint32_t d) { return rbf((__uint_as_float(a) + __uint_as_float(b)) + (__uint_as_float(c) + __uint_as_float(d))); };
            sts32(sb + SM_FV + frag_off(2 * tid),
                  pack2(ln_mod(bflo(in2), mb, sd, rsum(ha[4].x, ha[5].x, ha[6].x, ha[7].x), rsum(ha[0].x, ha[1].x, ha[2].x, ha[3].x)),
                        ln_mod(bfhi(in2), mb, sd, rsum(ha[4].y, ha[5].y, ha[6].y, ha[7].y), rsum(ha[0].y, ha[1].y, ha[2].y, ha[3].y))));
            bar_arrive(5, 384);
            mbar_wait(BAR(QB), 0);
            if (tid < 64) {
                const float* qx = (const float*)(sm + SM_QX) + tid;
                sts16(sb + SM_FQ + frag_off(tid), pack2((qx[0] + qx[64]) + (qx[128] + qx[192]), 0.f));
            }
            bar_arrive(6, 384);
        }
        asm volatile("setmaxnreg.inc.sync.aligned.u32 192;");
        float acc[128];
        float M = 0.f;
        uint32_t pa = sb + SM_XA + warp * 512 + lane * 16, ma = sb + SM_MX + (warp * 8 + g) * 4, pf = BAR(PF0);
        uint32_t blo = __reduce_or_sync(0xffffffffu, (((sb + SM_U) & 0x3FFFFu) >> 4) | 0x400000u);
        uint32_t* e1[4];
#pragma unroll
        for (int i = 0; i < 4; i++) e1[i] = gs + G_E1 + (warp * 8 + g) * 4 * 8192 + (rk * 2 + (j >> 6)) * 2048 + ((j >> 1) & 31) * 32 + t * 4;
#pragma unroll 1
        for (int h = 0; h < 2 * NUNITS; h++) {
            mbar_wait(pf, 0);
            const float m = __uint_as_float(lds32(ma));
            const uint4 pn = lds128(pa);
            wg_wait0();
#pragma unroll
            for (int i = 0; i < 128; i++) asm volatile("" : "+f"(acc[i]) :: "memory");
            if (h == 0) M = m;
            uint32_t b2 = 0x3f803f80u;
            if (__builtin_expect(__any_sync(0xffffffffu, m != M), 0)) {
                const float Mn = fmaxf(M, m), alpha = ex2(M - Mn), beta = ex2(m - Mn);
                M = Mn;
                b2 = pack2(beta, beta);
#pragma unroll
                for (int jj = 0; jj < 32; jj++) { acc[4 * jj] *= alpha; acc[4 * jj + 1] *= alpha; }
            }
            auto mul2 = [](uint32_t x, uint32_t y) { uint32_t r; asm("mul.rn.bf16x2 %0, %1, %2;" : "=r"(r) : "r"(x), "r"(y)); return r; };
            const uint4 p = make_uint4(mul2(pn.x, b2), mul2(pn.y, b2), mul2(pn.z, b2), mul2(pn.w, b2));
            if (tid == 0 && (h & 1)) TRACE_Q(48 + (h >> 1));
            wgmma_pv(acc, p, blo, h);
            if (lane == 0 && h > 0 && !(h & 1)) mbar_arrive(BAR(EB_UNIT0 + (h >> 1) - 1));
            blo += h == 11 ? -11 * 1024 : 1024;
            pa += (h == 5 || h == 11) ? -5 * 2048 : 2048;
            ma += 128; pf += 8;
            if (h == 2 * NUNITS - 3) {
                mbar_wait(BAR(JD), 0);
                const uint32_t hm = (*(const uint32_t*)(sm + SM_CLS + 16 + warp * 4) >> (g * 4)) ^ ((j >> 6) ? 15u : 0u);
#pragma unroll
                for (int i = 0; i < 4; i++) e1[i] += ((hm >> i) & 1) << 10;
            }
        }
#pragma unroll
        for (int vv = 0; vv < 2; vv++) {
            if (vv && M == 1.f) __trap();
            if (vv) wg_wait0(); else wg_wait1();
#pragma unroll
            for (int i = 0; i < 64; i++) asm volatile("" : "+f"(acc[vv * 64 + i]) :: "memory");
            if (tid == 0 && !vv) TRACE_Q(63);
#pragma unroll
            for (int i = 0; i < 4; i++) {
                const float* a = &acc[vv * 64 + i * 16];
                st_x4(e1[i] + i * 8192 + vv * 16, enc(pack2(a[0], a[1])), enc(pack2(a[4], a[5])), enc(pack2(a[8], a[9])), enc(pack2(a[12], a[13])));
            }
        }
        bar_arrive(3, 416);
        if (tid == 0) TRACE_Q(17);
#pragma unroll 1
        for (int pass = 0;; pass++) {
            if (j >= NFF && j < J_END && pass == (j >= J_RED)) {
                uint4 a[8], b[4];
                float c[4], e[4];
                const bool own = (warp >> 1) == rk;
                const uint32_t xa = sb + SM_FV + (warp & 1) * 64 + g * 8;
                if (lane == 0) mbar_expect(BAR(MBB), own ? 64 : 0);
#pragma unroll
                for (int i = 0; i < 2; i++) {
                    ldfrag(b, sb + SM_FS + rk * 512 + i * 256 + t * 16);
                    mbar_wait(BAR(IT_X + i), 0);
                    const uint32_t ab = sb + SM_U + B_X * 32768 + i * 16384 + a128;
                    load8<true>(a, [&](int s) { return ab + s * 2048; });
                    mma8(i ? e : c, a, b);
                }
                c[0] += e[0]; c[2] += e[2];
                if (!own) {
                    if (t == 0) st_async2(peer_addr(xa, rk ^ 1), c[0], c[2], peer_addr(BAR(MBB), rk ^ 1));
                } else {
                    mbar_wait(BAR(MBB), 0);
                    const float2 pp = *(const float2*)(sm + (xa - sb));
                    const float mine = t ? c[2] + pp.y : c[0] + pp.x, other = shx(mine, 4);
                    const uint32_t w = (warp & 1) * 8 + t * 4 + (g >> 1), val = enc(pack2(mine, other));
                    if (t < 2 && !(g & 1)) {
                        if (j < J_RED) st2_x1(gs + B_MB * 4096 + (j - NFF) * 16 + w, val);
                        else sts32(sb + SM_FV + 256 + w * 4, val);
                    }
                    __syncwarp();
                    if (j >= J_RED && lane < 4) mbar_arrive(BAR(QB));
                    if (lane == 0) TRACE(11);
                }
            }
            if (pass) break;
            uint4 a[8], a2[8];
            const uint32_t ab = sb + SM_U + B_WO * 32768 + a128;
            uint32_t* p3 = gs + (B_E3 + ((j >> 1) & 3)) * 4096 + (t >> 1) * 1024 + (rk * 2 + (warp >> 1)) * 256 + (j >> 3) * 16 + (warp & 1) * 8 + (t & 1) * 4 + (g >> 1);
            const uint32_t* pb = gs + near_off(B_E2 + (j >> 4), cls) + (((j >> 3) & 1) * 2 + lb4) * 256 + (lane & 15) * 2;
            pin(p3); pin(pb);
            uint2 bb[8];
            uint2 bq[2] = {make_uint2(0u, 0u), make_uint2(0u, 0u)};
            uint32_t xa = sb + SM_XA + lane * 16;
            pin(xa);
            bool h0 = false, h1 = false;
            auto idle = [&]() {
                if (!h0) {
                    h0 = __all_sync(0xffffffffu, mbar_test(BAR(IT_WO + (t & 1)), 0));
                    if (h0) load8<true>(a, [&](int s) { return ab + s * 2048; });
                }
                if (!h1) {
                    h1 = __all_sync(0xffffffffu, mbar_test(BAR(IT_WO + 2 + (t & 1)), 0));
                    if (h1) load8<true>(a2, [&](int s) { return ab + 16384 + s * 2048; });
                }
            };
            bar_sync(4, 416);
            idle();
            poll<128, 0, true>(bq, pb + warp * 64, idle);
            asm volatile("st.shared.v4.u32 [%0], {%1, %2, %3, %4};" :: "r"(xa + warp * 512), "r"(bq[0].x), "r"(bq[0].y), "r"(bq[1].x), "r"(bq[1].y) : "memory");
            bar_sync(2, 128);
#pragma unroll
            for (int i = 0; i < 4; i++) { const uint4 q = lds128(xa + i * 512); bb[2 * i] = make_uint2(q.x, q.y); bb[2 * i + 1] = make_uint2(q.z, q.w); }
            if (tid == 0) TRACE(21);
            float e[4][4];
#pragma unroll
            for (int s = 0; s < 16; s++) {
                if (s == 0 && !h0) { mbar_wait(BAR(IT_WO), 0); mbar_wait(BAR(IT_WO + 1), 0); load8<true>(a, [&](int q) { return ab + q * 2048; }); }
                if (s == 0 && !h1) { mbar_wait(BAR(IT_WO + 2), 0); mbar_wait(BAR(IT_WO + 3), 0); load8<true>(a2, [&](int q) { return ab + 16384 + q * 2048; }); }
                const int z = (s & 1) | (s & 2) << 2 | (s >> 2) << 1;
                const uint4& x = z < 8 ? a[z] : a2[z & 7];
                float (&d)[4] = e[(z >> 3) * 2 + (z & 1)];
                if (!(z & 6)) d[0] = d[1] = d[2] = d[3] = 0.f;
                mma(d, x.x, x.y, x.z, x.w, bb[z & 7].x, bb[z & 7].y);
            }
            float lo, hi;
            quad_pair((t & 2) ? (e[2][0] + e[3][0]) + (e[2][1] + e[3][1]) : (e[0][0] + e[1][0]) + (e[0][1] + e[1][1]),
                      (t & 2) ? (e[2][2] + e[3][2]) + (e[2][3] + e[3][3]) : (e[0][2] + e[1][2]) + (e[0][3] + e[1][3]), t, lo, hi);
            if (!(g & 1)) st_x1(p3, enc(pack2(lo, hi)));
            if (j < NFF) bar_arrive(8, 384); else if (j >= J_RED && j < J_END) bar_arrive(8, 192);
            if (tid == 0) TRACE(22);
        }
        if (j < NFF) {
            uint4 a[16];
            const uint32_t ad = sb + SM_U + B_DN * 32768 + warp * 8192 + (r8 + 8 * lb4) * 128 + (lb3 ^ r8) * 16;
            uint32_t rl = sb + SM_RED + lane * 16;
            uint32_t* p5 = gs + (B_E5 + warp * 4 + (t >> 1)) * 4096 + j * 16 + (t & 1) * 8 + g;
            pin(rl); pin(p5);
            if (lane == 0) mbar_expect(BAR(MBB), 4);
            auto ldd = [&]() {
#pragma unroll
                for (int s = 0; s < 16; s++) a[s] = ldsm<true>((ad ^ ((s & 3) * 32)) + (s >> 2) * 2048);
            };
            const uint32_t db = BAR(IT_DOWN + (warp ^ (j & 3)));
            mbar_wait(BAR(MBB), 0);
            const float4 st = ldsf4(sb + SM_RED + 2048);
            const bool hd = __all_sync(0xffffffffu, mbar_test(db, 0));
            if (hd) ldd();
            const float mu = (st.x + st.z) * (1.f / 512.f);
            float rstd;
            asm volatile("rsqrt.approx.ftz.f32 %0, %1;" : "=f"(rstd) : "f"(fmaxf(fmaf(-mu, mu, (st.y + st.w) * (1.f / 512.f)), 0.f) + 1e-5f));
            mbar_wait(BAR(QB), 1);
            if (tid == 0) TRACE(25);
            const float4 f0 = ldsf4(rl), f2 = ldsf4(rl + 1024), f1 = ldsf4(rl + 512), f3 = ldsf4(rl + 1536);
            const float gg = fmaf(rstd, fmaf(-mu, f0.z + f2.z, (f0.x + f0.y) + (f2.x + f2.y)), f0.w + f2.w);
            const float uu = fmaf(rstd, fmaf(-mu, f1.z + f3.z, (f1.x + f1.y) + (f3.x + f3.y)), f1.w + f3.w);
            const float hh = __fdividef(gg * uu, 1.f + ex2(-gg * fmaf(gg * gg, 0.10294324f, 2.3022082f)));
            uint32_t hb[4];
#pragma unroll
            for (int i = 0; i < 4; i++) hb[i] = pack2(__shfl_sync(0xffffffffu, hh, 2 * t + 8 * i), __shfl_sync(0xffffffffu, hh, 2 * t + 8 * i + 1));
            if (!hd) { mbar_wait(db, 0); ldd(); }
#pragma unroll
            for (int i = 0; i < 2; i++) {
                uint32_t res = 0;
#pragma unroll
                for (int k = 0; k < 4; k++) {
                    float c[4] = {0.f, 0.f, 0.f, 0.f};
                    const uint4 &x = a[i * 8 + k], &y = a[i * 8 + k + 4];
                    mma(c, x.x, x.y, x.z, x.w, hb[0], hb[1]);
                    mma(c, y.x, y.y, y.z, y.w, hb[2], hb[3]);
                    if (t == k) res = pack2(c[0], c[2]);
                }
                st2_x1(p5 + i * 8192, enc(res));
            }
            if (tid == 0) { TRACE(27); TRACE_GT(47); }
        }
    } else {
        const int u8 = tid - 128, w8 = warp - 4;
        const int v = w8 >> 2, wq4 = w8 & 3;
        {
            const float c0 = bflo(in1), c1 = bfhi(in1);
            sts32(sb + SM_FS + frag_off(2 * u8), pack2(__fdividef(c0, 1.f + __expf(-c0)), __fdividef(c1, 1.f + __expf(-c1))));
        }
        bar_sync(1, 256);
        asm volatile("barrier.cluster.wait.aligned;" ::: "memory");
        uint4 a[8], b[4]; float c[4];
        if (w8 < 2) {
            ldfrag(b, sb + SM_FS + (j >> 5) * 256 + t * 16);
            mbar_wait(BAR(IT_MODA), 0);
            if (u8 == 0) TRACE(12);
            const uint32_t ab = sb + SM_XA + w8 * 4096 + a16;
            load8<true>(a, [&](int s) { return ab + s * 512; });
            mma8(c, a, b);
            if (t < 2) st2_x1(gs + (B_HA + ((j >> 4) & 1) * 2 + w8) * 4096 + (j >> 5) * 256 + (j & 15) * 16 + t * 8 + g, encf(t ? c[2] : c[0]));
        }
        {
            mbar_wait(BAR(IT_WQ + 2 * v <= NCP ? 1 : IT_WQ + 2 * v), 0); mbar_wait(BAR(IT_WQ + 2 * v + 1 <= NCP ? 1 : IT_WQ + 2 * v + 1), 0);
            const uint32_t ab = sb + SM_U + 4 * 32768 + v * 16384 + a128;
            load8<true>(a, [&](int s) { return ab + s * 2048; });
            if (lane == 0) mbar_arrive(BAR(EB_WQ));
            bar_sync(5, 384);
            if (u8 == 0) TRACE(13);
            ldfrag(b, sb + SM_FV + v * 256 + t * 16);
            mma8(c, a, b);
            if (t < 2) {
                const float qv = t ? c[2] : c[0];
                const uint32_t qa_ = sb + SM_QX + ((rk * 2 + v) * 64 + wq4 * 16 + t * 8 + g) * 4;
                asm volatile("st.async.weak.shared::cluster.mbarrier::complete_tx::bytes.f32 [%0], %1, [%2];"
                             :: "r"(peer_addr(qa_, rk ^ 1)), "f"(qv), "r"(peer_addr(BAR(QB), rk ^ 1)) : "memory");
                sts32(qa_, __float_as_uint(qv));
            }
            __syncwarp();
            if (lane == 0) mbar_expect(BAR(QB), 64);
        }
        {
            mbar_wait(BAR(IT_WUK + (v ^ ((j >> 5) & 1))), 0); mbar_wait(BAR(IT_WUK + (v ^ ((j >> 5) & 1)) + 2), 0);
            const uint32_t ab = sb + SM_U + 5 * 32768 + (w8 * 16 + r8 + 8 * lb3) * 128;
            const uint32_t x16 = (lb4 ^ r8) * 16;
            load8<false>(a, [&](int s) { return ab + (s & 1) * 16384 + (x16 ^ ((s >> 1) * 32)); });
            bar_sync(6, 384);
            if (u8 == 0) TRACE(14);
            b[0] = lds128(sb + SM_FQ + t * 16); b[1] = lds128(sb + SM_FQ + 64 + t * 16);
            float e[4] = {0.f, 0.f, 0.f, 0.f};
            c[0] = c[1] = c[2] = c[3] = 0.f;
#pragma unroll
            for (int k = 0; k < 4; k++) {
                const uint32_t b0 = (k & 1) ? b[k >> 1].z : b[k >> 1].x, b1 = (k & 1) ? b[k >> 1].w : b[k >> 1].y;
                mma(c, a[2 * k].x, a[2 * k].y, a[2 * k].z, a[2 * k].w, b0, b1);
                mma(e, a[2 * k + 1].x, a[2 * k + 1].y, a[2 * k + 1].z, a[2 * k + 1].w, b0, b1);
            }
            const float mine = ((t & 1) ? ((t & 2) ? e[2] : e[0]) : ((t & 2) ? c[2] : c[0])) * 0.12751743f;
            const float other = shx(mine, 4);
            if (!(g & 1)) st2_x1(gs + (B_QA + rk * 8 + ((j >> 1) & 1) * 4 + (j >> 5)) * 4096 + w8 * 128 + ((j >> 2) & 7) * 16 + (g >> 1) * 4 + t, enc(pack2(mine, other)));
            if (u8 == 0) TRACE(15);
        }
        const uint32_t cls = ldcls();
        __nanosleep(QA_DELAY);
        {
            uint4 qb[8];
            const uint32_t* pq = gs + near_off(B_QA + rk * 8 + wq4, cls) + lane * 4;
            const uint32_t* pq2 = gs + near_off(B_QA + rk * 8 + 4 + wq4, cls) + lane * 4;
            if (lane == 0) {
                mbar_expect(BAR(QT), 4096);
                asm volatile("cp.async.bulk.shared::cluster.global.mbarrier::complete_tx::bytes [%0], [%1], 4096, [%2];"
                             :: "r"(sb + SM_U + 5 * 32768 + w8 * 4096), "l"(gs + near_off(B_QA + rk * 8 + w8, cls)), "r"(BAR(QT)) : "memory");
            }
            const uint32_t qs = sb + SM_U + 5 * 32768 + wq4 * 4096 + lane * 16;
            mbar_wait(BAR(QT), 0);
#pragma unroll
            for (int i = 0; i < 8; i++) { a[i] = lds128(qs + i * 512); qb[i] = lds128(qs + 16384 + i * 512); }
            poll<512, QA_SLEEP, true>(a, pq);
            poll<512, QA_SLEEP, true>(qb, pq2);
            if (lane == 0) mbar_arrive(BAR(EB_WUK));
            auto add2 = [](uint32_t x, uint32_t y) { uint32_t r; asm("add.rn.bf16x2 %0, %1, %2;" : "=r"(r) : "r"(x), "r"(y)); return r; };
#pragma unroll
            for (int i = 0; i < 8; i++) a[i] = make_uint4(add2(a[i].x, qb[i].x), add2(a[i].y, qb[i].y), add2(a[i].z, qb[i].z), add2(a[i].w, qb[i].w));
        }
        if (u8 == 0) TRACE(8);
        {
            float m = -INFINITY, l = 0.f;
            uint32_t xl = sb + SM_XB + w8 * 2048 + lane * 16, xr = peer_addr(xl, rk ^ 1), bsr = peer_addr(BAR(SF0 + v), rk ^ 1);
            uint32_t pa = sb + SM_XA + v * 2048 + wq4 * 512 + lane * 16, ma = sb + SM_MX + v * 128 + (wq4 * 8 + g) * 4;
            uint32_t fb = BAR(IT_CKV + v * 2), sf = BAR(SF0 + v);
            uint32_t dlo = __reduce_or_sync(0xffffffffu, (((sb + SM_U + v * 16384) & 0x3FFFFu) >> 4) | 0x10000u);
            if (STAG && v) __nanosleep(STAG);
#pragma unroll 1
            for (int n = 0; n < NUNITS; n++) {
                float d[2][16], sc[8];
#pragma unroll
                for (int i = 0; i < 2; i++) {
                    mbar_wait(fb + i * 8, 0);
                    wg_fence();
#pragma unroll
                    for (int s = 0; s < 8; s++) wgmma_rs_n32(d[i], a[s], (0x40000080ull << 32) | (dlo + i * 512 + (s >> 2) * 64 + (s & 3) * 2), s);
                    wg_commit();
                }
#pragma unroll
                for (int i = 0; i < 2; i++) {
                    if (i) wg_wait0(); else wg_wait1();
#pragma unroll
                    for (int k = 0; k < 16; k++) asm volatile("" : "+f"(d[i][k]) :: "memory");
                    sc[4 * i] = d[i][0] + d[i][6]; sc[4 * i + 1] = d[i][1] + d[i][7]; sc[4 * i + 2] = d[i][8] + d[i][14]; sc[4 * i + 3] = d[i][9] + d[i][15];
                    asm volatile("st.async.weak.shared::cluster.mbarrier::complete_tx::bytes.v4.f32 [%0], {%1, %2, %3, %4}, [%5];"
                                 :: "r"(xr + i * 1024), "f"(sc[4 * i]), "f"(sc[4 * i + 1]), "f"(sc[4 * i + 2]), "f"(sc[4 * i + 3]), "r"(bsr) : "memory");
                }
                if (u8 == 128) TRACE_Q(56 + (n < 6 ? n : -40));
                if (n >= 3) mbar_wait(BAR(EB_UNIT0 + n - 3), 0);
                dlo += n == 5 ? -5 * 2048 : 2048;
                fb += 32; xr ^= 512; bsr += 16;
                pin(fb); pin(xr); pin(bsr);
                mbar_wait(sf, 0);
                const float4 x = ldsf4(xl), y = ldsf4(xl + 1024);
                sc[0] += x.x; sc[1] += x.y; sc[2] += x.z; sc[3] += x.w; sc[4] += y.x; sc[5] += y.y; sc[6] += y.z; sc[7] += y.w;
                float pr[8];
#pragma unroll
                for (int i = 0; i < 8; i++) pr[i] = ex2(sc[i] - m);
                float mx = fmaxf(fmaxf(fmaxf(sc[0], sc[1]), fmaxf(sc[2], sc[3])), fmaxf(fmaxf(sc[4], sc[5]), fmaxf(sc[6], sc[7])));
                if (__builtin_expect(__any_sync(0xffffffffu, mx > m), 0)) {
                    mx = fmaxf(mx, shx(mx, 1));
                    mx = fmaxf(mx, shx(mx, 2));
                    const float mn = fmaxf(m, ceilf(mx * 0.0625f) * 16.f);
                    l *= ex2(m - mn);
                    m = mn;
#pragma unroll
                    for (int i = 0; i < 8; i++) pr[i] = ex2(sc[i] - m);
                }
                stsf(ma, m);
                asm volatile("st.shared.v4.u32 [%0], {%1, %2, %3, %4};" :: "r"(pa), "r"(pack2(pr[0], pr[1])), "r"(pack2(pr[2], pr[3])),
                             "r"(pack2(pr[4], pr[5])), "r"(pack2(pr[6], pr[7])) : "memory");
                __syncwarp();
                if (lane == 0) mbar_arrive(sf + (PF0 - SF0) * 8);
                l += ((pr[0] + pr[1]) + (pr[2] + pr[3])) + ((pr[4] + pr[5]) + (pr[6] + pr[7]));
                xl ^= 512; sf += 16; ma += 256; pa += (n == 2 || n == 5) ? -8192 : 4096;
            }
            l += shx(l, 1);
            l += shx(l, 2);
            float2* mlx = (float2*)(sm + SM_MX + 2048) + wq4 * 8 + g;
            if (v == 0) { *mlx = make_float2(m, l); bar_arrive(11, 256); }
            else {
                mbar_wait(BAR(JD), 0);
                bar_sync(11, 256);
                const float2 o = *mlx;
                const float mn = fmaxf(m, o.x);
                l = l * ex2(m - mn) + o.y * ex2(o.x - mn);
                if ((wq4 >> 1) == rk) st_x4(gs + (B_ML + wq4 * 8 + g) * 4096 + (t >> 1) * 1024 + (j >> 1) * 8 + (t & 1) * 4, encf(mn), encf(l), 1u, 1u);
            }
        }
        const int pi = j < NFF ? rk * 128 + w8 * 16 + (lane >> 1) : ((j - J_RED) & 15) * 16 + (w8 & 1) * 8 + g;
        const uint32_t xw = *(const uint32_t*)(xin + 2 * pi);
        const uint32_t one = (g & 1) ? 0x3f800000u : 0x00003f80u;
        const uint32_t* pm = gs + near_off(B_MB, cls) + pi;
        {
            const uint32_t ab = sb + SM_U + B_WUV * 32768 + v * 4096 + a128;
            uint32_t pa = sb + SM_PB + wq4 * 320 + frag_off(64 * v + 32 * (g >> 2) + 16 * (t & 1) + 8 * (t >> 1) + 2 * (g & 3));
            uint32_t fa = sb + SM_PB + g * 320 + t * 16;
            const uint32_t* pe = gs + G_E1 + j * 8192 + (w8 >> 1) * 2048 + ((((cls >> 1) ^ (w8 >> 1)) & 1) << 10) + (((w8 & 1) * 16 + t) * 8 + g) * 4;
            uint32_t* p2 = gs + (B_E2 + (j >> 4)) * 4096 + (t >> 1) * 1024 + (j & 12) * 64 + w8 * 32 + (j & 3) * 8 + (g & 6) + (t & 1);
            pin(pa); pin(fa); pin(pe); pin(p2);
            const uint32_t mk = (g & 1) ? 0xffff0000u : 0x0000ffffu, m0 = (g & 2) ? 0u : mk, m1 = (g & 2) ? mk : 0u;
            uint4 pv[4];
            bool hv = false;
            bar_sync(3, 416);
            uint4 wa = lds128(sb + SM_W + (wq4 * 4 + t) * 16);
            uint32_t wb[8] = {wa.x & m0, wa.x & m1, wa.y & m0, wa.y & m1, wa.z & m0, wa.z & m1, wa.w & m0, wa.w & m1};
            pv[0] = pv[1] = pv[2] = pv[3] = make_uint4(0u, 0u, 0u, 0u);
            float e[4][4];
            auto wsum = [&]() {
#pragma unroll
                for (int i = 0; i < 4; i++) {
                    e[i][0] = e[i][1] = e[i][2] = e[i][3] = 0.f;
                    mma(e[i], pv[i].x, pv[i].y, pv[i].z, pv[i].w, wb[2 * i], wb[2 * i + 1]);
                }
            };
            poll<512, E1_SLEEP, true>(pv, pe, [&]() {
                if (!hv) {
                    hv = __all_sync(0xffffffffu, mbar_test(BAR(IT_WUV + t), 0));
                    if (hv) load8<true>(a, [&](int s) { return ab + (s >> 1) * 8192 + (s & 1) * 2048; });
                }
            }, wsum);
            if (lane == 0) TRACE_Q(48 + w8);
            if (u8 == 0) TRACE_Q(18);
            float lo, hi2;
            float2 inv;
#pragma unroll 1
            for (int pass = 0;; pass++) {
                const float r0 = (t & 2) ? (e[0][2] + e[1][2]) + (e[2][2] + e[3][2]) : (e[0][0] + e[1][0]) + (e[2][0] + e[3][0]);
                const float r1 = (t & 2) ? (e[0][3] + e[1][3]) + (e[2][3] + e[3][3]) : (e[0][1] + e[1][1]) + (e[2][1] + e[3][1]);
                const uint32_t hi = pack2(r0, r1);
                sts32(pa, hi); sts32(pa + 1280, pack2(r0 - bflo(hi), r1 - bfhi(hi)));
                if (!hv) {
#pragma unroll 1
                    for (int i = 0; i < 4; i++) mbar_wait(BAR(IT_WUV + i), 0);
                    load8<true>(a, [&](int s) { return ab + (s >> 1) * 8192 + (s & 1) * 2048; });
                    hv = true;
                }
                bar_sync(1, 256);
                if (u8 == 0) TRACE(19);
                ldfrag(b, fa);
                mma8(c, a, b);
                mbar_wait(BAR(WR), 0);
                asm volatile("ld.shared.v2.f32 {%0, %1}, [%2];" : "=f"(inv.x), "=f"(inv.y) : "r"(sb + SM_FQ) : "memory");
                quad_pair(c[0] + c[1], c[2] + c[3], t, lo, hi2);
                if (__builtin_expect(__all_sync(0xffffffffu, pass || __float_as_uint(inv.y) == 0), 1)) break;
                wa = lds128(sb + SM_W2 + (wq4 * 4 + t) * 16);
                wb[0] = wa.x & m0; wb[1] = wa.x & m1; wb[2] = wa.y & m0; wb[3] = wa.y & m1; wb[4] = wa.z & m0; wb[5] = wa.z & m1; wb[6] = wa.w & m0; wb[7] = wa.w & m1;
                wsum();
                bar_sync(1, 256);
            }
            if (!(g & 1)) st_x1(p2, enc(pack2(lo * inv.x, hi2 * inv.x)));
            bar_arrive(4, 416);
            if (u8 == 0) TRACE(20);
        }
        if (j < NFF) {
            const uint32_t* p3 = gs + near_off(B_E3 + rk * 2 + v, cls) + wq4 * 256 + t * 16 + g * 2;
            const int od = lane & 1;
            uint32_t za = sb + SM_FZ + od * 576 + frag_off(w8 * 32 + (lane & 30));
            uint32_t fa = sb + SM_FZ + (g & 3) * 576 + ((lane ^ j) & 16) * 16 + t * 16, ya = sb + SM_Y + u8 * 4;
            uint32_t mb[3];
            uint4 a2[8];
            poll<1024, MB_SLEEP>(mb, pm);
            const uint32_t kk = pack2(1.f + bflo(mb[2]), 1.f + bfhi(mb[2]));
            sts32(za + 2 * 576, od ? mb[1] : kk);
            uint2 e3[4] = {make_uint2(0u, 0u), make_uint2(0u, 0u), make_uint2(0u, 0u), make_uint2(0u, 0u)};
            uint32_t ra = peer_addr(sb + SM_RED + (rk * 2 + v) * 512 + ((wq4 & 1) * 16 + (t >> 1) * 8 + g) * 16 + (t & 1) * 8, wq4 >> 1), tbo = peer_addr(BAR(QB), wq4 >> 1);
            pin(za); pin(fa); pin(ya); pin(ra); pin(tbo);
            if (lane == 0) mbar_expect(BAR(QB), 256);
            const uint32_t gb = BAR(IT_X + v * 2), ab = sb + SM_U + (B_X + v) * 32768 + a128;
            bool early = false, early2 = false;
            auto ldw = [&]() {
                if (!early) {
                    early = __all_sync(0xffffffffu, mbar_test(gb, 0));
                    if (early) load8<true>(a, [&](int s) { return ab + s * 2048; });
                }
                if (!early2) {
                    early2 = __all_sync(0xffffffffu, mbar_test(gb + 8, 0));
                    if (early2) load8<true>(a2, [&](int s) { return ab + 16384 + s * 2048; });
                }
            };
            bar_sync(8, 384);
            float s0[4], s1[4];
            auto sum = [&]() {
                s0[0] = s0[1] = s0[2] = s0[3] = s1[0] = s1[1] = s1[2] = s1[3] = 0.f;
                mma(s0, e3[0].x, e3[0].y, e3[1].x, e3[1].y, one, one); mma(s1, e3[2].x, e3[2].y, e3[3].x, e3[3].y, one, one);
            };
            poll<256, 0, true>(e3, p3, ldw, sum);
            if (u8 == 0) TRACE(23);
            const float y0 = fmaf(bflo(mb[0]), (t & 2) ? s0[2] + s1[2] : s0[0] + s1[0], bflo(xw)), y1 = fmaf(bfhi(mb[0]), (t & 2) ? s0[3] + s1[3] : s0[1] + s1[1], bfhi(xw));
            stsf(ya, od ? y1 : y0);
            const float z0 = y0 * bflo(kk), z1 = y1 * bfhi(kk);
            const uint32_t zh = pack2(z0, z1);
            sts32(za, od ? pack2(z0 - bflo(zh), z1 - bfhi(zh)) : zh);
            bar_sync(7, 288);
            if (u8 == 0) TRACE(24);
            ldfrag(b, fa);
            if (!early) { mbar_wait(gb, 0); load8<true>(a, [&](int s) { return ab + s * 2048; }); }
            {
                float e[4][4];
#pragma unroll
                for (int s = 0; s < 16; s++) {
                    if (s == 8 && !early2) { mbar_wait(gb + 8, 0); load8<true>(a2, [&](int q) { return ab + 16384 + q * 2048; }); }
                    const uint4& x = s < 8 ? a[s] : a2[s & 7];
                    const uint4& y = b[(s >> 1) & 3];
                    float (&d)[4] = e[(s >> 3) * 2 + (s & 1)];
                    if (!(s & 6)) d[0] = d[1] = d[2] = d[3] = 0.f;
                    mma(d, x.x, x.y, x.z, x.w, (s & 1) ? y.z : y.x, (s & 1) ? y.w : y.y);
                }
                const bool hi = t >> 1;
                const float k0 = hi ? e[2][2] + e[3][2] : e[0][0] + e[1][0], k1 = hi ? e[2][3] + e[3][3] : e[0][1] + e[1][1];
                const float o0 = hi ? e[2][0] + e[3][0] : e[0][2] + e[1][2], o1 = hi ? e[2][1] + e[3][1] : e[0][3] + e[1][3];
                st_async2(ra, k0 + shx(o0, 2), k1 + shx(o1, 2), tbo);
            }
        } else if (j >= J_RED && j < J_END && w8 < 2) {
            uint32_t ga[1], e3[4];
            poll<0, MB_SLEEP>(ga, pm);
            bar_sync(8, 192);
            poll<64, 100>(e3, gs + near_off(B_E3 + (pi >> 6), cls) + (pi & 48) * 16 + t * 64 + (pi & 15));
            float y0 = (bflo(e3[0]) + bflo(e3[1])) + (bflo(e3[2]) + bflo(e3[3])), y1 = (bfhi(e3[0]) + bfhi(e3[1])) + (bfhi(e3[2]) + bfhi(e3[3]));
#pragma unroll
            for (int o = 1; o < 4; o <<= 1) { y0 += shx(y0, o); y1 += shx(y1, o); }
            const int col = g + (t & 1) * 8;
            y0 = __shfl_sync(0xffffffffu, (t & 1) ? fmaf(bfhi(ga[0]), y1, bfhi(xw)) : fmaf(bflo(ga[0]), y0, bflo(xw)), (col >> 1) * 4 + (col & 1));
            uint16_t* po = (uint16_t*)out + (j - J_RED) * 32 + w8 * 16 + col;
            const uint32_t* pe = gs + near_off(B_E5 + j - J_RED, cls) + t * 16 + w8 * 8 + g;
            pin(po);
            const uint32_t sel = (g & 2) ? 0x3f800000u : 0x00003f80u;
            uint32_t yv[NFF / 4 + 1];
            float e[4][4], gb = 0.f;
#pragma unroll
            for (int i = 0; i <= NFF / 4; i++) yv[i] = 0u;
#pragma unroll 1
            for (uint32_t it = 0;; it++) {
#pragma unroll
                for (int i = 0; i < NFF / 4; i++) if (!yv[i]) ld_x(yv[i], pe + i * 64);
                if (__all_sync(0xffffffffu, !yv[NFF / 4] && mbar_test(BAR(QB), 1))) {
                    yv[NFF / 4] = lds32(sb + SM_FV + 256 + w8 * 32 + (col >> 1) * 4);
                    gb = (col & 1) ? bfhi(yv[NFF / 4]) : bflo(yv[NFF / 4]);
                }
                if (it > SPIN_LIMIT) __trap();
#pragma unroll
                for (int i = 0; i < 4; i++) {
                    e[i][0] = e[i][1] = e[i][2] = e[i][3] = 0.f;
                    mma(e[i], yv[4 * i], yv[4 * i + 1], i < 3 ? yv[(4 * i + 2) % (NFF / 4)] : 0u, i < 3 ? yv[(4 * i + 3) % (NFF / 4)] : 0u, sel, sel);
                }
                if (__all_sync(0xffffffffu, mint<NFF / 4 + 1>(yv) != 0)) break;
            }
            if (u8 == 0) TRACE(26);
            const float s = ((e[0][0] + e[0][2]) + (e[1][0] + e[1][2])) + ((e[2][0] + e[2][2]) + (e[3][0] + e[3][2]));
            asm volatile("{\n.reg .pred p;\nsetp.lt.u32 p, %2, 2;\n@p st.global.u16 [%0], %1;\n}" :: "l"(po), "h"((uint16_t)pack2(fmaf(gb, s, y0), 0.f)), "r"(t) : "memory");
            asm volatile("{\n.reg .pred p;\nsetp.eq.f32 p, %0, 0f7F7FFFFF;\n@p nanosleep.u32 0;\n}" :: "f"(((e[0][1] + e[0][3]) + (e[1][1] + e[1][3])) + ((e[2][1] + e[2][3]) + (e[3][1] + e[3][3]))));
            if (u8 == 0) TRACE(27);
        }
    }
}

typedef CUresult (*EncFn)(CUtensorMap*, CUtensorMapDataType, cuuint32_t, void*, const cuuint64_t*, const cuuint64_t*,
                          const cuuint32_t*, const cuuint32_t*, CUtensorMapInterleave, CUtensorMapSwizzle,
                          CUtensorMapL2promotion, CUtensorMapFloatOOBfill);

void make_map(EncFn enc_fn, CUtensorMap* m, const void* p, cuuint64_t d0, cuuint64_t d1, cuuint64_t d2, cuuint64_t d3,
              cuuint64_t s1, cuuint64_t s2, cuuint64_t s3, cuuint32_t b0, cuuint32_t b1, cuuint32_t b2, cuuint32_t b3, CUtensorMapSwizzle sw) {
    const cuuint64_t dims[4] = {d0, d1, d2, d3}, strides[3] = {s1, s2, s3};
    const cuuint32_t box[4] = {b0, b1, b2, b3}, es[4] = {1, 1, 1, 1};
    enc_fn(m, CU_TENSOR_MAP_DATA_TYPE_BFLOAT16, 4, (void*)p, dims, strides, box, es,
           CU_TENSOR_MAP_INTERLEAVE_NONE, sw, PROMO, CU_TENSOR_MAP_FLOAT_OOB_FILL_NONE);
}

uint32_t* scratch = nullptr;

struct Tune { const char* win; const char* late; int tau, t_off; const char* tail[3][4]; };
Tune tune = {"77777777755555555555555555555555555555544",
             "00000000000000888888888888888888888888888", 322, -360,
             {{"VVVVOOOOguguDDDD", "zzzzzzzzzzzzzzzz", "7777aaaaaaaa6789", "ebbb9ddddaaa2555"},
              {"VMVMVVOOOO", "zzzzzzzzzz", "9999999999", "8aaaaac999"},
              {"VVVVOOOOMM", "zzzzzzzzzz", "aaaaaaaa88", "b1111a9asb"}}};
bool ready = false;

}

extern "C" void kernel_launch(void* const* d_in, const int* in_sizes, int n_in, void* d_out, int out_size) {
    (void)in_sizes; (void)n_in; (void)out_size;
    static Maps maps;
    static const void* cached[12] = {};
    bool same = ready;
    for (int i = 0; i < 12 && same; i++) same = cached[i] == d_in[i];
    if (!same) {
        void* fn = nullptr;
        cudaDriverEntryPointQueryResult qr;
        cudaGetDriverEntryPoint("cuTensorMapEncodeTiled", &fn, cudaEnableDefault, &qr);
        EncFn e = (EncFn)fn;
        const CUtensorMapSwizzle S128 = CU_TENSOR_MAP_SWIZZLE_128B;
        make_map(e, &maps.m[MP_WQ], d_in[2], 64, 512, 64, 1, 8192, 128, 8192, 64, 64, 1, 1, S128);
        make_map(e, &maps.m[MP_WUK], d_in[3], 64, 512, 64, 1, 8192, 128, 8192, 64, 64, 1, 1, S128);
        make_map(e, &maps.m[MP_CKV], d_in[1], 64, 8, 8, 4096, 1024, 128, 8192, 64, 8, 4, 2, S128);
        make_map(e, &maps.m[MP_MODB], d_in[11], 3072, 512, 1, 1, 6144, 6144, 6144, 64, 128, 1, 1, S128);
        make_map(e, &maps.m[MP_WUV], d_in[4], 64, 512, 64, 1, 8192, 128, 8192, 64, 32, 2, 1, S128);
        make_map(e, &maps.m[MP_WO], d_in[5], 512, 4096, 1, 1, 1024, 1024, 1024, 64, 64, 1, 1, S128);
        make_map(e, &maps.m[MP_GATE], d_in[7], 1792, 512, 1, 1, 3584, 3584, 3584, 64, 128, 1, 1, S128);
        make_map(e, &maps.m[MP_UP], d_in[8], 1792, 512, 1, 1, 3584, 3584, 3584, 64, 128, 1, 1, S128);
        make_map(e, &maps.m[MP_DOWN], d_in[9], 64, 1792, 8, 1, 1024, 128, 1024, 64, 32, 2, 1, S128);
        for (int r = 0; r < 3; r++) {
            int ids[58], cnt[128] = {}, tn = tune.t_off - (W0 - 1) * tune.tau;
            uint2* sc = maps.sched[r];
            auto dig = [](char ch) { return ch >= 'a' ? ch - 'a' + 10 : ch >= 'A' ? ch - 'A' + 36 : ch - '0'; };
            for (int i = 0; i < 58; i++) sc[i] = make_uint2(0u, 0u);
            for (int i = 0;; i++) {
                int id = i, buf, dep, w, wl;
                if (i < IT_WUV) {
                    const int u = (i - IT_CKV) >> 2;
                    buf = i < IT_CKV ? 4 + ((i - 1) >> 2) : u % 6;
                    dep = i < IT_CKV || u < 4 ? -1 : u < 6 ? EB_WQ + u - 4 : EB_UNIT0 + u - 6;
                    w = dig(tune.win[i]); wl = dig(tune.late[i]);
                    if (i) tn += tune.tau;
                } else {
                    const char ch = tune.tail[r][0][i - IT_WUV];
                    if (!ch) break;
                    buf = ch == 'V' ? B_WUV : ch == 'O' ? B_WO : ch == 'D' ? B_DN : ch == 'u' ? B_X + 1 : B_X;
                    id = (ch == 'V' ? IT_WUV : ch == 'O' ? IT_WO : ch == 'D' ? IT_DOWN : ch == 'u' ? IT_X + 2 : IT_X) + cnt[(int)ch]++;
                    dep = EB_UNIT0 + (buf < 2 ? buf + 6 : buf);
                    w = dig(tune.tail[r][1][i - IT_WUV]); wl = dig(tune.tail[r][2][i - IT_WUV]);
                    tn += (r == 2 ? 64 : 32) * dig(tune.tail[r][3][i - IT_WUV]);
                }
                if (id < IT_X || id >= IT_DOWN ? (id - 1) & 3 : (id - IT_X) & 1) dep = -1;
                ids[i] = id;
                auto back = [&](int d) { return i < d ? 0 : (ids[i - d] && ids[i - d] <= NCP ? 1 : ids[i - d]) + 1; };
                sc[i].x = id | (buf * 4 + (id < IT_X || id >= IT_DOWN ? (id - 1) & 3 : ((id - IT_X) & 1) * 2)) << 6 | (dep + 1) << 11 | (w > 32 ? NEVER + 1 : back(w)) << 18 | (wl ? back(wl) : 0) << 25;
                const int mp = id < IT_CKV ? MP_WQ + ((id - 1) >> 2) : id < IT_WUV ? MP_CKV : id < IT_WO ? MP_WUV : id < IT_X ? MP_WO
                             : id >= IT_DOWN ? MP_DOWN : r ? MP_MODB : MP_GATE + ((id - IT_X) >> 1);
                const int step = mp == MP_CKV ? id - IT_CKV : mp == MP_WUV ? (id - IT_WUV) * 2 : mp == MP_DOWN ? id - IT_DOWN : id < IT_X ? (id - 1) & 3 : ((id - IT_X) & 1) * 2;
                sc[i].y = (tn & 0xffff) | (mp & 15) << 16 | step << 20;
            }
        }
        cudaGetSymbolAddress((void**)&scratch, g_scratch);
        scratch = (uint32_t*)(((uintptr_t)scratch + (2u << 20) - 1) & ~(uintptr_t)((2u << 20) - 1));
        cudaFuncSetAttribute(fused_kernel, cudaFuncAttributeMaxDynamicSharedMemorySize, SM_TOTAL);
        for (int i = 0; i < 12; i++) cached[i] = d_in[i];
        ready = true;
    }
    const First f = {{(const uint8_t*)d_in[2], (const uint8_t*)d_in[11]}, {(const __nv_bfloat16*)d_in[0], (const __nv_bfloat16*)d_in[10]}};
    fused_kernel<<<NCTA, NTHREADS, SM_TOTAL>>>(f, (__nv_bfloat16*)d_out, scratch, maps);
}
```

```cpp
#include <cuda_runtime.h>
#include <cuda_bf16.h>
#include <cuda.h>
#include <stdint.h>
#include <limits.h>

namespace {

constexpr int NCTA = 128;
constexpr int NTHREADS = 512;
constexpr int NUNITS = 8;
constexpr int NFF = 56, J_RED = 104, J_END = 120;
constexpr uint32_t SPIN_LIMIT = 1u << 22;

#define PROMO CU_TENSOR_MAP_L2_PROMOTION_L2_64B
#define NEAR_CLK 390
#define E1_EARLY 50
#define STAG 300
#define NUMA 1
#define NPROBE 5
#define NCP 2
#define W0 4
#define RD_ITEM 15
#define JAN_SLEEP 100
#define RD_SLEEP 400
#define HA_DELAY 200
#define H_SLEEP 100
#define QA_DELAY 600
#define QA_SLEEP 200
#define ML_DELAY 300
#define E1_SLEEP 50
#define MB_SLEEP 100
constexpr int B_WUV = 2, B_WO = 3, B_X = 4  , B_DN = 0;

constexpr int SM_U = 0;
constexpr int SM_XA = 6 * 32768;
constexpr int SM_XB = SM_XA + 12288;
constexpr int SM_MX = SM_XB + 16384;
constexpr int SM_FZ = SM_XB + 8192;
constexpr int SM_PB = SM_XB;
constexpr int SM_Y = SM_XB + 12288;
constexpr int SM_RED = SM_XB + 4096;
constexpr int SM_FS = SM_XB + 20480;
constexpr int SM_FV = SM_FS + 1024;
constexpr int SM_QX = SM_XA + 8192;
constexpr int SM_FQ = SM_FV + 512;
constexpr int SM_CLS = SM_FQ + 128;
constexpr int SM_W = SM_FQ + 256;
constexpr int SM_W2 = SM_MX + 2304;
constexpr int SM_SCR = SM_XA + 9216;
constexpr int SM_TR = SM_XB + 19456;
constexpr int SM_BAR = SM_W + 256;
constexpr int SM_TOTAL = SM_BAR + 1024;
static_assert(SM_TOTAL <= 232448, "smem");

enum { IT_MODA = 0, IT_WQ = 1, IT_WUK = 5, IT_CKV = 9, IT_WUV = 41, IT_WO = 45, IT_X = 49  , IT_DOWN = 53, NITEMS = 57,
       NEVER = 63,
       SF0 = 64,
       PF0 = 80,
       EB_UNIT0 = 96, MBB = 103,
       EB_WQ = 104, EB_WUK, QT, QB, JD, WR };

enum { MP_WQ = 0, MP_WUK, MP_CKV, MP_WUV, MP_DOWN, MP_WO, MP_GATE, MP_UP, MP_MODB, NMAPS };
struct First { const uint8_t* w[2]; const __nv_bfloat16* v[2]; };
struct Maps { CUtensorMap m[NMAPS]; uint2 sched[3][58]; };

enum { B_HA = 0,
       B_MB = 6,
       B_RD = 7,
       B_E2 = 8,
       B_QA = 16,
       B_ML = 32,
       B_E5 = 64,
       B_E3 = 80,
       B_PR = 96,
       B_TR = 100 };
constexpr int G_E1 = 1 << 19;
constexpr int G_TR = B_TR * 4096;
__device__ __align__(1024) uint32_t g_scratch[(8 << 20) / 4];

#define TRACE(slot) do {} while (0)
#define TRACE_Q(slot) do {} while (0)
#define TRACE_GT(slot) do {} while (0)

__device__ __forceinline__ uint32_t s2u(const void* p) { return (uint32_t)__cvta_generic_to_shared(p); }
__device__ __forceinline__ void mbar_init(uint32_t b, int c) { asm volatile("mbarrier.init.shared::cta.b64 [%0], %1;" :: "r"(b), "r"(c) : "memory"); }
__device__ __forceinline__ void mbar_expect(uint32_t b, uint32_t bytes) { asm volatile("mbarrier.arrive.expect_tx.shared::cta.b64 _, [%0], %1;" :: "r"(b), "r"(bytes) : "memory"); }
__device__ __forceinline__ void mbar_arrive(uint32_t b) { asm volatile("mbarrier.arrive.shared::cta.b64 _, [%0];" :: "r"(b) : "memory"); }
__device__ __forceinline__ void mbar_wait(uint32_t b, uint32_t ph) {
    asm volatile("{\n.reg .pred p;\nW: mbarrier.try_wait.parity.shared::cta.b64 p, [%0], %1;\n@!p bra W;\n}" :: "r"(b), "r"(ph) : "memory");
}
__device__ __forceinline__ void mbar_waitb(uint32_t b, uint32_t ph) {
    asm volatile("{\n.reg .pred p;\n.reg .u32 n;\nmov.u32 n, 0;\n"
                 "W: mbarrier.try_wait.parity.shared::cta.b64 p, [%0], %1;\n@p bra D;\n"
                 "add.u32 n, n, 1;\nsetp.lt.u32 p, n, 0x100000;\n@p bra W;\ntrap;\nD:\n}" :: "r"(b), "r"(ph) : "memory");
}
__device__ __forceinline__ uint32_t mbar_test(uint32_t b, uint32_t ph) {
    uint32_t ok;
    asm volatile("{\n.reg .pred p;\nmbarrier.test_wait.parity.shared::cta.b64 p, [%1], %2;\nselp.u32 %0, 1, 0, p;\n}" : "=r"(ok) : "r"(b), "r"(ph) : "memory");
    return ok;
}
__device__ __forceinline__ void bar_sync(int id, int n) { asm volatile("bar.sync %0, %1;" :: "r"(id), "r"(n) : "memory"); }
__device__ __forceinline__ void bar_arrive(int id, int n) { asm volatile("bar.arrive %0, %1;" :: "r"(id), "r"(n) : "memory"); }
__device__ __forceinline__ uint32_t peer_addr(uint32_t a, uint32_t rank) { uint32_t r; asm("mapa.shared::cluster.u32 %0, %1, %2;" : "=r"(r) : "r"(a), "r"(rank)); return r; }
__device__ __forceinline__ void st_async2(uint32_t a, float x, float y, uint32_t bar) {
    asm volatile("st.async.weak.shared::cluster.mbarrier::complete_tx::bytes.v2.f32 [%0], {%1, %2}, [%3];" :: "r"(a), "f"(x), "f"(y), "r"(bar) : "memory");
}
__device__ __forceinline__ uint32_t gtime() { uint32_t t; asm volatile("mov.u32 %0, %%globaltimer_lo;" : "=r"(t)); return t; }
__device__ __forceinline__ void fence_gpu() { asm volatile("fence.acq_rel.gpu;" ::: "memory"); }

__device__ __forceinline__ uint32_t enc(uint32_t b) { uint32_t r; asm("max.u32 %0, %1, 1;" : "=r"(r) : "r"(b)); return r; }
__device__ __forceinline__ uint32_t encf(float f) { return enc(__float_as_uint(f)); }
__device__ __forceinline__ void st_x1(uint32_t* p, uint32_t v) { asm volatile("st.relaxed.gpu.global.u32 [%0], %1;" :: "l"(p), "r"(v) : "memory"); }
__device__ __forceinline__ void st_x4(void* p, uint32_t a, uint32_t b, uint32_t c, uint32_t d) {
    asm volatile("st.relaxed.gpu.global.v4.u32 [%0], {%1, %2, %3, %4};" :: "l"(p), "r"(a), "r"(b), "r"(c), "r"(d) : "memory");
}
__device__ __forceinline__ void st2_x1(uint32_t* p, uint32_t v) { st_x1(p, v); st_x1(p + 1024, v); }
__device__ __forceinline__ void st2_x4(uint32_t* p, uint32_t a, uint32_t b, uint32_t c, uint32_t d) { st_x4(p, a, b, c, d); st_x4(p + 1024, a, b, c, d); }
__device__ __forceinline__ int near_off(int b, uint32_t cls) { return b * 4096 + (((__popc(b & 0x2C) ^ cls) & 1) << 10); }
__device__ __forceinline__ void ld_x(uint32_t& v, const void* p) { asm volatile("ld.relaxed.gpu.global.u32 %0, [%1];" : "=r"(v) : "l"(p) : "memory"); }
__device__ __forceinline__ void ld_x(uint4& v, const void* p) {
    asm volatile("ld.relaxed.gpu.global.v4.u32 {%0, %1, %2, %3}, [%4];" : "=r"(v.x), "=r"(v.y), "=r"(v.z), "=r"(v.w) : "l"(p) : "memory");
}
__device__ __forceinline__ void ld_x(uint2& v, const void* p) { asm volatile("ld.relaxed.gpu.global.v2.u32 {%0, %1}, [%2];" : "=r"(v.x), "=r"(v.y) : "l"(p) : "memory"); }
__device__ __forceinline__ uint32_t minw(uint32_t v) { return v; }
__device__ __forceinline__ uint32_t minw(const uint2& v) { return min(v.x, v.y); }
__device__ __forceinline__ uint32_t minw(const uint4& v) { return min(__vimin3_u32(v.x, v.y, v.z), v.w); }
template <int N> __device__ __forceinline__ uint32_t mint(const uint32_t* m) {
    if constexpr (N == 1) return m[0];
    else if constexpr (N == 2) return min(m[0], m[1]);
    else return __vimin3_u32(mint<(N + 2) / 3>(m), mint<(N + 1) / 3>(m + (N + 2) / 3), mint<N / 3>(m + (N + 2) / 3 + (N + 1) / 3));
}

template <int STRIDE, int S4 = 4 * STRIDE, typename T, int N>
__device__ __forceinline__ void poll_start(T (&v)[N], const void* base) {
#pragma unroll
    for (int i = 0; i < N; i++) ld_x(v[i], (const uint8_t*)base + (i & 3) * STRIDE + (i >> 2) * S4);
}
struct Nop { __device__ void operator()() const {} };
template <int STRIDE, int SLEEP, bool STARTED = false, int S4 = 4 * STRIDE, typename T, int N, typename F = Nop, typename G = Nop>
__device__ __forceinline__ void poll(T (&v)[N], const void* base, F idle = F(), G ahead = G()) {
    if (!STARTED) { poll_start<STRIDE, S4>(v, base); idle(); }
#pragma unroll 1
    for (uint32_t it = 0;; it++) {
        uint32_t m[N];
        ahead();
#pragma unroll
        for (int i = 0; i < N; i++) m[i] = minw(v[i]);
        if (__all_sync(0xffffffffu, mint<N>(m) != 0)) break;
        if (SLEEP && it > 0) __nanosleep(SLEEP);
#pragma unroll
        for (int i = 0; i < N; i++) if (!m[i]) ld_x(v[i], (const uint8_t*)base + (i & 3) * STRIDE + (i >> 2) * S4);
        idle();
        if (it > SPIN_LIMIT) __trap();
    }
}

__device__ __forceinline__ float bflo(uint32_t w) { return __uint_as_float(w << 16); }
__device__ __forceinline__ float bfhi(uint32_t w) { return __uint_as_float(w & 0xffff0000u); }
__device__ __forceinline__ uint32_t pack2(float lo, float hi) {
    uint32_t r; asm("cvt.rn.bf16x2.f32 %0, %1, %2;" : "=r"(r) : "f"(hi), "f"(lo)); return r;
}
__device__ __forceinline__ float rbf(float x) { return __uint_as_float(pack2(0.f, x)); }
__device__ __forceinline__ float ex2(float x) { float r; asm("ex2.approx.ftz.f32 %0, %1;" : "=f"(r) : "f"(x)); return r; }
__device__ __forceinline__ float shx(float v, int m) { return __shfl_xor_sync(0xffffffffu, v, m); }
__device__ __forceinline__ uint4 lds128(uint32_t a) { uint4 v; asm volatile("ld.shared.v4.u32 {%0, %1, %2, %3}, [%4];" : "=r"(v.x), "=r"(v.y), "=r"(v.z), "=r"(v.w) : "r"(a) : "memory"); return v; }
__device__ __forceinline__ uint32_t lds32(uint32_t a) { uint32_t v; asm volatile("ld.shared.u32 %0, [%1];" : "=r"(v) : "r"(a) : "memory"); return v; }
__device__ __forceinline__ void sts32(uint32_t a, uint32_t v) { asm volatile("st.shared.u32 [%0], %1;" :: "r"(a), "r"(v) : "memory"); }
__device__ __forceinline__ void sts16(uint32_t a, uint32_t v) { asm volatile("st.shared.u16 [%0], %1;" :: "r"(a), "h"((uint16_t)v) : "memory"); }
__device__ __forceinline__ int frag_off(int k) { return (k >> 5) * 64 + ((k >> 1) & 3) * 16 + ((k >> 4) & 1) * 8 + ((k >> 3) & 1) * 4 + (k & 1) * 2; }

template <bool TRANS>
__device__ __forceinline__ uint4 ldsm(uint32_t a) {
    uint4 r;
    if (TRANS) asm volatile("ldmatrix.sync.aligned.m8n8.x4.trans.shared.b16 {%0, %1, %2, %3}, [%4];" : "=r"(r.x), "=r"(r.y), "=r"(r.z), "=r"(r.w) : "r"(a) : "memory");
    else asm volatile("ldmatrix.sync.aligned.m8n8.x4.shared.b16 {%0, %1, %2, %3}, [%4];" : "=r"(r.x), "=r"(r.y), "=r"(r.z), "=r"(r.w) : "r"(a) : "memory");
    return r;
}
__device__ __forceinline__ void mma(float (&c)[4], uint32_t a0, uint32_t a1, uint32_t a2, uint32_t a3, uint32_t b0, uint32_t b1) {
    asm volatile("mma.sync.aligned.m16n8k16.row.col.f32.bf16.bf16.f32 {%0,%1,%2,%3}, {%4,%5,%6,%7}, {%8,%9}, {%0,%1,%2,%3};"
                 : "+f"(c[0]), "+f"(c[1]), "+f"(c[2]), "+f"(c[3]) : "r"(a0), "r"(a1), "r"(a2), "r"(a3), "r"(b0), "r"(b1));
}
template <bool TRANS, typename F>
__device__ __forceinline__ void load8(uint4 (&a)[8], F addr) {
    __syncwarp();
#pragma unroll
    for (int s = 0; s < 8; s++) a[s] = ldsm<TRANS>(addr(s));
}
__device__ __forceinline__ void mma8(float (&c)[4], const uint4 (&a)[8], const uint4 (&b)[4]) {
    float e[4][4];
#pragma unroll
    for (int s = 0; s < 8; s++) {
        if (s < 4) e[s][0] = e[s][1] = e[s][2] = e[s][3] = 0.f;
        mma(e[s & 3], a[s].x, a[s].y, a[s].z, a[s].w, (s & 1) ? b[s >> 1].z : b[s >> 1].x, (s & 1) ? b[s >> 1].w : b[s >> 1].y);
    }
#pragma unroll
    for (int i = 0; i < 4; i++) c[i] = (e[0][i] + e[1][i]) + (e[2][i] + e[3][i]);
}
__device__ __forceinline__ void ldfrag(uint4 (&b)[4], uint32_t a) {
    asm volatile("ld.shared.v4.u32 {%0,%1,%2,%3}, [%16];\nld.shared.v4.u32 {%4,%5,%6,%7}, [%16+64];\n"
                 "ld.shared.v4.u32 {%8,%9,%10,%11}, [%16+128];\nld.shared.v4.u32 {%12,%13,%14,%15}, [%16+192];\n"
                 : "=r"(b[0].x), "=r"(b[0].y), "=r"(b[0].z), "=r"(b[0].w), "=r"(b[1].x), "=r"(b[1].y), "=r"(b[1].z), "=r"(b[1].w),
                   "=r"(b[2].x), "=r"(b[2].y), "=r"(b[2].z), "=r"(b[2].w), "=r"(b[3].x), "=r"(b[3].y), "=r"(b[3].z), "=r"(b[3].w) : "r"(a) : "memory");
}
__device__ __forceinline__ void quad_pair(float x, float y, int t, float& lo, float& hi) {
    const float k = ((t & 1) ? y : x) + shx((t & 1) ? x : y, 1);
    lo = k + shx(k, 2); hi = shx(k, 4) + shx(k, 6);
}
__device__ __forceinline__ void pin(uint32_t& x) { asm volatile("" : "+r"(x)); }
template <typename T> __device__ __forceinline__ void pin(T*& x) { asm volatile("" : "+l"(x)); }
__device__ __forceinline__ float4 ldsf4(uint32_t a) { const uint4 v = lds128(a); return make_float4(__uint_as_float(v.x), __uint_as_float(v.y), __uint_as_float(v.z), __uint_as_float(v.w)); }
__device__ __forceinline__ float sum4(const float4& f) { return (f.x + f.y) + (f.z + f.w); }
__device__ __forceinline__ void stsf(uint32_t a, float v) { sts32(a, __float_as_uint(v)); }

__device__ __forceinline__ void wg_fence() { asm volatile("wgmma.fence.sync.aligned;" ::: "memory"); }
__device__ __forceinline__ void wg_commit() { asm volatile("wgmma.commit_group.sync.aligned;" ::: "memory"); }
__device__ __forceinline__ void wg_wait1() { asm volatile("wgmma.wait_group.sync.aligned 1;" ::: "memory"); }
__device__ __forceinline__ void wg_wait0() { asm volatile("wgmma.wait_group.sync.aligned 0;" ::: "memory"); }
#define R8(o) "+f"(d[o]), "+f"(d[o + 1]), "+f"(d[o + 2]), "+f"(d[o + 3]), "+f"(d[o + 4]), "+f"(d[o + 5]), "+f"(d[o + 6]), "+f"(d[o + 7])
__device__ __forceinline__ void wgmma_rs_n32(float (&d)[16], const uint4& a, uint64_t db, int acc) {
    asm volatile("{\n.reg .pred p;\nsetp.ne.b32 p, %21, 0;\n"
        "wgmma.mma_async.sync.aligned.m64n32k16.f32.bf16.bf16 "
        "{%0,%1,%2,%3,%4,%5,%6,%7,%8,%9,%10,%11,%12,%13,%14,%15}, {%16,%17,%18,%19}, %20, p, 1, 1, 0;\n}"
        : R8(0), R8(8) : "r"(a.x), "r"(a.y), "r"(a.z), "r"(a.w), "l"(db), "r"(acc));
}
#define PV_LO "{%0,%1,%2,%3,%4,%5,%6,%7,%8,%9,%10,%11,%12,%13,%14,%15,%16,%17,%18,%19,%20,%21,%22,%23,%24,%25,%26,%27,%28,%29,%30,%31,%32,%33,%34,%35,%36,%37,%38,%39,%40,%41,%42,%43,%44,%45,%46,%47,%48,%49,%50,%51,%52,%53,%54,%55,%56,%57,%58,%59,%60,%61,%62,%63}, "
#define PV_HI "{%64,%65,%66,%67,%68,%69,%70,%71,%72,%73,%74,%75,%76,%77,%78,%79,%80,%81,%82,%83,%84,%85,%86,%87,%88,%89,%90,%91,%92,%93,%94,%95,%96,%97,%98,%99,%100,%101,%102,%103,%104,%105,%106,%107,%108,%109,%110,%111,%112,%113,%114,%115,%116,%117,%118,%119,%120,%121,%122,%123,%124,%125,%126,%127}, "
__device__ __forceinline__ void wgmma_pv(float (&d)[128], const uint4& a, uint32_t blo, int acc) {
    asm volatile("{\n.reg .pred p;\n.reg .b32 u0, u1, u2, u3, t;\n.reg .b64 d0, d1, d2, d3;\nsetp.ne.b32 p, %133, 0;\n"
        "mov.b64 d0, {%132, 0x40000100};\nadd.u32 t, %132, 512;\nmov.b64 d1, {t, 0x40000100};\n"
        "add.u32 t, %132, 128;\nmov.b64 d2, {t, 0x40000100};\nadd.u32 t, %132, 640;\nmov.b64 d3, {t, 0x40000100};\n"
        "wgmma.fence.sync.aligned;\n"
        "wgmma.mma_async.sync.aligned.m64n128k16.f32.bf16.bf16 " PV_LO "{%128, u0, %129, u1}, d0, p, 1, 1, 1;\n"
        "wgmma.mma_async.sync.aligned.m64n128k16.f32.bf16.bf16 " PV_LO "{%130, u2, %131, u3}, d1, 1, 1, 1, 1;\n"
        "wgmma.commit_group.sync.aligned;\n"
        "wgmma.mma_async.sync.aligned.m64n128k16.f32.bf16.bf16 " PV_HI "{%128, u0, %129, u1}, d2, p, 1, 1, 1;\n"
        "wgmma.mma_async.sync.aligned.m64n128k16.f32.bf16.bf16 " PV_HI "{%130, u2, %131, u3}, d3, 1, 1, 1, 1;\n"
        "wgmma.commit_group.sync.aligned;\n}"
        : R8(0), R8(8), R8(16), R8(24), R8(32), R8(40), R8(48), R8(56), R8(64), R8(72), R8(80), R8(88), R8(96), R8(104), R8(112), R8(120)
        : "r"(a.x), "r"(a.y), "r"(a.z), "r"(a.w), "r"(blo), "r"(acc) : "memory");
}

template <int NW>
__device__ __forceinline__ void ln_stats(float s, float q, float sh, float* scr, int w, int lane, int bar, float& mean_b, float& sd_b) {
#pragma unroll
    for (int o = 16; o; o >>= 1) { s += shx(s, o); q += shx(q, o); }
    constexpr float n = 512.f / NW;
    if (lane == 0) { scr[w] = sh + s * (1.f / n); scr[NW + w] = q - s * s * (1.f / n); }
    bar_sync(bar, NW * 32);
    float mu = 0.f, m2 = 0.f;
#pragma unroll
    for (int i = 0; i < NW; i++) { mu += scr[i]; m2 += scr[NW + i]; }
    mu *= 1.f / NW;
#pragma unroll
    for (int i = 0; i < NW; i++) { const float d = scr[i] - mu; m2 = fmaf(n * d, d, m2); }
    mean_b = rbf(mu);
    sd_b = rbf(sqrtf(rbf(rbf(fmaxf(m2, 0.f) * (1.f / 512.f)) + 1e-5f)));
}
__device__ __forceinline__ float ln_mod(float x, float mean_b, float sd_b, float c, float s) {
    return rbf(rbf(__fdividef(rbf(x - mean_b), sd_b)) * rbf(1.f + c)) + s;
}

__global__ void __cluster_dims__(2, 1, 1) __launch_bounds__(NTHREADS, 1)
fused_kernel(const __grid_constant__ First F, __nv_bfloat16* __restrict__ out, uint32_t* __restrict__ gs, const __grid_constant__ Maps M) {
    extern __shared__ __align__(1024) uint8_t sm[];
    const uint32_t sb = s2u(sm);
    const int tid = threadIdx.x, lane = tid & 31;
    const int j = blockIdx.x, rk = j & 1;
    const int g = lane >> 2, t = lane & 3;
    const int r8 = lane & 7, lb3 = (lane >> 3) & 1, lb4 = lane >> 4;
    uint64_t pol;
    asm("createpolicy.fractional.L2::evict_first.b64 %0, 1.0;" : "=l"(pol));
    {
        auto cpa = [&](uint32_t d, const uint8_t* s) {
            asm volatile("cp.async.cg.shared.global.L2::cache_hint.L2::128B [%0], [%1], 16, %2;" :: "r"(d), "l"(s), "l"(pol) : "memory");
        };
        const uint32_t ut = threadIdx.x, uj = blockIdx.x;
        const uint8_t* w = F.w[ut >= 128];
        if (ut < 128) {
            const uint32_t dq = (sb + ut * 16) ^ ((ut * 2) & 0x70);
            const uint8_t* sq = w + (uint32_t)(((uj & 1) * 256 + (ut >> 3)) * 8192 + (uj >> 1) * 128 + (ut & 7) * 16);
#pragma unroll
            for (int i = 0; i < 4 * NCP; i++) cpa(dq + 4 * 32768 + i * 2048, sq + i * 131072);
        } else if (ut < 384) {
            const uint32_t dm = (sb + ut * 16) ^ ((ut * 2) & 0x10);
            const uint8_t* sa = w + (uint32_t)(((uj >> 5) * 128 + (ut >> 1) - 64) * 6144 + (uj & 31) * 32 + (ut & 1) * 16);
            cpa(dm + SM_XA - 2048, sa); cpa(dm + SM_XA + 2048, sa + 1024);
        }
        else if (ut == 480 && uj < 64) asm volatile("prefetch.global.L2 [%0];" :: "l"(F.v[(uj >> 3) & 1] + (uj & 7) * 64));
    }
    const int warp = __shfl_sync(0xffffffffu, tid >> 5, 0);
    const __nv_bfloat16* const xin = F.v[0];
    uint32_t* const pl = gs + (warp < 2 ? (B_PR + (j >> 5)) * 4096 + (j & 31) * 32 : G_E1 + j * 8192) + (warp & 1) * 1024 + lane;
    if (warp < 4) st_x1(pl, 1u);
    auto BAR = [&](int i) -> uint32_t { return sb + SM_BAR + i * 8; };
    const uint32_t a16 = (r8 + 8 * lb4) * 32 + ((lb3 ^ (r8 >> 2)) * 16);
    const uint32_t a128 = (r8 + 8 * lb4) * 128 + ((((warp & 3) * 2 + lb3) ^ r8) * 16);
    auto ldcls = [&]() -> uint32_t { return *(const volatile uint32_t*)(sm + SM_CLS); };
    auto clear_head = [&]() {
        st2_x1(gs + (B_HA + ((j >> 4) & 1) * 2 + lb4) * 4096 + (j >> 5) * 256 + (j & 15) * 16 + (lane & 15), 0u);
        st2_x4(gs + (B_QA + rk * 8 + ((j >> 1) & 1) * 4 + (j >> 5)) * 4096 + g * 128 + ((j >> 2) & 7) * 16 + t * 4, 0u, 0u, 0u, 0u);
        if (lane < 8) st2_x1(gs + B_RD * 4096 + j * 8 + lane, 0u);
    };
    auto tma = [&](uint32_t dst, const CUtensorMap* mp, uint32_t bar, int c0, int c1, int c2, int c3) {
        asm volatile("{\n.reg .pred p;\nelect.sync _|p, 0xffffffff;\n"
                     "@p cp.async.bulk.tensor.4d.shared::cluster.global.mbarrier::complete_tx::bytes.L2::cache_hint [%0], [%1, {%3, %4, %5, %6}], [%2], %7;\n}"
                     :: "r"(dst), "l"(mp), "r"(bar), "r"(c0), "r"(c1), "r"(c2), "r"(c3), "l"(pol) : "memory");
    };
    if (warp <= 12 || warp == 15) {
        const int grp = warp == 12 ? 0 : warp == 15 ? 13 : warp + 1;
        const uint32_t cnt = grp < 10 ? 1 : grp < 13 ? 4 : 8;
        if (lane == 0) {
#pragma unroll
            for (int i = 0; i < 8; i++) mbar_init(BAR(grp * 8 + i), (i < 2 && grp == 0) ? (i ? 128 : 256) : cnt);
        }
        __syncwarp();
        if (grp < 10 && lane < 8 && (grp || lane > NCP)) mbar_expect(BAR(grp * 8 + lane), grp >= 8 ? 4096 : (uint32_t)(grp * 8 + lane - IT_X) < 4 ? 16384 : 8192);
        asm volatile("fence.mbarrier_init.release.cluster;" ::: "memory");
        __syncwarp();
        if (warp == 12) {
#pragma unroll
            for (int i = NCP + 1; i < W0; i++) tma(sb + (15 + i) * 8192, &M.m[MP_WQ], BAR(i), 0, rk * 256 + (i - 1) * 64, j >> 1, 0);
        }
    } else if (warp == 13) {
        if (lane < NMAPS) asm volatile("prefetch.tensormap [%0];" :: "l"(&M.m[lane]) : "memory");
    } else if (warp == 14) {
        clear_head();
    }
    __syncthreads();
    uint32_t in1 = 0, in2 = 0;
    if (warp < 4) { in1 = *(const uint32_t*)(xin + 2 * tid); in2 = *(const uint32_t*)(xin + 256 + 2 * tid); }
    else if (warp < 12) in1 = *(const uint32_t*)(F.v[1] + 2 * (tid - 128));
    if (warp < 12) asm volatile("cp.async.mbarrier.arrive.noinc.shared::cta.b64 [%0];" :: "r"(BAR(warp < 4)) : "memory");
    asm volatile("barrier.cluster.arrive.relaxed.aligned;" ::: "memory");

    if (warp >= 12) {
    asm volatile("setmaxnreg.dec.sync.aligned.u32 64;");
    if (warp == 12) {
        static_assert(W0 > NCP && W0 <= 5 && NCP >= 1 && NCP <= 4, "W0");
        const uint2* sched = M.sched[j < NFF ? 0 : j < J_RED ? 1 : 2];
        uint2 en = sched[W0];
        const uint32_t t0 = gtime();
        const uint32_t sp = __reduce_or_sync(0xffffffffu, sb);
        const int cx = (j >> 1) * 64 + (j < NFF ? 0 : 1024 - NFF * 32);
#pragma unroll 1
        for (int i = W0; en.x; i++) {
            uint32_t e = en.x, st = (en.y >> 20) * 64;
            const uint32_t tn = t0 + (int16_t)en.y, mp = (en.y >> 16) & 15;
            if (mp == MP_WUV || mp == MP_WUK) { st ^= (j >> 5) * (mp == MP_WUV ? 128 : 64); e ^= (j >> 5) << 6; }
            if (mp == MP_GATE || mp == MP_UP) st ^= (j & 16) * 8;
            if (mp == MP_DOWN) { st ^= (j & 3) * 64; e ^= (j & 3) << 6; }
            en = sched[i + 1];
            if (mp == MP_MODB && j >= J_END) break;
            uint32_t c0 = mp == MP_WO ? (j & 7) * 64 : mp > MP_WO ? cx : 0;
            uint32_t c1 = mp == MP_CKV ? 0 : mp == MP_DOWN ? j * 32 : st + (mp == MP_WUV ? (j & 3) * 32 : mp == MP_WO ? (j >> 3) * 256 : rk * 256);
            uint32_t c2 = mp < MP_CKV ? j >> 1 : mp == MP_CKV ? rk * 4 : mp == MP_WUV ? (j >> 2) * 2 : mp == MP_DOWN ? st >> 5 : 0;
            uint32_t c3 = mp == MP_CKV ? st * 2 + (j & ~1) : 0;
            uint32_t dst = sp + ((e << 7) & 0x3e000), bar = sp + SM_BAR + (e & 63) * 8;
            const uint32_t w0 = (e >> 8) & 0x3f8, w1 = (e >> 15) & 0x3f8, w2 = (e >> 22) & 0x3f8, bb = sp + SM_BAR - 8;
            const CUtensorMap* pm = &M.m[mp];
            pin(dst); pin(bar); pin(c0); pin(c1); pin(c2); pin(c3); pin(pm);
            if (w0) mbar_wait(bb + w0, 0);
            if (w2) {
                mbar_wait(bb + w2, 0);
                while (!__any_sync(0xffffffffu, mbar_test(bb + w1, 0) | ((int)(gtime() - tn) > 0))) {}
            } else if (w1) mbar_wait(bb + w1, 0);
            tma(dst, pm, bar, c0, c1, c2, c3);
        }
    } else if (warp == 13) {
#pragma unroll
        for (int i = 0; i < 2; i++) st_x4(gs + (B_ML + rk * 16 + i * 8 + g) * 4096 + (t >> 1) * 1024 + (j >> 1) * 8 + (t & 1) * 4, 0u, 0u, 0u, 0u);
        if (lane < 16) st2_x4(gs + (B_E2 + (j >> 4)) * 4096 + (j & 15) * 64 + lane * 4, 0u, 0u, 0u, 0u);
        st2_x1(gs + (B_E3 + (j >> 5)) * 4096 + (j & 31) * 32 + lane, 0u);
        if (lane < 8) st2_x1(gs + B_MB * 4096 + j * 8 + lane, 0u);
        if (j < NFF) {
#pragma unroll
            for (int i = 0; i < 2; i++) st2_x4(gs + (B_E5 + i * 8 + g) * 4096 + j * 16 + t * 4, 0u, 0u, 0u, 0u);
        }
        bar_sync(9, 64);
        const uint32_t cs = ldcls();
#pragma unroll 1
        for (int i = 0; i < 32; i++) {
            st_x4(gs + G_E1 + j * 8192 + (i >> 3) * 2048 + ((((cs >> 1) ^ (i >> 3)) & 1) << 10) + (i & 7) * 128 + lane * 4, 0u, 0u, 0u, 0u);
            __nanosleep(JAN_SLEEP);
        }
        fence_gpu();
        if (lane < 8) st2_x1(gs + B_RD * 4096 + j * 8 + lane, 1u + (cs >> 1));
        if (lane == 0) TRACE(41);
        uint32_t rd[4];
        mbar_wait(BAR(IT_CKV + RD_ITEM), 0);
        poll<1024, RD_SLEEP>(rd, gs + near_off(B_RD, cs) + lane * 8);
#pragma unroll
        for (int i = 0; i < 4; i++) {
            const uint32_t m = __ballot_sync(0xffffffffu, rd[i] == 2u);
            if (lane == 0) sts32(sb + SM_CLS + 16 + i * 4, m);
        }
        __syncwarp();
        if (lane < 8) mbar_arrive(BAR(JD));
        if (lane == 0) TRACE(42);
    } else if (warp == 14) {
        uint2 ml[2];
        mbar_waitb(BAR(JD), 0);
        const uint32_t cls = ldcls();
        mbar_waitb(BAR(PF0 + 2 * NUNITS - 1), 0);
        __nanosleep(ML_DELAY);
        const uint32_t* pl2 = gs + near_off(B_ML + (j >> 2), cls) + lane * 8;
        const uint32_t wa = sb + SM_W + lb4 * 64 + t * 16 + (g & 3) * 4;
        poll_start<1024>(ml, pl2);
        uint32_t w0 = 0, w1 = 0, redo = 0;
        bool first = true;
#pragma unroll 1
        for (uint32_t it = 0;; it++) {
            const bool p0 = minw(ml[0]) != 0, p1 = minw(ml[1]) != 0;
            const int n = __popc(__ballot_sync(0xffffffffu, p0)) + __popc(__ballot_sync(0xffffffffu, p1));
            const uint32_t x0 = ml[0].x, x1 = ml[1].x;
            if (n < 64) {
                if (!p0) ld_x(ml[0], pl2);
                if (!p1) ld_x(ml[1], pl2 + 256);
            }
            if (n == 64 || (first && n >= E1_EARLY)) {
                auto ord = [](int x) { return x ^ ((x >> 31) & 0x7fffffff); };
                const int o0 = ord(x0), o1 = ord(x1);
                const float mm = __int_as_float(ord(__reduce_max_sync(0xffffffffu, max(p0 ? o0 : INT_MIN, p1 ? o1 : INT_MIN))));
                const float lo = __int_as_float(ord(__reduce_min_sync(0xffffffffu, min(p0 ? o0 : INT_MAX, p1 ? o1 : INT_MAX))));
                const uint32_t v0 = pack2(ex2((p0 ? __uint_as_float(x0) : lo) - mm), 0.f), v1 = pack2(ex2((p1 ? __uint_as_float(x1) : lo) - mm), 0.f);
                redo = !first && __any_sync(0xffffffffu, v0 != w0 || v1 != w1);
                w0 = v0; w1 = v1;
                sts32(wa - redo * (SM_W - SM_W2), w0 * 0x10001u); sts32(wa - redo * (SM_W - SM_W2) + 128, w1 * 0x10001u);
                if (first) bar_arrive(3, 416);
                first = false;
                if (n == 64) break;
            }
            if (it > SPIN_LIMIT) __trap();
        }
        if (lane == 0) TRACE_Q(37);
        float L = bflo(w0) * __uint_as_float(ml[0].y) + bflo(w1) * __uint_as_float(ml[1].y);
#pragma unroll
        for (int o = 16; o; o >>= 1) L += shx(L, o);
        if (lane == 0) *(float2*)(sm + SM_FQ) = make_float2(__frcp_rn(L), __uint_as_float(redo));
        __syncwarp();
        if (lane < 8) mbar_arrive(BAR(WR));
        if (lane == 0) TRACE(10);
        bar_sync(4, 416);
        clear_head();
        if (j < NFF) {
            uint32_t ya = sb + SM_Y + lane * 16, sa = peer_addr(sb + SM_RED + 2048 + rk * 8, lane & 1), tb = peer_addr(BAR(MBB), lane & 1);
            pin(ya); pin(sa); pin(tb);
            bar_sync(7, 288);
            const float4 y0 = ldsf4(ya), y1 = ldsf4(ya + 512);
            float s = sum4(y0) + sum4(y1);
            float q = (fmaf(y0.x, y0.x, y0.y * y0.y) + fmaf(y0.z, y0.z, y0.w * y0.w)) + (fmaf(y1.x, y1.x, y1.y * y1.y) + fmaf(y1.z, y1.z, y1.w * y1.w));
#pragma unroll
            for (int o = 16; o; o >>= 1) { s += shx(s, o); q += shx(q, o); }
            if (lane < 2) st_async2(sa, s, q, tb);
        }
    } else if (warp == 15) {
        mbar_waitb(BAR(IT_X - 1), 0);
        if (j < J_END) mbar_waitb(BAR(j < NFF ? NITEMS - 1 : MBB), 0);
    }
    } else if (warp < 4) {
        float* scr = (float*)(sm + SM_SCR);
        uint32_t cls;
        {
            uint2 ha[8];
            uint32_t best = 0xffffffffu;
            sts32(sb + SM_SCR + 64 + warp * 4, best);
            const float sh = __shfl_sync(0xffffffffu, bflo(in1), 0);
            const float v0 = bflo(in1) - sh, v1 = bfhi(in1) - sh, v2 = bflo(in2) - sh, v3 = bfhi(in2) - sh;
            float mb, sd;
            ln_stats<4>((v0 + v1) + (v2 + v3), (v0 * v0 + v1 * v1) + (v2 * v2 + v3 * v3), sh, scr, warp, lane, 2, mb, sd);
            if (!rk) in2 = in1;
#pragma unroll 1
            for (int i = 0; i < NPROBE; i++) {
                uint32_t t0, t1, o;
                asm volatile("mov.u32 %0, %%clock;" : "=r"(t0));
                asm volatile("atom.relaxed.gpu.global.exch.b32 %0, [%1], %2;" : "=r"(o) : "l"(pl), "r"(2u + i) : "memory");
                asm volatile("{\n.reg .pred p;\nsetp.ne.u32 p, %1, 0x1234567;\nmov.u32 %0, 0;\n@p mov.u32 %0, %%clock;\n}" : "=r"(t1) : "r"(o));
                best = min(best, t1 - t0);
                sts32(sb + SM_SCR + 64 + warp * 4, best);
                if (__all_sync(0xffffffffu, min(best, lds32(sb + SM_SCR + 64 + (warp ^ 1) * 4)) < NEAR_CLK)) break;
            }
            bar_sync(2, 128);
            const uint4 lt = *(const uint4*)(scr + 16);
            cls = NUMA ? ((lt.y < lt.x) ^ (__popc((B_PR + (j >> 5)) & 0x2C) & 1)) | (lt.w < lt.z) << 1 : 0;
            if (warp == 0) { if (lane == 0) sts32(sb + SM_CLS, cls); bar_arrive(9, 64); }
            if (tid == 0) TRACE(38);
            asm volatile("barrier.cluster.wait.aligned;" ::: "memory");
            mbar_wait(BAR(IT_MODA), 0);
            if (HA_DELAY) __nanosleep(HA_DELAY);
            poll<1024, H_SLEEP, false, 16384>(ha, gs + near_off(B_HA + rk * 2, cls) + 2 * tid);
            auto rsum = [](uint32_t a, uint32_t b, uint32_t c, uint32_t d) { return rbf((__uint_as_float(a) + __uint_as_float(b)) + (__uint_as_float(c) + __uint_as_float(d))); };
            sts32(sb + SM_FV + frag_off(2 * tid),
                  pack2(ln_mod(bflo(in2), mb, sd, rsum(ha[4].x, ha[5].x, ha[6].x, ha[7].x), rsum(ha[0].x, ha[1].x, ha[2].x, ha[3].x)),
                        ln_mod(bfhi(in2), mb, sd, rsum(ha[4].y, ha[5].y, ha[6].y, ha[7].y), rsum(ha[0].y, ha[1].y, ha[2].y, ha[3].y))));
            bar_arrive(5, 384);
            mbar_wait(BAR(QB), 0);
            if (tid < 64) {
                const float* qx = (const float*)(sm + SM_QX) + tid;
                sts16(sb + SM_FQ + frag_off(tid), pack2((qx[0] + qx[64]) + (qx[128] + qx[192]), 0.f));
            }
            bar_arrive(6, 384);
        }
        asm volatile("setmaxnreg.inc.sync.aligned.u32 192;");
        float acc[128];
        float M = 0.f;
        uint32_t pa = sb + SM_XA + warp * 512 + lane * 16, ma = sb + SM_MX + (warp * 8 + g) * 4, pf = BAR(PF0);
        uint32_t blo = __reduce_or_sync(0xffffffffu, (((sb + SM_U) & 0x3FFFFu) >> 4) | 0x400000u);
        uint32_t* e1[4];
#pragma unroll
        for (int i = 0; i < 4; i++) e1[i] = gs + G_E1 + (warp * 8 + g) * 4 * 8192 + (rk * 2 + (j >> 6)) * 2048 + ((j >> 1) & 31) * 32 + t * 4;
#pragma unroll 1
        for (int h = 0; h < 2 * NUNITS; h++) {
            mbar_wait(pf, 0);
            const float m = __uint_as_float(lds32(ma));
            const uint4 pn = lds128(pa);
            wg_wait0();
#pragma unroll
            for (int i = 0; i < 128; i++) asm volatile("" : "+f"(acc[i]) :: "memory");
            if (h == 0) M = m;
            uint32_t b2 = 0x3f803f80u;
            if (__builtin_expect(__any_sync(0xffffffffu, m != M), 0)) {
                const float Mn = fmaxf(M, m), alpha = ex2(M - Mn), beta = ex2(m - Mn);
                M = Mn;
                b2 = pack2(beta, beta);
#pragma unroll
                for (int jj = 0; jj < 32; jj++) { acc[4 * jj] *= alpha; acc[4 * jj + 1] *= alpha; }
            }
            auto mul2 = [](uint32_t x, uint32_t y) { uint32_t r; asm("mul.rn.bf16x2 %0, %1, %2;" : "=r"(r) : "r"(x), "r"(y)); return r; };
            const uint4 p = make_uint4(mul2(pn.x, b2), mul2(pn.y, b2), mul2(pn.z, b2), mul2(pn.w, b2));
            if (tid == 0 && (h & 1)) TRACE_Q(48 + (h >> 1));
            wgmma_pv(acc, p, blo, h);
            if (lane == 0 && h > 0 && !(h & 1)) mbar_arrive(BAR(EB_UNIT0 + (h >> 1) - 1));
            blo += h == 11 ? -11 * 1024 : 1024;
            pa += (h == 5 || h == 11) ? -5 * 2048 : 2048;
            ma += 128; pf += 8;
            if (h == 2 * NUNITS - 3) {
                mbar_wait(BAR(JD), 0);
                const uint32_t hm = (*(const uint32_t*)(sm + SM_CLS + 16 + warp * 4) >> (g * 4)) ^ ((j >> 6) ? 15u : 0u);
#pragma unroll
                for (int i = 0; i < 4; i++) e1[i] += ((hm >> i) & 1) << 10;
            }
        }
#pragma unroll
        for (int vv = 0; vv < 2; vv++) {
            if (vv && M == 1.f) __trap();
            if (vv) wg_wait0(); else wg_wait1();
#pragma unroll
            for (int i = 0; i < 64; i++) asm volatile("" : "+f"(acc[vv * 64 + i]) :: "memory");
            if (tid == 0 && !vv) TRACE_Q(63);
#pragma unroll
            for (int i = 0; i < 4; i++) {
                const float* a = &acc[vv * 64 + i * 16];
                st_x4(e1[i] + i * 8192 + vv * 16, enc(pack2(a[0], a[1])), enc(pack2(a[4], a[5])), enc(pack2(a[8], a[9])), enc(pack2(a[12], a[13])));
            }
        }
        bar_arrive(3, 416);
        if (tid == 0) TRACE_Q(17);
#pragma unroll 1
        for (int pass = 0;; pass++) {
            if (j >= NFF && j < J_END && pass == (j >= J_RED)) {
                uint4 a[8], b[4];
                float c[4], e[4];
                const bool own = (warp >> 1) == rk;
                const uint32_t xa = sb + SM_FV + (warp & 1) * 64 + g * 8;
                if (lane == 0) mbar_expect(BAR(MBB), own ? 64 : 0);
#pragma unroll
                for (int i = 0; i < 2; i++) {
                    ldfrag(b, sb + SM_FS + rk * 512 + i * 256 + t * 16);
                    mbar_wait(BAR(IT_X + i), 0);
                    const uint32_t ab = sb + SM_U + B_X * 32768 + i * 16384 + a128;
                    load8<true>(a, [&](int s) { return ab + s * 2048; });
                    mma8(i ? e : c, a, b);
                }
                c[0] += e[0]; c[2] += e[2];
                if (!own) {
                    if (t == 0) st_async2(peer_addr(xa, rk ^ 1), c[0], c[2], peer_addr(BAR(MBB), rk ^ 1));
                } else {
                    mbar_wait(BAR(MBB), 0);
                    const float2 pp = *(const float2*)(sm + (xa - sb));
                    const float mine = t ? c[2] + pp.y : c[0] + pp.x, other = shx(mine, 4);
                    const uint32_t w = (warp & 1) * 8 + t * 4 + (g >> 1), val = enc(pack2(mine, other));
                    if (t < 2 && !(g & 1)) {
                        if (j < J_RED) st2_x1(gs + B_MB * 4096 + (j - NFF) * 16 + w, val);
                        else sts32(sb + SM_FV + 256 + w * 4, val);
                    }
                    __syncwarp();
                    if (j >= J_RED && lane < 4) mbar_arrive(BAR(QB));
                    if (lane == 0) TRACE(11);
                }
            }
            if (pass) break;
            uint4 a[8], a2[8];
            const uint32_t ab = sb + SM_U + B_WO * 32768 + a128;
            uint32_t* p3 = gs + (B_E3 + ((j >> 1) & 3)) * 4096 + (t >> 1) * 1024 + (rk * 2 + (warp >> 1)) * 256 + (j >> 3) * 16 + (warp & 1) * 8 + (t & 1) * 4 + (g >> 1);
            const uint32_t* pb = gs + near_off(B_E2 + (j >> 4), cls) + (((j >> 3) & 1) * 2 + lb4) * 256 + (lane & 15) * 2;
            pin(p3); pin(pb);
            uint2 bb[8];
            uint2 bq[2] = {make_uint2(0u, 0u), make_uint2(0u, 0u)};
            uint32_t xa = sb + SM_XA + lane * 16;
            pin(xa);
            bool h0 = false, h1 = false;
            auto idle = [&]() {
                if (!h0) {
                    h0 = __all_sync(0xffffffffu, mbar_test(BAR(IT_WO + (t & 1)), 0));
                    if (h0) load8<true>(a, [&](int s) { return ab + s * 2048; });
                }
                if (!h1) {
                    h1 = __all_sync(0xffffffffu, mbar_test(BAR(IT_WO + 2 + (t & 1)), 0));
                    if (h1) load8<true>(a2, [&](int s) { return ab + 16384 + s * 2048; });
                }
            };
            bar_sync(4, 416);
            idle();
            poll<128, 0, true>(bq, pb + warp * 64, idle);
            asm volatile("st.shared.v4.u32 [%0], {%1, %2, %3, %4};" :: "r"(xa + warp * 512), "r"(bq[0].x), "r"(bq[0].y), "r"(bq[1].x), "r"(bq[1].y) : "memory");
            bar_sync(2, 128);
#pragma unroll
            for (int i = 0; i < 4; i++) { const uint4 q = lds128(xa + i * 512); bb[2 * i] = make_uint2(q.x, q.y); bb[2 * i + 1] = make_uint2(q.z, q.w); }
            if (tid == 0) TRACE(21);
            float e[4][4];
#pragma unroll
            for (int s = 0; s < 16; s++) {
                if (s == 0 && !h0) { mbar_wait(BAR(IT_WO), 0); mbar_wait(BAR(IT_WO + 1), 0); load8<true>(a, [&](int q) { return ab + q * 2048; }); }
                if (s == 0 && !h1) { mbar_wait(BAR(IT_WO + 2), 0); mbar_wait(BAR(IT_WO + 3), 0); load8<true>(a2, [&](int q) { return ab + 16384 + q * 2048; }); }
                const int z = (s & 1) | (s & 2) << 2 | (s >> 2) << 1;
                const uint4& x = z < 8 ? a[z] : a2[z & 7];
                float (&d)[4] = e[(z >> 3) * 2 + (z & 1)];
                if (!(z & 6)) d[0] = d[1] = d[2] = d[3] = 0.f;
                mma(d, x.x, x.y, x.z, x.w, bb[z & 7].x, bb[z & 7].y);
            }
            float lo, hi;
            quad_pair((t & 2) ? (e[2][0] + e[3][0]) + (e[2][1] + e[3][1]) : (e[0][0] + e[1][0]) + (e[0][1] + e[1][1]),
                      (t & 2) ? (e[2][2] + e[3][2]) + (e[2][3] + e[3][3]) : (e[0][2] + e[1][2]) + (e[0][3] + e[1][3]), t, lo, hi);
            if (!(g & 1)) st_x1(p3, enc(pack2(lo, hi)));
            if (j < NFF) bar_arrive(8, 384); else if (j >= J_RED && j < J_END) bar_arrive(8, 192);
            if (tid == 0) TRACE(22);
        }
        if (j < NFF) {
            uint4 a[16];
            const uint32_t ad = sb + SM_U + B_DN * 32768 + warp * 8192 + (r8 + 8 * lb4) * 128 + (lb3 ^ r8) * 16;
            uint32_t rl = sb + SM_RED + lane * 16;
            uint32_t* p5 = gs + (B_E5 + warp * 4 + (t >> 1)) * 4096 + j * 16 + (t & 1) * 8 + g;
            pin(rl); pin(p5);
            if (lane == 0) mbar_expect(BAR(MBB), 4);
            auto ldd = [&]() {
#pragma unroll
                for (int s = 0; s < 16; s++) a[s] = ldsm<true>((ad ^ ((s & 3) * 32)) + (s >> 2) * 2048);
            };
            const uint32_t db = BAR(IT_DOWN + (warp ^ (j & 3)));
            mbar_wait(BAR(MBB), 0);
            const float4 st = ldsf4(sb + SM_RED + 2048);
            const bool hd = __all_sync(0xffffffffu, mbar_test(db, 0));
            if (hd) ldd();
            const float mu = (st.x + st.z) * (1.f / 512.f);
            float rstd;
            asm volatile("rsqrt.approx.ftz.f32 %0, %1;" : "=f"(rstd) : "f"(fmaxf(fmaf(-mu, mu, (st.y + st.w) * (1.f / 512.f)), 0.f) + 1e-5f));
            mbar_wait(BAR(QB), 1);
            if (tid == 0) TRACE(25);
            const float4 f0 = ldsf4(rl), f2 = ldsf4(rl + 1024), f1 = ldsf4(rl + 512), f3 = ldsf4(rl + 1536);
            const float gg = fmaf(rstd, fmaf(-mu, f0.z + f2.z, (f0.x + f0.y) + (f2.x + f2.y)), f0.w + f2.w);
            const float uu = fmaf(rstd, fmaf(-mu, f1.z + f3.z, (f1.x + f1.y) + (f3.x + f3.y)), f1.w + f3.w);
            const float hh = __fdividef(gg * uu, 1.f + ex2(-gg * fmaf(gg * gg, 0.10294324f, 2.3022082f)));
            uint32_t hb[4];
#pragma unroll
            for (int i = 0; i < 4; i++) hb[i] = pack2(__shfl_sync(0xffffffffu, hh, 2 * t + 8 * i), __shfl_sync(0xffffffffu, hh, 2 * t + 8 * i + 1));
            auto down = [&]() {
#pragma unroll
                for (int i = 0; i < 2; i++) {
                    uint32_t res = 0;
#pragma unroll
                    for (int k = 0; k < 4; k++) {
                        float c[4] = {0.f, 0.f, 0.f, 0.f};
                        const uint4 &x = a[i * 8 + k], &y = a[i * 8 + k + 4];
                        mma(c, x.x, x.y, x.z, x.w, hb[0], hb[1]);
                        mma(c, y.x, y.y, y.z, y.w, hb[2], hb[3]);
                        if (t == k) res = pack2(c[0], c[2]);
                    }
                    st2_x1(p5 + i * 8192, enc(res));
                }
            };
            if (hd) down();
            else { mbar_wait(db, 0); ldd(); down(); asm volatile("// late" ::: "memory"); }
            if (tid == 0) { TRACE(27); TRACE_GT(47); }
        }
    } else {
        const int u8 = tid - 128, w8 = warp - 4;
        const int v = w8 >> 2, wq4 = w8 & 3;
        {
            const float c0 = bflo(in1), c1 = bfhi(in1);
            sts32(sb + SM_FS + frag_off(2 * u8), pack2(__fdividef(c0, 1.f + __expf(-c0)), __fdividef(c1, 1.f + __expf(-c1))));
        }
        bar_sync(1, 256);
        asm volatile("barrier.cluster.wait.aligned;" ::: "memory");
        uint4 a[8], b[4]; float c[4];
        if (w8 < 2) {
            ldfrag(b, sb + SM_FS + (j >> 5) * 256 + t * 16);
            mbar_wait(BAR(IT_MODA), 0);
            if (u8 == 0) TRACE(12);
            const uint32_t ab = sb + SM_XA + w8 * 4096 + a16;
            load8<true>(a, [&](int s) { return ab + s * 512; });
            mma8(c, a, b);
            if (t < 2) st2_x1(gs + (B_HA + ((j >> 4) & 1) * 2 + w8) * 4096 + (j >> 5) * 256 + (j & 15) * 16 + t * 8 + g, encf(t ? c[2] : c[0]));
        }
        {
            mbar_wait(BAR(IT_WQ + 2 * v <= NCP ? 1 : IT_WQ + 2 * v), 0); mbar_wait(BAR(IT_WQ + 2 * v + 1 <= NCP ? 1 : IT_WQ + 2 * v + 1), 0);
            const uint32_t ab = sb + SM_U + 4 * 32768 + v * 16384 + a128;
            load8<true>(a, [&](int s) { return ab + s * 2048; });
            if (lane == 0) mbar_arrive(BAR(EB_WQ));
            bar_sync(5, 384);
            if (u8 == 0) TRACE(13);
            ldfrag(b, sb + SM_FV + v * 256 + t * 16);
            mma8(c, a, b);
            if (t < 2) {
                const float qv = t ? c[2] : c[0];
                const uint32_t qa_ = sb + SM_QX + ((rk * 2 + v) * 64 + wq4 * 16 + t * 8 + g) * 4;
                asm volatile("st.async.weak.shared::cluster.mbarrier::complete_tx::bytes.f32 [%0], %1, [%2];"
                             :: "r"(peer_addr(qa_, rk ^ 1)), "f"(qv), "r"(peer_addr(BAR(QB), rk ^ 1)) : "memory");
                sts32(qa_, __float_as_uint(qv));
            }
            __syncwarp();
            if (lane == 0) mbar_expect(BAR(QB), 64);
        }
        {
            mbar_wait(BAR(IT_WUK + (v ^ ((j >> 5) & 1))), 0); mbar_wait(BAR(IT_WUK + (v ^ ((j >> 5) & 1)) + 2), 0);
            const uint32_t ab = sb + SM_U + 5 * 32768 + (w8 * 16 + r8 + 8 * lb3) * 128;
            const uint32_t x16 = (lb4 ^ r8) * 16;
            load8<false>(a, [&](int s) { return ab + (s & 1) * 16384 + (x16 ^ ((s >> 1) * 32)); });
            bar_sync(6, 384);
            if (u8 == 0) TRACE(14);
            b[0] = lds128(sb + SM_FQ + t * 16); b[1] = lds128(sb + SM_FQ + 64 + t * 16);
            float e[4] = {0.f, 0.f, 0.f, 0.f};
            c[0] = c[1] = c[2] = c[3] = 0.f;
#pragma unroll
            for (int k = 0; k < 4; k++) {
                const uint32_t b0 = (k & 1) ? b[k >> 1].z : b[k >> 1].x, b1 = (k & 1) ? b[k >> 1].w : b[k >> 1].y;
                mma(c, a[2 * k].x, a[2 * k].y, a[2 * k].z, a[2 * k].w, b0, b1);
                mma(e, a[2 * k + 1].x, a[2 * k + 1].y, a[2 * k + 1].z, a[2 * k + 1].w, b0, b1);
            }
            const float mine = ((t & 1) ? ((t & 2) ? e[2] : e[0]) : ((t & 2) ? c[2] : c[0])) * 0.12751743f;
            const float other = shx(mine, 4);
            if (!(g & 1)) st2_x1(gs + (B_QA + rk * 8 + ((j >> 1) & 1) * 4 + (j >> 5)) * 4096 + w8 * 128 + ((j >> 2) & 7) * 16 + (g >> 1) * 4 + t, enc(pack2(mine, other)));
            if (u8 == 0) TRACE(15);
        }
        const uint32_t cls = ldcls();
        __nanosleep(QA_DELAY);
        {
            uint4 qb[8];
            const uint32_t* pq = gs + near_off(B_QA + rk * 8 + wq4, cls) + lane * 4;
            const uint32_t* pq2 = gs + near_off(B_QA + rk * 8 + 4 + wq4, cls) + lane * 4;
            if (lane == 0) {
                mbar_expect(BAR(QT), 4096);
                asm volatile("cp.async.bulk.shared::cluster.global.mbarrier::complete_tx::bytes [%0], [%1], 4096, [%2];"
                             :: "r"(sb + SM_U + 5 * 32768 + w8 * 4096), "l"(gs + near_off(B_QA + rk * 8 + w8, cls)), "r"(BAR(QT)) : "memory");
            }
            const uint32_t qs = sb + SM_U + 5 * 32768 + wq4 * 4096 + lane * 16;
            mbar_wait(BAR(QT), 0);
#pragma unroll
            for (int i = 0; i < 8; i++) { a[i] = lds128(qs + i * 512); qb[i] = lds128(qs + 16384 + i * 512); }
            poll<512, QA_SLEEP, true>(a, pq);
            poll<512, QA_SLEEP, true>(qb, pq2);
            if (lane == 0) mbar_arrive(BAR(EB_WUK));
            auto add2 = [](uint32_t x, uint32_t y) { uint32_t r; asm("add.rn.bf16x2 %0, %1, %2;" : "=r"(r) : "r"(x), "r"(y)); return r; };
#pragma unroll
            for (int i = 0; i < 8; i++) a[i] = make_uint4(add2(a[i].x, qb[i].x), add2(a[i].y, qb[i].y), add2(a[i].z, qb[i].z), add2(a[i].w, qb[i].w));
        }
        if (u8 == 0) TRACE(8);
        {
            float m = -INFINITY, l = 0.f;
            uint32_t xl = sb + SM_XB + w8 * 2048 + lane * 16, xr = peer_addr(xl, rk ^ 1), bsr = peer_addr(BAR(SF0 + v), rk ^ 1);
            uint32_t pa = sb + SM_XA + v * 2048 + wq4 * 512 + lane * 16, ma = sb + SM_MX + v * 128 + (wq4 * 8 + g) * 4;
            uint32_t fb = BAR(IT_CKV + v * 2), sf = BAR(SF0 + v);
            uint32_t dlo = __reduce_or_sync(0xffffffffu, (((sb + SM_U + v * 16384) & 0x3FFFFu) >> 4) | 0x10000u);
            if (STAG && v) __nanosleep(STAG);
#pragma unroll 1
            for (int n = 0; n < NUNITS; n++) {
                float d[2][16], sc[8];
#pragma unroll
                for (int i = 0; i < 2; i++) {
                    mbar_wait(fb + i * 8, 0);
                    wg_fence();
#pragma unroll
                    for (int s = 0; s < 8; s++) wgmma_rs_n32(d[i], a[s], (0x40000080ull << 32) | (dlo + i * 512 + (s >> 2) * 64 + (s & 3) * 2), s);
                    wg_commit();
                }
#pragma unroll
                for (int i = 0; i < 2; i++) {
                    if (i) wg_wait0(); else wg_wait1();
#pragma unroll
                    for (int k = 0; k < 16; k++) asm volatile("" : "+f"(d[i][k]) :: "memory");
                    sc[4 * i] = d[i][0] + d[i][6]; sc[4 * i + 1] = d[i][1] + d[i][7]; sc[4 * i + 2] = d[i][8] + d[i][14]; sc[4 * i + 3] = d[i][9] + d[i][15];
                    asm volatile("st.async.weak.shared::cluster.mbarrier::complete_tx::bytes.v4.f32 [%0], {%1, %2, %3, %4}, [%5];"
                                 :: "r"(xr + i * 1024), "f"(sc[4 * i]), "f"(sc[4 * i + 1]), "f"(sc[4 * i + 2]), "f"(sc[4 * i + 3]), "r"(bsr) : "memory");
                }
                if (u8 == 128) TRACE_Q(56 + (n < 6 ? n : -40));
                if (n >= 3) mbar_wait(BAR(EB_UNIT0 + n - 3), 0);
                dlo += n == 5 ? -5 * 2048 : 2048;
                fb += 32; xr ^= 512; bsr += 16;
                pin(fb); pin(xr); pin(bsr);
                mbar_wait(sf, 0);
                const float4 x = ldsf4(xl), y = ldsf4(xl + 1024);
                sc[0] += x.x; sc[1] += x.y; sc[2] += x.z; sc[3] += x.w; sc[4] += y.x; sc[5] += y.y; sc[6] += y.z; sc[7] += y.w;
                float pr[8];
#pragma unroll
                for (int i = 0; i < 8; i++) pr[i] = ex2(sc[i] - m);
                float mx = fmaxf(fmaxf(fmaxf(sc[0], sc[1]), fmaxf(sc[2], sc[3])), fmaxf(fmaxf(sc[4], sc[5]), fmaxf(sc[6], sc[7])));
                if (__builtin_expect(__any_sync(0xffffffffu, mx > m), 0)) {
                    mx = fmaxf(mx, shx(mx, 1));
                    mx = fmaxf(mx, shx(mx, 2));
                    const float mn = fmaxf(m, ceilf(mx * 0.0625f) * 16.f);
                    l *= ex2(m - mn);
                    m = mn;
#pragma unroll
                    for (int i = 0; i < 8; i++) pr[i] = ex2(sc[i] - m);
                }
                stsf(ma, m);
                asm volatile("st.shared.v4.u32 [%0], {%1, %2, %3, %4};" :: "r"(pa), "r"(pack2(pr[0], pr[1])), "r"(pack2(pr[2], pr[3])),
                             "r"(pack2(pr[4], pr[5])), "r"(pack2(pr[6], pr[7])) : "memory");
                __syncwarp();
                if (lane == 0) mbar_arrive(sf + (PF0 - SF0) * 8);
                l += ((pr[0] + pr[1]) + (pr[2] + pr[3])) + ((pr[4] + pr[5]) + (pr[6] + pr[7]));
                xl ^= 512; sf += 16; ma += 256; pa += (n == 2 || n == 5) ? -8192 : 4096;
            }
            l += shx(l, 1);
            l += shx(l, 2);
            float2* mlx = (float2*)(sm + SM_MX + 2048) + wq4 * 8 + g;
            if (v == 0) { *mlx = make_float2(m, l); bar_arrive(11, 256); }
            else {
                mbar_wait(BAR(JD), 0);
                bar_sync(11, 256);
                const float2 o = *mlx;
                const float mn = fmaxf(m, o.x);
                l = l * ex2(m - mn) + o.y * ex2(o.x - mn);
                if ((wq4 >> 1) == rk) st_x4(gs + (B_ML + wq4 * 8 + g) * 4096 + (t >> 1) * 1024 + (j >> 1) * 8 + (t & 1) * 4, encf(mn), encf(l), 1u, 1u);
            }
        }
        const int pi = j < NFF ? rk * 128 + w8 * 16 + (lane >> 1) : ((j - J_RED) & 15) * 16 + (w8 & 1) * 8 + g;
        const uint32_t xw = *(const uint32_t*)(xin + 2 * pi);
        const uint32_t one = (g & 1) ? 0x3f800000u : 0x00003f80u;
        const uint32_t* pm = gs + near_off(B_MB, cls) + pi;
        {
            const uint32_t ab = sb + SM_U + B_WUV * 32768 + v * 4096 + a128;
            uint32_t pa = sb + SM_PB + wq4 * 320 + frag_off(64 * v + 32 * (g >> 2) + 16 * (t & 1) + 8 * (t >> 1) + 2 * (g & 3));
            uint32_t fa = sb + SM_PB + g * 320 + t * 16;
            const uint32_t* pe = gs + G_E1 + j * 8192 + (w8 >> 1) * 2048 + ((((cls >> 1) ^ (w8 >> 1)) & 1) << 10) + (((w8 & 1) * 16 + t) * 8 + g) * 4;
            uint32_t* p2 = gs + (B_E2 + (j >> 4)) * 4096 + (t >> 1) * 1024 + (j & 12) * 64 + w8 * 32 + (j & 3) * 8 + (g & 6) + (t & 1);
            pin(pa); pin(fa); pin(pe); pin(p2);
            const uint32_t mk = (g & 1) ? 0xffff0000u : 0x0000ffffu, m0 = (g & 2) ? 0u : mk, m1 = (g & 2) ? mk : 0u;
            uint4 pv[4];
            bool hv = false;
            bar_sync(3, 416);
            uint4 wa = lds128(sb + SM_W + (wq4 * 4 + t) * 16);
            uint32_t wb[8] = {wa.x & m0, wa.x & m1, wa.y & m0, wa.y & m1, wa.z & m0, wa.z & m1, wa.w & m0, wa.w & m1};
            pv[0] = pv[1] = pv[2] = pv[3] = make_uint4(0u, 0u, 0u, 0u);
            float e[4][4];
            auto wsum = [&]() {
#pragma unroll
                for (int i = 0; i < 4; i++) {
                    e[i][0] = e[i][1] = e[i][2] = e[i][3] = 0.f;
                    mma(e[i], pv[i].x, pv[i].y, pv[i].z, pv[i].w, wb[2 * i], wb[2 * i + 1]);
                }
            };
            poll<512, E1_SLEEP, true>(pv, pe, [&]() {
                if (!hv) {
                    hv = __all_sync(0xffffffffu, mbar_test(BAR(IT_WUV + t), 0));
                    if (hv) load8<true>(a, [&](int s) { return ab + (s >> 1) * 8192 + (s & 1) * 2048; });
                }
            }, wsum);
            if (lane == 0) TRACE_Q(48 + w8);
            if (u8 == 0) TRACE_Q(18);
            float lo, hi2;
            float2 inv;
#pragma unroll 1
            for (int pass = 0;; pass++) {
                const float r0 = (t & 2) ? (e[0][2] + e[1][2]) + (e[2][2] + e[3][2]) : (e[0][0] + e[1][0]) + (e[2][0] + e[3][0]);
                const float r1 = (t & 2) ? (e[0][3] + e[1][3]) + (e[2][3] + e[3][3]) : (e[0][1] + e[1][1]) + (e[2][1] + e[3][1]);
                const uint32_t hi = pack2(r0, r1);
                sts32(pa, hi); sts32(pa + 1280, pack2(r0 - bflo(hi), r1 - bfhi(hi)));
                if (!hv) {
#pragma unroll 1
                    for (int i = 0; i < 4; i++) mbar_wait(BAR(IT_WUV + i), 0);
                    load8<true>(a, [&](int s) { return ab + (s >> 1) * 8192 + (s & 1) * 2048; });
                    hv = true;
                }
                bar_sync(1, 256);
                if (u8 == 0) TRACE(19);
                ldfrag(b, fa);
                mma8(c, a, b);
                mbar_wait(BAR(WR), 0);
                asm volatile("ld.shared.v2.f32 {%0, %1}, [%2];" : "=f"(inv.x), "=f"(inv.y) : "r"(sb + SM_FQ) : "memory");
                quad_pair(c[0] + c[1], c[2] + c[3], t, lo, hi2);
                if (__builtin_expect(__all_sync(0xffffffffu, pass || __float_as_uint(inv.y) == 0), 1)) break;
                wa = lds128(sb + SM_W2 + (wq4 * 4 + t) * 16);
                wb[0] = wa.x & m0; wb[1] = wa.x & m1; wb[2] = wa.y & m0; wb[3] = wa.y & m1; wb[4] = wa.z & m0; wb[5] = wa.z & m1; wb[6] = wa.w & m0; wb[7] = wa.w & m1;
                wsum();
                bar_sync(1, 256);
            }
            if (!(g & 1)) st_x1(p2, enc(pack2(lo * inv.x, hi2 * inv.x)));
            bar_arrive(4, 416);
            if (u8 == 0) TRACE(20);
        }
        if (j < NFF) {
            const uint32_t* p3 = gs + near_off(B_E3 + rk * 2 + v, cls) + wq4 * 256 + t * 16 + g * 2;
            const int od = lane & 1;
            uint32_t za = sb + SM_FZ + od * 576 + frag_off(w8 * 32 + (lane & 30));
            uint32_t fa = sb + SM_FZ + (g & 3) * 576 + ((lane ^ j) & 16) * 16 + t * 16, ya = sb + SM_Y + u8 * 4;
            uint32_t mb[3];
            uint4 a2[8];
            poll<1024, MB_SLEEP>(mb, pm);
            const uint32_t kk = pack2(1.f + bflo(mb[2]), 1.f + bfhi(mb[2]));
            sts32(za + 2 * 576, od ? mb[1] : kk);
            uint2 e3[4] = {make_uint2(0u, 0u), make_uint2(0u, 0u), make_uint2(0u, 0u), make_uint2(0u, 0u)};
            uint32_t ra = peer_addr(sb + SM_RED + (rk * 2 + v) * 512 + ((wq4 & 1) * 16 + (t >> 1) * 8 + g) * 16 + (t & 1) * 8, wq4 >> 1), tbo = peer_addr(BAR(QB), wq4 >> 1);
            pin(za); pin(fa); pin(ya); pin(ra); pin(tbo);
            if (lane == 0) mbar_expect(BAR(QB), 256);
            const uint32_t gb = BAR(IT_X + v * 2), ab = sb + SM_U + (B_X + v) * 32768 + a128;
            bool early = false, early2 = false;
            auto ldw = [&]() {
                if (!early) {
                    early = __all_sync(0xffffffffu, mbar_test(gb, 0));
                    if (early) load8<true>(a, [&](int s) { return ab + s * 2048; });
                }
                if (!early2) {
                    early2 = __all_sync(0xffffffffu, mbar_test(gb + 8, 0));
                    if (early2) load8<true>(a2, [&](int s) { return ab + 16384 + s * 2048; });
                }
            };
            bar_sync(8, 384);
            float s0[4], s1[4];
            auto sum = [&]() {
                s0[0] = s0[1] = s0[2] = s0[3] = s1[0] = s1[1] = s1[2] = s1[3] = 0.f;
                mma(s0, e3[0].x, e3[0].y, e3[1].x, e3[1].y, one, one); mma(s1, e3[2].x, e3[2].y, e3[3].x, e3[3].y, one, one);
            };
            poll<256, 0, true>(e3, p3, ldw, sum);
            if (u8 == 0) TRACE(23);
            const float y0 = fmaf(bflo(mb[0]), (t & 2) ? s0[2] + s1[2] : s0[0] + s1[0], bflo(xw)), y1 = fmaf(bfhi(mb[0]), (t & 2) ? s0[3] + s1[3] : s0[1] + s1[1], bfhi(xw));
            stsf(ya, od ? y1 : y0);
            const float z0 = y0 * bflo(kk), z1 = y1 * bfhi(kk);
            const uint32_t zh = pack2(z0, z1);
            sts32(za, od ? pack2(z0 - bflo(zh), z1 - bfhi(zh)) : zh);
            bar_sync(7, 288);
            if (u8 == 0) TRACE(24);
            ldfrag(b, fa);
            if (!early) { mbar_wait(gb, 0); load8<true>(a, [&](int s) { return ab + s * 2048; }); }
            {
                float e[4][4];
#pragma unroll
                for (int s = 0; s < 16; s++) {
                    if (s == 8 && !early2) { mbar_wait(gb + 8, 0); load8<true>(a2, [&](int q) { return ab + 16384 + q * 2048; }); }
                    const uint4& x = s < 8 ? a[s] : a2[s & 7];
                    const uint4& y = b[(s >> 1) & 3];
                    float (&d)[4] = e[(s >> 3) * 2 + (s & 1)];
                    if (!(s & 6)) d[0] = d[1] = d[2] = d[3] = 0.f;
                    mma(d, x.x, x.y, x.z, x.w, (s & 1) ? y.z : y.x, (s & 1) ? y.w : y.y);
                }
                const bool hi = t >> 1;
                const float k0 = hi ? e[2][2] + e[3][2] : e[0][0] + e[1][0], k1 = hi ? e[2][3] + e[3][3] : e[0][1] + e[1][1];
                const float o0 = hi ? e[2][0] + e[3][0] : e[0][2] + e[1][2], o1 = hi ? e[2][1] + e[3][1] : e[0][3] + e[1][3];
                st_async2(ra, k0 + shx(o0, 2), k1 + shx(o1, 2), tbo);
            }
        } else if (j >= J_RED && j < J_END && w8 < 2) {
            uint32_t ga[1], e3[4];
            poll<0, MB_SLEEP>(ga, pm);
            bar_sync(8, 192);
            poll<64, 100>(e3, gs + near_off(B_E3 + (pi >> 6), cls) + (pi & 48) * 16 + t * 64 + (pi & 15));
            float y0 = (bflo(e3[0]) + bflo(e3[1])) + (bflo(e3[2]) + bflo(e3[3])), y1 = (bfhi(e3[0]) + bfhi(e3[1])) + (bfhi(e3[2]) + bfhi(e3[3]));
#pragma unroll
            for (int o = 1; o < 4; o <<= 1) { y0 += shx(y0, o); y1 += shx(y1, o); }
            const int col = g + (t & 1) * 8;
            y0 = __shfl_sync(0xffffffffu, (t & 1) ? fmaf(bfhi(ga[0]), y1, bfhi(xw)) : fmaf(bflo(ga[0]), y0, bflo(xw)), (col >> 1) * 4 + (col & 1));
            uint16_t* po = (uint16_t*)out + (j - J_RED) * 32 + w8 * 16 + col;
            const uint32_t* pe = gs + near_off(B_E5 + j - J_RED, cls) + t * 16 + w8 * 8 + g;
            pin(po);
            const uint32_t sel = (g & 2) ? 0x3f800000u : 0x00003f80u;
            uint32_t yv[NFF / 4 + 1];
            float e[4][4], gb = 0.f;
#pragma unroll
            for (int i = 0; i <= NFF / 4; i++) yv[i] = 0u;
#pragma unroll 1
            for (uint32_t it = 0;; it++) {
#pragma unroll
                for (int i = 0; i < NFF / 4; i++) if (!yv[i]) ld_x(yv[i], pe + i * 64);
                if (__all_sync(0xffffffffu, !yv[NFF / 4] && mbar_test(BAR(QB), 1))) {
                    yv[NFF / 4] = lds32(sb + SM_FV + 256 + w8 * 32 + (col >> 1) * 4);
                    gb = (col & 1) ? bfhi(yv[NFF / 4]) : bflo(yv[NFF / 4]);
                }
                if (it > SPIN_LIMIT) __trap();
#pragma unroll
                for (int i = 0; i < 4; i++) {
                    e[i][0] = e[i][1] = e[i][2] = e[i][3] = 0.f;
                    mma(e[i], yv[4 * i], yv[4 * i + 1], i < 3 ? yv[(4 * i + 2) % (NFF / 4)] : 0u, i < 3 ? yv[(4 * i + 3) % (NFF / 4)] : 0u, sel, sel);
                }
                if (__all_sync(0xffffffffu, mint<NFF / 4 + 1>(yv) != 0)) break;
            }
            if (u8 == 0) TRACE(26);
            const float s = ((e[0][0] + e[0][2]) + (e[1][0] + e[1][2])) + ((e[2][0] + e[2][2]) + (e[3][0] + e[3][2]));
            asm volatile("{\n.reg .pred p;\nsetp.lt.u32 p, %2, 2;\n@p st.global.u16 [%0], %1;\n}" :: "l"(po), "h"((uint16_t)pack2(fmaf(gb, s, y0), 0.f)), "r"(t) : "memory");
            asm volatile("{\n.reg .pred p;\nsetp.eq.f32 p, %0, 0f7F7FFFFF;\n@p nanosleep.u32 0;\n}" :: "f"(((e[0][1] + e[0][3]) + (e[1][1] + e[1][3])) + ((e[2][1] + e[2][3]) + (e[3][1] + e[3][3]))));
            if (u8 == 0) TRACE(27);
        }
    }
}

typedef CUresult (*EncFn)(CUtensorMap*, CUtensorMapDataType, cuuint32_t, void*, const cuuint64_t*, const cuuint64_t*,
                          const cuuint32_t*, const cuuint32_t*, CUtensorMapInterleave, CUtensorMapSwizzle,
                          CUtensorMapL2promotion, CUtensorMapFloatOOBfill);

void make_map(EncFn enc_fn, CUtensorMap* m, const void* p, cuuint64_t d0, cuuint64_t d1, cuuint64_t d2, cuuint64_t d3,
              cuuint64_t s1, cuuint64_t s2, cuuint64_t s3, cuuint32_t b0, cuuint32_t b1, cuuint32_t b2, cuuint32_t b3, CUtensorMapSwizzle sw) {
    const cuuint64_t dims[4] = {d0, d1, d2, d3}, strides[3] = {s1, s2, s3};
    const cuuint32_t box[4] = {b0, b1, b2, b3}, es[4] = {1, 1, 1, 1};
    enc_fn(m, CU_TENSOR_MAP_DATA_TYPE_BFLOAT16, 4, (void*)p, dims, strides, box, es,
           CU_TENSOR_MAP_INTERLEAVE_NONE, sw, PROMO, CU_TENSOR_MAP_FLOAT_OOB_FILL_NONE);
}

uint32_t* scratch = nullptr;

struct Tune { const char* win; const char* late; int tau, t_off; const char* tail[3][4]; };
Tune tune = {"77777777755555555555555555555555555555544",
             "00000000000000888888888888888888888888888", 322, -360,
             {{"VVVVOOOOguguDDDD", "zzzzzzzzzzzzzzzz", "7777aaaaaaaa6789", "ebbb9ddddaaa2555"},
              {"VMVMVVOOOO", "zzzzzzzzzz", "9999999999", "8aaaaac999"},
              {"VVVVOOOOMM", "zzzzzzzzzz", "aaaaaaaa88", "b1111a9asb"}}};
bool ready = false;

}

extern "C" void kernel_launch(void* const* d_in, const int* in_sizes, int n_in, void* d_out, int out_size) {
    (void)in_sizes; (void)n_in; (void)out_size;
    static Maps maps;
    static const void* cached[12] = {};
    bool same = ready;
    for (int i = 0; i < 12 && same; i++) same = cached[i] == d_in[i];
    if (!same) {
        void* fn = nullptr;
        cudaDriverEntryPointQueryResult qr;
        cudaGetDriverEntryPoint("cuTensorMapEncodeTiled", &fn, cudaEnableDefault, &qr);
        EncFn e = (EncFn)fn;
        const CUtensorMapSwizzle S128 = CU_TENSOR_MAP_SWIZZLE_128B;
        make_map(e, &maps.m[MP_WQ], d_in[2], 64, 512, 64, 1, 8192, 128, 8192, 64, 64, 1, 1, S128);
        make_map(e, &maps.m[MP_WUK], d_in[3], 64, 512, 64, 1, 8192, 128, 8192, 64, 64, 1, 1, S128);
        make_map(e, &maps.m[MP_CKV], d_in[1], 64, 8, 8, 4096, 1024, 128, 8192, 64, 8, 4, 2, S128);
        make_map(e, &maps.m[MP_MODB], d_in[11], 3072, 512, 1, 1, 6144, 6144, 6144, 64, 128, 1, 1, S128);
        make_map(e, &maps.m[MP_WUV], d_in[4], 64, 512, 64, 1, 8192, 128, 8192, 64, 32, 2, 1, S128);
        make_map(e, &maps.m[MP_WO], d_in[5], 512, 4096, 1, 1, 1024, 1024, 1024, 64, 64, 1, 1, S128);
        make_map(e, &maps.m[MP_GATE], d_in[7], 1792, 512, 1, 1, 3584, 3584, 3584, 64, 128, 1, 1, S128);
        make_map(e, &maps.m[MP_UP], d_in[8], 1792, 512, 1, 1, 3584, 3584, 3584, 64, 128, 1, 1, S128);
        make_map(e, &maps.m[MP_DOWN], d_in[9], 64, 1792, 8, 1, 1024, 128, 1024, 64, 32, 2, 1, S128);
        for (int r = 0; r < 3; r++) {
            int ids[58], cnt[128] = {}, tn = tune.t_off - (W0 - 1) * tune.tau;
            uint2* sc = maps.sched[r];
            auto dig = [](char ch) { return ch >= 'a' ? ch - 'a' + 10 : ch >= 'A' ? ch - 'A' + 36 : ch - '0'; };
            for (int i = 0; i < 58; i++) sc[i] = make_uint2(0u, 0u);
            for (int i = 0;; i++) {
                int id = i, buf, dep, w, wl;
                if (i < IT_WUV) {
                    const int u = (i - IT_CKV) >> 2;
                    buf = i < IT_CKV ? 4 + ((i - 1) >> 2) : u % 6;
                    dep = i < IT_CKV || u < 4 ? -1 : u < 6 ? EB_WQ + u - 4 : EB_UNIT0 + u - 6;
                    w = dig(tune.win[i]); wl = dig(tune.late[i]);
                    if (i) tn += tune.tau;
                } else {
                    const char ch = tune.tail[r][0][i - IT_WUV];
                    if (!ch) break;
                    buf = ch == 'V' ? B_WUV : ch == 'O' ? B_WO : ch == 'D' ? B_DN : ch == 'u' ? B_X + 1 : B_X;
                    id = (ch == 'V' ? IT_WUV : ch == 'O' ? IT_WO : ch == 'D' ? IT_DOWN : ch == 'u' ? IT_X + 2 : IT_X) + cnt[(int)ch]++;
                    dep = EB_UNIT0 + (buf < 2 ? buf + 6 : buf);
                    w = dig(tune.tail[r][1][i - IT_WUV]); wl = dig(tune.tail[r][2][i - IT_WUV]);
                    tn += (r == 2 ? 64 : 32) * dig(tune.tail[r][3][i - IT_WUV]);
                }
                if (id < IT_X || id >= IT_DOWN ? (id - 1) & 3 : (id - IT_X) & 1) dep = -1;
                ids[i] = id;
                auto back = [&](int d) { return i < d ? 0 : (ids[i - d] && ids[i - d] <= NCP ? 1 : ids[i - d]) + 1; };
                sc[i].x = id | (buf * 4 + (id < IT_X || id >= IT_DOWN ? (id - 1) & 3 : ((id - IT_X) & 1) * 2)) << 6 | (dep + 1) << 11 | (w > 32 ? NEVER + 1 : back(w)) << 18 | (wl ? back(wl) : 0) << 25;
                const int mp = id < IT_CKV ? MP_WQ + ((id - 1) >> 2) : id < IT_WUV ? MP_CKV : id < IT_WO ? MP_WUV : id < IT_X ? MP_WO
                             : id >= IT_DOWN ? MP_DOWN : r ? MP_MODB : MP_GATE + ((id - IT_X) >> 1);
                const int step = mp == MP_CKV ? id - IT_CKV : mp == MP_WUV ? (id - IT_WUV) * 2 : mp == MP_DOWN ? id - IT_DOWN : id < IT_X ? (id - 1) & 3 : ((id - IT_X) & 1) * 2;
                sc[i].y = (tn & 0xffff) | (mp & 15) << 16 | step << 20;
            }
        }
        cudaGetSymbolAddress((void**)&scratch, g_scratch);
        scratch = (uint32_t*)(((uintptr_t)scratch + (2u << 20) - 1) & ~(uintptr_t)((2u << 20) - 1));
        cudaFuncSetAttribute(fused_kernel, cudaFuncAttributeMaxDynamicSharedMemorySize, SM_TOTAL);
        for (int i = 0; i < 12; i++) cached[i] = d_in[i];
        ready = true;
    }
    const First f = {{(const uint8_t*)d_in[2], (const uint8_t*)d_in[11]}, {(const __nv_bfloat16*)d_in[0], (const __nv_bfloat16*)d_in[10]}};
    fused_kernel<<<NCTA, NTHREADS, SM_TOTAL>>>(f, (__nv_bfloat16*)d_out, scratch, maps);
}
```

```cpp
#include <cuda_runtime.h>
#include <cuda_bf16.h>
#include <cuda.h>
#include <stdint.h>
#include <limits.h>

namespace {

constexpr int NCTA = 128;
constexpr int NTHREADS = 512;
constexpr int NUNITS = 8;
constexpr int NFF = 56, J_RED = 104, J_END = 120;
constexpr uint32_t SPIN_LIMIT = 1u << 22;

#define NEAR_CLK 390
#define E1_EARLY 50
#define STAG 300
#define NUMA 1
#define NPROBE 5
#define NCP 2
#define W0 4
#define RD_ITEM 15
#define JAN_SLEEP 100
#define RD_SLEEP 400
#define HA_DELAY 200
#define H_SLEEP 100
#define QA_DELAY 600
#define QA_SLEEP 200
#define ML_DELAY 300
#define E1_SLEEP 50
#define MB_SLEEP 100
constexpr int B_WUV = 2, B_WO = 3, B_X = 4  , B_DN = 0;

constexpr int SM_U = 0;
constexpr int SM_XA = 6 * 32768;
constexpr int SM_XB = SM_XA + 12288;
constexpr int SM_MX = SM_XB + 16384;
constexpr int SM_FZ = SM_XB + 8192;
constexpr int SM_PB = SM_XB;
constexpr int SM_Y = SM_XB + 12288;
constexpr int SM_RED = SM_XB + 4096;
constexpr int SM_FS = SM_XB + 20480;
constexpr int SM_FV = SM_FS + 1024;
constexpr int SM_QX = SM_XA + 8192;
constexpr int SM_FQ = SM_FV + 512;
constexpr int SM_CLS = SM_FQ + 128;
constexpr int SM_W = SM_FQ + 256;
constexpr int SM_W2 = SM_MX + 2304;
constexpr int SM_SCR = SM_XA + 9216;
constexpr int SM_BAR = SM_W + 256;
constexpr int SM_TOTAL = SM_BAR + 1024;
static_assert(SM_TOTAL <= 232448, "smem");

enum { IT_MODA = 0, IT_WQ = 1, IT_WUK = 5, IT_CKV = 9, IT_WUV = 41, IT_WO = 45, IT_X = 49  , IT_DOWN = 53, NITEMS = 57,
       NEVER = 63,
       SF0 = 64,
       PF0 = 80,
       EB_UNIT0 = 96, MBB = 103,
       EB_WQ = 104, EB_WUK, QT, QB, JD, WR };

enum { MP_WQ = 0, MP_WUK, MP_CKV, MP_WUV, MP_DOWN, MP_WO, MP_GATE, MP_UP, MP_MODB, NMAPS };
struct First { const uint8_t* w[2]; const __nv_bfloat16* v[2]; };
struct Maps { CUtensorMap m[NMAPS]; uint2 sched[3][58]; };

enum { B_HA = 0,
       B_MB = 6,
       B_RD = 7,
       B_E2 = 8,
       B_QA = 16,
       B_ML = 32,
       B_E5 = 64,
       B_E3 = 80,
       B_PR = 96,
       B_TR = 100 };
constexpr int G_E1 = 1 << 19;
__device__ __align__(1024) uint32_t g_scratch[(8 << 20) / 4];

#define TRACE(slot) do {} while (0)
#define TRACE_Q(slot) do {} while (0)
#define TRACE_GT(slot) do {} while (0)

__device__ __forceinline__ uint32_t s2u(const void* p) { return (uint32_t)__cvta_generic_to_shared(p); }
__device__ __forceinline__ void mbar_init(uint32_t b, int c) { asm volatile("mbarrier.init.shared::cta.b64 [%0], %1;" :: "r"(b), "r"(c) : "memory"); }
__device__ __forceinline__ void mbar_expect(uint32_t b, uint32_t bytes) { asm volatile("mbarrier.arrive.expect_tx.shared::cta.b64 _, [%0], %1;" :: "r"(b), "r"(bytes) : "memory"); }
__device__ __forceinline__ void mbar_arrive(uint32_t b) { asm volatile("mbarrier.arrive.shared::cta.b64 _, [%0];" :: "r"(b) : "memory"); }
__device__ __forceinline__ void mbar_wait(uint32_t b, uint32_t ph) {
    asm volatile("{\n.reg .pred p;\nW: mbarrier.try_wait.parity.shared::cta.b64 p, [%0], %1;\n@!p bra W;\n}" :: "r"(b), "r"(ph) : "memory");
}
__device__ __forceinline__ void mbar_waitb(uint32_t b, uint32_t ph) {
    asm volatile("{\n.reg .pred p;\n.reg .u32 n;\nmov.u32 n, 0;\n"
                 "W: mbarrier.try_wait.parity.shared::cta.b64 p, [%0], %1;\n@p bra D;\n"
                 "add.u32 n, n, 1;\nsetp.lt.u32 p, n, 0x100000;\n@p bra W;\ntrap;\nD:\n}" :: "r"(b), "r"(ph) : "memory");
}
__device__ __forceinline__ uint32_t mbar_test(uint32_t b, uint32_t ph) {
    uint32_t ok;
    asm volatile("{\n.reg .pred p;\nmbarrier.test_wait.parity.shared::cta.b64 p, [%1], %2;\nselp.u32 %0, 1, 0, p;\n}" : "=r"(ok) : "r"(b), "r"(ph) : "memory");
    return ok;
}
__device__ __forceinline__ void bar_sync(int id, int n) { asm volatile("bar.sync %0, %1;" :: "r"(id), "r"(n) : "memory"); }
__device__ __forceinline__ void bar_arrive(int id, int n) { asm volatile("bar.arrive %0, %1;" :: "r"(id), "r"(n) : "memory"); }
__device__ __forceinline__ uint32_t peer_addr(uint32_t a, uint32_t rank) { uint32_t r; asm("mapa.shared::cluster.u32 %0, %1, %2;" : "=r"(r) : "r"(a), "r"(rank)); return r; }
__device__ __forceinline__ void st_async2(uint32_t a, float x, float y, uint32_t bar) {
    asm volatile("st.async.weak.shared::cluster.mbarrier::complete_tx::bytes.v2.f32 [%0], {%1, %2}, [%3];" :: "r"(a), "f"(x), "f"(y), "r"(bar) : "memory");
}
__device__ __forceinline__ uint32_t gtime() { uint32_t t; asm volatile("mov.u32 %0, %%globaltimer_lo;" : "=r"(t)); return t; }
__device__ __forceinline__ void fence_gpu() { asm volatile("fence.acq_rel.gpu;" ::: "memory"); }

__device__ __forceinline__ uint32_t enc(uint32_t b) { uint32_t r; asm("max.u32 %0, %1, 1;" : "=r"(r) : "r"(b)); return r; }
__device__ __forceinline__ uint32_t encf(float f) { return enc(__float_as_uint(f)); }
__device__ __forceinline__ void st_x1(uint32_t* p, uint32_t v) { asm volatile("st.relaxed.gpu.global.u32 [%0], %1;" :: "l"(p), "r"(v) : "memory"); }
__device__ __forceinline__ void st_x4(void* p, uint32_t a, uint32_t b, uint32_t c, uint32_t d) {
    asm volatile("st.relaxed.gpu.global.v4.u32 [%0], {%1, %2, %3, %4};" :: "l"(p), "r"(a), "r"(b), "r"(c), "r"(d) : "memory");
}
__device__ __forceinline__ void st2_x1(uint32_t* p, uint32_t v) { st_x1(p, v); st_x1(p + 1024, v); }
__device__ __forceinline__ void st2_x4(uint32_t* p, uint32_t a, uint32_t b, uint32_t c, uint32_t d) { st_x4(p, a, b, c, d); st_x4(p + 1024, a, b, c, d); }
__device__ __forceinline__ int near_off(int b, uint32_t cls) { return b * 4096 + (((__popc(b & 0x2C) ^ cls) & 1) << 10); }
__device__ __forceinline__ void ld_x(uint32_t& v, const void* p) { asm volatile("ld.relaxed.gpu.global.u32 %0, [%1];" : "=r"(v) : "l"(p) : "memory"); }
__device__ __forceinline__ void ld_x(uint4& v, const void* p) {
    asm volatile("ld.relaxed.gpu.global.v4.u32 {%0, %1, %2, %3}, [%4];" : "=r"(v.x), "=r"(v.y), "=r"(v.z), "=r"(v.w) : "l"(p) : "memory");
}
__device__ __forceinline__ void ld_x(uint2& v, const void* p) { asm volatile("ld.relaxed.gpu.global.v2.u32 {%0, %1}, [%2];" : "=r"(v.x), "=r"(v.y) : "l"(p) : "memory"); }
__device__ __forceinline__ uint32_t minw(uint32_t v) { return v; }
__device__ __forceinline__ uint32_t minw(const uint2& v) { return min(v.x, v.y); }
__device__ __forceinline__ uint32_t minw(const uint4& v) { return min(__vimin3_u32(v.x, v.y, v.z), v.w); }
template <int N> __device__ __forceinline__ uint32_t mint(const uint32_t* m) {
    if constexpr (N == 1) return m[0];
    else if constexpr (N == 2) return min(m[0], m[1]);
    else return __vimin3_u32(mint<(N + 2) / 3>(m), mint<(N + 1) / 3>(m + (N + 2) / 3), mint<N / 3>(m + (N + 2) / 3 + (N + 1) / 3));
}

template <int STRIDE, int S4 = 4 * STRIDE, typename T, int N>
__device__ __forceinline__ void poll_start(T (&v)[N], const void* base) {
#pragma unroll
    for (int i = 0; i < N; i++) ld_x(v[i], (const uint8_t*)base + (i & 3) * STRIDE + (i >> 2) * S4);
}
struct Nop { __device__ void operator()() const {} };
template <int STRIDE, int SLEEP, bool STARTED = false, int S4 = 4 * STRIDE, typename T, int N, typename F = Nop, typename G = Nop>
__device__ __forceinline__ void poll(T (&v)[N], const void* base, F idle = F(), G ahead = G()) {
    if (!STARTED) { poll_start<STRIDE, S4>(v, base); idle(); }
#pragma unroll 1
    for (uint32_t it = 0;; it++) {
        uint32_t m[N];
        ahead();
#pragma unroll
        for (int i = 0; i < N; i++) m[i] = minw(v[i]);
        if (__all_sync(0xffffffffu, mint<N>(m) != 0)) break;
        if (SLEEP && it > 0) __nanosleep(SLEEP);
#pragma unroll
        for (int i = 0; i < N; i++) if (!m[i]) ld_x(v[i], (const uint8_t*)base + (i & 3) * STRIDE + (i >> 2) * S4);
        idle();
        if (it > SPIN_LIMIT) __trap();
    }
}

__device__ __forceinline__ float bflo(uint32_t w) { return __uint_as_float(w << 16); }
__device__ __forceinline__ float bfhi(uint32_t w) { return __uint_as_float(w & 0xffff0000u); }
__device__ __forceinline__ uint32_t pack2(float lo, float hi) {
    uint32_t r; asm("cvt.rn.bf16x2.f32 %0, %1, %2;" : "=r"(r) : "f"(hi), "f"(lo)); return r;
}
__device__ __forceinline__ float rbf(float x) { return __uint_as_float(pack2(0.f, x)); }
__device__ __forceinline__ float ex2(float x) { float r; asm("ex2.approx.ftz.f32 %0, %1;" : "=f"(r) : "f"(x)); return r; }
__device__ __forceinline__ float shx(float v, int m) { return __shfl_xor_sync(0xffffffffu, v, m); }
__device__ __forceinline__ uint4 lds128(uint32_t a) { uint4 v; asm volatile("ld.shared.v4.u32 {%0, %1, %2, %3}, [%4];" : "=r"(v.x), "=r"(v.y), "=r"(v.z), "=r"(v.w) : "r"(a) : "memory"); return v; }
__device__ __forceinline__ uint32_t lds32(uint32_t a) { uint32_t v; asm volatile("ld.shared.u32 %0, [%1];" : "=r"(v) : "r"(a) : "memory"); return v; }
__device__ __forceinline__ void sts32(uint32_t a, uint32_t v) { asm volatile("st.shared.u32 [%0], %1;" :: "r"(a), "r"(v) : "memory"); }
__device__ __forceinline__ void sts16(uint32_t a, uint32_t v) { asm volatile("st.shared.u16 [%0], %1;" :: "r"(a), "h"((uint16_t)v) : "memory"); }
__device__ __forceinline__ int frag_off(int k) { return (k >> 5) * 64 + ((k >> 1) & 3) * 16 + ((k >> 4) & 1) * 8 + ((k >> 3) & 1) * 4 + (k & 1) * 2; }

template <bool TRANS>
__device__ __forceinline__ uint4 ldsm(uint32_t a) {
    uint4 r;
    if (TRANS) asm volatile("ldmatrix.sync.aligned.m8n8.x4.trans.shared.b16 {%0, %1, %2, %3}, [%4];" : "=r"(r.x), "=r"(r.y), "=r"(r.z), "=r"(r.w) : "r"(a) : "memory");
    else asm volatile("ldmatrix.sync.aligned.m8n8.x4.shared.b16 {%0, %1, %2, %3}, [%4];" : "=r"(r.x), "=r"(r.y), "=r"(r.z), "=r"(r.w) : "r"(a) : "memory");
    return r;
}
__device__ __forceinline__ void mma(float (&c)[4], uint32_t a0, uint32_t a1, uint32_t a2, uint32_t a3, uint32_t b0, uint32_t b1) {
    asm volatile("mma.sync.aligned.m16n8k16.row.col.f32.bf16.bf16.f32 {%0,%1,%2,%3}, {%4,%5,%6,%7}, {%8,%9}, {%0,%1,%2,%3};"
                 : "+f"(c[0]), "+f"(c[1]), "+f"(c[2]), "+f"(c[3]) : "r"(a0), "r"(a1), "r"(a2), "r"(a3), "r"(b0), "r"(b1));
}
template <bool TRANS, typename F>
__device__ __forceinline__ void load8(uint4 (&a)[8], F addr) {
    __syncwarp();
#pragma unroll
    for (int s = 0; s < 8; s++) a[s] = ldsm<TRANS>(addr(s));
}
__device__ __forceinline__ void mma8(float (&c)[4], const uint4 (&a)[8], const uint4 (&b)[4]) {
    float e[4][4];
#pragma unroll
    for (int s = 0; s < 8; s++) {
        if (s < 4) e[s][0] = e[s][1] = e[s][2] = e[s][3] = 0.f;
        mma(e[s & 3], a[s].x, a[s].y, a[s].z, a[s].w, (s & 1) ? b[s >> 1].z : b[s >> 1].x, (s & 1) ? b[s >> 1].w : b[s >> 1].y);
    }
#pragma unroll
    for (int i = 0; i < 4; i++) c[i] = (e[0][i] + e[1][i]) + (e[2][i] + e[3][i]);
}
__device__ __forceinline__ void ldfrag(uint4 (&b)[4], uint32_t a) {
    asm volatile("ld.shared.v4.u32 {%0,%1,%2,%3}, [%16];\nld.shared.v4.u32 {%4,%5,%6,%7}, [%16+64];\n"
                 "ld.shared.v4.u32 {%8,%9,%10,%11}, [%16+128];\nld.shared.v4.u32 {%12,%13,%14,%15}, [%16+192];\n"
                 : "=r"(b[0].x), "=r"(b[0].y), "=r"(b[0].z), "=r"(b[0].w), "=r"(b[1].x), "=r"(b[1].y), "=r"(b[1].z), "=r"(b[1].w),
                   "=r"(b[2].x), "=r"(b[2].y), "=r"(b[2].z), "=r"(b[2].w), "=r"(b[3].x), "=r"(b[3].y), "=r"(b[3].z), "=r"(b[3].w) : "r"(a) : "memory");
}
__device__ __forceinline__ void quad_pair(float x, float y, int t, float& lo, float& hi) {
    const float k = ((t & 1) ? y : x) + shx((t & 1) ? x : y, 1);
    lo = k + shx(k, 2); hi = shx(k, 4) + shx(k, 6);
}
__device__ __forceinline__ void pin(uint32_t& x) { asm volatile("" : "+r"(x)); }
template <typename T> __device__ __forceinline__ void pin(T*& x) { asm volatile("" : "+l"(x)); }
__device__ __forceinline__ float4 ldsf4(uint32_t a) { const uint4 v = lds128(a); return make_float4(__uint_as_float(v.x), __uint_as_float(v.y), __uint_as_float(v.z), __uint_as_float(v.w)); }
__device__ __forceinline__ float sum4(const float4& f) { return (f.x + f.y) + (f.z + f.w); }
__device__ __forceinline__ void stsf(uint32_t a, float v) { sts32(a, __float_as_uint(v)); }

__device__ __forceinline__ void wg_fence() { asm volatile("wgmma.fence.sync.aligned;" ::: "memory"); }
__device__ __forceinline__ void wg_commit() { asm volatile("wgmma.commit_group.sync.aligned;" ::: "memory"); }
__device__ __forceinline__ void wg_wait1() { asm volatile("wgmma.wait_group.sync.aligned 1;" ::: "memory"); }
__device__ __forceinline__ void wg_wait0() { asm volatile("wgmma.wait_group.sync.aligned 0;" ::: "memory"); }
#define R8(o) "+f"(d[o]), "+f"(d[o + 1]), "+f"(d[o + 2]), "+f"(d[o + 3]), "+f"(d[o + 4]), "+f"(d[o + 5]), "+f"(d[o + 6]), "+f"(d[o + 7])
__device__ __forceinline__ void wgmma_rs_n32(float (&d)[16], const uint4& a, uint64_t db, int acc) {
    asm volatile("{\n.reg .pred p;\nsetp.ne.b32 p, %21, 0;\n"
        "wgmma.mma_async.sync.aligned.m64n32k16.f32.bf16.bf16 "
        "{%0,%1,%2,%3,%4,%5,%6,%7,%8,%9,%10,%11,%12,%13,%14,%15}, {%16,%17,%18,%19}, %20, p, 1, 1, 0;\n}"
        : R8(0), R8(8) : "r"(a.x), "r"(a.y), "r"(a.z), "r"(a.w), "l"(db), "r"(acc));
}
#define PV_LO "{%0,%1,%2,%3,%4,%5,%6,%7,%8,%9,%10,%11,%12,%13,%14,%15,%16,%17,%18,%19,%20,%21,%22,%23,%24,%25,%26,%27,%28,%29,%30,%31,%32,%33,%34,%35,%36,%37,%38,%39,%40,%41,%42,%43,%44,%45,%46,%47,%48,%49,%50,%51,%52,%53,%54,%55,%56,%57,%58,%59,%60,%61,%62,%63}, "
#define PV_HI "{%64,%65,%66,%67,%68,%69,%70,%71,%72,%73,%74,%75,%76,%77,%78,%79,%80,%81,%82,%83,%84,%85,%86,%87,%88,%89,%90,%91,%92,%93,%94,%95,%96,%97,%98,%99,%100,%101,%102,%103,%104,%105,%106,%107,%108,%109,%110,%111,%112,%113,%114,%115,%116,%117,%118,%119,%120,%121,%122,%123,%124,%125,%126,%127}, "
__device__ __forceinline__ void wgmma_pv(float (&d)[128], const uint4& a, uint32_t blo, int acc) {
    asm volatile("{\n.reg .pred p;\n.reg .b32 u0, u1, u2, u3, t;\n.reg .b64 d0, d1, d2, d3;\nsetp.ne.b32 p, %133, 0;\n"
        "mov.b64 d0, {%132, 0x40000100};\nadd.u32 t, %132, 512;\nmov.b64 d1, {t, 0x40000100};\n"
        "add.u32 t, %132, 128;\nmov.b64 d2, {t, 0x40000100};\nadd.u32 t, %132, 640;\nmov.b64 d3, {t, 0x40000100};\n"
        "wgmma.fence.sync.aligned;\n"
        "wgmma.mma_async.sync.aligned.m64n128k16.f32.bf16.bf16 " PV_LO "{%128, u0, %129, u1}, d0, p, 1, 1, 1;\n"
        "wgmma.mma_async.sync.aligned.m64n128k16.f32.bf16.bf16 " PV_LO "{%130, u2, %131, u3}, d1, 1, 1, 1, 1;\n"
        "wgmma.commit_group.sync.aligned;\n"
        "wgmma.mma_async.sync.aligned.m64n128k16.f32.bf16.bf16 " PV_HI "{%128, u0, %129, u1}, d2, p, 1, 1, 1;\n"
        "wgmma.mma_async.sync.aligned.m64n128k16.f32.bf16.bf16 " PV_HI "{%130, u2, %131, u3}, d3, 1, 1, 1, 1;\n"
        "wgmma.commit_group.sync.aligned;\n}"
        : R8(0), R8(8), R8(16), R8(24), R8(32), R8(40), R8(48), R8(56), R8(64), R8(72), R8(80), R8(88), R8(96), R8(104), R8(112), R8(120)
        : "r"(a.x), "r"(a.y), "r"(a.z), "r"(a.w), "r"(blo), "r"(acc) : "memory");
}

template <int NW>
__device__ __forceinline__ void ln_stats(float s, float q, float sh, float* scr, int w, int lane, int bar, float& mean_b, float& sd_b) {
#pragma unroll
    for (int o = 16; o; o >>= 1) { s += shx(s, o); q += shx(q, o); }
    constexpr float n = 512.f / NW;
    if (lane == 0) { scr[w] = sh + s * (1.f / n); scr[NW + w] = q - s * s * (1.f / n); }
    bar_sync(bar, NW * 32);
    float mu = 0.f, m2 = 0.f;
#pragma unroll
    for (int i = 0; i < NW; i++) { mu += scr[i]; m2 += scr[NW + i]; }
    mu *= 1.f / NW;
#pragma unroll
    for (int i = 0; i < NW; i++) { const float d = scr[i] - mu; m2 = fmaf(n * d, d, m2); }
    mean_b = rbf(mu);
    sd_b = rbf(sqrtf(rbf(rbf(fmaxf(m2, 0.f) * (1.f / 512.f)) + 1e-5f)));
}
__device__ __forceinline__ float ln_mod(float x, float mean_b, float sd_b, float c, float s) {
    return rbf(rbf(__fdividef(rbf(x - mean_b), sd_b)) * rbf(1.f + c)) + s;
}

__global__ void __cluster_dims__(2, 1, 1) __launch_bounds__(NTHREADS, 1)
fused_kernel(const __grid_constant__ First F, __nv_bfloat16* __restrict__ out, uint32_t* __restrict__ gs, const __grid_constant__ Maps M) {
    extern __shared__ __align__(1024) uint8_t sm[];
    const uint32_t sb = s2u(sm);
    const int tid = threadIdx.x, lane = tid & 31;
    const int j = blockIdx.x, rk = j & 1;
    const int g = lane >> 2, t = lane & 3;
    const int r8 = lane & 7, lb3 = (lane >> 3) & 1, lb4 = lane >> 4;
    uint64_t pol;
    asm("createpolicy.fractional.L2::evict_first.b64 %0, 1.0;" : "=l"(pol));
    {
        auto cpa = [&](uint32_t d, const uint8_t* s) {
            asm volatile("cp.async.cg.shared.global.L2::cache_hint.L2::128B [%0], [%1], 16, %2;" :: "r"(d), "l"(s), "l"(pol) : "memory");
        };
        const uint32_t ut = threadIdx.x, uj = blockIdx.x;
        const uint8_t* w = F.w[ut >= 128];
        if (ut < 128) {
            const uint32_t dq = (sb + ut * 16) ^ ((ut * 2) & 0x70);
            const uint8_t* sq = w + (uint32_t)(((uj & 1) * 256 + (ut >> 3)) * 8192 + (uj >> 1) * 128 + (ut & 7) * 16);
#pragma unroll
            for (int i = 0; i < 4 * NCP; i++) cpa(dq + 4 * 32768 + i * 2048, sq + i * 131072);
        } else if (ut < 384) {
            const uint32_t dm = (sb + ut * 16) ^ ((ut * 2) & 0x10);
            const uint8_t* sa = w + (uint32_t)(((uj >> 5) * 128 + (ut >> 1) - 64) * 6144 + (uj & 31) * 32 + (ut & 1) * 16);
            cpa(dm + SM_XA - 2048, sa); cpa(dm + SM_XA + 2048, sa + 1024);
        }
        else if (ut == 480 && uj < 64) asm volatile("prefetch.global.L2 [%0];" :: "l"(F.v[(uj >> 3) & 1] + (uj & 7) * 64));
    }
    const int warp = __shfl_sync(0xffffffffu, tid >> 5, 0);
    const __nv_bfloat16* const xin = F.v[0];
    uint32_t* const pl = gs + (warp < 2 ? (B_PR + (j >> 5)) * 4096 + (j & 31) * 32 : G_E1 + j * 8192) + (warp & 1) * 1024 + lane;
    if (warp < 4) st_x1(pl, 1u);
    auto BAR = [&](int i) -> uint32_t { return sb + SM_BAR + i * 8; };
    const uint32_t a16 = (r8 + 8 * lb4) * 32 + ((lb3 ^ (r8 >> 2)) * 16);
    const uint32_t a128 = (r8 + 8 * lb4) * 128 + ((((warp & 3) * 2 + lb3) ^ r8) * 16);
    auto ldcls = [&]() -> uint32_t { return *(const volatile uint32_t*)(sm + SM_CLS); };
    auto clear_head = [&]() {
        st2_x1(gs + (B_HA + ((j >> 4) & 1) * 2 + lb4) * 4096 + (j >> 5) * 256 + (j & 15) * 16 + (lane & 15), 0u);
        st2_x4(gs + (B_QA + rk * 8 + ((j >> 1) & 1) * 4 + (j >> 5)) * 4096 + g * 128 + ((j >> 2) & 7) * 16 + t * 4, 0u, 0u, 0u, 0u);
        if (lane < 8) st2_x1(gs + B_RD * 4096 + j * 8 + lane, 0u);
    };
    auto tma = [&](uint32_t dst, const CUtensorMap* mp, uint32_t bar, int c0, int c1, int c2, int c3) {
        asm volatile("{\n.reg .pred p;\nelect.sync _|p, 0xffffffff;\n"
                     "@p cp.async.bulk.tensor.4d.shared::cluster.global.mbarrier::complete_tx::bytes.L2::cache_hint [%0], [%1, {%3, %4, %5, %6}], [%2], %7;\n}"
                     :: "r"(dst), "l"(mp), "r"(bar), "r"(c0), "r"(c1), "r"(c2), "r"(c3), "l"(pol) : "memory");
    };
    if (warp <= 12 || warp == 15) {
        const int grp = warp == 12 ? 0 : warp == 15 ? 13 : warp + 1;
        const uint32_t cnt = grp < 10 ? 1 : grp < 13 ? 4 : 8;
        if (lane == 0) {
#pragma unroll
            for (int i = 0; i < 8; i++) mbar_init(BAR(grp * 8 + i), (i < 2 && grp == 0) ? (i ? 128 : 256) : cnt);
        }
        __syncwarp();
        if (grp < 10 && lane < 8 && (grp || lane > NCP)) mbar_expect(BAR(grp * 8 + lane), grp >= 8 ? 4096 : (uint32_t)(grp * 8 + lane - IT_X) < 4 ? 16384 : 8192);
        asm volatile("fence.mbarrier_init.release.cluster;" ::: "memory");
        __syncwarp();
        if (warp == 12) {
#pragma unroll
            for (int i = NCP + 1; i < W0; i++) tma(sb + (15 + i) * 8192, &M.m[MP_WQ], BAR(i), 0, rk * 256 + (i - 1) * 64, j >> 1, 0);
        }
    } else if (warp == 13) {
        if (lane < NMAPS) asm volatile("prefetch.tensormap [%0];" :: "l"(&M.m[lane]) : "memory");
    } else if (warp == 14) {
        clear_head();
    }
    __syncthreads();
    uint32_t in1 = 0, in2 = 0;
    if (warp < 4) { in1 = *(const uint32_t*)(xin + 2 * tid); in2 = *(const uint32_t*)(xin + 256 + 2 * tid); }
    else if (warp < 12) in1 = *(const uint32_t*)(F.v[1] + 2 * (tid - 128));
    if (warp < 12) asm volatile("cp.async.mbarrier.arrive.noinc.shared::cta.b64 [%0];" :: "r"(BAR(warp < 4)) : "memory");
    asm volatile("barrier.cluster.arrive.relaxed.aligned;" ::: "memory");

    if (warp >= 12) {
    asm volatile("setmaxnreg.dec.sync.aligned.u32 64;");
    if (warp == 12) {
        static_assert(W0 > NCP && W0 <= 5 && NCP >= 1 && NCP <= 4, "W0");
        const uint2* sched = M.sched[j < NFF ? 0 : j < J_RED ? 1 : 2];
        uint2 en = sched[W0];
        const uint32_t t0 = gtime();
        const uint32_t sp = __reduce_or_sync(0xffffffffu, sb);
        const int cx = (j >> 1) * 64 + (j < NFF ? 0 : 1024 - NFF * 32);
#pragma unroll 1
        for (int i = W0; en.x; i++) {
            uint32_t e = en.x, st = (en.y >> 20) * 64;
            const uint32_t tn = t0 + (int16_t)en.y, mp = (en.y >> 16) & 15;
            if (mp == MP_WUV || mp == MP_WUK) { st ^= (j >> 5) * (mp == MP_WUV ? 128 : 64); e ^= (j >> 5) << 6; }
            if (mp == MP_GATE || mp == MP_UP) st ^= (j & 16) * 8;
            if (mp == MP_DOWN) { st ^= (j & 3) * 64; e ^= (j & 3) << 6; }
            en = sched[i + 1];
            if (mp == MP_MODB && j >= J_END) break;
            uint32_t c0 = mp == MP_WO ? (j & 7) * 64 : mp > MP_WO ? cx : 0;
            uint32_t c1 = mp == MP_CKV ? 0 : mp == MP_DOWN ? j * 32 : st + (mp == MP_WUV ? (j & 3) * 32 : mp == MP_WO ? (j >> 3) * 256 : rk * 256);
            uint32_t c2 = mp < MP_CKV ? j >> 1 : mp == MP_CKV ? rk * 4 : mp == MP_WUV ? (j >> 2) * 2 : mp == MP_DOWN ? st >> 5 : 0;
            uint32_t c3 = mp == MP_CKV ? st * 2 + (j & ~1) : 0;
            uint32_t dst = sp + ((e << 7) & 0x3e000), bar = sp + SM_BAR + (e & 63) * 8;
            const uint32_t w0 = (e >> 8) & 0x3f8, w1 = (e >> 15) & 0x3f8, w2 = (e >> 22) & 0x3f8, bb = sp + SM_BAR - 8;
            const CUtensorMap* pm = &M.m[mp];
            pin(dst); pin(bar); pin(c0); pin(c1); pin(c2); pin(c3); pin(pm);
            if (w0) mbar_wait(bb + w0, 0);
            if (w2) {
                mbar_wait(bb + w2, 0);
                while (!__any_sync(0xffffffffu, mbar_test(bb + w1, 0) | ((int)(gtime() - tn) > 0))) {}
            } else if (w1) mbar_wait(bb + w1, 0);
            tma(dst, pm, bar, c0, c1, c2, c3);
        }
    } else if (warp == 13) {
#pragma unroll
        for (int i = 0; i < 2; i++) st_x4(gs + (B_ML + rk * 16 + i * 8 + g) * 4096 + (t >> 1) * 1024 + (j >> 1) * 8 + (t & 1) * 4, 0u, 0u, 0u, 0u);
        if (lane < 16) st2_x4(gs + (B_E2 + (j >> 4)) * 4096 + (j & 15) * 64 + lane * 4, 0u, 0u, 0u, 0u);
        st2_x1(gs + (B_E3 + (j >> 5)) * 4096 + (j & 31) * 32 + lane, 0u);
        if (lane < 8) st2_x1(gs + B_MB * 4096 + j * 8 + lane, 0u);
        if (j < NFF) {
#pragma unroll
            for (int i = 0; i < 2; i++) st2_x4(gs + (B_E5 + i * 8 + g) * 4096 + j * 16 + t * 4, 0u, 0u, 0u, 0u);
        }
        bar_sync(9, 64);
        const uint32_t cs = ldcls();
#pragma unroll 1
        for (int i = 0; i < 32; i++) {
            st_x4(gs + G_E1 + j * 8192 + (i >> 3) * 2048 + ((((cs >> 1) ^ (i >> 3)) & 1) << 10) + (i & 7) * 128 + lane * 4, 0u, 0u, 0u, 0u);
            __nanosleep(JAN_SLEEP);
        }
        fence_gpu();
        if (lane < 8) st2_x1(gs + B_RD * 4096 + j * 8 + lane, 1u + (cs >> 1));
        if (lane == 0) TRACE(41);
        uint32_t rd[4];
        mbar_wait(BAR(IT_CKV + RD_ITEM), 0);
        poll<1024, RD_SLEEP>(rd, gs + near_off(B_RD, cs) + lane * 8);
#pragma unroll
        for (int i = 0; i < 4; i++) {
            const uint32_t m = __ballot_sync(0xffffffffu, rd[i] == 2u);
            if (lane == 0) sts32(sb + SM_CLS + 16 + i * 4, m);
        }
        __syncwarp();
        if (lane < 8) mbar_arrive(BAR(JD));
        if (lane == 0) TRACE(42);
    } else if (warp == 14) {
        uint2 ml[2];
        mbar_waitb(BAR(JD), 0);
        const uint32_t cls = ldcls();
        mbar_waitb(BAR(PF0 + 2 * NUNITS - 1), 0);
        __nanosleep(ML_DELAY);
        const uint32_t* pl2 = gs + near_off(B_ML + (j >> 2), cls) + lane * 8;
        const uint32_t wa = sb + SM_W + lb4 * 64 + t * 16 + (g & 3) * 4;
        poll_start<1024>(ml, pl2);
        uint32_t w0 = 0, w1 = 0, redo = 0;
        bool first = true;
#pragma unroll 1
        for (uint32_t it = 0;; it++) {
            const bool p0 = minw(ml[0]) != 0, p1 = minw(ml[1]) != 0;
            const int n = __popc(__ballot_sync(0xffffffffu, p0)) + __popc(__ballot_sync(0xffffffffu, p1));
            const uint32_t x0 = ml[0].x, x1 = ml[1].x;
            if (n < 64) {
                if (!p0) ld_x(ml[0], pl2);
                if (!p1) ld_x(ml[1], pl2 + 256);
            }
            if (n == 64 || (first && n >= E1_EARLY)) {
                auto ord = [](int x) { return x ^ ((x >> 31) & 0x7fffffff); };
                const int o0 = ord(x0), o1 = ord(x1);
                const float mm = __int_as_float(ord(__reduce_max_sync(0xffffffffu, max(p0 ? o0 : INT_MIN, p1 ? o1 : INT_MIN))));
                const float lo = __int_as_float(ord(__reduce_min_sync(0xffffffffu, min(p0 ? o0 : INT_MAX, p1 ? o1 : INT_MAX))));
                const uint32_t v0 = pack2(ex2((p0 ? __uint_as_float(x0) : lo) - mm), 0.f), v1 = pack2(ex2((p1 ? __uint_as_float(x1) : lo) - mm), 0.f);
                redo = !first && __any_sync(0xffffffffu, v0 != w0 || v1 != w1);
                w0 = v0; w1 = v1;
                sts32(wa - redo * (SM_W - SM_W2), w0 * 0x10001u); sts32(wa - redo * (SM_W - SM_W2) + 128, w1 * 0x10001u);
                if (first) bar_arrive(3, 416);
                first = false;
                if (n == 64) break;
            }
            if (it > SPIN_LIMIT) __trap();
        }
        if (lane == 0) TRACE_Q(37);
        float L = bflo(w0) * __uint_as_float(ml[0].y) + bflo(w1) * __uint_as_float(ml[1].y);
#pragma unroll
        for (int o = 16; o; o >>= 1) L += shx(L, o);
        if (lane == 0) *(float2*)(sm + SM_FQ) = make_float2(__frcp_rn(L), __uint_as_float(redo));
        __syncwarp();
        if (lane < 8) mbar_arrive(BAR(WR));
        if (lane == 0) TRACE(10);
        bar_sync(4, 416);
        clear_head();
        if (j < NFF) {
            uint32_t ya = sb + SM_Y + lane * 16, sa = peer_addr(sb + SM_RED + 2048 + rk * 8, lane & 1), tb = peer_addr(BAR(MBB), lane & 1);
            pin(ya); pin(sa); pin(tb);
            bar_sync(7, 288);
            const float4 y0 = ldsf4(ya), y1 = ldsf4(ya + 512);
            float s = sum4(y0) + sum4(y1);
            float q = (fmaf(y0.x, y0.x, y0.y * y0.y) + fmaf(y0.z, y0.z, y0.w * y0.w)) + (fmaf(y1.x, y1.x, y1.y * y1.y) + fmaf(y1.z, y1.z, y1.w * y1.w));
#pragma unroll
            for (int o = 16; o; o >>= 1) { s += shx(s, o); q += shx(q, o); }
            if (lane < 2) st_async2(sa, s, q, tb);
        }
    } else if (warp == 15) {
        mbar_waitb(BAR(IT_X - 1), 0);
        if (j < J_END) mbar_waitb(BAR(j < NFF ? NITEMS - 1 : MBB), 0);
    }
    } else if (warp < 4) {
        float* scr = (float*)(sm + SM_SCR);
        uint32_t cls;
        {
            uint2 ha[8];
            uint32_t best = 0xffffffffu;
            sts32(sb + SM_SCR + 64 + warp * 4, best);
            const float sh = __shfl_sync(0xffffffffu, bflo(in1), 0);
            const float v0 = bflo(in1) - sh, v1 = bfhi(in1) - sh, v2 = bflo(in2) - sh, v3 = bfhi(in2) - sh;
            float mb, sd;
            ln_stats<4>((v0 + v1) + (v2 + v3), (v0 * v0 + v1 * v1) + (v2 * v2 + v3 * v3), sh, scr, warp, lane, 2, mb, sd);
            if (!rk) in2 = in1;
#pragma unroll 1
            for (int i = 0; i < NPROBE; i++) {
                uint32_t t0, t1, o;
                asm volatile("mov.u32 %0, %%clock;" : "=r"(t0));
                asm volatile("atom.relaxed.gpu.global.exch.b32 %0, [%1], %2;" : "=r"(o) : "l"(pl), "r"(2u + i) : "memory");
                asm volatile("{\n.reg .pred p;\nsetp.ne.u32 p, %1, 0x1234567;\nmov.u32 %0, 0;\n@p mov.u32 %0, %%clock;\n}" : "=r"(t1) : "r"(o));
                best = min(best, t1 - t0);
                sts32(sb + SM_SCR + 64 + warp * 4, best);
                if (__all_sync(0xffffffffu, min(best, lds32(sb + SM_SCR + 64 + (warp ^ 1) * 4)) < NEAR_CLK)) break;
            }
            bar_sync(2, 128);
            const uint4 lt = *(const uint4*)(scr + 16);
            cls = NUMA ? ((lt.y < lt.x) ^ (__popc((B_PR + (j >> 5)) & 0x2C) & 1)) | (lt.w < lt.z) << 1 : 0;
            if (warp == 0) { if (lane == 0) sts32(sb + SM_CLS, cls); bar_arrive(9, 64); }
            if (tid == 0) TRACE(38);
            asm volatile("barrier.cluster.wait.aligned;" ::: "memory");
            mbar_wait(BAR(IT_MODA), 0);
            if (HA_DELAY) __nanosleep(HA_DELAY);
            poll<1024, H_SLEEP, false, 16384>(ha, gs + near_off(B_HA + rk * 2, cls) + 2 * tid);
            auto rsum = [](uint32_t a, uint32_t b, uint32_t c, uint32_t d) { return rbf((__uint_as_float(a) + __uint_as_float(b)) + (__uint_as_float(c) + __uint_as_float(d))); };
            sts32(sb + SM_FV + frag_off(2 * tid),
                  pack2(ln_mod(bflo(in2), mb, sd, rsum(ha[4].x, ha[5].x, ha[6].x, ha[7].x), rsum(ha[0].x, ha[1].x, ha[2].x, ha[3].x)),
                        ln_mod(bfhi(in2), mb, sd, rsum(ha[4].y, ha[5].y, ha[6].y, ha[7].y), rsum(ha[0].y, ha[1].y, ha[2].y, ha[3].y))));
            bar_arrive(5, 384);
            mbar_wait(BAR(QB), 0);
            if (tid < 64) {
                const float* qx = (const float*)(sm + SM_QX) + tid;
                sts16(sb + SM_FQ + frag_off(tid), pack2((qx[0] + qx[64]) + (qx[128] + qx[192]), 0.f));
            }
            bar_arrive(6, 384);
        }
        asm volatile("setmaxnreg.inc.sync.aligned.u32 192;");
        float acc[128];
        float M = 0.f;
        uint32_t pa = sb + SM_XA + warp * 512 + lane * 16, ma = sb + SM_MX + (warp * 8 + g) * 4, pf = BAR(PF0);
        uint32_t blo = __reduce_or_sync(0xffffffffu, (((sb + SM_U) & 0x3FFFFu) >> 4) | 0x400000u);
        uint32_t* e1[4];
#pragma unroll
        for (int i = 0; i < 4; i++) e1[i] = gs + G_E1 + (warp * 8 + g) * 4 * 8192 + (rk * 2 + (j >> 6)) * 2048 + ((j >> 1) & 31) * 32 + t * 4;
#pragma unroll 1
        for (int h = 0; h < 2 * NUNITS; h++) {
            mbar_wait(pf, 0);
            const float m = __uint_as_float(lds32(ma));
            const uint4 pn = lds128(pa);
            wg_wait0();
#pragma unroll
            for (int i = 0; i < 128; i++) asm volatile("" : "+f"(acc[i]) :: "memory");
            if (h == 0) M = m;
            uint32_t b2 = 0x3f803f80u;
            if (__builtin_expect(__any_sync(0xffffffffu, m != M), 0)) {
                const float Mn = fmaxf(M, m), alpha = ex2(M - Mn), beta = ex2(m - Mn);
                M = Mn;
                b2 = pack2(beta, beta);
#pragma unroll
                for (int jj = 0; jj < 32; jj++) { acc[4 * jj] *= alpha; acc[4 * jj + 1] *= alpha; }
            }
            auto mul2 = [](uint32_t x, uint32_t y) { uint32_t r; asm("mul.rn.bf16x2 %0, %1, %2;" : "=r"(r) : "r"(x), "r"(y)); return r; };
            const uint4 p = make_uint4(mul2(pn.x, b2), mul2(pn.y, b2), mul2(pn.z, b2), mul2(pn.w, b2));
            if (tid == 0 && (h & 1)) TRACE_Q(48 + (h >> 1));
            wgmma_pv(acc, p, blo, h);
            if (lane == 0 && h > 0 && !(h & 1)) mbar_arrive(BAR(EB_UNIT0 + (h >> 1) - 1));
            blo += h == 11 ? -11 * 1024 : 1024;
            pa += (h == 5 || h == 11) ? -5 * 2048 : 2048;
            ma += 128; pf += 8;
            if (h == 2 * NUNITS - 3) {
                mbar_wait(BAR(JD), 0);
                const uint32_t hm = (*(const uint32_t*)(sm + SM_CLS + 16 + warp * 4) >> (g * 4)) ^ ((j >> 6) ? 15u : 0u);
#pragma unroll
                for (int i = 0; i < 4; i++) e1[i] += ((hm >> i) & 1) << 10;
            }
        }
#pragma unroll
        for (int vv = 0; vv < 2; vv++) {
            if (vv && M == 1.f) __trap();
            if (vv) wg_wait0(); else wg_wait1();
#pragma unroll
            for (int i = 0; i < 64; i++) asm volatile("" : "+f"(acc[vv * 64 + i]) :: "memory");
            if (tid == 0 && !vv) TRACE_Q(63);
#pragma unroll
            for (int i = 0; i < 4; i++) {
                const float* a = &acc[vv * 64 + i * 16];
                st_x4(e1[i] + i * 8192 + vv * 16, enc(pack2(a[0], a[1])), enc(pack2(a[4], a[5])), enc(pack2(a[8], a[9])), enc(pack2(a[12], a[13])));
            }
        }
        bar_arrive(3, 416);
        if (tid == 0) TRACE_Q(17);
#pragma unroll 1
        for (int pass = 0;; pass++) {
            if (j >= NFF && j < J_END && pass == (j >= J_RED)) {
                uint4 a[8], b[4];
                float c[4], e[4];
                const bool own = (warp >> 1) == rk;
                const uint32_t xa = sb + SM_FV + (warp & 1) * 64 + g * 8;
                if (lane == 0) mbar_expect(BAR(MBB), own ? 64 : 0);
#pragma unroll
                for (int i = 0; i < 2; i++) {
                    ldfrag(b, sb + SM_FS + rk * 512 + i * 256 + t * 16);
                    mbar_wait(BAR(IT_X + i), 0);
                    const uint32_t ab = sb + SM_U + B_X * 32768 + i * 16384 + a128;
                    load8<true>(a, [&](int s) { return ab + s * 2048; });
                    mma8(i ? e : c, a, b);
                }
                c[0] += e[0]; c[2] += e[2];
                if (!own) {
                    if (t == 0) st_async2(peer_addr(xa, rk ^ 1), c[0], c[2], peer_addr(BAR(MBB), rk ^ 1));
                } else {
                    mbar_wait(BAR(MBB), 0);
                    const float2 pp = *(const float2*)(sm + (xa - sb));
                    const float mine = t ? c[2] + pp.y : c[0] + pp.x, other = shx(mine, 4);
                    const uint32_t w = (warp & 1) * 8 + t * 4 + (g >> 1), val = enc(pack2(mine, other));
                    if (t < 2 && !(g & 1)) {
                        if (j < J_RED) st2_x1(gs + B_MB * 4096 + (j - NFF) * 16 + w, val);
                        else sts32(sb + SM_FV + 256 + w * 4, val);
                    }
                    __syncwarp();
                    if (j >= J_RED && lane < 4) mbar_arrive(BAR(QB));
                    if (lane == 0) TRACE(11);
                }
            }
            if (pass) break;
            uint4 a[8], a2[8];
            const uint32_t ab = sb + SM_U + B_WO * 32768 + a128;
            uint32_t* p3 = gs + (B_E3 + ((j >> 1) & 3)) * 4096 + (t >> 1) * 1024 + (rk * 2 + (warp >> 1)) * 256 + (j >> 3) * 16 + (warp & 1) * 8 + (t & 1) * 4 + (g >> 1);
            const uint32_t* pb = gs + near_off(B_E2 + (j >> 4), cls) + (((j >> 3) & 1) * 2 + lb4) * 256 + (lane & 15) * 2;
            pin(p3); pin(pb);
            uint2 bb[8];
            uint2 bq[2] = {make_uint2(0u, 0u), make_uint2(0u, 0u)};
            uint32_t xa = sb + SM_XA + lane * 16;
            pin(xa);
            bool h0 = false, h1 = false;
            auto idle = [&]() {
                if (!h0) {
                    h0 = __all_sync(0xffffffffu, mbar_test(BAR(IT_WO + (t & 1)), 0));
                    if (h0) load8<true>(a, [&](int s) { return ab + s * 2048; });
                }
                if (!h1) {
                    h1 = __all_sync(0xffffffffu, mbar_test(BAR(IT_WO + 2 + (t & 1)), 0));
                    if (h1) load8<true>(a2, [&](int s) { return ab + 16384 + s * 2048; });
                }
            };
            bar_sync(4, 416);
            idle();
            poll<128, 0, true>(bq, pb + warp * 64, idle);
            asm volatile("st.shared.v4.u32 [%0], {%1, %2, %3, %4};" :: "r"(xa + warp * 512), "r"(bq[0].x), "r"(bq[0].y), "r"(bq[1].x), "r"(bq[1].y) : "memory");
            bar_sync(2, 128);
#pragma unroll
            for (int i = 0; i < 4; i++) { const uint4 q = lds128(xa + i * 512); bb[2 * i] = make_uint2(q.x, q.y); bb[2 * i + 1] = make_uint2(q.z, q.w); }
            if (tid == 0) TRACE(21);
            float e[4][4];
#pragma unroll
            for (int s = 0; s < 16; s++) {
                if (s == 0 && !h0) { mbar_wait(BAR(IT_WO), 0); mbar_wait(BAR(IT_WO + 1), 0); load8<true>(a, [&](int q) { return ab + q * 2048; }); }
                if (s == 0 && !h1) { mbar_wait(BAR(IT_WO + 2), 0); mbar_wait(BAR(IT_WO + 3), 0); load8<true>(a2, [&](int q) { return ab + 16384 + q * 2048; }); }
                const int z = (s & 1) | (s & 2) << 2 | (s >> 2) << 1;
                const uint4& x = z < 8 ? a[z] : a2[z & 7];
                float (&d)[4] = e[(z >> 3) * 2 + (z & 1)];
                if (!(z & 6)) d[0] = d[1] = d[2] = d[3] = 0.f;
                mma(d, x.x, x.y, x.z, x.w, bb[z & 7].x, bb[z & 7].y);
            }
            float lo, hi;
            quad_pair((t & 2) ? (e[2][0] + e[3][0]) + (e[2][1] + e[3][1]) : (e[0][0] + e[1][0]) + (e[0][1] + e[1][1]),
                      (t & 2) ? (e[2][2] + e[3][2]) + (e[2][3] + e[3][3]) : (e[0][2] + e[1][2]) + (e[0][3] + e[1][3]), t, lo, hi);
            if (!(g & 1)) st_x1(p3, enc(pack2(lo, hi)));
            if (j < NFF) bar_arrive(8, 384); else if (j >= J_RED && j < J_END) bar_arrive(8, 192);
            if (tid == 0) TRACE(22);
        }
        if (j < NFF) {
            uint4 a[16];
            const uint32_t ad = sb + SM_U + B_DN * 32768 + warp * 8192 + (r8 + 8 * lb4) * 128 + (lb3 ^ r8) * 16;
            uint32_t rl = sb + SM_RED + lane * 16;
            uint32_t* p5 = gs + (B_E5 + warp * 4 + (t >> 1)) * 4096 + j * 16 + (t & 1) * 8 + g;
            pin(rl); pin(p5);
            if (lane == 0) mbar_expect(BAR(MBB), 4);
            auto ldd = [&]() {
#pragma unroll
                for (int s = 0; s < 16; s++) a[s] = ldsm<true>((ad ^ ((s & 3) * 32)) + (s >> 2) * 2048);
            };
            const uint32_t db = BAR(IT_DOWN + (warp ^ (j & 3)));
            mbar_wait(BAR(MBB), 0);
            const float4 st = ldsf4(sb + SM_RED + 2048);
            const bool hd = __all_sync(0xffffffffu, mbar_test(db, 0));
            if (hd) ldd();
            const float mu = (st.x + st.z) * (1.f / 512.f);
            float rstd;
            asm volatile("rsqrt.approx.ftz.f32 %0, %1;" : "=f"(rstd) : "f"(fmaxf(fmaf(-mu, mu, (st.y + st.w) * (1.f / 512.f)), 0.f) + 1e-5f));
            mbar_wait(BAR(QB), 1);
            if (tid == 0) TRACE(25);
            const float4 f0 = ldsf4(rl), f2 = ldsf4(rl + 1024), f1 = ldsf4(rl + 512), f3 = ldsf4(rl + 1536);
            const float gg = fmaf(rstd, fmaf(-mu, f0.z + f2.z, (f0.x + f0.y) + (f2.x + f2.y)), f0.w + f2.w);
            const float uu = fmaf(rstd, fmaf(-mu, f1.z + f3.z, (f1.x + f1.y) + (f3.x + f3.y)), f1.w + f3.w);
            const float hh = __fdividef(gg * uu, 1.f + ex2(-gg * fmaf(gg * gg, 0.10294324f, 2.3022082f)));
            uint32_t hb[4];
#pragma unroll
            for (int i = 0; i < 4; i++) hb[i] = pack2(__shfl_sync(0xffffffffu, hh, 2 * t + 8 * i), __shfl_sync(0xffffffffu, hh, 2 * t + 8 * i + 1));
            auto down = [&]() {
#pragma unroll
                for (int i = 0; i < 2; i++) {
                    uint32_t res = 0;
#pragma unroll
                    for (int k = 0; k < 4; k++) {
                        float c[4] = {0.f, 0.f, 0.f, 0.f};
                        const uint4 &x = a[i * 8 + k], &y = a[i * 8 + k + 4];
                        mma(c, x.x, x.y, x.z, x.w, hb[0], hb[1]);
                        mma(c, y.x, y.y, y.z, y.w, hb[2], hb[3]);
                        if (t == k) res = pack2(c[0], c[2]);
                    }
                    st2_x1(p5 + i * 8192, enc(res));
                }
            };
            if (hd) down();
            else { mbar_wait(db, 0); ldd(); down(); asm volatile("// late" ::: "memory"); }
            if (tid == 0) { TRACE(27); TRACE_GT(47); }
        }
    } else {
        const int u8 = tid - 128, w8 = warp - 4;
        const int v = w8 >> 2, wq4 = w8 & 3;
        {
            const float c0 = bflo(in1), c1 = bfhi(in1);
            sts32(sb + SM_FS + frag_off(2 * u8), pack2(__fdividef(c0, 1.f + __expf(-c0)), __fdividef(c1, 1.f + __expf(-c1))));
        }
        bar_sync(1, 256);
        asm volatile("barrier.cluster.wait.aligned;" ::: "memory");
        uint4 a[8], b[4]; float c[4];
        if (w8 < 2) {
            ldfrag(b, sb + SM_FS + (j >> 5) * 256 + t * 16);
            mbar_wait(BAR(IT_MODA), 0);
            if (u8 == 0) TRACE(12);
            const uint32_t ab = sb + SM_XA + w8 * 4096 + a16;
            load8<true>(a, [&](int s) { return ab + s * 512; });
            mma8(c, a, b);
            if (t < 2) st2_x1(gs + (B_HA + ((j >> 4) & 1) * 2 + w8) * 4096 + (j >> 5) * 256 + (j & 15) * 16 + t * 8 + g, encf(t ? c[2] : c[0]));
        }
        {
            mbar_wait(BAR(IT_WQ + 2 * v <= NCP ? 1 : IT_WQ + 2 * v), 0); mbar_wait(BAR(IT_WQ + 2 * v + 1 <= NCP ? 1 : IT_WQ + 2 * v + 1), 0);
            const uint32_t ab = sb + SM_U + 4 * 32768 + v * 16384 + a128;
            load8<true>(a, [&](int s) { return ab + s * 2048; });
            if (lane == 0) mbar_arrive(BAR(EB_WQ));
            bar_sync(5, 384);
            if (u8 == 0) TRACE(13);
            ldfrag(b, sb + SM_FV + v * 256 + t * 16);
            mma8(c, a, b);
            if (t < 2) {
                const float qv = t ? c[2] : c[0];
                const uint32_t qa_ = sb + SM_QX + ((rk * 2 + v) * 64 + wq4 * 16 + t * 8 + g) * 4;
                asm volatile("st.async.weak.shared::cluster.mbarrier::complete_tx::bytes.f32 [%0], %1, [%2];"
                             :: "r"(peer_addr(qa_, rk ^ 1)), "f"(qv), "r"(peer_addr(BAR(QB), rk ^ 1)) : "memory");
                sts32(qa_, __float_as_uint(qv));
            }
            __syncwarp();
            if (lane == 0) mbar_expect(BAR(QB), 64);
        }
        {
            mbar_wait(BAR(IT_WUK + (v ^ ((j >> 5) & 1))), 0); mbar_wait(BAR(IT_WUK + (v ^ ((j >> 5) & 1)) + 2), 0);
            const uint32_t ab = sb + SM_U + 5 * 32768 + (w8 * 16 + r8 + 8 * lb3) * 128;
            const uint32_t x16 = (lb4 ^ r8) * 16;
            load8<false>(a, [&](int s) { return ab + (s & 1) * 16384 + (x16 ^ ((s >> 1) * 32)); });
            bar_sync(6, 384);
            if (u8 == 0) TRACE(14);
            b[0] = lds128(sb + SM_FQ + t * 16); b[1] = lds128(sb + SM_FQ + 64 + t * 16);
            float e[4] = {0.f, 0.f, 0.f, 0.f};
            c[0] = c[1] = c[2] = c[3] = 0.f;
#pragma unroll
            for (int k = 0; k < 4; k++) {
                const uint32_t b0 = (k & 1) ? b[k >> 1].z : b[k >> 1].x, b1 = (k & 1) ? b[k >> 1].w : b[k >> 1].y;
                mma(c, a[2 * k].x, a[2 * k].y, a[2 * k].z, a[2 * k].w, b0, b1);
                mma(e, a[2 * k + 1].x, a[2 * k + 1].y, a[2 * k + 1].z, a[2 * k + 1].w, b0, b1);
            }
            const float mine = ((t & 1) ? ((t & 2) ? e[2] : e[0]) : ((t & 2) ? c[2] : c[0])) * 0.12751743f;
            const float other = shx(mine, 4);
            if (!(g & 1)) st2_x1(gs + (B_QA + rk * 8 + ((j >> 1) & 1) * 4 + (j >> 5)) * 4096 + w8 * 128 + ((j >> 2) & 7) * 16 + (g >> 1) * 4 + t, enc(pack2(mine, other)));
            if (u8 == 0) TRACE(15);
        }
        const uint32_t cls = ldcls();
        __nanosleep(QA_DELAY);
        {
            uint4 qb[8];
            const uint32_t* pq = gs + near_off(B_QA + rk * 8 + wq4, cls) + lane * 4;
            const uint32_t* pq2 = gs + near_off(B_QA + rk * 8 + 4 + wq4, cls) + lane * 4;
            if (lane == 0) {
                mbar_expect(BAR(QT), 4096);
                asm volatile("cp.async.bulk.shared::cluster.global.mbarrier::complete_tx::bytes [%0], [%1], 4096, [%2];"
                             :: "r"(sb + SM_U + 5 * 32768 + w8 * 4096), "l"(gs + near_off(B_QA + rk * 8 + w8, cls)), "r"(BAR(QT)) : "memory");
            }
            const uint32_t qs = sb + SM_U + 5 * 32768 + wq4 * 4096 + lane * 16;
            mbar_wait(BAR(QT), 0);
#pragma unroll
            for (int i = 0; i < 8; i++) { a[i] = lds128(qs + i * 512); qb[i] = lds128(qs + 16384 + i * 512); }
            poll<512, QA_SLEEP, true>(a, pq);
            poll<512, QA_SLEEP, true>(qb, pq2);
            if (lane == 0) mbar_arrive(BAR(EB_WUK));
            auto add2 = [](uint32_t x, uint32_t y) { uint32_t r; asm("add.rn.bf16x2 %0, %1, %2;" : "=r"(r) : "r"(x), "r"(y)); return r; };
#pragma unroll
            for (int i = 0; i < 8; i++) a[i] = make_uint4(add2(a[i].x, qb[i].x), add2(a[i].y, qb[i].y), add2(a[i].z, qb[i].z), add2(a[i].w, qb[i].w));
        }
        if (u8 == 0) TRACE(8);
        {
            float m = -INFINITY, l = 0.f;
            uint32_t xl = sb + SM_XB + w8 * 2048 + lane * 16, xr = peer_addr(xl, rk ^ 1), bsr = peer_addr(BAR(SF0 + v), rk ^ 1);
            uint32_t pa = sb + SM_XA + v * 2048 + wq4 * 512 + lane * 16, ma = sb + SM_MX + v * 128 + (wq4 * 8 + g) * 4;
            uint32_t fb = BAR(IT_CKV + v * 2), sf = BAR(SF0 + v);
            uint32_t dlo = __reduce_or_sync(0xffffffffu, (((sb + SM_U + v * 16384) & 0x3FFFFu) >> 4) | 0x10000u);
            if (STAG && v) __nanosleep(STAG);
#pragma unroll 1
            for (int n = 0; n < NUNITS; n++) {
                float d[2][16], sc[8];
#pragma unroll
                for (int i = 0; i < 2; i++) {
                    mbar_wait(fb + i * 8, 0);
                    wg_fence();
#pragma unroll
                    for (int s = 0; s < 8; s++) wgmma_rs_n32(d[i], a[s], (0x40000080ull << 32) | (dlo + i * 512 + (s >> 2) * 64 + (s & 3) * 2), s);
                    wg_commit();
                }
#pragma unroll
                for (int i = 0; i < 2; i++) {
                    if (i) wg_wait0(); else wg_wait1();
#pragma unroll
                    for (int k = 0; k < 16; k++) asm volatile("" : "+f"(d[i][k]) :: "memory");
                    sc[4 * i] = d[i][0] + d[i][6]; sc[4 * i + 1] = d[i][1] + d[i][7]; sc[4 * i + 2] = d[i][8] + d[i][14]; sc[4 * i + 3] = d[i][9] + d[i][15];
                    asm volatile("st.async.weak.shared::cluster.mbarrier::complete_tx::bytes.v4.f32 [%0], {%1, %2, %3, %4}, [%5];"
                                 :: "r"(xr + i * 1024), "f"(sc[4 * i]), "f"(sc[4 * i + 1]), "f"(sc[4 * i + 2]), "f"(sc[4 * i + 3]), "r"(bsr) : "memory");
                }
                if (u8 == 128) TRACE_Q(56 + (n < 6 ? n : -40));
                if (n >= 3) mbar_wait(BAR(EB_UNIT0 + n - 3), 0);
                dlo += n == 5 ? -5 * 2048 : 2048;
                fb += 32; xr ^= 512; bsr += 16;
                pin(fb); pin(xr); pin(bsr);
                mbar_wait(sf, 0);
                const float4 x = ldsf4(xl), y = ldsf4(xl + 1024);
                sc[0] += x.x; sc[1] += x.y; sc[2] += x.z; sc[3] += x.w; sc[4] += y.x; sc[5] += y.y; sc[6] += y.z; sc[7] += y.w;
                float pr[8];
#pragma unroll
                for (int i = 0; i < 8; i++) pr[i] = ex2(sc[i] - m);
                float mx = fmaxf(fmaxf(fmaxf(sc[0], sc[1]), fmaxf(sc[2], sc[3])), fmaxf(fmaxf(sc[4], sc[5]), fmaxf(sc[6], sc[7])));
                if (__builtin_expect(__any_sync(0xffffffffu, mx > m), 0)) {
                    mx = fmaxf(mx, shx(mx, 1));
                    mx = fmaxf(mx, shx(mx, 2));
                    const float mn = fmaxf(m, ceilf(mx * 0.0625f) * 16.f);
                    l *= ex2(m - mn);
                    m = mn;
#pragma unroll
                    for (int i = 0; i < 8; i++) pr[i] = ex2(sc[i] - m);
                }
                stsf(ma, m);
                asm volatile("st.shared.v4.u32 [%0], {%1, %2, %3, %4};" :: "r"(pa), "r"(pack2(pr[0], pr[1])), "r"(pack2(pr[2], pr[3])),
                             "r"(pack2(pr[4], pr[5])), "r"(pack2(pr[6], pr[7])) : "memory");
                __syncwarp();
                if (lane == 0) mbar_arrive(sf + (PF0 - SF0) * 8);
                l += ((pr[0] + pr[1]) + (pr[2] + pr[3])) + ((pr[4] + pr[5]) + (pr[6] + pr[7]));
                xl ^= 512; sf += 16; ma += 256; pa += (n == 2 || n == 5) ? -8192 : 4096;
            }
            l += shx(l, 1);
            l += shx(l, 2);
            float2* mlx = (float2*)(sm + SM_MX + 2048) + wq4 * 8 + g;
            if (v == 0) { *mlx = make_float2(m, l); bar_arrive(11, 256); }
            else {
                mbar_wait(BAR(JD), 0);
                bar_sync(11, 256);
                const float2 o = *mlx;
                const float mn = fmaxf(m, o.x);
                l = l * ex2(m - mn) + o.y * ex2(o.x - mn);
                if ((wq4 >> 1) == rk) st_x4(gs + (B_ML + wq4 * 8 + g) * 4096 + (t >> 1) * 1024 + (j >> 1) * 8 + (t & 1) * 4, encf(mn), encf(l), 1u, 1u);
            }
        }
        const int pi = j < NFF ? rk * 128 + w8 * 16 + (lane >> 1) : ((j - J_RED) & 15) * 16 + (w8 & 1) * 8 + g;
        const uint32_t xw = *(const uint32_t*)(xin + 2 * pi);
        const uint32_t one = (g & 1) ? 0x3f800000u : 0x00003f80u;
        const uint32_t* pm = gs + near_off(B_MB, cls) + pi;
        {
            const uint32_t ab = sb + SM_U + B_WUV * 32768 + v * 4096 + a128;
            uint32_t pa = sb + SM_PB + wq4 * 320 + frag_off(64 * v + 32 * (g >> 2) + 16 * (t & 1) + 8 * (t >> 1) + 2 * (g & 3));
            uint32_t fa = sb + SM_PB + g * 320 + t * 16;
            const uint32_t* pe = gs + G_E1 + j * 8192 + (w8 >> 1) * 2048 + ((((cls >> 1) ^ (w8 >> 1)) & 1) << 10) + (((w8 & 1) * 16 + t) * 8 + g) * 4;
            uint32_t* p2 = gs + (B_E2 + (j >> 4)) * 4096 + (t >> 1) * 1024 + (j & 12) * 64 + w8 * 32 + (j & 3) * 8 + (g & 6) + (t & 1);
            pin(pa); pin(fa); pin(pe); pin(p2);
            const uint32_t mk = (g & 1) ? 0xffff0000u : 0x0000ffffu, m0 = (g & 2) ? 0u : mk, m1 = (g & 2) ? mk : 0u;
            uint4 pv[4];
            bool hv = false;
            bar_sync(3, 416);
            uint4 wa = lds128(sb + SM_W + (wq4 * 4 + t) * 16);
            uint32_t wb[8] = {wa.x & m0, wa.x & m1, wa.y & m0, wa.y & m1, wa.z & m0, wa.z & m1, wa.w & m0, wa.w & m1};
            pv[0] = pv[1] = pv[2] = pv[3] = make_uint4(0u, 0u, 0u, 0u);
            float e[4][4];
            auto wsum = [&]() {
#pragma unroll
                for (int i = 0; i < 4; i++) {
                    e[i][0] = e[i][1] = e[i][2] = e[i][3] = 0.f;
                    mma(e[i], pv[i].x, pv[i].y, pv[i].z, pv[i].w, wb[2 * i], wb[2 * i + 1]);
                }
            };
            poll<512, E1_SLEEP, true>(pv, pe, [&]() {
                if (!hv) {
                    hv = __all_sync(0xffffffffu, mbar_test(BAR(IT_WUV + t), 0));
                    if (hv) load8<true>(a, [&](int s) { return ab + (s >> 1) * 8192 + (s & 1) * 2048; });
                }
            }, wsum);
            if (lane == 0) TRACE_Q(48 + w8);
            if (u8 == 0) TRACE_Q(18);
            float lo, hi2;
            float2 inv;
#pragma unroll 1
            for (int pass = 0;; pass++) {
                const float r0 = (t & 2) ? (e[0][2] + e[1][2]) + (e[2][2] + e[3][2]) : (e[0][0] + e[1][0]) + (e[2][0] + e[3][0]);
                const float r1 = (t & 2) ? (e[0][3] + e[1][3]) + (e[2][3] + e[3][3]) : (e[0][1] + e[1][1]) + (e[2][1] + e[3][1]);
                const uint32_t hi = pack2(r0, r1);
                sts32(pa, hi); sts32(pa + 1280, pack2(r0 - bflo(hi), r1 - bfhi(hi)));
                if (!hv) {
#pragma unroll 1
                    for (int i = 0; i < 4; i++) mbar_wait(BAR(IT_WUV + i), 0);
                    load8<true>(a, [&](int s) { return ab + (s >> 1) * 8192 + (s & 1) * 2048; });
                    hv = true;
                }
                bar_sync(1, 256);
                if (u8 == 0) TRACE(19);
                ldfrag(b, fa);
                mma8(c, a, b);
                mbar_wait(BAR(WR), 0);
                asm volatile("ld.shared.v2.f32 {%0, %1}, [%2];" : "=f"(inv.x), "=f"(inv.y) : "r"(sb + SM_FQ) : "memory");
                quad_pair(c[0] + c[1], c[2] + c[3], t, lo, hi2);
                if (__builtin_expect(__all_sync(0xffffffffu, pass || __float_as_uint(inv.y) == 0), 1)) break;
                wa = lds128(sb + SM_W2 + (wq4 * 4 + t) * 16);
                wb[0] = wa.x & m0; wb[1] = wa.x & m1; wb[2] = wa.y & m0; wb[3] = wa.y & m1; wb[4] = wa.z & m0; wb[5] = wa.z & m1; wb[6] = wa.w & m0; wb[7] = wa.w & m1;
                wsum();
                bar_sync(1, 256);
            }
            if (!(g & 1)) st_x1(p2, enc(pack2(lo * inv.x, hi2 * inv.x)));
            bar_arrive(4, 416);
            if (u8 == 0) TRACE(20);
        }
        if (j < NFF) {
            const uint32_t* p3 = gs + near_off(B_E3 + rk * 2 + v, cls) + wq4 * 256 + t * 16 + g * 2;
            const int od = lane & 1;
            uint32_t za = sb + SM_FZ + od * 576 + frag_off(w8 * 32 + (lane & 30));
            uint32_t fa = sb + SM_FZ + (g & 3) * 576 + ((lane ^ j) & 16) * 16 + t * 16, ya = sb + SM_Y + u8 * 4;
            uint32_t mb[3];
            uint4 a2[8];
            poll<1024, MB_SLEEP>(mb, pm);
            const uint32_t kk = pack2(1.f + bflo(mb[2]), 1.f + bfhi(mb[2]));
            sts32(za + 2 * 576, od ? mb[1] : kk);
            uint2 e3[4] = {make_uint2(0u, 0u), make_uint2(0u, 0u), make_uint2(0u, 0u), make_uint2(0u, 0u)};
            uint32_t ra = peer_addr(sb + SM_RED + (rk * 2 + v) * 512 + ((wq4 & 1) * 16 + (t >> 1) * 8 + g) * 16 + (t & 1) * 8, wq4 >> 1), tbo = peer_addr(BAR(QB), wq4 >> 1);
            pin(za); pin(fa); pin(ya); pin(ra); pin(tbo);
            if (lane == 0) mbar_expect(BAR(QB), 256);
            const uint32_t gb = BAR(IT_X + v * 2), ab = sb + SM_U + (B_X + v) * 32768 + a128;
            bool early = false, early2 = false;
            auto ldw = [&]() {
                if (!early) {
                    early = __all_sync(0xffffffffu, mbar_test(gb, 0));
                    if (early) load8<true>(a, [&](int s) { return ab + s * 2048; });
                }
                if (!early2) {
                    early2 = __all_sync(0xffffffffu, mbar_test(gb + 8, 0));
                    if (early2) load8<true>(a2, [&](int s) { return ab + 16384 + s * 2048; });
                }
            };
            bar_sync(8, 384);
            float s0[4], s1[4];
            auto sum = [&]() {
                s0[0] = s0[1] = s0[2] = s0[3] = s1[0] = s1[1] = s1[2] = s1[3] = 0.f;
                mma(s0, e3[0].x, e3[0].y, e3[1].x, e3[1].y, one, one); mma(s1, e3[2].x, e3[2].y, e3[3].x, e3[3].y, one, one);
            };
            poll<256, 0, true>(e3, p3, ldw, sum);
            if (u8 == 0) TRACE(23);
            const float y0 = fmaf(bflo(mb[0]), (t & 2) ? s0[2] + s1[2] : s0[0] + s1[0], bflo(xw)), y1 = fmaf(bfhi(mb[0]), (t & 2) ? s0[3] + s1[3] : s0[1] + s1[1], bfhi(xw));
            stsf(ya, od ? y1 : y0);
            const float z0 = y0 * bflo(kk), z1 = y1 * bfhi(kk);
            const uint32_t zh = pack2(z0, z1);
            sts32(za, od ? pack2(z0 - bflo(zh), z1 - bfhi(zh)) : zh);
            bar_sync(7, 288);
            if (u8 == 0) TRACE(24);
            ldfrag(b, fa);
            if (!early) { mbar_wait(gb, 0); load8<true>(a, [&](int s) { return ab + s * 2048; }); }
            {
                float e[4][4];
#pragma unroll
                for (int s = 0; s < 16; s++) {
                    if (s == 8 && !early2) { mbar_wait(gb + 8, 0); load8<true>(a2, [&](int q) { return ab + 16384 + q * 2048; }); }
                    const uint4& x = s < 8 ? a[s] : a2[s & 7];
                    const uint4& y = b[(s >> 1) & 3];
                    float (&d)[4] = e[(s >> 3) * 2 + (s & 1)];
                    if (!(s & 6)) d[0] = d[1] = d[2] = d[3] = 0.f;
                    mma(d, x.x, x.y, x.z, x.w, (s & 1) ? y.z : y.x, (s & 1) ? y.w : y.y);
                }
                const bool hi = t >> 1;
                const float k0 = hi ? e[2][2] + e[3][2] : e[0][0] + e[1][0], k1 = hi ? e[2][3] + e[3][3] : e[0][1] + e[1][1];
                const float o0 = hi ? e[2][0] + e[3][0] : e[0][2] + e[1][2], o1 = hi ? e[2][1] + e[3][1] : e[0][3] + e[1][3];
                st_async2(ra, k0 + shx(o0, 2), k1 + shx(o1, 2), tbo);
            }
        } else if (j >= J_RED && j < J_END && w8 < 2) {
            uint32_t ga[1], e3[4];
            poll<0, MB_SLEEP>(ga, pm);
            bar_sync(8, 192);
            poll<64, 100>(e3, gs + near_off(B_E3 + (pi >> 6), cls) + (pi & 48) * 16 + t * 64 + (pi & 15));
            float y0 = (bflo(e3[0]) + bflo(e3[1])) + (bflo(e3[2]) + bflo(e3[3])), y1 = (bfhi(e3[0]) + bfhi(e3[1])) + (bfhi(e3[2]) + bfhi(e3[3]));
#pragma unroll
            for (int o = 1; o < 4; o <<= 1) { y0 += shx(y0, o); y1 += shx(y1, o); }
            const int col = g + (t & 1) * 8;
            y0 = __shfl_sync(0xffffffffu, (t & 1) ? fmaf(bfhi(ga[0]), y1, bfhi(xw)) : fmaf(bflo(ga[0]), y0, bflo(xw)), (col >> 1) * 4 + (col & 1));
            uint16_t* po = (uint16_t*)out + (j - J_RED) * 32 + w8 * 16 + col;
            const uint32_t* pe = gs + near_off(B_E5 + j - J_RED, cls) + t * 16 + w8 * 8 + g;
            pin(po);
            const uint32_t sel = (g & 2) ? 0x3f800000u : 0x00003f80u;
            uint32_t yv[NFF / 4 + 1];
            float e[4][4], gb = 0.f;
#pragma unroll
            for (int i = 0; i <= NFF / 4; i++) yv[i] = 0u;
#pragma unroll 1
            for (uint32_t it = 0;; it++) {
#pragma unroll
                for (int i = 0; i < NFF / 4; i++) if (!yv[i]) ld_x(yv[i], pe + i * 64);
                if (__all_sync(0xffffffffu, !yv[NFF / 4] && mbar_test(BAR(QB), 1))) {
                    yv[NFF / 4] = lds32(sb + SM_FV + 256 + w8 * 32 + (col >> 1) * 4);
                    gb = (col & 1) ? bfhi(yv[NFF / 4]) : bflo(yv[NFF / 4]);
                }
                if (it > SPIN_LIMIT) __trap();
#pragma unroll
                for (int i = 0; i < 4; i++) {
                    e[i][0] = e[i][1] = e[i][2] = e[i][3] = 0.f;
                    mma(e[i], yv[4 * i], yv[4 * i + 1], i < 3 ? yv[(4 * i + 2) % (NFF / 4)] : 0u, i < 3 ? yv[(4 * i + 3) % (NFF / 4)] : 0u, sel, sel);
                }
                if (__all_sync(0xffffffffu, mint<NFF / 4 + 1>(yv) != 0)) break;
            }
            if (u8 == 0) TRACE(26);
            const float s = ((e[0][0] + e[0][2]) + (e[1][0] + e[1][2])) + ((e[2][0] + e[2][2]) + (e[3][0] + e[3][2]));
            asm volatile("{\n.reg .pred p;\nsetp.lt.u32 p, %2, 2;\n@p st.global.u16 [%0], %1;\n}" :: "l"(po), "h"((uint16_t)pack2(fmaf(gb, s, y0), 0.f)), "r"(t) : "memory");
            asm volatile("{\n.reg .pred p;\nsetp.eq.f32 p, %0, 0f7F7FFFFF;\n@p nanosleep.u32 0;\n}" :: "f"(((e[0][1] + e[0][3]) + (e[1][1] + e[1][3])) + ((e[2][1] + e[2][3]) + (e[3][1] + e[3][3]))));
            if (u8 == 0) TRACE(27);
        }
    }
}

typedef CUresult (*EncFn)(CUtensorMap*, CUtensorMapDataType, cuuint32_t, void*, const cuuint64_t*, const cuuint64_t*,
                          const cuuint32_t*, const cuuint32_t*, CUtensorMapInterleave, CUtensorMapSwizzle,
                          CUtensorMapL2promotion, CUtensorMapFloatOOBfill);

void make_map(EncFn enc_fn, CUtensorMap* m, const void* p, cuuint64_t d0, cuuint64_t d1, cuuint64_t d2, cuuint64_t d3,
              cuuint64_t s1, cuuint64_t s2, cuuint64_t s3, cuuint32_t b0, cuuint32_t b1, cuuint32_t b2, cuuint32_t b3, CUtensorMapSwizzle sw) {
    const cuuint64_t dims[4] = {d0, d1, d2, d3}, strides[3] = {s1, s2, s3};
    const cuuint32_t box[4] = {b0, b1, b2, b3}, es[4] = {1, 1, 1, 1};
    enc_fn(m, CU_TENSOR_MAP_DATA_TYPE_BFLOAT16, 4, (void*)p, dims, strides, box, es,
           CU_TENSOR_MAP_INTERLEAVE_NONE, sw, CU_TENSOR_MAP_L2_PROMOTION_L2_128B, CU_TENSOR_MAP_FLOAT_OOB_FILL_NONE);
}

uint32_t* scratch = nullptr;

struct Tune { const char* win; const char* late; int tau, t_off; const char* tail[3][4]; };
Tune tune = {"77777777755555555555555555555555555555544",
             "00000000000000888888888888888888888888888", 322, -380,
             {{"VVVVOOOOguguDDDD", "zzzzzzzzzzzzzzzz", "7777aaaaaaaa6789", "ebbb9ddddaaa2555"},
              {"VMVMVVOOOO", "zzzzzzzzzz", "9999999999", "8aaaaac999"},
              {"VVVVOOOOMM", "zzzzzzzzzz", "aaaaaaaa88", "b1111a9asb"}}};
bool ready = false;

}

extern "C" void kernel_launch(void* const* d_in, const int* in_sizes, int n_in, void* d_out, int out_size) {
    (void)in_sizes; (void)n_in; (void)out_size;
    static Maps maps;
    static const void* cached[12] = {};
    bool same = ready;
    for (int i = 0; i < 12 && same; i++) same = cached[i] == d_in[i];
    if (!same) {
        void* fn = nullptr;
        cudaDriverEntryPointQueryResult qr;
        cudaGetDriverEntryPoint("cuTensorMapEncodeTiled", &fn, cudaEnableDefault, &qr);
        EncFn e = (EncFn)fn;
        const CUtensorMapSwizzle S128 = CU_TENSOR_MAP_SWIZZLE_128B;
        make_map(e, &maps.m[MP_WQ], d_in[2], 64, 512, 64, 1, 8192, 128, 8192, 64, 64, 1, 1, S128);
        make_map(e, &maps.m[MP_WUK], d_in[3], 64, 512, 64, 1, 8192, 128, 8192, 64, 64, 1, 1, S128);
        make_map(e, &maps.m[MP_CKV], d_in[1], 64, 8, 8, 4096, 1024, 128, 8192, 64, 8, 4, 2, S128);
        make_map(e, &maps.m[MP_MODB], d_in[11], 3072, 512, 1, 1, 6144, 6144, 6144, 64, 128, 1, 1, S128);
        make_map(e, &maps.m[MP_WUV], d_in[4], 64, 512, 64, 1, 8192, 128, 8192, 64, 32, 2, 1, S128);
        make_map(e, &maps.m[MP_WO], d_in[5], 512, 4096, 1, 1, 1024, 1024, 1024, 64, 64, 1, 1, S128);
        make_map(e, &maps.m[MP_GATE], d_in[7], 1792, 512, 1, 1, 3584, 3584, 3584, 64, 128, 1, 1, S128);
        make_map(e, &maps.m[MP_UP], d_in[8], 1792, 512, 1, 1, 3584, 3584, 3584, 64, 128, 1, 1, S128);
        make_map(e, &maps.m[MP_DOWN], d_in[9], 64, 1792, 8, 1, 1024, 128, 1024, 64, 32, 2, 1, S128);
        for (int r = 0; r < 3; r++) {
            int ids[58], cnt[128] = {}, tn = tune.t_off - (W0 - 1) * tune.tau;
            uint2* sc = maps.sched[r];
            auto dig = [](char ch) { return ch >= 'a' ? ch - 'a' + 10 : ch >= 'A' ? ch - 'A' + 36 : ch - '0'; };
            for (int i = 0; i < 58; i++) sc[i] = make_uint2(0u, 0u);
            for (int i = 0;; i++) {
                int id = i, buf, dep, w, wl;
                if (i < IT_WUV) {
                    const int u = (i - IT_CKV) >> 2;
                    buf = i < IT_CKV ? 4 + ((i - 1) >> 2) : u % 6;
                    dep = i < IT_CKV || u < 4 ? -1 : u < 6 ? EB_WQ + u - 4 : EB_UNIT0 + u - 6;
                    w = dig(tune.win[i]); wl = dig(tune.late[i]);
                    if (i) tn += tune.tau;
                } else {
                    const char ch = tune.tail[r][0][i - IT_WUV];
                    if (!ch) break;
                    buf = ch == 'V' ? B_WUV : ch == 'O' ? B_WO : ch == 'D' ? B_DN : ch == 'u' ? B_X + 1 : B_X;
                    id = (ch == 'V' ? IT_WUV : ch == 'O' ? IT_WO : ch == 'D' ? IT_DOWN : ch == 'u' ? IT_X + 2 : IT_X) + cnt[(int)ch]++;
                    dep = EB_UNIT0 + (buf < 2 ? buf + 6 : buf);
                    w = dig(tune.tail[r][1][i - IT_WUV]); wl = dig(tune.tail[r][2][i - IT_WUV]);
                    tn += (r == 2 ? 64 : 32) * dig(tune.tail[r][3][i - IT_WUV]);
                }
                if (id < IT_X || id >= IT_DOWN ? (id - 1) & 3 : (id - IT_X) & 1) dep = -1;
                ids[i] = id;
                auto back = [&](int d) { return i < d ? 0 : (ids[i - d] && ids[i - d] <= NCP ? 1 : ids[i - d]) + 1; };
                sc[i].x = id | (buf * 4 + (id < IT_X || id >= IT_DOWN ? (id - 1) & 3 : ((id - IT_X) & 1) * 2)) << 6 | (dep + 1) << 11 | (w > 32 ? NEVER + 1 : back(w)) << 18 | (wl ? back(wl) : 0) << 25;
                const int mp = id < IT_CKV ? MP_WQ + ((id - 1) >> 2) : id < IT_WUV ? MP_CKV : id < IT_WO ? MP_WUV : id < IT_X ? MP_WO
                             : id >= IT_DOWN ? MP_DOWN : r ? MP_MODB : MP_GATE + ((id - IT_X) >> 1);
                const int step = mp == MP_CKV ? id - IT_CKV : mp == MP_WUV ? (id - IT_WUV) * 2 : mp == MP_DOWN ? id - IT_DOWN : id < IT_X ? (id - 1) & 3 : ((id - IT_X) & 1) * 2;
                sc[i].y = (tn & 0xffff) | (mp & 15) << 16 | step << 20;
            }
        }
        cudaGetSymbolAddress((void**)&scratch, g_scratch);
        scratch = (uint32_t*)(((uintptr_t)scratch + (2u << 20) - 1) & ~(uintptr_t)((2u << 20) - 1));
        cudaFuncSetAttribute(fused_kernel, cudaFuncAttributeMaxDynamicSharedMemorySize, SM_TOTAL);
        for (int i = 0; i < 12; i++) cached[i] = d_in[i];
        ready = true;
    }
    const First f = {{(const uint8_t*)d_in[2], (const uint8_t*)d_in[11]}, {(const __nv_bfloat16*)d_in[0], (const __nv_bfloat16*)d_in[10]}};
    fused_kernel<<<NCTA, NTHREADS, SM_TOTAL>>>(f, (__nv_bfloat16*)d_out, scratch, maps);
}
```

```cpp
#include <cuda_runtime.h>
#include <cuda_bf16.h>
#include <cuda.h>
#include <stdint.h>
#include <limits.h>

namespace {

constexpr int NCTA = 128;
constexpr int NTHREADS = 512;
constexpr int NUNITS = 8;
constexpr int NFF = 56, J_RED = 104, J_END = 120;
constexpr uint32_t SPIN_LIMIT = 1u << 22;

#define NEAR_CLK 390
#define E1_EARLY 50
#define STAG 300
#define NUMA 1
#define NPROBE 5
#define NCP 2
#define W0 4
#define RD_ITEM 15
#define JAN_SLEEP 100
#define RD_SLEEP 400
#define HA_DELAY 200
#define H_SLEEP 100
#define QA_DELAY 600
#define QA_SLEEP 200
#define ML_DELAY 300
#define E1_SLEEP 50
#define MB_SLEEP 100
constexpr int B_WUV = 2, B_WO = 3, B_X = 4  , B_DN = 0;

constexpr int SM_U = 0;
constexpr int SM_XA = 6 * 32768;
constexpr int SM_XB = SM_XA + 12288;
constexpr int SM_MX = SM_XB + 16384;
constexpr int SM_FZ = SM_XB + 8192;
constexpr int SM_PB = SM_XB;
constexpr int SM_Y = SM_XB + 12288;
constexpr int SM_RED = SM_XB + 4096;
constexpr int SM_FS = SM_XB + 20480;
constexpr int SM_FV = SM_FS + 1024;
constexpr int SM_QX = SM_XA + 8192;
constexpr int SM_FQ = SM_FV + 512;
constexpr int SM_CLS = SM_FQ + 128;
constexpr int SM_W = SM_FQ + 256;
constexpr int SM_W2 = SM_MX + 2304;
constexpr int SM_SCR = SM_XA + 9216;
constexpr int SM_BAR = SM_W + 256;
constexpr int SM_TOTAL = SM_BAR + 1024;
static_assert(SM_TOTAL <= 232448, "smem");

enum { IT_MODA = 0, IT_WQ = 1, IT_WUK = 5, IT_CKV = 9, IT_WUV = 41, IT_WO = 45, IT_X = 49  , IT_DOWN = 53, NITEMS = 57,
       NEVER = 63,
       SF0 = 64,
       PF0 = 80,
       EB_UNIT0 = 96, MBB = 103,
       EB_WQ = 104, EB_WUK, QT, QB, JD, WR };

enum { MP_WQ = 0, MP_WUK, MP_CKV, MP_WUV, MP_DOWN, MP_WO, MP_GATE, MP_UP, MP_MODB, NMAPS };
struct First { const uint8_t* w[2]; const __nv_bfloat16* v[2]; };
struct Maps { CUtensorMap m[NMAPS]; uint2 sched[3][58]; };

enum { B_HA = 0,
       B_MB = 6,
       B_RD = 7,
       B_E2 = 8,
       B_QA = 16,
       B_ML = 32,
       B_E5 = 64,
       B_E3 = 80,
       B_PR = 96,
       B_TR = 100 };
constexpr int G_E1 = 1 << 19;
__device__ __align__(1024) uint32_t g_scratch[(8 << 20) / 4];

#define TRACE(slot) do {} while (0)
#define TRACE_Q(slot) do {} while (0)
#define TRACE_GT(slot) do {} while (0)

__device__ __forceinline__ uint32_t s2u(const void* p) { return (uint32_t)__cvta_generic_to_shared(p); }
__device__ __forceinline__ void mbar_init(uint32_t b, int c) { asm volatile("mbarrier.init.shared::cta.b64 [%0], %1;" :: "r"(b), "r"(c) : "memory"); }
__device__ __forceinline__ void mbar_expect(uint32_t b, uint32_t bytes) { asm volatile("mbarrier.arrive.expect_tx.shared::cta.b64 _, [%0], %1;" :: "r"(b), "r"(bytes) : "memory"); }
__device__ __forceinline__ void mbar_arrive(uint32_t b) { asm volatile("mbarrier.arrive.shared::cta.b64 _, [%0];" :: "r"(b) : "memory"); }
__device__ __forceinline__ void mbar_wait(uint32_t b, uint32_t ph) {
    asm volatile("{\n.reg .pred p;\nW: mbarrier.try_wait.parity.shared::cta.b64 p, [%0], %1;\n@!p bra W;\n}" :: "r"(b), "r"(ph) : "memory");
}
__device__ __forceinline__ void mbar_waitb(uint32_t b, uint32_t ph) {
    asm volatile("{\n.reg .pred p;\n.reg .u32 n;\nmov.u32 n, 0;\n"
                 "W: mbarrier.try_wait.parity.shared::cta.b64 p, [%0], %1;\n@p bra D;\n"
                 "add.u32 n, n, 1;\nsetp.lt.u32 p, n, 0x100000;\n@p bra W;\ntrap;\nD:\n}" :: "r"(b), "r"(ph) : "memory");
}
__device__ __forceinline__ uint32_t mbar_test(uint32_t b, uint32_t ph) {
    uint32_t ok;
    asm volatile("{\n.reg .pred p;\nmbarrier.test_wait.parity.shared::cta.b64 p, [%1], %2;\nselp.u32 %0, 1, 0, p;\n}" : "=r"(ok) : "r"(b), "r"(ph) : "memory");
    return ok;
}
__device__ __forceinline__ void bar_sync(int id, int n) { asm volatile("bar.sync %0, %1;" :: "r"(id), "r"(n) : "memory"); }
__device__ __forceinline__ void bar_arrive(int id, int n) { asm volatile("bar.arrive %0, %1;" :: "r"(id), "r"(n) : "memory"); }
__device__ __forceinline__ uint32_t peer_addr(uint32_t a, uint32_t rank) { uint32_t r; asm("mapa.shared::cluster.u32 %0, %1, %2;" : "=r"(r) : "r"(a), "r"(rank)); return r; }
__device__ __forceinline__ void st_async2(uint32_t a, float x, float y, uint32_t bar) {
    asm volatile("st.async.weak.shared::cluster.mbarrier::complete_tx::bytes.v2.f32 [%0], {%1, %2}, [%3];" :: "r"(a), "f"(x), "f"(y), "r"(bar) : "memory");
}
__device__ __forceinline__ uint32_t gtime() { uint32_t t; asm volatile("mov.u32 %0, %%globaltimer_lo;" : "=r"(t)); return t; }
__device__ __forceinline__ void fence_gpu() { asm volatile("fence.acq_rel.gpu;" ::: "memory"); }

__device__ __forceinline__ uint32_t enc(uint32_t b) { uint32_t r; asm("max.u32 %0, %1, 1;" : "=r"(r) : "r"(b)); return r; }
__device__ __forceinline__ uint32_t encf(float f) { return enc(__float_as_uint(f)); }
__device__ __forceinline__ void st_x1(uint32_t* p, uint32_t v) { asm volatile("st.relaxed.gpu.global.u32 [%0], %1;" :: "l"(p), "r"(v) : "memory"); }
__device__ __forceinline__ void st_x4(void* p, uint32_t a, uint32_t b, uint32_t c, uint32_t d) {
    asm volatile("st.relaxed.gpu.global.v4.u32 [%0], {%1, %2, %3, %4};" :: "l"(p), "r"(a), "r"(b), "r"(c), "r"(d) : "memory");
}
__device__ __forceinline__ void st2_x1(uint32_t* p, uint32_t v) { st_x1(p, v); st_x1(p + 1024, v); }
__device__ __forceinline__ void st2_x4(uint32_t* p, uint32_t a, uint32_t b, uint32_t c, uint32_t d) { st_x4(p, a, b, c, d); st_x4(p + 1024, a, b, c, d); }
__device__ __forceinline__ int near_off(int b, uint32_t cls) { return b * 4096 + (((__popc(b & 0x2C) ^ cls) & 1) << 10); }
__device__ __forceinline__ void ld_x(uint32_t& v, const void* p) { asm volatile("ld.relaxed.gpu.global.u32 %0, [%1];" : "=r"(v) : "l"(p) : "memory"); }
__device__ __forceinline__ void ld_x(uint4& v, const void* p) {
    asm volatile("ld.relaxed.gpu.global.v4.u32 {%0, %1, %2, %3}, [%4];" : "=r"(v.x), "=r"(v.y), "=r"(v.z), "=r"(v.w) : "l"(p) : "memory");
}
__device__ __forceinline__ void ld_x(uint2& v, const void* p) { asm volatile("ld.relaxed.gpu.global.v2.u32 {%0, %1}, [%2];" : "=r"(v.x), "=r"(v.y) : "l"(p) : "memory"); }
__device__ __forceinline__ uint32_t minw(uint32_t v) { return v; }
__device__ __forceinline__ uint32_t minw(const uint2& v) { return min(v.x, v.y); }
__device__ __forceinline__ uint32_t minw(const uint4& v) { return min(__vimin3_u32(v.x, v.y, v.z), v.w); }
template <int N> __device__ __forceinline__ uint32_t mint(const uint32_t* m) {
    if constexpr (N == 1) return m[0];
    else if constexpr (N == 2) return min(m[0], m[1]);
    else return __vimin3_u32(mint<(N + 2) / 3>(m), mint<(N + 1) / 3>(m + (N + 2) / 3), mint<N / 3>(m + (N + 2) / 3 + (N + 1) / 3));
}

template <int STRIDE, int S4 = 4 * STRIDE, typename T, int N>
__device__ __forceinline__ void poll_start(T (&v)[N], const void* base) {
#pragma unroll
    for (int i = 0; i < N; i++) ld_x(v[i], (const uint8_t*)base + (i & 3) * STRIDE + (i >> 2) * S4);
}
struct Nop { __device__ void operator()() const {} };
template <int STRIDE, int SLEEP, bool STARTED = false, int S4 = 4 * STRIDE, typename T, int N, typename F = Nop, typename G = Nop>
__device__ __forceinline__ void poll(T (&v)[N], const void* base, F idle = F(), G ahead = G()) {
    if (!STARTED) { poll_start<STRIDE, S4>(v, base); idle(); }
#pragma unroll 1
    for (uint32_t it = 0;; it++) {
        uint32_t m[N];
        ahead();
#pragma unroll
        for (int i = 0; i < N; i++) m[i] = minw(v[i]);
        if (__all_sync(0xffffffffu, mint<N>(m) != 0)) break;
        if (SLEEP && it > 0) __nanosleep(SLEEP);
#pragma unroll
        for (int i = 0; i < N; i++) if (!m[i]) ld_x(v[i], (const uint8_t*)base + (i & 3) * STRIDE + (i >> 2) * S4);
        idle();
        if (it > SPIN_LIMIT) __trap();
    }
}

__device__ __forceinline__ float bflo(uint32_t w) { return __uint_as_float(w << 16); }
__device__ __forceinline__ float bfhi(uint32_t w) { return __uint_as_float(w & 0xffff0000u); }
__device__ __forceinline__ uint32_t pack2(float lo, float hi) {
    uint32_t r; asm("cvt.rn.bf16x2.f32 %0, %1, %2;" : "=r"(r) : "f"(hi), "f"(lo)); return r;
}
__device__ __forceinline__ float rbf(float x) { return __uint_as_float(pack2(0.f, x)); }
__device__ __forceinline__ float ex2(float x) { float r; asm("ex2.approx.ftz.f32 %0, %1;" : "=f"(r) : "f"(x)); return r; }
__device__ __forceinline__ float shx(float v, int m) { return __shfl_xor_sync(0xffffffffu, v, m); }
__device__ __forceinline__ uint4 lds128(uint32_t a) { uint4 v; asm volatile("ld.shared.v4.u32 {%0, %1, %2, %3}, [%4];" : "=r"(v.x), "=r"(v.y), "=r"(v.z), "=r"(v.w) : "r"(a) : "memory"); return v; }
__device__ __forceinline__ uint32_t lds32(uint32_t a) { uint32_t v; asm volatile("ld.shared.u32 %0, [%1];" : "=r"(v) : "r"(a) : "memory"); return v; }
__device__ __forceinline__ void sts32(uint32_t a, uint32_t v) { asm volatile("st.shared.u32 [%0], %1;" :: "r"(a), "r"(v) : "memory"); }
__device__ __forceinline__ void sts16(uint32_t a, uint32_t v) { asm volatile("st.shared.u16 [%0], %1;" :: "r"(a), "h"((uint16_t)v) : "memory"); }
__device__ __forceinline__ int frag_off(int k) { return (k >> 5) * 64 + ((k >> 1) & 3) * 16 + ((k >> 4) & 1) * 8 + ((k >> 3) & 1) * 4 + (k & 1) * 2; }

template <bool TRANS>
__device__ __forceinline__ uint4 ldsm(uint32_t a) {
    uint4 r;
    if (TRANS) asm volatile("ldmatrix.sync.aligned.m8n8.x4.trans.shared.b16 {%0, %1, %2, %3}, [%4];" : "=r"(r.x), "=r"(r.y), "=r"(r.z), "=r"(r.w) : "r"(a) : "memory");
    else asm volatile("ldmatrix.sync.aligned.m8n8.x4.shared.b16 {%0, %1, %2, %3}, [%4];" : "=r"(r.x), "=r"(r.y), "=r"(r.z), "=r"(r.w) : "r"(a) : "memory");
    return r;
}
__device__ __forceinline__ void mma(float (&c)[4], uint32_t a0, uint32_t a1, uint32_t a2, uint32_t a3, uint32_t b0, uint32_t b1) {
    asm volatile("mma.sync.aligned.m16n8k16.row.col.f32.bf16.bf16.f32 {%0,%1,%2,%3}, {%4,%5,%6,%7}, {%8,%9}, {%0,%1,%2,%3};"
                 : "+f"(c[0]), "+f"(c[1]), "+f"(c[2]), "+f"(c[3]) : "r"(a0), "r"(a1), "r"(a2), "r"(a3), "r"(b0), "r"(b1));
}
template <bool TRANS, typename F>
__device__ __forceinline__ void load8(uint4 (&a)[8], F addr) {
    __syncwarp();
#pragma unroll
    for (int s = 0; s < 8; s++) a[s] = ldsm<TRANS>(addr(s));
}
__device__ __forceinline__ void mma8(float (&c)[4], const uint4 (&a)[8], const uint4 (&b)[4]) {
    float e[4][4];
#pragma unroll
    for (int s = 0; s < 8; s++) {
        if (s < 4) e[s][0] = e[s][1] = e[s][2] = e[s][3] = 0.f;
        mma(e[s & 3], a[s].x, a[s].y, a[s].z, a[s].w, (s & 1) ? b[s >> 1].z : b[s >> 1].x, (s & 1) ? b[s >> 1].w : b[s >> 1].y);
    }
#pragma unroll
    for (int i = 0; i < 4; i++) c[i] = (e[0][i] + e[1][i]) + (e[2][i] + e[3][i]);
}
__device__ __forceinline__ void ldfrag(uint4 (&b)[4], uint32_t a) {
    asm volatile("ld.shared.v4.u32 {%0,%1,%2,%3}, [%16];\nld.shared.v4.u32 {%4,%5,%6,%7}, [%16+64];\n"
                 "ld.shared.v4.u32 {%8,%9,%10,%11}, [%16+128];\nld.shared.v4.u32 {%12,%13,%14,%15}, [%16+192];\n"
                 : "=r"(b[0].x), "=r"(b[0].y), "=r"(b[0].z), "=r"(b[0].w), "=r"(b[1].x), "=r"(b[1].y), "=r"(b[1].z), "=r"(b[1].w),
                   "=r"(b[2].x), "=r"(b[2].y), "=r"(b[2].z), "=r"(b[2].w), "=r"(b[3].x), "=r"(b[3].y), "=r"(b[3].z), "=r"(b[3].w) : "r"(a) : "memory");
}
__device__ __forceinline__ void quad_pair(float x, float y, int t, float& lo, float& hi) {
    const float k = ((t & 1) ? y : x) + shx((t & 1) ? x : y, 1);
    lo = k + shx(k, 2); hi = shx(k, 4) + shx(k, 6);
}
__device__ __forceinline__ void pin(uint32_t& x) { asm volatile("" : "+r"(x)); }
template <typename T> __device__ __forceinline__ void pin(T*& x) { asm volatile("" : "+l"(x)); }
__device__ __forceinline__ float4 ldsf4(uint32_t a) { const uint4 v = lds128(a); return make_float4(__uint_as_float(v.x), __uint_as_float(v.y), __uint_as_float(v.z), __uint_as_float(v.w)); }
__device__ __forceinline__ float sum4(const float4& f) { return (f.x + f.y) + (f.z + f.w); }
__device__ __forceinline__ void stsf(uint32_t a, float v) { sts32(a, __float_as_uint(v)); }

__device__ __forceinline__ void wg_fence() { asm volatile("wgmma.fence.sync.aligned;" ::: "memory"); }
__device__ __forceinline__ void wg_commit() { asm volatile("wgmma.commit_group.sync.aligned;" ::: "memory"); }
__device__ __forceinline__ void wg_wait1() { asm volatile("wgmma.wait_group.sync.aligned 1;" ::: "memory"); }
__device__ __forceinline__ void wg_wait0() { asm volatile("wgmma.wait_group.sync.aligned 0;" ::: "memory"); }
#define R8(o) "+f"(d[o]), "+f"(d[o + 1]), "+f"(d[o + 2]), "+f"(d[o + 3]), "+f"(d[o + 4]), "+f"(d[o + 5]), "+f"(d[o + 6]), "+f"(d[o + 7])
__device__ __forceinline__ void wgmma_rs_n32(float (&d)[16], const uint4& a, uint64_t db, int acc) {
    asm volatile("{\n.reg .pred p;\nsetp.ne.b32 p, %21, 0;\n"
        "wgmma.mma_async.sync.aligned.m64n32k16.f32.bf16.bf16 "
        "{%0,%1,%2,%3,%4,%5,%6,%7,%8,%9,%10,%11,%12,%13,%14,%15}, {%16,%17,%18,%19}, %20, p, 1, 1, 0;\n}"
        : R8(0), R8(8) : "r"(a.x), "r"(a.y), "r"(a.z), "r"(a.w), "l"(db), "r"(acc));
}
#define PV_LO "{%0,%1,%2,%3,%4,%5,%6,%7,%8,%9,%10,%11,%12,%13,%14,%15,%16,%17,%18,%19,%20,%21,%22,%23,%24,%25,%26,%27,%28,%29,%30,%31,%32,%33,%34,%35,%36,%37,%38,%39,%40,%41,%42,%43,%44,%45,%46,%47,%48,%49,%50,%51,%52,%53,%54,%55,%56,%57,%58,%59,%60,%61,%62,%63}, "
#define PV_HI "{%64,%65,%66,%67,%68,%69,%70,%71,%72,%73,%74,%75,%76,%77,%78,%79,%80,%81,%82,%83,%84,%85,%86,%87,%88,%89,%90,%91,%92,%93,%94,%95,%96,%97,%98,%99,%100,%101,%102,%103,%104,%105,%106,%107,%108,%109,%110,%111,%112,%113,%114,%115,%116,%117,%118,%119,%120,%121,%122,%123,%124,%125,%126,%127}, "
__device__ __forceinline__ void wgmma_pv(float (&d)[128], const uint4& a, uint32_t blo, int acc) {
    asm volatile("{\n.reg .pred p;\n.reg .b32 u0, u1, u2, u3, t;\n.reg .b64 d0, d1, d2, d3;\nsetp.ne.b32 p, %133, 0;\n"
        "mov.b64 d0, {%132, 0x40000100};\nadd.u32 t, %132, 512;\nmov.b64 d1, {t, 0x40000100};\n"
        "add.u32 t, %132, 128;\nmov.b64 d2, {t, 0x40000100};\nadd.u32 t, %132, 640;\nmov.b64 d3, {t, 0x40000100};\n"
        "wgmma.fence.sync.aligned;\n"
        "wgmma.mma_async.sync.aligned.m64n128k16.f32.bf16.bf16 " PV_LO "{%128, u0, %129, u1}, d0, p, 1, 1, 1;\n"
        "wgmma.mma_async.sync.aligned.m64n128k16.f32.bf16.bf16 " PV_LO "{%130, u2, %131, u3}, d1, 1, 1, 1, 1;\n"
        "wgmma.commit_group.sync.aligned;\n"
        "wgmma.mma_async.sync.aligned.m64n128k16.f32.bf16.bf16 " PV_HI "{%128, u0, %129, u1}, d2, p, 1, 1, 1;\n"
        "wgmma.mma_async.sync.aligned.m64n128k16.f32.bf16.bf16 " PV_HI "{%130, u2, %131, u3}, d3, 1, 1, 1, 1;\n"
        "wgmma.commit_group.sync.aligned;\n}"
        : R8(0), R8(8), R8(16), R8(24), R8(32), R8(40), R8(48), R8(56), R8(64), R8(72), R8(80), R8(88), R8(96), R8(104), R8(112), R8(120)
        : "r"(a.x), "r"(a.y), "r"(a.z), "r"(a.w), "r"(blo), "r"(acc) : "memory");
}

template <int NW>
__device__ __forceinline__ void ln_stats(float s, float q, float sh, float* scr, int w, int lane, int bar, float& mean_b, float& sd_b) {
#pragma unroll
    for (int o = 16; o; o >>= 1) { s += shx(s, o); q += shx(q, o); }
    constexpr float n = 512.f / NW;
    if (lane == 0) { scr[w] = sh + s * (1.f / n); scr[NW + w] = q - s * s * (1.f / n); }
    bar_sync(bar, NW * 32);
    float mu = 0.f, m2 = 0.f;
#pragma unroll
    for (int i = 0; i < NW; i++) { mu += scr[i]; m2 += scr[NW + i]; }
    mu *= 1.f / NW;
#pragma unroll
    for (int i = 0; i < NW; i++) { const float d = scr[i] - mu; m2 = fmaf(n * d, d, m2); }
    mean_b = rbf(mu);
    sd_b = rbf(sqrtf(rbf(rbf(fmaxf(m2, 0.f) * (1.f / 512.f)) + 1e-5f)));
}
__device__ __forceinline__ float ln_mod(float x, float mean_b, float sd_b, float c, float s) {
    return rbf(rbf(__fdividef(rbf(x - mean_b), sd_b)) * rbf(1.f + c)) + s;
}

__global__ void __cluster_dims__(2, 1, 1) __launch_bounds__(NTHREADS, 1)
fused_kernel(const __grid_constant__ First F, __nv_bfloat16* __restrict__ out, uint32_t* __restrict__ gs, const __grid_constant__ Maps M) {
    extern __shared__ __align__(1024) uint8_t sm[];
    const uint32_t sb = s2u(sm);
    const int tid = threadIdx.x, lane = tid & 31;
    const int j = blockIdx.x, rk = j & 1;
    const int g = lane >> 2, t = lane & 3;
    const int r8 = lane & 7, lb3 = (lane >> 3) & 1, lb4 = lane >> 4;
    uint64_t pol;
    asm("createpolicy.fractional.L2::evict_first.b64 %0, 1.0;" : "=l"(pol));
    {
        auto cpa = [&](uint32_t d, const uint8_t* s) {
            asm volatile("cp.async.cg.shared.global.L2::cache_hint.L2::128B [%0], [%1], 16, %2;" :: "r"(d), "l"(s), "l"(pol) : "memory");
        };
        const uint32_t ut = threadIdx.x, uj = blockIdx.x;
        const uint8_t* w = F.w[ut >= 128];
        if (ut < 128) {
            const uint32_t dq = (sb + ut * 16) ^ ((ut * 2) & 0x70);
            const uint8_t* sq = w + (uint32_t)(((uj & 1) * 256 + (ut >> 3)) * 8192 + (uj >> 1) * 128 + (ut & 7) * 16);
#pragma unroll
            for (int i = 0; i < 4 * NCP; i++) cpa(dq + 4 * 32768 + i * 2048, sq + i * 131072);
        } else if (ut < 384) {
            const uint32_t dm = (sb + ut * 16) ^ ((ut * 2) & 0x10);
            const uint8_t* sa = w + (uint32_t)(((uj >> 5) * 128 + (ut >> 1) - 64) * 6144 + (uj & 31) * 32 + (ut & 1) * 16);
            cpa(dm + SM_XA - 2048, sa); cpa(dm + SM_XA + 2048, sa + 1024);
        }
        else if (ut == 480 && uj < 64) asm volatile("prefetch.global.L2 [%0];" :: "l"(F.v[(uj >> 3) & 1] + (uj & 7) * 64));
    }
    const int warp = __shfl_sync(0xffffffffu, tid >> 5, 0);
    const __nv_bfloat16* const xin = F.v[0];
    uint32_t* const pl = gs + (warp < 2 ? (B_PR + (j >> 5)) * 4096 + (j & 31) * 32 : G_E1 + j * 8192) + (warp & 1) * 1024 + lane;
    if (warp < 4) st_x1(pl, 1u);
    auto BAR = [&](int i) -> uint32_t { return sb + SM_BAR + i * 8; };
    const uint32_t a16 = (r8 + 8 * lb4) * 32 + ((lb3 ^ (r8 >> 2)) * 16);
    const uint32_t a128 = (r8 + 8 * lb4) * 128 + ((((warp & 3) * 2 + lb3) ^ r8) * 16);
    auto ldcls = [&]() -> uint32_t { return *(const volatile uint32_t*)(sm + SM_CLS); };
    auto clear_head = [&]() {
        st2_x1(gs + (B_HA + ((j >> 4) & 1) * 2 + lb4) * 4096 + (j >> 5) * 256 + (j & 15) * 16 + (lane & 15), 0u);
        st2_x4(gs + (B_QA + rk * 8 + ((j >> 1) & 1) * 4 + (j >> 5)) * 4096 + g * 128 + ((j >> 2) & 7) * 16 + t * 4, 0u, 0u, 0u, 0u);
        if (lane < 8) st2_x1(gs + B_RD * 4096 + j * 8 + lane, 0u);
    };
    auto tma = [&](uint32_t dst, const CUtensorMap* mp, uint32_t bar, int c0, int c1, int c2, int c3) {
        asm volatile("{\n.reg .pred p;\nelect.sync _|p, 0xffffffff;\n"
                     "@p cp.async.bulk.tensor.4d.shared::cluster.global.mbarrier::complete_tx::bytes.L2::cache_hint [%0], [%1, {%3, %4, %5, %6}], [%2], %7;\n}"
                     :: "r"(dst), "l"(mp), "r"(bar), "r"(c0), "r"(c1), "r"(c2), "r"(c3), "l"(pol) : "memory");
    };
    if (warp <= 12 || warp == 15) {
        const int grp = warp == 12 ? 0 : warp == 15 ? 13 : warp + 1;
        const uint32_t cnt = grp < 10 ? 1 : grp < 13 ? 4 : 8;
        if (lane == 0) {
#pragma unroll
            for (int i = 0; i < 8; i++) mbar_init(BAR(grp * 8 + i), (i < 2 && grp == 0) ? (i ? 128 : 256) : cnt);
        }
        __syncwarp();
        if (grp < 10 && lane < 8 && (grp || lane > NCP)) mbar_expect(BAR(grp * 8 + lane), grp >= 8 ? 4096 : (uint32_t)(grp * 8 + lane - IT_X) < 4 ? 16384 : 8192);
        asm volatile("fence.mbarrier_init.release.cluster;" ::: "memory");
        __syncwarp();
        if (warp == 12) {
#pragma unroll
            for (int i = NCP + 1; i < W0; i++) tma(sb + (15 + i) * 8192, &M.m[MP_WQ], BAR(i), 0, rk * 256 + (i - 1) * 64, j >> 1, 0);
        }
    } else if (warp == 13) {
        if (lane < NMAPS) asm volatile("prefetch.tensormap [%0];" :: "l"(&M.m[lane]) : "memory");
    } else if (warp == 14) {
        clear_head();
    }
    __syncthreads();
    uint32_t in1 = 0, in2 = 0;
    if (warp < 4) { in1 = *(const uint32_t*)(xin + 2 * tid); in2 = *(const uint32_t*)(xin + 256 + 2 * tid); }
    else if (warp < 12) in1 = *(const uint32_t*)(F.v[1] + 2 * (tid - 128));
    if (warp < 12) asm volatile("cp.async.mbarrier.arrive.noinc.shared::cta.b64 [%0];" :: "r"(BAR(warp < 4)) : "memory");
    asm volatile("barrier.cluster.arrive.relaxed.aligned;" ::: "memory");

    if (warp >= 12) {
    asm volatile("setmaxnreg.dec.sync.aligned.u32 64;");
    if (warp == 12) {
        static_assert(W0 > NCP && W0 <= 5 && NCP >= 1 && NCP <= 4, "W0");
        const uint2* sched = M.sched[j < NFF ? 0 : j < J_RED ? 1 : 2];
        uint2 en = sched[W0];
        const uint32_t t0 = gtime();
        const uint32_t sp = __reduce_or_sync(0xffffffffu, sb);
        const int cx = (j >> 1) * 64 + (j < NFF ? 0 : 1024 - NFF * 32);
#pragma unroll 1
        for (int i = W0; en.x; i++) {
            uint32_t e = en.x, st = (en.y >> 20) * 64;
            const uint32_t tn = t0 + (int16_t)en.y, mp = (en.y >> 16) & 15;
            if (mp == MP_WUV || mp == MP_WUK) { st ^= (j >> 5) * (mp == MP_WUV ? 128 : 64); e ^= (j >> 5) << 6; }
            if (mp == MP_GATE || mp == MP_UP) st ^= (j & 16) * 8;
            if (mp == MP_DOWN) { st ^= (j & 3) * 64; e ^= (j & 3) << 6; }
            en = sched[i + 1];
            if (mp == MP_MODB && j >= J_END) break;
            uint32_t c0 = mp == MP_WO ? (j & 7) * 64 : mp > MP_WO ? cx : 0;
            uint32_t c1 = mp == MP_CKV ? 0 : mp == MP_DOWN ? j * 32 : st + (mp == MP_WUV ? (j & 3) * 32 : mp == MP_WO ? (j >> 3) * 256 : rk * 256);
            uint32_t c2 = mp < MP_CKV ? j >> 1 : mp == MP_CKV ? rk * 4 : mp == MP_WUV ? (j >> 2) * 2 : mp == MP_DOWN ? st >> 5 : 0;
            uint32_t c3 = mp == MP_CKV ? st * 2 + (j & ~1) : 0;
            uint32_t dst = sp + ((e << 7) & 0x3e000), bar = sp + SM_BAR + (e & 63) * 8;
            const uint32_t w0 = (e >> 8) & 0x3f8, w1 = (e >> 15) & 0x3f8, w2 = (e >> 22) & 0x3f8, bb = sp + SM_BAR - 8;
            const CUtensorMap* pm = &M.m[mp];
            pin(dst); pin(bar); pin(c0); pin(c1); pin(c2); pin(c3); pin(pm);
            if (w0) mbar_wait(bb + w0, 0);
            if (w2) {
                mbar_wait(bb + w2, 0);
                while (!__any_sync(0xffffffffu, mbar_test(bb + w1, 0) | ((int)(gtime() - tn) > 0))) {}
            } else if (w1) mbar_wait(bb + w1, 0);
            tma(dst, pm, bar, c0, c1, c2, c3);
        }
    } else if (warp == 13) {
#pragma unroll
        for (int i = 0; i < 2; i++) st_x4(gs + (B_ML + rk * 16 + i * 8 + g) * 4096 + (t >> 1) * 1024 + (j >> 1) * 8 + (t & 1) * 4, 0u, 0u, 0u, 0u);
        if (lane < 16) st2_x4(gs + (B_E2 + (j >> 4)) * 4096 + (j & 15) * 64 + lane * 4, 0u, 0u, 0u, 0u);
        st2_x1(gs + (B_E3 + (j >> 5)) * 4096 + (j & 31) * 32 + lane, 0u);
        if (lane < 8) st2_x1(gs + B_MB * 4096 + j * 8 + lane, 0u);
        if (j < NFF) {
#pragma unroll
            for (int i = 0; i < 2; i++) st2_x4(gs + (B_E5 + i * 8 + g) * 4096 + j * 16 + t * 4, 0u, 0u, 0u, 0u);
        }
        bar_sync(9, 64);
        const uint32_t cs = ldcls();
#pragma unroll 1
        for (int i = 0; i < 32; i++) {
            st_x4(gs + G_E1 + j * 8192 + (i >> 3) * 2048 + ((((cs >> 1) ^ (i >> 3)) & 1) << 10) + (i & 7) * 128 + lane * 4, 0u, 0u, 0u, 0u);
            __nanosleep(JAN_SLEEP);
        }
        fence_gpu();
        if (lane < 8) st2_x1(gs + B_RD * 4096 + j * 8 + lane, 1u + (cs >> 1));
        if (lane == 0) TRACE(41);
        uint32_t rd[4];
        mbar_wait(BAR(IT_CKV + RD_ITEM), 0);
        poll<1024, RD_SLEEP>(rd, gs + near_off(B_RD, cs) + lane * 8);
#pragma unroll
        for (int i = 0; i < 4; i++) {
            const uint32_t m = __ballot_sync(0xffffffffu, rd[i] == 2u);
            if (lane == 0) sts32(sb + SM_CLS + 16 + i * 4, m);
        }
        __syncwarp();
        if (lane < 8) mbar_arrive(BAR(JD));
        if (lane == 0) TRACE(42);
    } else if (warp == 14) {
        uint2 ml[2];
        mbar_waitb(BAR(JD), 0);
        const uint32_t cls = ldcls();
        mbar_waitb(BAR(PF0 + 2 * NUNITS - 1), 0);
        __nanosleep(ML_DELAY);
        const uint32_t* pl2 = gs + near_off(B_ML + (j >> 2), cls) + lane * 8;
        const uint32_t wa = sb + SM_W + lb4 * 64 + t * 16 + (g & 3) * 4;
        poll_start<1024>(ml, pl2);
        uint32_t w0 = 0, w1 = 0, redo = 0;
        bool first = true;
#pragma unroll 1
        for (uint32_t it = 0;; it++) {
            const bool p0 = minw(ml[0]) != 0, p1 = minw(ml[1]) != 0;
            const int n = __popc(__ballot_sync(0xffffffffu, p0)) + __popc(__ballot_sync(0xffffffffu, p1));
            const uint32_t x0 = ml[0].x, x1 = ml[1].x;
            if (n < 64) {
                if (!p0) ld_x(ml[0], pl2);
                if (!p1) ld_x(ml[1], pl2 + 256);
            }
            if (n == 64 || (first && n >= E1_EARLY)) {
                auto ord = [](int x) { return x ^ ((x >> 31) & 0x7fffffff); };
                const int o0 = ord(x0), o1 = ord(x1);
                const float mm = __int_as_float(ord(__reduce_max_sync(0xffffffffu, max(p0 ? o0 : INT_MIN, p1 ? o1 : INT_MIN))));
                const float lo = __int_as_float(ord(__reduce_min_sync(0xffffffffu, min(p0 ? o0 : INT_MAX, p1 ? o1 : INT_MAX))));
                const uint32_t v0 = pack2(ex2((p0 ? __uint_as_float(x0) : lo) - mm), 0.f), v1 = pack2(ex2((p1 ? __uint_as_float(x1) : lo) - mm), 0.f);
                redo = !first && __any_sync(0xffffffffu, v0 != w0 || v1 != w1);
                w0 = v0; w1 = v1;
                sts32(wa - redo * (SM_W - SM_W2), w0 * 0x10001u); sts32(wa - redo * (SM_W - SM_W2) + 128, w1 * 0x10001u);
                if (first) bar_arrive(3, 416);
                first = false;
                if (n == 64) break;
            }
            if (it > SPIN_LIMIT) __trap();
        }
        if (lane == 0) TRACE_Q(37);
        float L = bflo(w0) * __uint_as_float(ml[0].y) + bflo(w1) * __uint_as_float(ml[1].y);
#pragma unroll
        for (int o = 16; o; o >>= 1) L += shx(L, o);
        if (lane == 0) *(float2*)(sm + SM_FQ) = make_float2(__frcp_rn(L), __uint_as_float(redo));
        __syncwarp();
        if (lane < 8) mbar_arrive(BAR(WR));
        if (lane == 0) TRACE(10);
        bar_sync(4, 416);
        clear_head();
        if (j < NFF) {
            uint32_t ya = sb + SM_Y + lane * 16, sa = peer_addr(sb + SM_RED + 2048 + rk * 8, lane & 1), tb = peer_addr(BAR(MBB), lane & 1);
            pin(ya); pin(sa); pin(tb);
            bar_sync(7, 288);
            const float4 y0 = ldsf4(ya), y1 = ldsf4(ya + 512);
            float s = sum4(y0) + sum4(y1);
            float q = (fmaf(y0.x, y0.x, y0.y * y0.y) + fmaf(y0.z, y0.z, y0.w * y0.w)) + (fmaf(y1.x, y1.x, y1.y * y1.y) + fmaf(y1.z, y1.z, y1.w * y1.w));
#pragma unroll
            for (int o = 16; o; o >>= 1) { s += shx(s, o); q += shx(q, o); }
            if (lane < 2) st_async2(sa, s, q, tb);
        }
    } else if (warp == 15) {
        mbar_waitb(BAR(IT_X - 1), 0);
        if (j < J_END) mbar_waitb(BAR(j < NFF ? NITEMS - 1 : MBB), 0);
    }
    } else if (warp < 4) {
        float* scr = (float*)(sm + SM_SCR);
        uint32_t cls;
        {
            uint2 ha[8];
            uint32_t best = 0xffffffffu;
            sts32(sb + SM_SCR + 64 + warp * 4, best);
            const float sh = __shfl_sync(0xffffffffu, bflo(in1), 0);
            const float v0 = bflo(in1) - sh, v1 = bfhi(in1) - sh, v2 = bflo(in2) - sh, v3 = bfhi(in2) - sh;
            float mb, sd;
            ln_stats<4>((v0 + v1) + (v2 + v3), (v0 * v0 + v1 * v1) + (v2 * v2 + v3 * v3), sh, scr, warp, lane, 2, mb, sd);
            if (!rk) in2 = in1;
#pragma unroll 1
            for (int i = 0; i < NPROBE; i++) {
                uint32_t t0, t1, o;
                asm volatile("mov.u32 %0, %%clock;" : "=r"(t0));
                asm volatile("atom.relaxed.gpu.global.exch.b32 %0, [%1], %2;" : "=r"(o) : "l"(pl), "r"(2u + i) : "memory");
                asm volatile("{\n.reg .pred p;\nsetp.ne.u32 p, %1, 0x1234567;\nmov.u32 %0, 0;\n@p mov.u32 %0, %%clock;\n}" : "=r"(t1) : "r"(o));
                best = min(best, t1 - t0);
                sts32(sb + SM_SCR + 64 + warp * 4, best);
                if (__all_sync(0xffffffffu, min(best, lds32(sb + SM_SCR + 64 + (warp ^ 1) * 4)) < NEAR_CLK)) break;
            }
            bar_sync(2, 128);
            const uint4 lt = *(const uint4*)(scr + 16);
            cls = NUMA ? ((lt.y < lt.x) ^ (__popc((B_PR + (j >> 5)) & 0x2C) & 1)) | (lt.w < lt.z) << 1 : 0;
            if (warp == 0) { if (lane == 0) sts32(sb + SM_CLS, cls); bar_arrive(9, 64); }
            if (tid == 0) TRACE(38);
            asm volatile("barrier.cluster.wait.aligned;" ::: "memory");
            mbar_wait(BAR(IT_MODA), 0);
            if (HA_DELAY) __nanosleep(HA_DELAY);
            poll<1024, H_SLEEP, false, 16384>(ha, gs + near_off(B_HA + rk * 2, cls) + 2 * tid);
            auto rsum = [](uint32_t a, uint32_t b, uint32_t c, uint32_t d) { return rbf((__uint_as_float(a) + __uint_as_float(b)) + (__uint_as_float(c) + __uint_as_float(d))); };
            sts32(sb + SM_FV + frag_off(2 * tid),
                  pack2(ln_mod(bflo(in2), mb, sd, rsum(ha[4].x, ha[5].x, ha[6].x, ha[7].x), rsum(ha[0].x, ha[1].x, ha[2].x, ha[3].x)),
                        ln_mod(bfhi(in2), mb, sd, rsum(ha[4].y, ha[5].y, ha[6].y, ha[7].y), rsum(ha[0].y, ha[1].y, ha[2].y, ha[3].y))));
            bar_arrive(5, 384);
            mbar_wait(BAR(QB), 0);
            if (tid < 64) {
                const float* qx = (const float*)(sm + SM_QX) + tid;
                sts16(sb + SM_FQ + frag_off(tid), pack2((qx[0] + qx[64]) + (qx[128] + qx[192]), 0.f));
            }
            bar_arrive(6, 384);
        }
        asm volatile("setmaxnreg.inc.sync.aligned.u32 192;");
        float acc[128];
        float M = 0.f;
        uint32_t pa = sb + SM_XA + warp * 512 + lane * 16, ma = sb + SM_MX + (warp * 8 + g) * 4, pf = BAR(PF0);
        uint32_t blo = __reduce_or_sync(0xffffffffu, (((sb + SM_U) & 0x3FFFFu) >> 4) | 0x400000u);
        uint32_t* e1[4];
#pragma unroll
        for (int i = 0; i < 4; i++) e1[i] = gs + G_E1 + (warp * 8 + g) * 4 * 8192 + (rk * 2 + (j >> 6)) * 2048 + ((j >> 1) & 31) * 32 + t * 4;
#pragma unroll 1
        for (int h = 0; h < 2 * NUNITS; h++) {
            mbar_wait(pf, 0);
            const float m = __uint_as_float(lds32(ma));
            const uint4 pn = lds128(pa);
            wg_wait0();
#pragma unroll
            for (int i = 0; i < 128; i++) asm volatile("" : "+f"(acc[i]) :: "memory");
            if (h == 0) M = m;
            uint32_t b2 = 0x3f803f80u;
            if (__builtin_expect(__any_sync(0xffffffffu, m != M), 0)) {
                const float Mn = fmaxf(M, m), alpha = ex2(M - Mn), beta = ex2(m - Mn);
                M = Mn;
                b2 = pack2(beta, beta);
#pragma unroll
                for (int jj = 0; jj < 32; jj++) { acc[4 * jj] *= alpha; acc[4 * jj + 1] *= alpha; }
            }
            auto mul2 = [](uint32_t x, uint32_t y) { uint32_t r; asm("mul.rn.bf16x2 %0, %1, %2;" : "=r"(r) : "r"(x), "r"(y)); return r; };
            const uint4 p = make_uint4(mul2(pn.x, b2), mul2(pn.y, b2), mul2(pn.z, b2), mul2(pn.w, b2));
            if (tid == 0 && (h & 1)) TRACE_Q(48 + (h >> 1));
            wgmma_pv(acc, p, blo, h);
            if (lane == 0 && h > 0 && !(h & 1)) mbar_arrive(BAR(EB_UNIT0 + (h >> 1) - 1));
            blo += h == 11 ? -11 * 1024 : 1024;
            pa += (h == 5 || h == 11) ? -5 * 2048 : 2048;
            ma += 128; pf += 8;
            if (h == 2 * NUNITS - 3) {
                mbar_wait(BAR(JD), 0);
                const uint32_t hm = (*(const uint32_t*)(sm + SM_CLS + 16 + warp * 4) >> (g * 4)) ^ ((j >> 6) ? 15u : 0u);
#pragma unroll
                for (int i = 0; i < 4; i++) e1[i] += ((hm >> i) & 1) << 10;
            }
        }
#pragma unroll
        for (int vv = 0; vv < 2; vv++) {
            if (vv && M == 1.f) __trap();
            if (vv) wg_wait0(); else wg_wait1();
#pragma unroll
            for (int i = 0; i < 64; i++) asm volatile("" : "+f"(acc[vv * 64 + i]) :: "memory");
            if (tid == 0 && !vv) TRACE_Q(63);
#pragma unroll
            for (int i = 0; i < 4; i++) {
                const float* a = &acc[vv * 64 + i * 16];
                st_x4(e1[i] + i * 8192 + vv * 16, enc(pack2(a[0], a[1])), enc(pack2(a[4], a[5])), enc(pack2(a[8], a[9])), enc(pack2(a[12], a[13])));
            }
        }
        bar_arrive(3, 416);
        if (tid == 0) TRACE_Q(17);
#pragma unroll 1
        for (int pass = 0;; pass++) {
            if (j >= NFF && j < J_END && pass == (j >= J_RED)) {
                uint4 a[8], b[4];
                float c[4], e[4];
                const bool own = (warp >> 1) == rk;
                const uint32_t xa = sb + SM_FV + (warp & 1) * 64 + g * 8;
                if (lane == 0) mbar_expect(BAR(MBB), own ? 64 : 0);
#pragma unroll
                for (int i = 0; i < 2; i++) {
                    ldfrag(b, sb + SM_FS + rk * 512 + i * 256 + t * 16);
                    mbar_wait(BAR(IT_X + i), 0);
                    const uint32_t ab = sb + SM_U + B_X * 32768 + i * 16384 + a128;
                    load8<true>(a, [&](int s) { return ab + s * 2048; });
                    mma8(i ? e : c, a, b);
                }
                c[0] += e[0]; c[2] += e[2];
                if (!own) {
                    if (t == 0) st_async2(peer_addr(xa, rk ^ 1), c[0], c[2], peer_addr(BAR(MBB), rk ^ 1));
                } else {
                    mbar_wait(BAR(MBB), 0);
                    const float2 pp = *(const float2*)(sm + (xa - sb));
                    const float mine = t ? c[2] + pp.y : c[0] + pp.x, other = shx(mine, 4);
                    const uint32_t w = (warp & 1) * 8 + t * 4 + (g >> 1), val = enc(pack2(mine, other));
                    if (t < 2 && !(g & 1)) {
                        if (j < J_RED) st2_x1(gs + B_MB * 4096 + (j - NFF) * 16 + w, val);
                        else sts32(sb + SM_FV + 256 + w * 4, val);
                    }
                    __syncwarp();
                    if (j >= J_RED && lane < 4) mbar_arrive(BAR(QB));
                    if (lane == 0) TRACE(11);
                }
            }
            if (pass) break;
            uint4 a[8], a2[8];
            const uint32_t ab = sb + SM_U + B_WO * 32768 + a128;
            uint32_t* p3 = gs + (B_E3 + ((j >> 1) & 3)) * 4096 + (t >> 1) * 1024 + (rk * 2 + (warp >> 1)) * 256 + (j >> 3) * 16 + (warp & 1) * 8 + (t & 1) * 4 + (g >> 1);
            const uint32_t* pb = gs + near_off(B_E2 + (j >> 4), cls) + (((j >> 3) & 1) * 2 + lb4) * 256 + (lane & 15) * 2;
            pin(p3); pin(pb);
            uint2 bb[8];
            uint2 bq[2] = {make_uint2(0u, 0u), make_uint2(0u, 0u)};
            uint32_t xa = sb + SM_XA + lane * 16;
            pin(xa);
            bool h0 = false, h1 = false;
            auto idle = [&]() {
                if (!h0) {
                    h0 = __all_sync(0xffffffffu, mbar_test(BAR(IT_WO + (t & 1)), 0));
                    if (h0) load8<true>(a, [&](int s) { return ab + s * 2048; });
                }
                if (!h1) {
                    h1 = __all_sync(0xffffffffu, mbar_test(BAR(IT_WO + 2 + (t & 1)), 0));
                    if (h1) load8<true>(a2, [&](int s) { return ab + 16384 + s * 2048; });
                }
            };
            bar_sync(4, 416);
            idle();
            poll<128, 0, true>(bq, pb + warp * 64, idle);
            asm volatile("st.shared.v4.u32 [%0], {%1, %2, %3, %4};" :: "r"(xa + warp * 512), "r"(bq[0].x), "r"(bq[0].y), "r"(bq[1].x), "r"(bq[1].y) : "memory");
            bar_sync(2, 128);
#pragma unroll
            for (int i = 0; i < 4; i++) { const uint4 q = lds128(xa + i * 512); bb[2 * i] = make_uint2(q.x, q.y); bb[2 * i + 1] = make_uint2(q.z, q.w); }
            if (tid == 0) TRACE(21);
            float e[4][4];
#pragma unroll
            for (int s = 0; s < 16; s++) {
                if (s == 0 && !h0) { mbar_wait(BAR(IT_WO), 0); mbar_wait(BAR(IT_WO + 1), 0); load8<true>(a, [&](int q) { return ab + q * 2048; }); }
                if (s == 0 && !h1) { mbar_wait(BAR(IT_WO + 2), 0); mbar_wait(BAR(IT_WO + 3), 0); load8<true>(a2, [&](int q) { return ab + 16384 + q * 2048; }); }
                const int z = (s & 1) | (s & 2) << 2 | (s >> 2) << 1;
                const uint4& x = z < 8 ? a[z] : a2[z & 7];
                float (&d)[4] = e[(z >> 3) * 2 + (z & 1)];
                if (!(z & 6)) d[0] = d[1] = d[2] = d[3] = 0.f;
                mma(d, x.x, x.y, x.z, x.w, bb[z & 7].x, bb[z & 7].y);
            }
            float lo, hi;
            quad_pair((t & 2) ? (e[2][0] + e[3][0]) + (e[2][1] + e[3][1]) : (e[0][0] + e[1][0]) + (e[0][1] + e[1][1]),
                      (t & 2) ? (e[2][2] + e[3][2]) + (e[2][3] + e[3][3]) : (e[0][2] + e[1][2]) + (e[0][3] + e[1][3]), t, lo, hi);
            if (!(g & 1)) st_x1(p3, enc(pack2(lo, hi)));
            if (j < NFF) bar_arrive(8, 384); else if (j >= J_RED && j < J_END) bar_arrive(8, 192);
            if (tid == 0) TRACE(22);
        }
        if (j < NFF) {
            uint4 a[16];
            const uint32_t ad = sb + SM_U + B_DN * 32768 + warp * 8192 + (r8 + 8 * lb4) * 128 + (lb3 ^ r8) * 16;
            uint32_t rl = sb + SM_RED + lane * 16;
            uint32_t* p5 = gs + (B_E5 + warp * 4 + (t >> 1)) * 4096 + j * 16 + (t & 1) * 8 + g;
            pin(rl); pin(p5);
            if (lane == 0) mbar_expect(BAR(MBB), 4);
            auto ldd = [&]() {
#pragma unroll
                for (int s = 0; s < 16; s++) a[s] = ldsm<true>((ad ^ ((s & 3) * 32)) + (s >> 2) * 2048);
            };
            const uint32_t db = BAR(IT_DOWN + (warp ^ (j & 3)));
            mbar_wait(BAR(MBB), 0);
            const float4 st = ldsf4(sb + SM_RED + 2048);
            const bool hd = __all_sync(0xffffffffu, mbar_test(db, 0));
            if (hd) ldd();
            const float mu = (st.x + st.z) * (1.f / 512.f);
            float rstd;
            asm volatile("rsqrt.approx.ftz.f32 %0, %1;" : "=f"(rstd) : "f"(fmaxf(fmaf(-mu, mu, (st.y + st.w) * (1.f / 512.f)), 0.f) + 1e-5f));
            mbar_wait(BAR(QB), 1);
            if (tid == 0) TRACE(25);
            const float4 f0 = ldsf4(rl), f2 = ldsf4(rl + 1024), f1 = ldsf4(rl + 512), f3 = ldsf4(rl + 1536);
            const float gg = fmaf(rstd, fmaf(-mu, f0.z + f2.z, (f0.x + f0.y) + (f2.x + f2.y)), f0.w + f2.w);
            const float uu = fmaf(rstd, fmaf(-mu, f1.z + f3.z, (f1.x + f1.y) + (f3.x + f3.y)), f1.w + f3.w);
            const float hh = __fdividef(gg * uu, 1.f + ex2(-gg * fmaf(gg * gg, 0.10294324f, 2.3022082f)));
            uint32_t hb[4];
#pragma unroll
            for (int i = 0; i < 4; i++) hb[i] = pack2(__shfl_sync(0xffffffffu, hh, 2 * t + 8 * i), __shfl_sync(0xffffffffu, hh, 2 * t + 8 * i + 1));
            auto down = [&]() {
#pragma unroll
                for (int i = 0; i < 2; i++) {
                    uint32_t res = 0;
#pragma unroll
                    for (int k = 0; k < 4; k++) {
                        float c[4] = {0.f, 0.f, 0.f, 0.f};
                        const uint4 &x = a[i * 8 + k], &y = a[i * 8 + k + 4];
                        mma(c, x.x, x.y, x.z, x.w, hb[0], hb[1]);
                        mma(c, y.x, y.y, y.z, y.w, hb[2], hb[3]);
                        if (t == k) res = pack2(c[0], c[2]);
                    }
                    st2_x1(p5 + i * 8192, enc(res));
                }
            };
            if (hd) down();
            else { mbar_wait(db, 0); ldd(); down(); asm volatile("// late" ::: "memory"); }
            if (tid == 0) { TRACE(27); TRACE_GT(47); }
        }
    } else {
        const int u8 = tid - 128, w8 = warp - 4;
        const int v = w8 >> 2, wq4 = w8 & 3;
        {
            const float c0 = bflo(in1), c1 = bfhi(in1);
            sts32(sb + SM_FS + frag_off(2 * u8), pack2(__fdividef(c0, 1.f + __expf(-c0)), __fdividef(c1, 1.f + __expf(-c1))));
        }
        bar_sync(1, 256);
        asm volatile("barrier.cluster.wait.aligned;" ::: "memory");
        uint4 a[8], b[4]; float c[4];
        if (w8 < 2) {
            ldfrag(b, sb + SM_FS + (j >> 5) * 256 + t * 16);
            mbar_wait(BAR(IT_MODA), 0);
            if (u8 == 0) TRACE(12);
            const uint32_t ab = sb + SM_XA + w8 * 4096 + a16;
            load8<true>(a, [&](int s) { return ab + s * 512; });
            mma8(c, a, b);
            if (t < 2) st2_x1(gs + (B_HA + ((j >> 4) & 1) * 2 + w8) * 4096 + (j >> 5) * 256 + (j & 15) * 16 + t * 8 + g, encf(t ? c[2] : c[0]));
        }
        {
            mbar_wait(BAR(IT_WQ + 2 * v <= NCP ? 1 : IT_WQ + 2 * v), 0); mbar_wait(BAR(IT_WQ + 2 * v + 1 <= NCP ? 1 : IT_WQ + 2 * v + 1), 0);
            const uint32_t ab = sb + SM_U + 4 * 32768 + v * 16384 + a128;
            load8<true>(a, [&](int s) { return ab + s * 2048; });
            if (lane == 0) mbar_arrive(BAR(EB_WQ));
            bar_sync(5, 384);
            if (u8 == 0) TRACE(13);
            ldfrag(b, sb + SM_FV + v * 256 + t * 16);
            mma8(c, a, b);
            if (t < 2) {
                const float qv = t ? c[2] : c[0];
                const uint32_t qa_ = sb + SM_QX + ((rk * 2 + v) * 64 + wq4 * 16 + t * 8 + g) * 4;
                asm volatile("st.async.weak.shared::cluster.mbarrier::complete_tx::bytes.f32 [%0], %1, [%2];"
                             :: "r"(peer_addr(qa_, rk ^ 1)), "f"(qv), "r"(peer_addr(BAR(QB), rk ^ 1)) : "memory");
                sts32(qa_, __float_as_uint(qv));
            }
            __syncwarp();
            if (lane == 0) mbar_expect(BAR(QB), 64);
        }
        {
            mbar_wait(BAR(IT_WUK + (v ^ ((j >> 5) & 1))), 0); mbar_wait(BAR(IT_WUK + (v ^ ((j >> 5) & 1)) + 2), 0);
            const uint32_t ab = sb + SM_U + 5 * 32768 + (w8 * 16 + r8 + 8 * lb3) * 128;
            const uint32_t x16 = (lb4 ^ r8) * 16;
            load8<false>(a, [&](int s) { return ab + (s & 1) * 16384 + (x16 ^ ((s >> 1) * 32)); });
            bar_sync(6, 384);
            if (u8 == 0) TRACE(14);
            b[0] = lds128(sb + SM_FQ + t * 16); b[1] = lds128(sb + SM_FQ + 64 + t * 16);
            float e[4] = {0.f, 0.f, 0.f, 0.f};
            c[0] = c[1] = c[2] = c[3] = 0.f;
#pragma unroll
            for (int k = 0; k < 4; k++) {
                const uint32_t b0 = (k & 1) ? b[k >> 1].z : b[k >> 1].x, b1 = (k & 1) ? b[k >> 1].w : b[k >> 1].y;
                mma(c, a[2 * k].x, a[2 * k].y, a[2 * k].z, a[2 * k].w, b0, b1);
                mma(e, a[2 * k + 1].x, a[2 * k + 1].y, a[2 * k + 1].z, a[2 * k + 1].w, b0, b1);
            }
            const float mine = ((t & 1) ? ((t & 2) ? e[2] : e[0]) : ((t & 2) ? c[2] : c[0])) * 0.12751743f;
            const float other = shx(mine, 4);
            if (!(g & 1)) st2_x1(gs + (B_QA + rk * 8 + ((j >> 1) & 1) * 4 + (j >> 5)) * 4096 + w8 * 128 + ((j >> 2) & 7) * 16 + (g >> 1) * 4 + t, enc(pack2(mine, other)));
            if (u8 == 0) TRACE(15);
        }
        const uint32_t cls = ldcls();
        __nanosleep(QA_DELAY);
        {
            uint4 qb[8];
            const uint32_t* pq = gs + near_off(B_QA + rk * 8 + wq4, cls) + lane * 4;
            const uint32_t* pq2 = gs + near_off(B_QA + rk * 8 + 4 + wq4, cls) + lane * 4;
            if (lane == 0) {
                mbar_expect(BAR(QT), 4096);
                asm volatile("cp.async.bulk.shared::cluster.global.mbarrier::complete_tx::bytes [%0], [%1], 4096, [%2];"
                             :: "r"(sb + SM_U + 5 * 32768 + w8 * 4096), "l"(gs + near_off(B_QA + rk * 8 + w8, cls)), "r"(BAR(QT)) : "memory");
            }
            const uint32_t qs = sb + SM_U + 5 * 32768 + wq4 * 4096 + lane * 16;
            mbar_wait(BAR(QT), 0);
#pragma unroll
            for (int i = 0; i < 8; i++) { a[i] = lds128(qs + i * 512); qb[i] = lds128(qs + 16384 + i * 512); }
            poll<512, QA_SLEEP, true>(a, pq);
            poll<512, QA_SLEEP, true>(qb, pq2);
            if (lane == 0) mbar_arrive(BAR(EB_WUK));
            auto add2 = [](uint32_t x, uint32_t y) { uint32_t r; asm("add.rn.bf16x2 %0, %1, %2;" : "=r"(r) : "r"(x), "r"(y)); return r; };
#pragma unroll
            for (int i = 0; i < 8; i++) a[i] = make_uint4(add2(a[i].x, qb[i].x), add2(a[i].y, qb[i].y), add2(a[i].z, qb[i].z), add2(a[i].w, qb[i].w));
        }
        if (u8 == 0) TRACE(8);
        {
            float m = -INFINITY, l = 0.f;
            uint32_t xl = sb + SM_XB + w8 * 2048 + lane * 16, xr = peer_addr(xl, rk ^ 1), bsr = peer_addr(BAR(SF0 + v), rk ^ 1);
            uint32_t pa = sb + SM_XA + v * 2048 + wq4 * 512 + lane * 16, ma = sb + SM_MX + v * 128 + (wq4 * 8 + g) * 4;
            uint32_t fb = BAR(IT_CKV + v * 2), sf = BAR(SF0 + v);
            uint32_t dlo = __reduce_or_sync(0xffffffffu, (((sb + SM_U + v * 16384) & 0x3FFFFu) >> 4) | 0x10000u);
            if (STAG && v) __nanosleep(STAG);
#pragma unroll 1
            for (int n = 0; n < NUNITS; n++) {
                float d[2][16], sc[8];
#pragma unroll
                for (int i = 0; i < 2; i++) {
                    mbar_wait(fb + i * 8, 0);
                    wg_fence();
#pragma unroll
                    for (int s = 0; s < 8; s++) wgmma_rs_n32(d[i], a[s], (0x40000080ull << 32) | (dlo + i * 512 + (s >> 2) * 64 + (s & 3) * 2), s);
                    wg_commit();
                }
#pragma unroll
                for (int i = 0; i < 2; i++) {
                    if (i) wg_wait0(); else wg_wait1();
#pragma unroll
                    for (int k = 0; k < 16; k++) asm volatile("" : "+f"(d[i][k]) :: "memory");
                    sc[4 * i] = d[i][0] + d[i][6]; sc[4 * i + 1] = d[i][1] + d[i][7]; sc[4 * i + 2] = d[i][8] + d[i][14]; sc[4 * i + 3] = d[i][9] + d[i][15];
                    asm volatile("st.async.weak.shared::cluster.mbarrier::complete_tx::bytes.v4.f32 [%0], {%1, %2, %3, %4}, [%5];"
                                 :: "r"(xr + i * 1024), "f"(sc[4 * i]), "f"(sc[4 * i + 1]), "f"(sc[4 * i + 2]), "f"(sc[4 * i + 3]), "r"(bsr) : "memory");
                }
                if (u8 == 128) TRACE_Q(56 + (n < 6 ? n : -40));
                if (n >= 3) mbar_wait(BAR(EB_UNIT0 + n - 3), 0);
                dlo += n == 5 ? -5 * 2048 : 2048;
                fb += 32; xr ^= 512; bsr += 16;
                pin(fb); pin(xr); pin(bsr);
                mbar_wait(sf, 0);
                const float4 x = ldsf4(xl), y = ldsf4(xl + 1024);
                sc[0] += x.x; sc[1] += x.y; sc[2] += x.z; sc[3] += x.w; sc[4] += y.x; sc[5] += y.y; sc[6] += y.z; sc[7] += y.w;
                float pr[8];
#pragma unroll
                for (int i = 0; i < 8; i++) pr[i] = ex2(sc[i] - m);
                float mx = fmaxf(fmaxf(fmaxf(sc[0], sc[1]), fmaxf(sc[2], sc[3])), fmaxf(fmaxf(sc[4], sc[5]), fmaxf(sc[6], sc[7])));
                if (__builtin_expect(__any_sync(0xffffffffu, mx > m), 0)) {
                    mx = fmaxf(mx, shx(mx, 1));
                    mx = fmaxf(mx, shx(mx, 2));
                    const float mn = fmaxf(m, ceilf(mx * 0.0625f) * 16.f);
                    l *= ex2(m - mn);
                    m = mn;
#pragma unroll
                    for (int i = 0; i < 8; i++) pr[i] = ex2(sc[i] - m);
                }
                stsf(ma, m);
                asm volatile("st.shared.v4.u32 [%0], {%1, %2, %3, %4};" :: "r"(pa), "r"(pack2(pr[0], pr[1])), "r"(pack2(pr[2], pr[3])),
                             "r"(pack2(pr[4], pr[5])), "r"(pack2(pr[6], pr[7])) : "memory");
                __syncwarp();
                if (lane == 0) mbar_arrive(sf + (PF0 - SF0) * 8);
                l += ((pr[0] + pr[1]) + (pr[2] + pr[3])) + ((pr[4] + pr[5]) + (pr[6] + pr[7]));
                xl ^= 512; sf += 16; ma += 256; pa += (n == 2 || n == 5) ? -8192 : 4096;
            }
            l += shx(l, 1);
            l += shx(l, 2);
            float2* mlx = (float2*)(sm + SM_MX + 2048) + wq4 * 8 + g;
            if (v == 0) { *mlx = make_float2(m, l); bar_arrive(11, 256); }
            else {
                mbar_wait(BAR(JD), 0);
                bar_sync(11, 256);
                const float2 o = *mlx;
                const float mn = fmaxf(m, o.x);
                l = l * ex2(m - mn) + o.y * ex2(o.x - mn);
                if ((wq4 >> 1) == rk) st_x4(gs + (B_ML + wq4 * 8 + g) * 4096 + (t >> 1) * 1024 + (j >> 1) * 8 + (t & 1) * 4, encf(mn), encf(l), 1u, 1u);
            }
        }
        const int pi = j < NFF ? rk * 128 + w8 * 16 + (lane >> 1) : ((j - J_RED) & 15) * 16 + (w8 & 1) * 8 + g;
        const uint32_t xw = *(const uint32_t*)(xin + 2 * pi);
        const uint32_t one = (g & 1) ? 0x3f800000u : 0x00003f80u;
        const uint32_t* pm = gs + near_off(B_MB, cls) + pi;
        {
            const uint32_t ab = sb + SM_U + B_WUV * 32768 + v * 4096 + a128;
            uint32_t pa = sb + SM_PB + wq4 * 320 + frag_off(64 * v + 32 * (g >> 2) + 16 * (t & 1) + 8 * (t >> 1) + 2 * (g & 3));
            uint32_t fa = sb + SM_PB + g * 320 + t * 16;
            const uint32_t* pe = gs + G_E1 + j * 8192 + (w8 >> 1) * 2048 + ((((cls >> 1) ^ (w8 >> 1)) & 1) << 10) + (((w8 & 1) * 16 + t) * 8 + g) * 4;
            uint32_t* p2 = gs + (B_E2 + (j >> 4)) * 4096 + (t >> 1) * 1024 + (j & 12) * 64 + w8 * 32 + (j & 3) * 8 + (g & 6) + (t & 1);
            pin(pa); pin(fa); pin(pe); pin(p2);
            const uint32_t mk = (g & 1) ? 0xffff0000u : 0x0000ffffu, m0 = (g & 2) ? 0u : mk, m1 = (g & 2) ? mk : 0u;
            uint4 pv[4];
            bool hv = false;
            bar_sync(3, 416);
            uint4 wa = lds128(sb + SM_W + (wq4 * 4 + t) * 16);
            uint32_t wb[8] = {wa.x & m0, wa.x & m1, wa.y & m0, wa.y & m1, wa.z & m0, wa.z & m1, wa.w & m0, wa.w & m1};
            pv[0] = pv[1] = pv[2] = pv[3] = make_uint4(0u, 0u, 0u, 0u);
            float e[4][4];
            auto wsum = [&]() {
#pragma unroll
                for (int i = 0; i < 4; i++) {
                    e[i][0] = e[i][1] = e[i][2] = e[i][3] = 0.f;
                    mma(e[i], pv[i].x, pv[i].y, pv[i].z, pv[i].w, wb[2 * i], wb[2 * i + 1]);
                }
            };
            poll<512, E1_SLEEP, true>(pv, pe, [&]() {
                if (!hv) {
                    hv = __all_sync(0xffffffffu, mbar_test(BAR(IT_WUV + t), 0));
                    if (hv) load8<true>(a, [&](int s) { return ab + (s >> 1) * 8192 + (s & 1) * 2048; });
                }
            }, wsum);
            if (lane == 0) TRACE_Q(48 + w8);
            if (u8 == 0) TRACE_Q(18);
            float lo, hi2;
            float2 inv;
#pragma unroll 1
            for (int pass = 0;; pass++) {
                const float r0 = (t & 2) ? (e[0][2] + e[1][2]) + (e[2][2] + e[3][2]) : (e[0][0] + e[1][0]) + (e[2][0] + e[3][0]);
                const float r1 = (t & 2) ? (e[0][3] + e[1][3]) + (e[2][3] + e[3][3]) : (e[0][1] + e[1][1]) + (e[2][1] + e[3][1]);
                const uint32_t hi = pack2(r0, r1);
                sts32(pa, hi); sts32(pa + 1280, pack2(r0 - bflo(hi), r1 - bfhi(hi)));
                if (!hv) {
#pragma unroll 1
                    for (int i = 0; i < 4; i++) mbar_wait(BAR(IT_WUV + i), 0);
                    load8<true>(a, [&](int s) { return ab + (s >> 1) * 8192 + (s & 1) * 2048; });
                    hv = true;
                }
                bar_sync(1, 256);
                if (u8 == 0) TRACE(19);
                ldfrag(b, fa);
                mma8(c, a, b);
                mbar_wait(BAR(WR), 0);
                asm volatile("ld.shared.v2.f32 {%0, %1}, [%2];" : "=f"(inv.x), "=f"(inv.y) : "r"(sb + SM_FQ) : "memory");
                quad_pair(c[0] + c[1], c[2] + c[3], t, lo, hi2);
                if (__builtin_expect(__all_sync(0xffffffffu, pass || __float_as_uint(inv.y) == 0), 1)) break;
                wa = lds128(sb + SM_W2 + (wq4 * 4 + t) * 16);
                wb[0] = wa.x & m0; wb[1] = wa.x & m1; wb[2] = wa.y & m0; wb[3] = wa.y & m1; wb[4] = wa.z & m0; wb[5] = wa.z & m1; wb[6] = wa.w & m0; wb[7] = wa.w & m1;
                wsum();
                bar_sync(1, 256);
            }
            if (!(g & 1)) st_x1(p2, enc(pack2(lo * inv.x, hi2 * inv.x)));
            bar_arrive(4, 416);
            if (u8 == 0) TRACE(20);
        }
        if (j < NFF) {
            const uint32_t* p3 = gs + near_off(B_E3 + rk * 2 + v, cls) + wq4 * 256 + t * 16 + g * 2;
            const int od = lane & 1;
            uint32_t za = sb + SM_FZ + od * 576 + frag_off(w8 * 32 + (lane & 30));
            uint32_t fa = sb + SM_FZ + (g & 3) * 576 + ((lane ^ j) & 16) * 16 + t * 16, ya = sb + SM_Y + u8 * 4;
            uint32_t mb[3];
            uint4 a2[8];
            poll<1024, MB_SLEEP>(mb, pm);
            const uint32_t kk = pack2(1.f + bflo(mb[2]), 1.f + bfhi(mb[2]));
            sts32(za + 2 * 576, od ? mb[1] : kk);
            uint2 e3[4] = {make_uint2(0u, 0u), make_uint2(0u, 0u), make_uint2(0u, 0u), make_uint2(0u, 0u)};
            uint32_t ra = peer_addr(sb + SM_RED + (rk * 2 + v) * 512 + ((wq4 & 1) * 16 + (t >> 1) * 8 + g) * 16 + (t & 1) * 8, wq4 >> 1), tbo = peer_addr(BAR(QB), wq4 >> 1);
            pin(za); pin(fa); pin(ya); pin(ra); pin(tbo);
            if (lane == 0) mbar_expect(BAR(QB), 256);
            const uint32_t gb = BAR(IT_X + v * 2), ab = sb + SM_U + (B_X + v) * 32768 + a128;
            bool early = false, early2 = false;
            auto ldw = [&]() {
                if (!early) {
                    early = __all_sync(0xffffffffu, mbar_test(gb, 0));
                    if (early) load8<true>(a, [&](int s) { return ab + s * 2048; });
                }
                if (!early2) {
                    early2 = __all_sync(0xffffffffu, mbar_test(gb + 8, 0));
                    if (early2) load8<true>(a2, [&](int s) { return ab + 16384 + s * 2048; });
                }
            };
            bar_sync(8, 384);
            float s0[4], s1[4];
            auto sum = [&]() {
                s0[0] = s0[1] = s0[2] = s0[3] = s1[0] = s1[1] = s1[2] = s1[3] = 0.f;
                mma(s0, e3[0].x, e3[0].y, e3[1].x, e3[1].y, one, one); mma(s1, e3[2].x, e3[2].y, e3[3].x, e3[3].y, one, one);
            };
            poll<256, 0, true>(e3, p3, ldw, sum);
            if (u8 == 0) TRACE(23);
            const float y0 = fmaf(bflo(mb[0]), (t & 2) ? s0[2] + s1[2] : s0[0] + s1[0], bflo(xw)), y1 = fmaf(bfhi(mb[0]), (t & 2) ? s0[3] + s1[3] : s0[1] + s1[1], bfhi(xw));
            stsf(ya, od ? y1 : y0);
            const float z0 = y0 * bflo(kk), z1 = y1 * bfhi(kk);
            const uint32_t zh = pack2(z0, z1);
            sts32(za, od ? pack2(z0 - bflo(zh), z1 - bfhi(zh)) : zh);
            bar_sync(7, 288);
            if (u8 == 0) TRACE(24);
            ldfrag(b, fa);
            if (!early) { mbar_wait(gb, 0); load8<true>(a, [&](int s) { return ab + s * 2048; }); }
            {
                float e[4][4];
#pragma unroll
                for (int s = 0; s < 16; s++) {
                    if (s == 8 && !early2) { mbar_wait(gb + 8, 0); load8<true>(a2, [&](int q) { return ab + 16384 + q * 2048; }); }
                    const uint4& x = s < 8 ? a[s] : a2[s & 7];
                    const uint4& y = b[(s >> 1) & 3];
                    float (&d)[4] = e[(s >> 3) * 2 + (s & 1)];
                    if (!(s & 6)) d[0] = d[1] = d[2] = d[3] = 0.f;
                    mma(d, x.x, x.y, x.z, x.w, (s & 1) ? y.z : y.x, (s & 1) ? y.w : y.y);
                }
                const bool hi = t >> 1;
                const float k0 = hi ? e[2][2] + e[3][2] : e[0][0] + e[1][0], k1 = hi ? e[2][3] + e[3][3] : e[0][1] + e[1][1];
                const float o0 = hi ? e[2][0] + e[3][0] : e[0][2] + e[1][2], o1 = hi ? e[2][1] + e[3][1] : e[0][3] + e[1][3];
                st_async2(ra, k0 + shx(o0, 2), k1 + shx(o1, 2), tbo);
            }
        } else if (j >= J_RED && j < J_END && w8 < 2) {
            uint32_t ga[1], e3[4];
            poll<0, MB_SLEEP>(ga, pm);
            bar_sync(8, 192);
            poll<64, 100>(e3, gs + near_off(B_E3 + (pi >> 6), cls) + (pi & 48) * 16 + t * 64 + (pi & 15));
            float y0 = (bflo(e3[0]) + bflo(e3[1])) + (bflo(e3[2]) + bflo(e3[3])), y1 = (bfhi(e3[0]) + bfhi(e3[1])) + (bfhi(e3[2]) + bfhi(e3[3]));
#pragma unroll
            for (int o = 1; o < 4; o <<= 1) { y0 += shx(y0, o); y1 += shx(y1, o); }
            const int col = g + (t & 1) * 8;
            y0 = __shfl_sync(0xffffffffu, (t & 1) ? fmaf(bfhi(ga[0]), y1, bfhi(xw)) : fmaf(bflo(ga[0]), y0, bflo(xw)), (col >> 1) * 4 + (col & 1));
            uint16_t* po = (uint16_t*)out + (j - J_RED) * 32 + w8 * 16 + col;
            const uint32_t* pe = gs + near_off(B_E5 + j - J_RED, cls) + t * 16 + w8 * 8 + g;
            pin(po);
            const uint32_t sel = (g & 2) ? 0x3f800000u : 0x00003f80u;
            uint32_t yv[NFF / 4 + 1];
            float e[4][4], gb = 0.f;
#pragma unroll
            for (int i = 0; i <= NFF / 4; i++) yv[i] = 0u;
#pragma unroll 1
            for (uint32_t it = 0;; it++) {
#pragma unroll
                for (int i = 0; i < NFF / 4; i++) if (!yv[i]) ld_x(yv[i], pe + i * 64);
                if (__all_sync(0xffffffffu, !yv[NFF / 4] && mbar_test(BAR(QB), 1))) {
                    yv[NFF / 4] = lds32(sb + SM_FV + 256 + w8 * 32 + (col >> 1) * 4);
                    gb = (col & 1) ? bfhi(yv[NFF / 4]) : bflo(yv[NFF / 4]);
                }
                if (it > SPIN_LIMIT) __trap();
#pragma unroll
                for (int i = 0; i < 4; i++) {
                    e[i][0] = e[i][1] = e[i][2] = e[i][3] = 0.f;
                    mma(e[i], yv[4 * i], yv[4 * i + 1], i < 3 ? yv[(4 * i + 2) % (NFF / 4)] : 0u, i < 3 ? yv[(4 * i + 3) % (NFF / 4)] : 0u, sel, sel);
                }
                if (__all_sync(0xffffffffu, mint<NFF / 4 + 1>(yv) != 0)) break;
            }
            if (u8 == 0) TRACE(26);
            const float s = ((e[0][0] + e[0][2]) + (e[1][0] + e[1][2])) + ((e[2][0] + e[2][2]) + (e[3][0] + e[3][2]));
            asm volatile("{\n.reg .pred p;\nsetp.lt.u32 p, %2, 2;\n@p st.global.u16 [%0], %1;\n}" :: "l"(po), "h"((uint16_t)pack2(fmaf(gb, s, y0), 0.f)), "r"(t) : "memory");
            asm volatile("{\n.reg .pred p;\nsetp.eq.f32 p, %0, 0f7F7FFFFF;\n@p nanosleep.u32 0;\n}" :: "f"(((e[0][1] + e[0][3]) + (e[1][1] + e[1][3])) + ((e[2][1] + e[2][3]) + (e[3][1] + e[3][3]))));
            if (u8 == 0) TRACE(27);
        }
    }
}

typedef CUresult (*EncFn)(CUtensorMap*, CUtensorMapDataType, cuuint32_t, void*, const cuuint64_t*, const cuuint64_t*,
                          const cuuint32_t*, const cuuint32_t*, CUtensorMapInterleave, CUtensorMapSwizzle,
                          CUtensorMapL2promotion, CUtensorMapFloatOOBfill);

void make_map(EncFn enc_fn, CUtensorMap* m, const void* p, cuuint64_t d0, cuuint64_t d1, cuuint64_t d2, cuuint64_t d3,
              cuuint64_t s1, cuuint64_t s2, cuuint64_t s3, cuuint32_t b0, cuuint32_t b1, cuuint32_t b2, cuuint32_t b3, CUtensorMapSwizzle sw) {
    const cuuint64_t dims[4] = {d0, d1, d2, d3}, strides[3] = {s1, s2, s3};
    const cuuint32_t box[4] = {b0, b1, b2, b3}, es[4] = {1, 1, 1, 1};
    enc_fn(m, CU_TENSOR_MAP_DATA_TYPE_BFLOAT16, 4, (void*)p, dims, strides, box, es,
           CU_TENSOR_MAP_INTERLEAVE_NONE, sw, CU_TENSOR_MAP_L2_PROMOTION_L2_128B, CU_TENSOR_MAP_FLOAT_OOB_FILL_NONE);
}

uint32_t* scratch = nullptr;

struct Tune { const char* win; const char* late; int tau, t_off; const char* tail[3][4]; };
Tune tune = {"77777777755555555555555555555555555555544",
             "00000000000000888888888888888888888888888", 321, -380,
             {{"VVVVOOOOguguDDDD", "zzzzzzzzzzzzzzzz", "7777aaaaaaaa6789", "96gl98s3d0fa700p"},
              {"VMVMVVOOOO", "zzzzzzzzzz", "9999999999", "8af0f0h4j9"},
              {"VVVVOOOOMM", "zzzzzzzzzz", "aaaaaaaa88", "b1113a9eo3"}}};
bool ready = false;

}

extern "C" void kernel_launch(void* const* d_in, const int* in_sizes, int n_in, void* d_out, int out_size) {
    (void)in_sizes; (void)n_in; (void)out_size;
    static Maps maps;
    static const void* cached[12] = {};
    bool same = ready;
    for (int i = 0; i < 12 && same; i++) same = cached[i] == d_in[i];
    if (!same) {
        void* fn = nullptr;
        cudaDriverEntryPointQueryResult qr;
        cudaGetDriverEntryPoint("cuTensorMapEncodeTiled", &fn, cudaEnableDefault, &qr);
        EncFn e = (EncFn)fn;
        const CUtensorMapSwizzle S128 = CU_TENSOR_MAP_SWIZZLE_128B;
        make_map(e, &maps.m[MP_WQ], d_in[2], 64, 512, 64, 1, 8192, 128, 8192, 64, 64, 1, 1, S128);
        make_map(e, &maps.m[MP_WUK], d_in[3], 64, 512, 64, 1, 8192, 128, 8192, 64, 64, 1, 1, S128);
        make_map(e, &maps.m[MP_CKV], d_in[1], 64, 8, 8, 4096, 1024, 128, 8192, 64, 8, 4, 2, S128);
        make_map(e, &maps.m[MP_MODB], d_in[11], 3072, 512, 1, 1, 6144, 6144, 6144, 64, 128, 1, 1, S128);
        make_map(e, &maps.m[MP_WUV], d_in[4], 64, 512, 64, 1, 8192, 128, 8192, 64, 32, 2, 1, S128);
        make_map(e, &maps.m[MP_WO], d_in[5], 512, 4096, 1, 1, 1024, 1024, 1024, 64, 64, 1, 1, S128);
        make_map(e, &maps.m[MP_GATE], d_in[7], 1792, 512, 1, 1, 3584, 3584, 3584, 64, 128, 1, 1, S128);
        make_map(e, &maps.m[MP_UP], d_in[8], 1792, 512, 1, 1, 3584, 3584, 3584, 64, 128, 1, 1, S128);
        make_map(e, &maps.m[MP_DOWN], d_in[9], 64, 1792, 8, 1, 1024, 128, 1024, 64, 32, 2, 1, S128);
        for (int r = 0; r < 3; r++) {
            int ids[58], cnt[128] = {}, tn = tune.t_off - (W0 - 1) * tune.tau;
            uint2* sc = maps.sched[r];
            auto dig = [](char ch) { return ch >= 'a' ? ch - 'a' + 10 : ch >= 'A' ? ch - 'A' + 36 : ch - '0'; };
            for (int i = 0; i < 58; i++) sc[i] = make_uint2(0u, 0u);
            for (int i = 0;; i++) {
                int id = i, buf, dep, w, wl;
                if (i < IT_WUV) {
                    const int u = (i - IT_CKV) >> 2;
                    buf = i < IT_CKV ? 4 + ((i - 1) >> 2) : u % 6;
                    dep = i < IT_CKV || u < 4 ? -1 : u < 6 ? EB_WQ + u - 4 : EB_UNIT0 + u - 6;
                    w = dig(tune.win[i]); wl = dig(tune.late[i]);
                    if (i) tn += tune.tau;
                } else {
                    const char ch = tune.tail[r][0][i - IT_WUV];
                    if (!ch) break;
                    buf = ch == 'V' ? B_WUV : ch == 'O' ? B_WO : ch == 'D' ? B_DN : ch == 'u' ? B_X + 1 : B_X;
                    id = (ch == 'V' ? IT_WUV : ch == 'O' ? IT_WO : ch == 'D' ? IT_DOWN : ch == 'u' ? IT_X + 2 : IT_X) + cnt[(int)ch]++;
                    dep = EB_UNIT0 + (buf < 2 ? buf + 6 : buf);
                    w = dig(tune.tail[r][1][i - IT_WUV]); wl = dig(tune.tail[r][2][i - IT_WUV]);
                    tn += (r == 2 ? 64 : 32) * dig(tune.tail[r][3][i - IT_WUV]);
                }
                if (id < IT_X || id >= IT_DOWN ? (id - 1) & 3 : (id - IT_X) & 1) dep = -1;
                ids[i] = id;
                auto back = [&](int d) { return i < d ? 0 : (ids[i - d] && ids[i - d] <= NCP ? 1 : ids[i - d]) + 1; };
                sc[i].x = id | (buf * 4 + (id < IT_X || id >= IT_DOWN ? (id - 1) & 3 : ((id - IT_X) & 1) * 2)) << 6 | (dep + 1) << 11 | (w > 32 ? NEVER + 1 : back(w)) << 18 | (wl ? back(wl) : 0) << 25;
                const int mp = id < IT_CKV ? MP_WQ + ((id - 1) >> 2) : id < IT_WUV ? MP_CKV : id < IT_WO ? MP_WUV : id < IT_X ? MP_WO
                             : id >= IT_DOWN ? MP_DOWN : r ? MP_MODB : MP_GATE + ((id - IT_X) >> 1);
                const int step = mp == MP_CKV ? id - IT_CKV : mp == MP_WUV ? (id - IT_WUV) * 2 : mp == MP_DOWN ? id - IT_DOWN : id < IT_X ? (id - 1) & 3 : ((id - IT_X) & 1) * 2;
                sc[i].y = (tn & 0xffff) | (mp & 15) << 16 | step << 20;
            }
        }
        cudaGetSymbolAddress((void**)&scratch, g_scratch);
        scratch = (uint32_t*)(((uintptr_t)scratch + (2u << 20) - 1) & ~(uintptr_t)((2u << 20) - 1));
        cudaFuncSetAttribute(fused_kernel, cudaFuncAttributeMaxDynamicSharedMemorySize, SM_TOTAL);
        for (int i = 0; i < 12; i++) cached[i] = d_in[i];
        ready = true;
    }
    const First f = {{(const uint8_t*)d_in[2], (const uint8_t*)d_in[11]}, {(const __nv_bfloat16*)d_in[0], (const __nv_bfloat16*)d_in[10]}};
    fused_kernel<<<NCTA, NTHREADS, SM_TOTAL>>>(f, (__nv_bfloat16*)d_out, scratch, maps);
}
```

```cpp
#include <cuda_runtime.h>
#include <cuda_bf16.h>
#include <cuda.h>
#include <stdint.h>
#include <limits.h>

namespace {

constexpr int NCTA = 128;
constexpr int NTHREADS = 512;
constexpr int NUNITS = 8;
constexpr int NFF = 56, J_RED = 104, J_END = 120;
constexpr uint32_t SPIN_LIMIT = 1u << 22;

#define NEAR_CLK 390
#define E1_EARLY 50
#define STAG 300
#define NUMA 1
#define NPROBE 5
#define NCP 2
#define W0 4
#define RD_ITEM 15
#define JAN_SLEEP 100
#define RD_SLEEP 400
#define HA_DELAY 200
#define H_SLEEP 100
#define QA_DELAY 600
#define QA_SLEEP 200
#define ML_DELAY 300
#define E1_SLEEP 50
#define MB_SLEEP 100
constexpr int B_WUV = 2, B_WO = 3, B_X = 4  , B_DN = 0;

constexpr int SM_U = 0;
constexpr int SM_XA = 6 * 32768;
constexpr int SM_XB = SM_XA + 12288;
constexpr int SM_MX = SM_XB + 16384;
constexpr int SM_FZ = SM_XB + 8192;
constexpr int SM_PB = SM_XB;
constexpr int SM_Y = SM_XB + 12288;
constexpr int SM_RED = SM_XB + 4096;
constexpr int SM_FS = SM_XB + 20480;
constexpr int SM_FV = SM_FS + 1024;
constexpr int SM_QX = SM_XA + 8192;
constexpr int SM_FQ = SM_FV + 512;
constexpr int SM_CLS = SM_FQ + 128;
constexpr int SM_W = SM_FQ + 256;
constexpr int SM_W2 = SM_MX + 2304;
constexpr int SM_SCR = SM_XA + 9216;
constexpr int SM_BAR = SM_W + 256;
constexpr int SM_TOTAL = SM_BAR + 1024;
static_assert(SM_TOTAL <= 232448, "smem");

enum { IT_MODA = 0, IT_WQ = 1, IT_WUK = 5, IT_CKV = 9, IT_WUV = 41, IT_WO = 45, IT_X = 49  , IT_DOWN = 53, NITEMS = 57,
       NEVER = 63,
       SF0 = 64,
       PF0 = 80,
       EB_UNIT0 = 96, MBB = 103,
       EB_WQ = 104, EB_WUK, QT, QB, JD, WR };

enum { MP_WQ = 0, MP_WUK, MP_CKV, MP_WUV, MP_DOWN, MP_WO, MP_GATE, MP_UP, MP_MODB, NMAPS };
struct First { const uint8_t* w[2]; const __nv_bfloat16* v[2]; };
struct Maps { CUtensorMap m[NMAPS]; uint2 sched[3][58]; };

enum { B_HA = 0,
       B_MB = 6,
       B_RD = 7,
       B_E2 = 8,
       B_QA = 16,
       B_ML = 32,
       B_E5 = 64,
       B_E3 = 80,
       B_PR = 96,
       B_TR = 100 };
constexpr int G_E1 = 1 << 19;
__device__ __align__(1024) uint32_t g_scratch[(8 << 20) / 4];

#define TRACE(slot) do {} while (0)
#define TRACE_Q(slot) do {} while (0)
#define TRACE_GT(slot) do {} while (0)

__device__ __forceinline__ uint32_t s2u(const void* p) { return (uint32_t)__cvta_generic_to_shared(p); }
__device__ __forceinline__ void mbar_init(uint32_t b, int c) { asm volatile("mbarrier.init.shared::cta.b64 [%0], %1;" :: "r"(b), "r"(c) : "memory"); }
__device__ __forceinline__ void mbar_expect(uint32_t b, uint32_t bytes) { asm volatile("mbarrier.arrive.expect_tx.shared::cta.b64 _, [%0], %1;" :: "r"(b), "r"(bytes) : "memory"); }
__device__ __forceinline__ void mbar_arrive(uint32_t b) { asm volatile("mbarrier.arrive.shared::cta.b64 _, [%0];" :: "r"(b) : "memory"); }
__device__ __forceinline__ void mbar_wait(uint32_t b, uint32_t ph) {
    asm volatile("{\n.reg .pred p;\nW: mbarrier.try_wait.parity.shared::cta.b64 p, [%0], %1;\n@!p bra W;\n}" :: "r"(b), "r"(ph) : "memory");
}
__device__ __forceinline__ void mbar_waitb(uint32_t b, uint32_t ph) {
    asm volatile("{\n.reg .pred p;\n.reg .u32 n;\nmov.u32 n, 0;\n"
                 "W: mbarrier.try_wait.parity.shared::cta.b64 p, [%0], %1;\n@p bra D;\n"
                 "add.u32 n, n, 1;\nsetp.lt.u32 p, n, 0x100000;\n@p bra W;\ntrap;\nD:\n}" :: "r"(b), "r"(ph) : "memory");
}
__device__ __forceinline__ uint32_t mbar_test(uint32_t b, uint32_t ph) {
    uint32_t ok;
    asm volatile("{\n.reg .pred p;\nmbarrier.test_wait.parity.shared::cta.b64 p, [%1], %2;\nselp.u32 %0, 1, 0, p;\n}" : "=r"(ok) : "r"(b), "r"(ph) : "memory");
    return ok;
}
__device__ __forceinline__ void bar_sync(int id, int n) { asm volatile("bar.sync %0, %1;" :: "r"(id), "r"(n) : "memory"); }
__device__ __forceinline__ void bar_arrive(int id, int n) { asm volatile("bar.arrive %0, %1;" :: "r"(id), "r"(n) : "memory"); }
__device__ __forceinline__ uint32_t peer_addr(uint32_t a, uint32_t rank) { uint32_t r; asm("mapa.shared::cluster.u32 %0, %1, %2;" : "=r"(r) : "r"(a), "r"(rank)); return r; }
__device__ __forceinline__ void st_async2(uint32_t a, float x, float y, uint32_t bar) {
    asm volatile("st.async.weak.shared::cluster.mbarrier::complete_tx::bytes.v2.f32 [%0], {%1, %2}, [%3];" :: "r"(a), "f"(x), "f"(y), "r"(bar) : "memory");
}
__device__ __forceinline__ uint32_t gtime() { uint32_t t; asm volatile("mov.u32 %0, %%globaltimer_lo;" : "=r"(t)); return t; }
__device__ __forceinline__ void fence_gpu() { asm volatile("fence.acq_rel.gpu;" ::: "memory"); }

__device__ __forceinline__ uint32_t enc(uint32_t b) { uint32_t r; asm("max.u32 %0, %1, 1;" : "=r"(r) : "r"(b)); return r; }
__device__ __forceinline__ uint32_t encf(float f) { return enc(__float_as_uint(f)); }
__device__ __forceinline__ void st_x1(uint32_t* p, uint32_t v) { asm volatile("st.relaxed.gpu.global.u32 [%0], %1;" :: "l"(p), "r"(v) : "memory"); }
__device__ __forceinline__ void st_x4(void* p, uint32_t a, uint32_t b, uint32_t c, uint32_t d) {
    asm volatile("st.relaxed.gpu.global.v4.u32 [%0], {%1, %2, %3, %4};" :: "l"(p), "r"(a), "r"(b), "r"(c), "r"(d) : "memory");
}
__device__ __forceinline__ void st2_x1(uint32_t* p, uint32_t v) { st_x1(p, v); st_x1(p + 1024, v); }
__device__ __forceinline__ void st2_x4(uint32_t* p, uint32_t a, uint32_t b, uint32_t c, uint32_t d) { st_x4(p, a, b, c, d); st_x4(p + 1024, a, b, c, d); }
__device__ __forceinline__ int near_off(int b, uint32_t cls) { return b * 4096 + (((__popc(b & 0x2C) ^ cls) & 1) << 10); }
__device__ __forceinline__ void ld_x(uint32_t& v, const void* p) { asm volatile("ld.relaxed.gpu.global.u32 %0, [%1];" : "=r"(v) : "l"(p) : "memory"); }
__device__ __forceinline__ void ld_x(uint4& v, const void* p) {
    asm volatile("ld.relaxed.gpu.global.v4.u32 {%0, %1, %2, %3}, [%4];" : "=r"(v.x), "=r"(v.y), "=r"(v.z), "=r"(v.w) : "l"(p) : "memory");
}
__device__ __forceinline__ void ld_x(uint2& v, const void* p) { asm volatile("ld.relaxed.gpu.global.v2.u32 {%0, %1}, [%2];" : "=r"(v.x), "=r"(v.y) : "l"(p) : "memory"); }
__device__ __forceinline__ uint32_t minw(uint32_t v) { return v; }
__device__ __forceinline__ uint32_t minw(const uint2& v) { return min(v.x, v.y); }
__device__ __forceinline__ uint32_t minw(const uint4& v) { return min(__vimin3_u32(v.x, v.y, v.z), v.w); }
template <int N> __device__ __forceinline__ uint32_t mint(const uint32_t* m) {
    if constexpr (N == 1) return m[0];
    else if constexpr (N == 2) return min(m[0], m[1]);
    else return __vimin3_u32(mint<(N + 2) / 3>(m), mint<(N + 1) / 3>(m + (N + 2) / 3), mint<N / 3>(m + (N + 2) / 3 + (N + 1) / 3));
}

template <int STRIDE, int S4 = 4 * STRIDE, typename T, int N>
__device__ __forceinline__ void poll_start(T (&v)[N], const void* base) {
#pragma unroll
    for (int i = 0; i < N; i++) ld_x(v[i], (const uint8_t*)base + (i & 3) * STRIDE + (i >> 2) * S4);
}
struct Nop { __device__ void operator()() const {} };
template <int STRIDE, int SLEEP, bool STARTED = false, int S4 = 4 * STRIDE, typename T, int N, typename F = Nop, typename G = Nop>
__device__ __forceinline__ void poll(T (&v)[N], const void* base, F idle = F(), G ahead = G()) {
    if (!STARTED) { poll_start<STRIDE, S4>(v, base); idle(); }
#pragma unroll 1
    for (uint32_t it = 0;; it++) {
        uint32_t m[N];
        ahead();
#pragma unroll
        for (int i = 0; i < N; i++) m[i] = minw(v[i]);
        if (__all_sync(0xffffffffu, mint<N>(m) != 0)) break;
        if (SLEEP && it > 0) __nanosleep(SLEEP);
#pragma unroll
        for (int i = 0; i < N; i++) if (!m[i]) ld_x(v[i], (const uint8_t*)base + (i & 3) * STRIDE + (i >> 2) * S4);
        idle();
        if (it > SPIN_LIMIT) __trap();
    }
}

__device__ __forceinline__ float bflo(uint32_t w) { return __uint_as_float(w << 16); }
__device__ __forceinline__ float bfhi(uint32_t w) { return __uint_as_float(w & 0xffff0000u); }
__device__ __forceinline__ uint32_t pack2(float lo, float hi) {
    uint32_t r; asm("cvt.rn.bf16x2.f32 %0, %1, %2;" : "=r"(r) : "f"(hi), "f"(lo)); return r;
}
__device__ __forceinline__ float rbf(float x) { return __uint_as_float(pack2(0.f, x)); }
__device__ __forceinline__ float ex2(float x) { float r; asm("ex2.approx.ftz.f32 %0, %1;" : "=f"(r) : "f"(x)); return r; }
__device__ __forceinline__ float shx(float v, int m) { return __shfl_xor_sync(0xffffffffu, v, m); }
__device__ __forceinline__ uint4 lds128(uint32_t a) { uint4 v; asm volatile("ld.shared.v4.u32 {%0, %1, %2, %3}, [%4];" : "=r"(v.x), "=r"(v.y), "=r"(v.z), "=r"(v.w) : "r"(a) : "memory"); return v; }
__device__ __forceinline__ uint32_t lds32(uint32_t a) { uint32_t v; asm volatile("ld.shared.u32 %0, [%1];" : "=r"(v) : "r"(a) : "memory"); return v; }
__device__ __forceinline__ void sts32(uint32_t a, uint32_t v) { asm volatile("st.shared.u32 [%0], %1;" :: "r"(a), "r"(v) : "memory"); }
__device__ __forceinline__ void sts16(uint32_t a, uint32_t v) { asm volatile("st.shared.u16 [%0], %1;" :: "r"(a), "h"((uint16_t)v) : "memory"); }
__device__ __forceinline__ int frag_off(int k) { return (k >> 5) * 64 + ((k >> 1) & 3) * 16 + ((k >> 4) & 1) * 8 + ((k >> 3) & 1) * 4 + (k & 1) * 2; }

template <bool TRANS>
__device__ __forceinline__ uint4 ldsm(uint32_t a) {
    uint4 r;
    if (TRANS) asm volatile("ldmatrix.sync.aligned.m8n8.x4.trans.shared.b16 {%0, %1, %2, %3}, [%4];" : "=r"(r.x), "=r"(r.y), "=r"(r.z), "=r"(r.w) : "r"(a) : "memory");
    else asm volatile("ldmatrix.sync.aligned.m8n8.x4.shared.b16 {%0, %1, %2, %3}, [%4];" : "=r"(r.x), "=r"(r.y), "=r"(r.z), "=r"(r.w) : "r"(a) : "memory");
    return r;
}
__device__ __forceinline__ void mma(float (&c)[4], uint32_t a0, uint32_t a1, uint32_t a2, uint32_t a3, uint32_t b0, uint32_t b1) {
    asm volatile("mma.sync.aligned.m16n8k16.row.col.f32.bf16.bf16.f32 {%0,%1,%2,%3}, {%4,%5,%6,%7}, {%8,%9}, {%0,%1,%2,%3};"
                 : "+f"(c[0]), "+f"(c[1]), "+f"(c[2]), "+f"(c[3]) : "r"(a0), "r"(a1), "r"(a2), "r"(a3), "r"(b0), "r"(b1));
}
template <bool TRANS, typename F>
__device__ __forceinline__ void load8(uint4 (&a)[8], F addr) {
    __syncwarp();
#pragma unroll
    for (int s = 0; s < 8; s++) a[s] = ldsm<TRANS>(addr(s));
}
__device__ __forceinline__ void mma8(float (&c)[4], const uint4 (&a)[8], const uint4 (&b)[4]) {
    float e[4][4];
#pragma unroll
    for (int s = 0; s < 8; s++) {
        if (s < 4) e[s][0] = e[s][1] = e[s][2] = e[s][3] = 0.f;
        mma(e[s & 3], a[s].x, a[s].y, a[s].z, a[s].w, (s & 1) ? b[s >> 1].z : b[s >> 1].x, (s & 1) ? b[s >> 1].w : b[s >> 1].y);
    }
#pragma unroll
    for (int i = 0; i < 4; i++) c[i] = (e[0][i] + e[1][i]) + (e[2][i] + e[3][i]);
}
__device__ __forceinline__ void ldfrag(uint4 (&b)[4], uint32_t a) {
    asm volatile("ld.shared.v4.u32 {%0,%1,%2,%3}, [%16];\nld.shared.v4.u32 {%4,%5,%6,%7}, [%16+64];\n"
                 "ld.shared.v4.u32 {%8,%9,%10,%11}, [%16+128];\nld.shared.v4.u32 {%12,%13,%14,%15}, [%16+192];\n"
                 : "=r"(b[0].x), "=r"(b[0].y), "=r"(b[0].z), "=r"(b[0].w), "=r"(b[1].x), "=r"(b[1].y), "=r"(b[1].z), "=r"(b[1].w),
                   "=r"(b[2].x), "=r"(b[2].y), "=r"(b[2].z), "=r"(b[2].w), "=r"(b[3].x), "=r"(b[3].y), "=r"(b[3].z), "=r"(b[3].w) : "r"(a) : "memory");
}
__device__ __forceinline__ void quad_pair(float x, float y, int t, float& lo, float& hi) {
    const float k = ((t & 1) ? y : x) + shx((t & 1) ? x : y, 1);
    lo = k + shx(k, 2); hi = shx(k, 4) + shx(k, 6);
}
__device__ __forceinline__ void pin(uint32_t& x) { asm volatile("" : "+r"(x)); }
template <typename T> __device__ __forceinline__ void pin(T*& x) { asm volatile("" : "+l"(x)); }
__device__ __forceinline__ float4 ldsf4(uint32_t a) { const uint4 v = lds128(a); return make_float4(__uint_as_float(v.x), __uint_as_float(v.y), __uint_as_float(v.z), __uint_as_float(v.w)); }
__device__ __forceinline__ float sum4(const float4& f) { return (f.x + f.y) + (f.z + f.w); }
__device__ __forceinline__ void stsf(uint32_t a, float v) { sts32(a, __float_as_uint(v)); }

__device__ __forceinline__ void wg_fence() { asm volatile("wgmma.fence.sync.aligned;" ::: "memory"); }
__device__ __forceinline__ void wg_commit() { asm volatile("wgmma.commit_group.sync.aligned;" ::: "memory"); }
__device__ __forceinline__ void wg_wait1() { asm volatile("wgmma.wait_group.sync.aligned 1;" ::: "memory"); }
__device__ __forceinline__ void wg_wait0() { asm volatile("wgmma.wait_group.sync.aligned 0;" ::: "memory"); }
#define R8(o) "+f"(d[o]), "+f"(d[o + 1]), "+f"(d[o + 2]), "+f"(d[o + 3]), "+f"(d[o + 4]), "+f"(d[o + 5]), "+f"(d[o + 6]), "+f"(d[o + 7])
__device__ __forceinline__ void wgmma_rs_n32(float (&d)[16], const uint4& a, uint64_t db, int acc) {
    asm volatile("{\n.reg .pred p;\nsetp.ne.b32 p, %21, 0;\n"
        "wgmma.mma_async.sync.aligned.m64n32k16.f32.bf16.bf16 "
        "{%0,%1,%2,%3,%4,%5,%6,%7,%8,%9,%10,%11,%12,%13,%14,%15}, {%16,%17,%18,%19}, %20, p, 1, 1, 0;\n}"
        : R8(0), R8(8) : "r"(a.x), "r"(a.y), "r"(a.z), "r"(a.w), "l"(db), "r"(acc));
}
#define PV_LO "{%0,%1,%2,%3,%4,%5,%6,%7,%8,%9,%10,%11,%12,%13,%14,%15,%16,%17,%18,%19,%20,%21,%22,%23,%24,%25,%26,%27,%28,%29,%30,%31,%32,%33,%34,%35,%36,%37,%38,%39,%40,%41,%42,%43,%44,%45,%46,%47,%48,%49,%50,%51,%52,%53,%54,%55,%56,%57,%58,%59,%60,%61,%62,%63}, "
#define PV_HI "{%64,%65,%66,%67,%68,%69,%70,%71,%72,%73,%74,%75,%76,%77,%78,%79,%80,%81,%82,%83,%84,%85,%86,%87,%88,%89,%90,%91,%92,%93,%94,%95,%96,%97,%98,%99,%100,%101,%102,%103,%104,%105,%106,%107,%108,%109,%110,%111,%112,%113,%114,%115,%116,%117,%118,%119,%120,%121,%122,%123,%124,%125,%126,%127}, "
__device__ __forceinline__ void wgmma_pv(float (&d)[128], const uint4& a, uint32_t blo, int acc) {
    asm volatile("{\n.reg .pred p;\n.reg .b32 u0, u1, u2, u3, t;\n.reg .b64 d0, d1, d2, d3;\nsetp.ne.b32 p, %133, 0;\n"
        "mov.b64 d0, {%132, 0x40000100};\nadd.u32 t, %132, 512;\nmov.b64 d1, {t, 0x40000100};\n"
        "add.u32 t, %132, 128;\nmov.b64 d2, {t, 0x40000100};\nadd.u32 t, %132, 640;\nmov.b64 d3, {t, 0x40000100};\n"
        "wgmma.fence.sync.aligned;\n"
        "wgmma.mma_async.sync.aligned.m64n128k16.f32.bf16.bf16 " PV_LO "{%128, u0, %129, u1}, d0, p, 1, 1, 1;\n"
        "wgmma.mma_async.sync.aligned.m64n128k16.f32.bf16.bf16 " PV_LO "{%130, u2, %131, u3}, d1, 1, 1, 1, 1;\n"
        "wgmma.commit_group.sync.aligned;\n"
        "wgmma.mma_async.sync.aligned.m64n128k16.f32.bf16.bf16 " PV_HI "{%128, u0, %129, u1}, d2, p, 1, 1, 1;\n"
        "wgmma.mma_async.sync.aligned.m64n128k16.f32.bf16.bf16 " PV_HI "{%130, u2, %131, u3}, d3, 1, 1, 1, 1;\n"
        "wgmma.commit_group.sync.aligned;\n}"
        : R8(0), R8(8), R8(16), R8(24), R8(32), R8(40), R8(48), R8(56), R8(64), R8(72), R8(80), R8(88), R8(96), R8(104), R8(112), R8(120)
        : "r"(a.x), "r"(a.y), "r"(a.z), "r"(a.w), "r"(blo), "r"(acc) : "memory");
}

template <int NW>
__device__ __forceinline__ void ln_stats(float s, float q, float sh, float* scr, int w, int lane, int bar, float& mean_b, float& sd_b) {
#pragma unroll
    for (int o = 16; o; o >>= 1) { s += shx(s, o); q += shx(q, o); }
    constexpr float n = 512.f / NW;
    if (lane == 0) { scr[w] = sh + s * (1.f / n); scr[NW + w] = q - s * s * (1.f / n); }
    bar_sync(bar, NW * 32);
    float mu = 0.f, m2 = 0.f;
#pragma unroll
    for (int i = 0; i < NW; i++) { mu += scr[i]; m2 += scr[NW + i]; }
    mu *= 1.f / NW;
#pragma unroll
    for (int i = 0; i < NW; i++) { const float d = scr[i] - mu; m2 = fmaf(n * d, d, m2); }
    mean_b = rbf(mu);
    sd_b = rbf(sqrtf(rbf(rbf(fmaxf(m2, 0.f) * (1.f / 512.f)) + 1e-5f)));
}
__device__ __forceinline__ float ln_mod(float x, float mean_b, float sd_b, float c, float s) {
    return rbf(rbf(__fdividef(rbf(x - mean_b), sd_b)) * rbf(1.f + c)) + s;
}

__global__ void __cluster_dims__(2, 1, 1) __launch_bounds__(NTHREADS, 1)
fused_kernel(const __grid_constant__ First F, __nv_bfloat16* __restrict__ out, uint32_t* __restrict__ gs, const __grid_constant__ Maps M) {
    extern __shared__ __align__(1024) uint8_t sm[];
    const uint32_t sb = s2u(sm);
    const int tid = threadIdx.x, lane = tid & 31;
    const int j = blockIdx.x, rk = j & 1;
    const int g = lane >> 2, t = lane & 3;
    const int r8 = lane & 7, lb3 = (lane >> 3) & 1, lb4 = lane >> 4;
    uint64_t pol;
    asm("createpolicy.fractional.L2::evict_first.b64 %0, 1.0;" : "=l"(pol));
    {
        auto cpa = [&](uint32_t d, const uint8_t* s) {
            asm volatile("cp.async.cg.shared.global.L2::cache_hint.L2::128B [%0], [%1], 16, %2;" :: "r"(d), "l"(s), "l"(pol) : "memory");
        };
        const uint32_t ut = threadIdx.x, uj = blockIdx.x;
        const uint8_t* w = F.w[ut >= 128];
        if (ut < 128) {
            const uint32_t dq = (sb + ut * 16) ^ ((ut * 2) & 0x70);
            const uint8_t* sq = w + (uint32_t)(((uj & 1) * 256 + (ut >> 3)) * 8192 + (uj >> 1) * 128 + (ut & 7) * 16);
#pragma unroll
            for (int i = 0; i < 4 * NCP; i++) cpa(dq + 4 * 32768 + i * 2048, sq + i * 131072);
        } else if (ut < 384) {
            const uint32_t dm = (sb + ut * 16) ^ ((ut * 2) & 0x10);
            const uint8_t* sa = w + (uint32_t)(((uj >> 5) * 128 + (ut >> 1) - 64) * 6144 + (uj & 31) * 32 + (ut & 1) * 16);
            cpa(dm + SM_XA - 2048, sa); cpa(dm + SM_XA + 2048, sa + 1024);
        }
        else if (ut == 480 && uj < 64) asm volatile("prefetch.global.L2 [%0];" :: "l"(F.v[(uj >> 3) & 1] + (uj & 7) * 64));
    }
    const int warp = __shfl_sync(0xffffffffu, tid >> 5, 0);
    const __nv_bfloat16* const xin = F.v[0];
    uint32_t* const pl = gs + (warp < 2 ? (B_PR + (j >> 5)) * 4096 + (j & 31) * 32 : G_E1 + j * 8192) + (warp & 1) * 1024 + lane;
    if (warp < 4) st_x1(pl, 1u);
    auto BAR = [&](int i) -> uint32_t { return sb + SM_BAR + i * 8; };
    const uint32_t a16 = (r8 + 8 * lb4) * 32 + ((lb3 ^ (r8 >> 2)) * 16);
    const uint32_t a128 = (r8 + 8 * lb4) * 128 + ((((warp & 3) * 2 + lb3) ^ r8) * 16);
    auto ldcls = [&]() -> uint32_t { return *(const volatile uint32_t*)(sm + SM_CLS); };
    auto clear_head = [&]() {
        st2_x1(gs + (B_HA + ((j >> 4) & 1) * 2 + lb4) * 4096 + (j >> 5) * 256 + (j & 15) * 16 + (lane & 15), 0u);
        st2_x4(gs + (B_QA + rk * 8 + ((j >> 1) & 1) * 4 + (j >> 5)) * 4096 + g * 128 + ((j >> 2) & 7) * 16 + t * 4, 0u, 0u, 0u, 0u);
        if (lane < 8) st2_x1(gs + B_RD * 4096 + j * 8 + lane, 0u);
    };
    auto tma = [&](uint32_t dst, const CUtensorMap* mp, uint32_t bar, int c0, int c1, int c2, int c3) {
        asm volatile("{\n.reg .pred p;\nelect.sync _|p, 0xffffffff;\n"
                     "@p cp.async.bulk.tensor.4d.shared::cluster.global.mbarrier::complete_tx::bytes.L2::cache_hint [%0], [%1, {%3, %4, %5, %6}], [%2], %7;\n}"
                     :: "r"(dst), "l"(mp), "r"(bar), "r"(c0), "r"(c1), "r"(c2), "r"(c3), "l"(pol) : "memory");
    };
    if (warp <= 12 || warp == 15) {
        const int grp = warp == 12 ? 0 : warp == 15 ? 13 : warp + 1;
        const uint32_t cnt = grp < 10 ? 1 : grp < 13 ? 4 : 8;
        if (lane == 0) {
#pragma unroll
            for (int i = 0; i < 8; i++) mbar_init(BAR(grp * 8 + i), (i < 2 && grp == 0) ? (i ? 128 : 256) : cnt);
        }
        __syncwarp();
        if (grp < 10 && lane < 8 && (grp || lane > NCP)) mbar_expect(BAR(grp * 8 + lane), grp >= 8 ? 4096 : (uint32_t)(grp * 8 + lane - IT_X) < 4 ? 16384 : 8192);
        asm volatile("fence.mbarrier_init.release.cluster;" ::: "memory");
        __syncwarp();
        if (warp == 12) {
#pragma unroll
            for (int i = NCP + 1; i < W0; i++) tma(sb + (15 + i) * 8192, &M.m[MP_WQ], BAR(i), 0, rk * 256 + (i - 1) * 64, j >> 1, 0);
        }
    } else if (warp == 13) {
        if (lane < NMAPS) asm volatile("prefetch.tensormap [%0];" :: "l"(&M.m[lane]) : "memory");
    } else if (warp == 14) {
        clear_head();
    }
    __syncthreads();
    uint32_t in1 = 0, in2 = 0;
    if (warp < 4) { in1 = *(const uint32_t*)(xin + 2 * tid); in2 = *(const uint32_t*)(xin + 256 + 2 * tid); }
    else if (warp < 12) in1 = *(const uint32_t*)(F.v[1] + 2 * (tid - 128));
    if (warp < 12) asm volatile("cp.async.mbarrier.arrive.noinc.shared::cta.b64 [%0];" :: "r"(BAR(warp < 4)) : "memory");
    asm volatile("barrier.cluster.arrive.relaxed.aligned;" ::: "memory");

    if (warp >= 12) {
    asm volatile("setmaxnreg.dec.sync.aligned.u32 64;");
    if (warp == 12) {
        static_assert(W0 > NCP && W0 <= 5 && NCP >= 1 && NCP <= 4, "W0");
        const uint2* sched = M.sched[j < NFF ? 0 : j < J_RED ? 1 : 2];
        uint2 en = sched[W0];
        const uint32_t t0 = gtime();
        const uint32_t sp = __reduce_or_sync(0xffffffffu, sb);
        const int cx = (j >> 1) * 64 + (j < NFF ? 0 : 1024 - NFF * 32);
#pragma unroll 1
        for (int i = W0; en.x; i++) {
            uint32_t e = en.x, st = (en.y >> 20) * 64;
            const uint32_t tn = t0 + (int16_t)en.y, mp = (en.y >> 16) & 15;
            if (mp == MP_GATE || mp == MP_UP) st ^= (j & 16) * 8;
            if (mp == MP_DOWN) { st ^= (j & 3) * 64; e ^= (j & 3) << 6; }
            en = sched[i + 1];
            if (mp == MP_MODB && j >= J_END) break;
            uint32_t c0 = mp == MP_WO ? (j & 7) * 64 : mp > MP_WO ? cx : 0;
            uint32_t c1 = mp == MP_CKV ? 0 : mp == MP_DOWN ? j * 32 : st + (mp == MP_WUV ? (j & 3) * 32 : mp == MP_WO ? (j >> 3) * 256 : rk * 256);
            uint32_t c2 = mp < MP_CKV ? j >> 1 : mp == MP_CKV ? rk * 4 : mp == MP_WUV ? (j >> 2) * 2 : mp == MP_DOWN ? st >> 5 : 0;
            uint32_t c3 = mp == MP_CKV ? st * 2 + (j & ~1) : 0;
            uint32_t dst = sp + ((e << 7) & 0x3e000), bar = sp + SM_BAR + (e & 63) * 8;
            const uint32_t w0 = (e >> 8) & 0x3f8, w1 = (e >> 15) & 0x3f8, w2 = (e >> 22) & 0x3f8, bb = sp + SM_BAR - 8;
            const CUtensorMap* pm = &M.m[mp];
            pin(dst); pin(bar); pin(c0); pin(c1); pin(c2); pin(c3); pin(pm);
            if (w0) mbar_wait(bb + w0, 0);
            if (w2) {
                mbar_wait(bb + w2, 0);
                while (!__any_sync(0xffffffffu, mbar_test(bb + w1, 0) | ((int)(gtime() - tn) > 0))) {}
            } else if (w1) mbar_wait(bb + w1, 0);
            tma(dst, pm, bar, c0, c1, c2, c3);
        }
    } else if (warp == 13) {
#pragma unroll
        for (int i = 0; i < 2; i++) st_x4(gs + (B_ML + rk * 16 + i * 8 + g) * 4096 + (t >> 1) * 1024 + (j >> 1) * 8 + (t & 1) * 4, 0u, 0u, 0u, 0u);
        if (lane < 16) st2_x4(gs + (B_E2 + (j >> 4)) * 4096 + (j & 15) * 64 + lane * 4, 0u, 0u, 0u, 0u);
        st2_x1(gs + (B_E3 + (j >> 5)) * 4096 + (j & 31) * 32 + lane, 0u);
        if (lane < 8) st2_x1(gs + B_MB * 4096 + j * 8 + lane, 0u);
        if (j < NFF) {
#pragma unroll
            for (int i = 0; i < 2; i++) st2_x4(gs + (B_E5 + i * 8 + g) * 4096 + j * 16 + t * 4, 0u, 0u, 0u, 0u);
        }
        bar_sync(9, 64);
        const uint32_t cs = ldcls();
#pragma unroll 1
        for (int i = 0; i < 32; i++) {
            st_x4(gs + G_E1 + j * 8192 + (i >> 3) * 2048 + ((((cs >> 1) ^ (i >> 3)) & 1) << 10) + (i & 7) * 128 + lane * 4, 0u, 0u, 0u, 0u);
            __nanosleep(JAN_SLEEP);
        }
        fence_gpu();
        if (lane < 8) st2_x1(gs + B_RD * 4096 + j * 8 + lane, 1u + (cs >> 1));
        if (lane == 0) TRACE(41);
        uint32_t rd[4];
        mbar_wait(BAR(IT_CKV + RD_ITEM), 0);
        poll<1024, RD_SLEEP>(rd, gs + near_off(B_RD, cs) + lane * 8);
#pragma unroll
        for (int i = 0; i < 4; i++) {
            const uint32_t m = __ballot_sync(0xffffffffu, rd[i] == 2u);
            if (lane == 0) sts32(sb + SM_CLS + 16 + i * 4, m);
        }
        __syncwarp();
        if (lane < 8) mbar_arrive(BAR(JD));
        if (lane == 0) TRACE(42);
    } else if (warp == 14) {
        uint2 ml[2];
        mbar_waitb(BAR(JD), 0);
        const uint32_t cls = ldcls();
        mbar_waitb(BAR(PF0 + 2 * NUNITS - 1), 0);
        __nanosleep(ML_DELAY);
        const uint32_t* pl2 = gs + near_off(B_ML + (j >> 2), cls) + lane * 8;
        const uint32_t wa = sb + SM_W + lb4 * 64 + t * 16 + (g & 3) * 4;
        poll_start<1024>(ml, pl2);
        uint32_t w0 = 0, w1 = 0, redo = 0;
        bool first = true;
#pragma unroll 1
        for (uint32_t it = 0;; it++) {
            const bool p0 = minw(ml[0]) != 0, p1 = minw(ml[1]) != 0;
            const int n = __popc(__ballot_sync(0xffffffffu, p0)) + __popc(__ballot_sync(0xffffffffu, p1));
            const uint32_t x0 = ml[0].x, x1 = ml[1].x;
            if (n < 64) {
                if (!p0) ld_x(ml[0], pl2);
                if (!p1) ld_x(ml[1], pl2 + 256);
            }
            if (n == 64 || (first && n >= E1_EARLY)) {
                auto ord = [](int x) { return x ^ ((x >> 31) & 0x7fffffff); };
                const int o0 = ord(x0), o1 = ord(x1);
                const float mm = __int_as_float(ord(__reduce_max_sync(0xffffffffu, max(p0 ? o0 : INT_MIN, p1 ? o1 : INT_MIN))));
                const float lo = __int_as_float(ord(__reduce_min_sync(0xffffffffu, min(p0 ? o0 : INT_MAX, p1 ? o1 : INT_MAX))));
                const uint32_t v0 = pack2(ex2((p0 ? __uint_as_float(x0) : lo) - mm), 0.f), v1 = pack2(ex2((p1 ? __uint_as_float(x1) : lo) - mm), 0.f);
                redo = !first && __any_sync(0xffffffffu, v0 != w0 || v1 != w1);
                w0 = v0; w1 = v1;
                sts32(wa - redo * (SM_W - SM_W2), w0 * 0x10001u); sts32(wa - redo * (SM_W - SM_W2) + 128, w1 * 0x10001u);
                if (first) bar_arrive(3, 416);
                first = false;
                if (n == 64) break;
            }
            if (it > SPIN_LIMIT) __trap();
        }
        if (lane == 0) TRACE_Q(37);
        float L = bflo(w0) * __uint_as_float(ml[0].y) + bflo(w1) * __uint_as_float(ml[1].y);
#pragma unroll
        for (int o = 16; o; o >>= 1) L += shx(L, o);
        if (lane == 0) *(float2*)(sm + SM_FQ) = make_float2(__frcp_rn(L), __uint_as_float(redo));
        __syncwarp();
        if (lane < 8) mbar_arrive(BAR(WR));
        if (lane == 0) TRACE(10);
        bar_sync(4, 416);
        clear_head();
        if (j < NFF) {
            uint32_t ya = sb + SM_Y + lane * 16, sa = peer_addr(sb + SM_RED + 2048 + rk * 8, lane & 1), tb = peer_addr(BAR(MBB), lane & 1);
            pin(ya); pin(sa); pin(tb);
            bar_sync(7, 288);
            const float4 y0 = ldsf4(ya), y1 = ldsf4(ya + 512);
            float s = sum4(y0) + sum4(y1);
            float q = (fmaf(y0.x, y0.x, y0.y * y0.y) + fmaf(y0.z, y0.z, y0.w * y0.w)) + (fmaf(y1.x, y1.x, y1.y * y1.y) + fmaf(y1.z, y1.z, y1.w * y1.w));
#pragma unroll
            for (int o = 16; o; o >>= 1) { s += shx(s, o); q += shx(q, o); }
            if (lane < 2) st_async2(sa, s, q, tb);
        }
    } else if (warp == 15) {
        mbar_waitb(BAR(IT_X - 1), 0);
        if (j < J_END) mbar_waitb(BAR(j < NFF ? NITEMS - 1 : MBB), 0);
    }
    } else if (warp < 4) {
        float* scr = (float*)(sm + SM_SCR);
        uint32_t cls;
        {
            uint2 ha[8];
            uint32_t best = 0xffffffffu;
            sts32(sb + SM_SCR + 64 + warp * 4, best);
            const float sh = __shfl_sync(0xffffffffu, bflo(in1), 0);
            const float v0 = bflo(in1) - sh, v1 = bfhi(in1) - sh, v2 = bflo(in2) - sh, v3 = bfhi(in2) - sh;
            float mb, sd;
            ln_stats<4>((v0 + v1) + (v2 + v3), (v0 * v0 + v1 * v1) + (v2 * v2 + v3 * v3), sh, scr, warp, lane, 2, mb, sd);
            if (!rk) in2 = in1;
#pragma unroll 1
            for (int i = 0; i < NPROBE; i++) {
                uint32_t t0, t1, o;
                asm volatile("mov.u32 %0, %%clock;" : "=r"(t0));
                asm volatile("atom.relaxed.gpu.global.exch.b32 %0, [%1], %2;" : "=r"(o) : "l"(pl), "r"(2u + i) : "memory");
                asm volatile("{\n.reg .pred p;\nsetp.ne.u32 p, %1, 0x1234567;\nmov.u32 %0, 0;\n@p mov.u32 %0, %%clock;\n}" : "=r"(t1) : "r"(o));
                best = min(best, t1 - t0);
                sts32(sb + SM_SCR + 64 + warp * 4, best);
                if (__all_sync(0xffffffffu, min(best, lds32(sb + SM_SCR + 64 + (warp ^ 1) * 4)) < NEAR_CLK)) break;
            }
            bar_sync(2, 128);
            const uint4 lt = *(const uint4*)(scr + 16);
            cls = NUMA ? ((lt.y < lt.x) ^ (__popc((B_PR + (j >> 5)) & 0x2C) & 1)) | (lt.w < lt.z) << 1 : 0;
            if (warp == 0) { if (lane == 0) sts32(sb + SM_CLS, cls); bar_arrive(9, 64); }
            if (tid == 0) TRACE(38);
            asm volatile("barrier.cluster.wait.aligned;" ::: "memory");
            mbar_wait(BAR(IT_MODA), 0);
            if (HA_DELAY) __nanosleep(HA_DELAY);
            poll<1024, H_SLEEP, false, 16384>(ha, gs + near_off(B_HA + rk * 2, cls) + 2 * tid);
            auto rsum = [](uint32_t a, uint32_t b, uint32_t c, uint32_t d) { return rbf((__uint_as_float(a) + __uint_as_float(b)) + (__uint_as_float(c) + __uint_as_float(d))); };
            sts32(sb + SM_FV + frag_off(2 * tid),
                  pack2(ln_mod(bflo(in2), mb, sd, rsum(ha[4].x, ha[5].x, ha[6].x, ha[7].x), rsum(ha[0].x, ha[1].x, ha[2].x, ha[3].x)),
                        ln_mod(bfhi(in2), mb, sd, rsum(ha[4].y, ha[5].y, ha[6].y, ha[7].y), rsum(ha[0].y, ha[1].y, ha[2].y, ha[3].y))));
            bar_arrive(5, 384);
            mbar_wait(BAR(QB), 0);
            if (tid < 64) {
                const float* qx = (const float*)(sm + SM_QX) + tid;
                sts16(sb + SM_FQ + frag_off(tid), pack2((qx[0] + qx[64]) + (qx[128] + qx[192]), 0.f));
            }
            bar_arrive(6, 384);
        }
        asm volatile("setmaxnreg.inc.sync.aligned.u32 192;");
        float acc[128];
        float M = 0.f;
        uint32_t pa = sb + SM_XA + warp * 512 + lane * 16, ma = sb + SM_MX + (warp * 8 + g) * 4, pf = BAR(PF0);
        uint32_t blo = __reduce_or_sync(0xffffffffu, (((sb + SM_U) & 0x3FFFFu) >> 4) | 0x400000u);
        uint32_t* e1[4];
#pragma unroll
        for (int i = 0; i < 4; i++) e1[i] = gs + G_E1 + (warp * 8 + g) * 4 * 8192 + (rk * 2 + (j >> 6)) * 2048 + ((j >> 1) & 31) * 32 + t * 4;
#pragma unroll 1
        for (int h = 0; h < 2 * NUNITS; h++) {
            mbar_wait(pf, 0);
            const float m = __uint_as_float(lds32(ma));
            const uint4 pn = lds128(pa);
            wg_wait0();
#pragma unroll
            for (int i = 0; i < 128; i++) asm volatile("" : "+f"(acc[i]) :: "memory");
            if (h == 0) M = m;
            uint32_t b2 = 0x3f803f80u;
            if (__builtin_expect(__any_sync(0xffffffffu, m != M), 0)) {
                const float Mn = fmaxf(M, m), alpha = ex2(M - Mn), beta = ex2(m - Mn);
                M = Mn;
                b2 = pack2(beta, beta);
#pragma unroll
                for (int jj = 0; jj < 32; jj++) { acc[4 * jj] *= alpha; acc[4 * jj + 1] *= alpha; }
            }
            auto mul2 = [](uint32_t x, uint32_t y) { uint32_t r; asm("mul.rn.bf16x2 %0, %1, %2;" : "=r"(r) : "r"(x), "r"(y)); return r; };
            const uint4 p = make_uint4(mul2(pn.x, b2), mul2(pn.y, b2), mul2(pn.z, b2), mul2(pn.w, b2));
            if (tid == 0 && (h & 1)) TRACE_Q(48 + (h >> 1));
            wgmma_pv(acc, p, blo, h);
            if (lane == 0 && h > 0 && !(h & 1)) mbar_arrive(BAR(EB_UNIT0 + (h >> 1) - 1));
            blo += h == 11 ? -11 * 1024 : 1024;
            pa += (h == 5 || h == 11) ? -5 * 2048 : 2048;
            ma += 128; pf += 8;
            if (h == 2 * NUNITS - 3) {
                mbar_wait(BAR(JD), 0);
                const uint32_t hm = (*(const uint32_t*)(sm + SM_CLS + 16 + warp * 4) >> (g * 4)) ^ ((j >> 6) ? 15u : 0u);
#pragma unroll
                for (int i = 0; i < 4; i++) e1[i] += ((hm >> i) & 1) << 10;
            }
        }
#pragma unroll
        for (int vv = 0; vv < 2; vv++) {
            if (vv && M == 1.f) __trap();
            if (vv) wg_wait0(); else wg_wait1();
#pragma unroll
            for (int i = 0; i < 64; i++) asm volatile("" : "+f"(acc[vv * 64 + i]) :: "memory");
            if (tid == 0 && !vv) TRACE_Q(63);
#pragma unroll
            for (int i = 0; i < 4; i++) {
                const float* a = &acc[vv * 64 + i * 16];
                st_x4(e1[i] + i * 8192 + vv * 16, enc(pack2(a[0], a[1])), enc(pack2(a[4], a[5])), enc(pack2(a[8], a[9])), enc(pack2(a[12], a[13])));
            }
        }
        bar_arrive(3, 416);
        if (tid == 0) TRACE_Q(17);
#pragma unroll 1
        for (int pass = 0;; pass++) {
            if (j >= NFF && j < J_END && pass == (j >= J_RED)) {
                uint4 a[8], b[4];
                float c[4], e[4];
                const bool own = (warp >> 1) == rk;
                const uint32_t xa = sb + SM_FV + (warp & 1) * 64 + g * 8;
                if (lane == 0) mbar_expect(BAR(MBB), own ? 64 : 0);
#pragma unroll
                for (int i = 0; i < 2; i++) {
                    ldfrag(b, sb + SM_FS + rk * 512 + i * 256 + t * 16);
                    mbar_wait(BAR(IT_X + i), 0);
                    const uint32_t ab = sb + SM_U + B_X * 32768 + i * 16384 + a128;
                    load8<true>(a, [&](int s) { return ab + s * 2048; });
                    mma8(i ? e : c, a, b);
                }
                c[0] += e[0]; c[2] += e[2];
                if (!own) {
                    if (t == 0) st_async2(peer_addr(xa, rk ^ 1), c[0], c[2], peer_addr(BAR(MBB), rk ^ 1));
                } else {
                    mbar_wait(BAR(MBB), 0);
                    const float2 pp = *(const float2*)(sm + (xa - sb));
                    const float mine = t ? c[2] + pp.y : c[0] + pp.x, other = shx(mine, 4);
                    const uint32_t w = (warp & 1) * 8 + t * 4 + (g >> 1), val = enc(pack2(mine, other));
                    if (t < 2 && !(g & 1)) {
                        if (j < J_RED) st2_x1(gs + B_MB * 4096 + (j - NFF) * 16 + w, val);
                        else sts32(sb + SM_FV + 256 + w * 4, val);
                    }
                    __syncwarp();
                    if (j >= J_RED && lane < 4) mbar_arrive(BAR(QB));
                    if (lane == 0) TRACE(11);
                }
            }
            if (pass) break;
            uint4 a[8], a2[8];
            const uint32_t ab = sb + SM_U + B_WO * 32768 + a128;
            uint32_t* p3 = gs + (B_E3 + ((j >> 1) & 3)) * 4096 + (t >> 1) * 1024 + (rk * 2 + (warp >> 1)) * 256 + (j >> 3) * 16 + (warp & 1) * 8 + (t & 1) * 4 + (g >> 1);
            const uint32_t* pb = gs + near_off(B_E2 + (j >> 4), cls) + (((j >> 3) & 1) * 2 + lb4) * 256 + (lane & 15) * 2;
            pin(p3); pin(pb);
            uint2 bb[8];
            uint2 bq[2] = {make_uint2(0u, 0u), make_uint2(0u, 0u)};
            uint32_t xa = sb + SM_XA + lane * 16;
            pin(xa);
            bool h0 = false, h1 = false;
            auto idle = [&]() {
                if (!h0) {
                    h0 = __all_sync(0xffffffffu, mbar_test(BAR(IT_WO + (t & 1)), 0));
                    if (h0) load8<true>(a, [&](int s) { return ab + s * 2048; });
                }
                if (!h1) {
                    h1 = __all_sync(0xffffffffu, mbar_test(BAR(IT_WO + 2 + (t & 1)), 0));
                    if (h1) load8<true>(a2, [&](int s) { return ab + 16384 + s * 2048; });
                }
            };
            bar_sync(4, 416);
            idle();
            poll<128, 0, true>(bq, pb + warp * 64, idle);
            asm volatile("st.shared.v4.u32 [%0], {%1, %2, %3, %4};" :: "r"(xa + warp * 512), "r"(bq[0].x), "r"(bq[0].y), "r"(bq[1].x), "r"(bq[1].y) : "memory");
            bar_sync(2, 128);
#pragma unroll
            for (int i = 0; i < 4; i++) { const uint4 q = lds128(xa + i * 512); bb[2 * i] = make_uint2(q.x, q.y); bb[2 * i + 1] = make_uint2(q.z, q.w); }
            if (tid == 0) TRACE(21);
            float e[4][4];
#pragma unroll
            for (int s = 0; s < 16; s++) {
                if (s == 0 && !h0) { mbar_wait(BAR(IT_WO), 0); mbar_wait(BAR(IT_WO + 1), 0); load8<true>(a, [&](int q) { return ab + q * 2048; }); }
                if (s == 0 && !h1) { mbar_wait(BAR(IT_WO + 2), 0); mbar_wait(BAR(IT_WO + 3), 0); load8<true>(a2, [&](int q) { return ab + 16384 + q * 2048; }); }
                const int z = (s & 1) | (s & 2) << 2 | (s >> 2) << 1;
                const uint4& x = z < 8 ? a[z] : a2[z & 7];
                float (&d)[4] = e[(z >> 3) * 2 + (z & 1)];
                if (!(z & 6)) d[0] = d[1] = d[2] = d[3] = 0.f;
                mma(d, x.x, x.y, x.z, x.w, bb[z & 7].x, bb[z & 7].y);
            }
            float lo, hi;
            quad_pair((t & 2) ? (e[2][0] + e[3][0]) + (e[2][1] + e[3][1]) : (e[0][0] + e[1][0]) + (e[0][1] + e[1][1]),
                      (t & 2) ? (e[2][2] + e[3][2]) + (e[2][3] + e[3][3]) : (e[0][2] + e[1][2]) + (e[0][3] + e[1][3]), t, lo, hi);
            if (!(g & 1)) st_x1(p3, enc(pack2(lo, hi)));
            if (j < NFF) bar_arrive(8, 384); else if (j >= J_RED && j < J_END) bar_arrive(8, 192);
            if (tid == 0) TRACE(22);
        }
        if (j < NFF) {
            uint4 a[16];
            const uint32_t ad = sb + SM_U + B_DN * 32768 + warp * 8192 + (r8 + 8 * lb4) * 128 + (lb3 ^ r8) * 16;
            uint32_t rl = sb + SM_RED + lane * 16;
            uint32_t* p5 = gs + (B_E5 + warp * 4 + (t >> 1)) * 4096 + j * 16 + (t & 1) * 8 + g;
            pin(rl); pin(p5);
            if (lane == 0) mbar_expect(BAR(MBB), 4);
            auto ldd = [&]() {
#pragma unroll
                for (int s = 0; s < 16; s++) a[s] = ldsm<true>((ad ^ ((s & 3) * 32)) + (s >> 2) * 2048);
            };
            const uint32_t db = BAR(IT_DOWN + (warp ^ (j & 3)));
            mbar_wait(BAR(MBB), 0);
            const float4 st = ldsf4(sb + SM_RED + 2048);
            const bool hd = __all_sync(0xffffffffu, mbar_test(db, 0));
            if (hd) ldd();
            const float mu = (st.x + st.z) * (1.f / 512.f);
            float rstd;
            asm volatile("rsqrt.approx.ftz.f32 %0, %1;" : "=f"(rstd) : "f"(fmaxf(fmaf(-mu, mu, (st.y + st.w) * (1.f / 512.f)), 0.f) + 1e-5f));
            mbar_wait(BAR(QB), 1);
            if (tid == 0) TRACE(25);
            const float4 f0 = ldsf4(rl), f2 = ldsf4(rl + 1024), f1 = ldsf4(rl + 512), f3 = ldsf4(rl + 1536);
            const float gg = fmaf(rstd, fmaf(-mu, f0.z + f2.z, (f0.x + f0.y) + (f2.x + f2.y)), f0.w + f2.w);
            const float uu = fmaf(rstd, fmaf(-mu, f1.z + f3.z, (f1.x + f1.y) + (f3.x + f3.y)), f1.w + f3.w);
            const float hh = __fdividef(gg * uu, 1.f + ex2(-gg * fmaf(gg * gg, 0.10294324f, 2.3022082f)));
            uint32_t hb[4];
#pragma unroll
            for (int i = 0; i < 4; i++) hb[i] = pack2(__shfl_sync(0xffffffffu, hh, 2 * t + 8 * i), __shfl_sync(0xffffffffu, hh, 2 * t + 8 * i + 1));
            auto down = [&]() {
#pragma unroll
                for (int i = 0; i < 2; i++) {
                    uint32_t res = 0;
#pragma unroll
                    for (int k = 0; k < 4; k++) {
                        float c[4] = {0.f, 0.f, 0.f, 0.f};
                        const uint4 &x = a[i * 8 + k], &y = a[i * 8 + k + 4];
                        mma(c, x.x, x.y, x.z, x.w, hb[0], hb[1]);
                        mma(c, y.x, y.y, y.z, y.w, hb[2], hb[3]);
                        if (t == k) res = pack2(c[0], c[2]);
                    }
                    st2_x1(p5 + i * 8192, enc(res));
                }
            };
            if (hd) down();
            else { mbar_wait(db, 0); ldd(); down(); asm volatile("// late" ::: "memory"); }
            if (tid == 0) { TRACE(27); TRACE_GT(47); }
        }
    } else {
        const int u8 = tid - 128, w8 = warp - 4;
        const int v = w8 >> 2, wq4 = w8 & 3;
        {
            const float c0 = bflo(in1), c1 = bfhi(in1);
            sts32(sb + SM_FS + frag_off(2 * u8), pack2(__fdividef(c0, 1.f + __expf(-c0)), __fdividef(c1, 1.f + __expf(-c1))));
        }
        bar_sync(1, 256);
        asm volatile("barrier.cluster.wait.aligned;" ::: "memory");
        uint4 a[8], b[4]; float c[4];
        if (w8 < 2) {
            ldfrag(b, sb + SM_FS + (j >> 5) * 256 + t * 16);
            mbar_wait(BAR(IT_MODA), 0);
            if (u8 == 0) TRACE(12);
            const uint32_t ab = sb + SM_XA + w8 * 4096 + a16;
            load8<true>(a, [&](int s) { return ab + s * 512; });
            mma8(c, a, b);
            if (t < 2) st2_x1(gs + (B_HA + ((j >> 4) & 1) * 2 + w8) * 4096 + (j >> 5) * 256 + (j & 15) * 16 + t * 8 + g, encf(t ? c[2] : c[0]));
        }
        {
            mbar_wait(BAR(IT_WQ + 2 * v <= NCP ? 1 : IT_WQ + 2 * v), 0); mbar_wait(BAR(IT_WQ + 2 * v + 1 <= NCP ? 1 : IT_WQ + 2 * v + 1), 0);
            const uint32_t ab = sb + SM_U + 4 * 32768 + v * 16384 + a128;
            load8<true>(a, [&](int s) { return ab + s * 2048; });
            if (lane == 0) mbar_arrive(BAR(EB_WQ));
            bar_sync(5, 384);
            if (u8 == 0) TRACE(13);
            ldfrag(b, sb + SM_FV + v * 256 + t * 16);
            mma8(c, a, b);
            if (t < 2) {
                const float qv = t ? c[2] : c[0];
                const uint32_t qa_ = sb + SM_QX + ((rk * 2 + v) * 64 + wq4 * 16 + t * 8 + g) * 4;
                asm volatile("st.async.weak.shared::cluster.mbarrier::complete_tx::bytes.f32 [%0], %1, [%2];"
                             :: "r"(peer_addr(qa_, rk ^ 1)), "f"(qv), "r"(peer_addr(BAR(QB), rk ^ 1)) : "memory");
                sts32(qa_, __float_as_uint(qv));
            }
            __syncwarp();
            if (lane == 0) mbar_expect(BAR(QB), 64);
        }
        {
            mbar_wait(BAR(IT_WUK + v), 0); mbar_wait(BAR(IT_WUK + v + 2), 0);
            const uint32_t ab = sb + SM_U + 5 * 32768 + (w8 * 16 + r8 + 8 * lb3) * 128;
            const uint32_t x16 = (lb4 ^ r8) * 16;
            load8<false>(a, [&](int s) { return ab + (s & 1) * 16384 + (x16 ^ ((s >> 1) * 32)); });
            bar_sync(6, 384);
            if (u8 == 0) TRACE(14);
            b[0] = lds128(sb + SM_FQ + t * 16); b[1] = lds128(sb + SM_FQ + 64 + t * 16);
            float e[4] = {0.f, 0.f, 0.f, 0.f};
            c[0] = c[1] = c[2] = c[3] = 0.f;
#pragma unroll
            for (int k = 0; k < 4; k++) {
                const uint32_t b0 = (k & 1) ? b[k >> 1].z : b[k >> 1].x, b1 = (k & 1) ? b[k >> 1].w : b[k >> 1].y;
                mma(c, a[2 * k].x, a[2 * k].y, a[2 * k].z, a[2 * k].w, b0, b1);
                mma(e, a[2 * k + 1].x, a[2 * k + 1].y, a[2 * k + 1].z, a[2 * k + 1].w, b0, b1);
            }
            const float mine = ((t & 1) ? ((t & 2) ? e[2] : e[0]) : ((t & 2) ? c[2] : c[0])) * 0.12751743f;
            const float other = shx(mine, 4);
            if (!(g & 1)) st2_x1(gs + (B_QA + rk * 8 + ((j >> 1) & 1) * 4 + (j >> 5)) * 4096 + w8 * 128 + ((j >> 2) & 7) * 16 + (g >> 1) * 4 + t, enc(pack2(mine, other)));
            if (u8 == 0) TRACE(15);
        }
        const uint32_t cls = ldcls();
        __nanosleep(QA_DELAY);
        {
            uint4 qb[8];
            const uint32_t* pq = gs + near_off(B_QA + rk * 8 + wq4, cls) + lane * 4;
            const uint32_t* pq2 = gs + near_off(B_QA + rk * 8 + 4 + wq4, cls) + lane * 4;
            if (lane == 0) {
                mbar_expect(BAR(QT), 4096);
                asm volatile("cp.async.bulk.shared::cluster.global.mbarrier::complete_tx::bytes [%0], [%1], 4096, [%2];"
                             :: "r"(sb + SM_U + 5 * 32768 + w8 * 4096), "l"(gs + near_off(B_QA + rk * 8 + w8, cls)), "r"(BAR(QT)) : "memory");
            }
            const uint32_t qs = sb + SM_U + 5 * 32768 + wq4 * 4096 + lane * 16;
            mbar_wait(BAR(QT), 0);
#pragma unroll
            for (int i = 0; i < 8; i++) { a[i] = lds128(qs + i * 512); qb[i] = lds128(qs + 16384 + i * 512); }
            poll<512, QA_SLEEP, true>(a, pq);
            poll<512, QA_SLEEP, true>(qb, pq2);
            if (lane == 0) mbar_arrive(BAR(EB_WUK));
            auto add2 = [](uint32_t x, uint32_t y) { uint32_t r; asm("add.rn.bf16x2 %0, %1, %2;" : "=r"(r) : "r"(x), "r"(y)); return r; };
#pragma unroll
            for (int i = 0; i < 8; i++) a[i] = make_uint4(add2(a[i].x, qb[i].x), add2(a[i].y, qb[i].y), add2(a[i].z, qb[i].z), add2(a[i].w, qb[i].w));
        }
        if (u8 == 0) TRACE(8);
        {
            float m = -INFINITY, l = 0.f;
            uint32_t xl = sb + SM_XB + w8 * 2048 + lane * 16, xr = peer_addr(xl, rk ^ 1), bsr = peer_addr(BAR(SF0 + v), rk ^ 1);
            uint32_t pa = sb + SM_XA + v * 2048 + wq4 * 512 + lane * 16, ma = sb + SM_MX + v * 128 + (wq4 * 8 + g) * 4;
            uint32_t fb = BAR(IT_CKV + v * 2), sf = BAR(SF0 + v);
            uint32_t dlo = __reduce_or_sync(0xffffffffu, (((sb + SM_U + v * 16384) & 0x3FFFFu) >> 4) | 0x10000u);
            if (STAG && v) __nanosleep(STAG);
#pragma unroll 1
            for (int n = 0; n < NUNITS; n++) {
                float d[2][16], sc[8];
#pragma unroll
                for (int i = 0; i < 2; i++) {
                    mbar_wait(fb + i * 8, 0);
                    wg_fence();
#pragma unroll
                    for (int s = 0; s < 8; s++) wgmma_rs_n32(d[i], a[s], (0x40000080ull << 32) | (dlo + i * 512 + (s >> 2) * 64 + (s & 3) * 2), s);
                    wg_commit();
                }
#pragma unroll
                for (int i = 0; i < 2; i++) {
                    if (i) wg_wait0(); else wg_wait1();
#pragma unroll
                    for (int k = 0; k < 16; k++) asm volatile("" : "+f"(d[i][k]) :: "memory");
                    sc[4 * i] = d[i][0] + d[i][6]; sc[4 * i + 1] = d[i][1] + d[i][7]; sc[4 * i + 2] = d[i][8] + d[i][14]; sc[4 * i + 3] = d[i][9] + d[i][15];
                    asm volatile("st.async.weak.shared::cluster.mbarrier::complete_tx::bytes.v4.f32 [%0], {%1, %2, %3, %4}, [%5];"
                                 :: "r"(xr + i * 1024), "f"(sc[4 * i]), "f"(sc[4 * i + 1]), "f"(sc[4 * i + 2]), "f"(sc[4 * i + 3]), "r"(bsr) : "memory");
                }
                if (u8 == 128) TRACE_Q(56 + (n < 6 ? n : -40));
                if (n >= 3) mbar_wait(BAR(EB_UNIT0 + n - 3), 0);
                dlo += n == 5 ? -5 * 2048 : 2048;
                fb += 32; xr ^= 512; bsr += 16;
                pin(fb); pin(xr); pin(bsr);
                mbar_wait(sf, 0);
                const float4 x = ldsf4(xl), y = ldsf4(xl + 1024);
                sc[0] += x.x; sc[1] += x.y; sc[2] += x.z; sc[3] += x.w; sc[4] += y.x; sc[5] += y.y; sc[6] += y.z; sc[7] += y.w;
                float pr[8];
#pragma unroll
                for (int i = 0; i < 8; i++) pr[i] = ex2(sc[i] - m);
                float mx = fmaxf(fmaxf(fmaxf(sc[0], sc[1]), fmaxf(sc[2], sc[3])), fmaxf(fmaxf(sc[4], sc[5]), fmaxf(sc[6], sc[7])));
                if (__builtin_expect(__any_sync(0xffffffffu, mx > m), 0)) {
                    mx = fmaxf(mx, shx(mx, 1));
                    mx = fmaxf(mx, shx(mx, 2));
                    const float mn = fmaxf(m, ceilf(mx * 0.0625f) * 16.f);
                    l *= ex2(m - mn);
                    m = mn;
#pragma unroll
                    for (int i = 0; i < 8; i++) pr[i] = ex2(sc[i] - m);
                }
                stsf(ma, m);
                asm volatile("st.shared.v4.u32 [%0], {%1, %2, %3, %4};" :: "r"(pa), "r"(pack2(pr[0], pr[1])), "r"(pack2(pr[2], pr[3])),
                             "r"(pack2(pr[4], pr[5])), "r"(pack2(pr[6], pr[7])) : "memory");
                __syncwarp();
                if (lane == 0) mbar_arrive(sf + (PF0 - SF0) * 8);
                l += ((pr[0] + pr[1]) + (pr[2] + pr[3])) + ((pr[4] + pr[5]) + (pr[6] + pr[7]));
                xl ^= 512; sf += 16; ma += 256; pa += (n == 2 || n == 5) ? -8192 : 4096;
            }
            l += shx(l, 1);
            l += shx(l, 2);
            float2* mlx = (float2*)(sm + SM_MX + 2048) + wq4 * 8 + g;
            if (v == 0) { *mlx = make_float2(m, l); bar_arrive(11, 256); }
            else {
                mbar_wait(BAR(JD), 0);
                bar_sync(11, 256);
                const float2 o = *mlx;
                const float mn = fmaxf(m, o.x);
                l = l * ex2(m - mn) + o.y * ex2(o.x - mn);
                if ((wq4 >> 1) == rk) st_x4(gs + (B_ML + wq4 * 8 + g) * 4096 + (t >> 1) * 1024 + (j >> 1) * 8 + (t & 1) * 4, encf(mn), encf(l), 1u, 1u);
            }
        }
        const int pi = j < NFF ? rk * 128 + w8 * 16 + (lane >> 1) : ((j - J_RED) & 15) * 16 + (w8 & 1) * 8 + g;
        const uint32_t xw = *(const uint32_t*)(xin + 2 * pi);
        const uint32_t one = (g & 1) ? 0x3f800000u : 0x00003f80u;
        const uint32_t* pm = gs + near_off(B_MB, cls) + pi;
        {
            const uint32_t ab = sb + SM_U + B_WUV * 32768 + v * 4096 + a128;
            uint32_t pa = sb + SM_PB + wq4 * 320 + frag_off(64 * v + 32 * (g >> 2) + 16 * (t & 1) + 8 * (t >> 1) + 2 * (g & 3));
            uint32_t fa = sb + SM_PB + g * 320 + t * 16;
            const uint32_t* pe = gs + G_E1 + j * 8192 + (w8 >> 1) * 2048 + ((((cls >> 1) ^ (w8 >> 1)) & 1) << 10) + (((w8 & 1) * 16 + t) * 8 + g) * 4;
            uint32_t* p2 = gs + (B_E2 + (j >> 4)) * 4096 + (t >> 1) * 1024 + (j & 12) * 64 + w8 * 32 + (j & 3) * 8 + (g & 6) + (t & 1);
            pin(pa); pin(fa); pin(pe); pin(p2);
            const uint32_t mk = (g & 1) ? 0xffff0000u : 0x0000ffffu, m0 = (g & 2) ? 0u : mk, m1 = (g & 2) ? mk : 0u;
            uint4 pv[4];
            bool hv = false;
            bar_sync(3, 416);
            uint4 wa = lds128(sb + SM_W + (wq4 * 4 + t) * 16);
            uint32_t wb[8] = {wa.x & m0, wa.x & m1, wa.y & m0, wa.y & m1, wa.z & m0, wa.z & m1, wa.w & m0, wa.w & m1};
            pv[0] = pv[1] = pv[2] = pv[3] = make_uint4(0u, 0u, 0u, 0u);
            float e[4][4];
            auto wsum = [&]() {
#pragma unroll
                for (int i = 0; i < 4; i++) {
                    e[i][0] = e[i][1] = e[i][2] = e[i][3] = 0.f;
                    mma(e[i], pv[i].x, pv[i].y, pv[i].z, pv[i].w, wb[2 * i], wb[2 * i + 1]);
                }
            };
            poll<512, E1_SLEEP, true>(pv, pe, [&]() {
                if (!hv) {
                    hv = __all_sync(0xffffffffu, mbar_test(BAR(IT_WUV + t), 0));
                    if (hv) load8<true>(a, [&](int s) { return ab + (s >> 1) * 8192 + (s & 1) * 2048; });
                }
            }, wsum);
            if (lane == 0) TRACE_Q(48 + w8);
            if (u8 == 0) TRACE_Q(18);
            float lo, hi2;
            float2 inv;
#pragma unroll 1
            for (int pass = 0;; pass++) {
                const float r0 = (t & 2) ? (e[0][2] + e[1][2]) + (e[2][2] + e[3][2]) : (e[0][0] + e[1][0]) + (e[2][0] + e[3][0]);
                const float r1 = (t & 2) ? (e[0][3] + e[1][3]) + (e[2][3] + e[3][3]) : (e[0][1] + e[1][1]) + (e[2][1] + e[3][1]);
                const uint32_t hi = pack2(r0, r1);
                sts32(pa, hi); sts32(pa + 1280, pack2(r0 - bflo(hi), r1 - bfhi(hi)));
                if (!hv) {
#pragma unroll 1
                    for (int i = 0; i < 4; i++) mbar_wait(BAR(IT_WUV + i), 0);
                    load8<true>(a, [&](int s) { return ab + (s >> 1) * 8192 + (s & 1) * 2048; });
                    hv = true;
                }
                bar_sync(1, 256);
                if (u8 == 0) TRACE(19);
                ldfrag(b, fa);
                mma8(c, a, b);
                mbar_wait(BAR(WR), 0);
                asm volatile("ld.shared.v2.f32 {%0, %1}, [%2];" : "=f"(inv.x), "=f"(inv.y) : "r"(sb + SM_FQ) : "memory");
                quad_pair(c[0] + c[1], c[2] + c[3], t, lo, hi2);
                if (__builtin_expect(__all_sync(0xffffffffu, pass || __float_as_uint(inv.y) == 0), 1)) break;
                wa = lds128(sb + SM_W2 + (wq4 * 4 + t) * 16);
                wb[0] = wa.x & m0; wb[1] = wa.x & m1; wb[2] = wa.y & m0; wb[3] = wa.y & m1; wb[4] = wa.z & m0; wb[5] = wa.z & m1; wb[6] = wa.w & m0; wb[7] = wa.w & m1;
                wsum();
                bar_sync(1, 256);
            }
            if (!(g & 1)) st_x1(p2, enc(pack2(lo * inv.x, hi2 * inv.x)));
            bar_arrive(4, 416);
            if (u8 == 0) TRACE(20);
        }
        if (j < NFF) {
            const uint32_t* p3 = gs + near_off(B_E3 + rk * 2 + v, cls) + wq4 * 256 + t * 16 + g * 2;
            const int od = lane & 1;
            uint32_t za = sb + SM_FZ + od * 576 + frag_off(w8 * 32 + (lane & 30));
            uint32_t fa = sb + SM_FZ + (g & 3) * 576 + ((lane ^ j) & 16) * 16 + t * 16, ya = sb + SM_Y + u8 * 4;
            uint32_t mb[3];
            uint4 a2[8];
            poll<1024, MB_SLEEP>(mb, pm);
            const uint32_t kk = pack2(1.f + bflo(mb[2]), 1.f + bfhi(mb[2]));
            sts32(za + 2 * 576, od ? mb[1] : kk);
            uint2 e3[4] = {make_uint2(0u, 0u), make_uint2(0u, 0u), make_uint2(0u, 0u), make_uint2(0u, 0u)};
            uint32_t ra = peer_addr(sb + SM_RED + (rk * 2 + v) * 512 + ((wq4 & 1) * 16 + (t >> 1) * 8 + g) * 16 + (t & 1) * 8, wq4 >> 1), tbo = peer_addr(BAR(QB), wq4 >> 1);
            pin(za); pin(fa); pin(ya); pin(ra); pin(tbo);
            if (lane == 0) mbar_expect(BAR(QB), 256);
            const uint32_t gb = BAR(IT_X + v * 2), ab = sb + SM_U + (B_X + v) * 32768 + a128;
            bool early = false, early2 = false;
            auto ldw = [&]() {
                if (!early) {
                    early = __all_sync(0xffffffffu, mbar_test(gb, 0));
                    if (early) load8<true>(a, [&](int s) { return ab + s * 2048; });
                }
                if (!early2) {
                    early2 = __all_sync(0xffffffffu, mbar_test(gb + 8, 0));
                    if (early2) load8<true>(a2, [&](int s) { return ab + 16384 + s * 2048; });
                }
            };
            bar_sync(8, 384);
            float s0[4], s1[4];
            auto sum = [&]() {
                s0[0] = s0[1] = s0[2] = s0[3] = s1[0] = s1[1] = s1[2] = s1[3] = 0.f;
                mma(s0, e3[0].x, e3[0].y, e3[1].x, e3[1].y, one, one); mma(s1, e3[2].x, e3[2].y, e3[3].x, e3[3].y, one, one);
            };
            poll<256, 0, true>(e3, p3, ldw, sum);
            if (u8 == 0) TRACE(23);
            const float y0 = fmaf(bflo(mb[0]), (t & 2) ? s0[2] + s1[2] : s0[0] + s1[0], bflo(xw)), y1 = fmaf(bfhi(mb[0]), (t & 2) ? s0[3] + s1[3] : s0[1] + s1[1], bfhi(xw));
            stsf(ya, od ? y1 : y0);
            const float z0 = y0 * bflo(kk), z1 = y1 * bfhi(kk);
            const uint32_t zh = pack2(z0, z1);
            sts32(za, od ? pack2(z0 - bflo(zh), z1 - bfhi(zh)) : zh);
            bar_sync(7, 288);
            if (u8 == 0) TRACE(24);
            ldfrag(b, fa);
            if (!early) { mbar_wait(gb, 0); load8<true>(a, [&](int s) { return ab + s * 2048; }); }
            {
                float e[4][4];
#pragma unroll
                for (int s = 0; s < 16; s++) {
                    if (s == 8 && !early2) { mbar_wait(gb + 8, 0); load8<true>(a2, [&](int q) { return ab + 16384 + q * 2048; }); }
                    const uint4& x = s < 8 ? a[s] : a2[s & 7];
                    const uint4& y = b[(s >> 1) & 3];
                    float (&d)[4] = e[(s >> 3) * 2 + (s & 1)];
                    if (!(s & 6)) d[0] = d[1] = d[2] = d[3] = 0.f;
                    mma(d, x.x, x.y, x.z, x.w, (s & 1) ? y.z : y.x, (s & 1) ? y.w : y.y);
                }
                const bool hi = t >> 1;
                const float k0 = hi ? e[2][2] + e[3][2] : e[0][0] + e[1][0], k1 = hi ? e[2][3] + e[3][3] : e[0][1] + e[1][1];
                const float o0 = hi ? e[2][0] + e[3][0] : e[0][2] + e[1][2], o1 = hi ? e[2][1] + e[3][1] : e[0][3] + e[1][3];
                st_async2(ra, k0 + shx(o0, 2), k1 + shx(o1, 2), tbo);
            }
        } else if (j >= J_RED && j < J_END && w8 < 2) {
            uint32_t ga[1], e3[4];
            poll<0, MB_SLEEP>(ga, pm);
            bar_sync(8, 192);
            poll<64, 100>(e3, gs + near_off(B_E3 + (pi >> 6), cls) + (pi & 48) * 16 + t * 64 + (pi & 15));
            float y0 = (bflo(e3[0]) + bflo(e3[1])) + (bflo(e3[2]) + bflo(e3[3])), y1 = (bfhi(e3[0]) + bfhi(e3[1])) + (bfhi(e3[2]) + bfhi(e3[3]));
#pragma unroll
            for (int o = 1; o < 4; o <<= 1) { y0 += shx(y0, o); y1 += shx(y1, o); }
            const int col = g + (t & 1) * 8;
            y0 = __shfl_sync(0xffffffffu, (t & 1) ? fmaf(bfhi(ga[0]), y1, bfhi(xw)) : fmaf(bflo(ga[0]), y0, bflo(xw)), (col >> 1) * 4 + (col & 1));
            uint16_t* po = (uint16_t*)out + (j - J_RED) * 32 + w8 * 16 + col;
            const uint32_t* pe = gs + near_off(B_E5 + j - J_RED, cls) + t * 16 + w8 * 8 + g;
            pin(po);
            const uint32_t sel = (g & 2) ? 0x3f800000u : 0x00003f80u;
            uint32_t yv[NFF / 4 + 1];
            float e[4][4], gb = 0.f;
#pragma unroll
            for (int i = 0; i <= NFF / 4; i++) yv[i] = 0u;
#pragma unroll 1
            for (uint32_t it = 0;; it++) {
#pragma unroll
                for (int i = 0; i < NFF / 4; i++) if (!yv[i]) ld_x(yv[i], pe + i * 64);
                if (__all_sync(0xffffffffu, !yv[NFF / 4] && mbar_test(BAR(QB), 1))) {
                    yv[NFF / 4] = lds32(sb + SM_FV + 256 + w8 * 32 + (col >> 1) * 4);
                    gb = (col & 1) ? bfhi(yv[NFF / 4]) : bflo(yv[NFF / 4]);
                }
                if (it > SPIN_LIMIT) __trap();
#pragma unroll
                for (int i = 0; i < 4; i++) {
                    e[i][0] = e[i][1] = e[i][2] = e[i][3] = 0.f;
                    mma(e[i], yv[4 * i], yv[4 * i + 1], i < 3 ? yv[(4 * i + 2) % (NFF / 4)] : 0u, i < 3 ? yv[(4 * i + 3) % (NFF / 4)] : 0u, sel, sel);
                }
                if (__all_sync(0xffffffffu, mint<NFF / 4 + 1>(yv) != 0)) break;
            }
            if (u8 == 0) TRACE(26);
            const float s = ((e[0][0] + e[0][2]) + (e[1][0] + e[1][2])) + ((e[2][0] + e[2][2]) + (e[3][0] + e[3][2]));
            asm volatile("{\n.reg .pred p;\nsetp.lt.u32 p, %2, 2;\n@p st.global.u16 [%0], %1;\n}" :: "l"(po), "h"((uint16_t)pack2(fmaf(gb, s, y0), 0.f)), "r"(t) : "memory");
            asm volatile("{\n.reg .pred p;\nsetp.eq.f32 p, %0, 0f7F7FFFFF;\n@p nanosleep.u32 0;\n}" :: "f"(((e[0][1] + e[0][3]) + (e[1][1] + e[1][3])) + ((e[2][1] + e[2][3]) + (e[3][1] + e[3][3]))));
            if (u8 == 0) TRACE(27);
        }
    }
}

typedef CUresult (*EncFn)(CUtensorMap*, CUtensorMapDataType, cuuint32_t, void*, const cuuint64_t*, const cuuint64_t*,
                          const cuuint32_t*, const cuuint32_t*, CUtensorMapInterleave, CUtensorMapSwizzle,
                          CUtensorMapL2promotion, CUtensorMapFloatOOBfill);

void make_map(EncFn enc_fn, CUtensorMap* m, const void* p, cuuint64_t d0, cuuint64_t d1, cuuint64_t d2, cuuint64_t d3,
              cuuint64_t s1, cuuint64_t s2, cuuint64_t s3, cuuint32_t b0, cuuint32_t b1, cuuint32_t b2, cuuint32_t b3, CUtensorMapSwizzle sw) {
    const cuuint64_t dims[4] = {d0, d1, d2, d3}, strides[3] = {s1, s2, s3};
    const cuuint32_t box[4] = {b0, b1, b2, b3}, es[4] = {1, 1, 1, 1};
    enc_fn(m, CU_TENSOR_MAP_DATA_TYPE_BFLOAT16, 4, (void*)p, dims, strides, box, es,
           CU_TENSOR_MAP_INTERLEAVE_NONE, sw, CU_TENSOR_MAP_L2_PROMOTION_L2_128B, CU_TENSOR_MAP_FLOAT_OOB_FILL_NONE);
}

uint32_t* scratch = nullptr;

struct Tune { const char* win; const char* late; int tau, t_off; const char* tail[3][4]; };
Tune tune = {"77777777755555555555555555555555555555544",
             "00000000000000888888888888888888888888888", 322, -380,
             {{"VVVVOOOOguguDDDD", "zzzzzzzzzzzzzzzz", "7777aaaaaaaa6789", "97fl98o7d77b777b"},
              {"VMVMVVOOOO", "zzzzzzzzzz", "9999999999", "4ab8c9a7j7"},
              {"VVVVOOOOMM", "zzzzzzzzzz", "aaaaaaaa88", "b33336aco3"}}};
bool ready = false;

}

extern "C" void kernel_launch(void* const* d_in, const int* in_sizes, int n_in, void* d_out, int out_size) {
    (void)in_sizes; (void)n_in; (void)out_size;
    static Maps maps;
    static const void* cached[12] = {};
    bool same = ready;
    for (int i = 0; i < 12 && same; i++) same = cached[i] == d_in[i];
    if (!same) {
        void* fn = nullptr;
        cudaDriverEntryPointQueryResult qr;
        cudaGetDriverEntryPoint("cuTensorMapEncodeTiled", &fn, cudaEnableDefault, &qr);
        EncFn e = (EncFn)fn;
        const CUtensorMapSwizzle S128 = CU_TENSOR_MAP_SWIZZLE_128B;
        make_map(e, &maps.m[MP_WQ], d_in[2], 64, 512, 64, 1, 8192, 128, 8192, 64, 64, 1, 1, S128);
        make_map(e, &maps.m[MP_WUK], d_in[3], 64, 512, 64, 1, 8192, 128, 8192, 64, 64, 1, 1, S128);
        make_map(e, &maps.m[MP_CKV], d_in[1], 64, 8, 8, 4096, 1024, 128, 8192, 64, 8, 4, 2, S128);
        make_map(e, &maps.m[MP_MODB], d_in[11], 3072, 512, 1, 1, 6144, 6144, 6144, 64, 128, 1, 1, S128);
        make_map(e, &maps.m[MP_WUV], d_in[4], 64, 512, 64, 1, 8192, 128, 8192, 64, 32, 2, 1, S128);
        make_map(e, &maps.m[MP_WO], d_in[5], 512, 4096, 1, 1, 1024, 1024, 1024, 64, 64, 1, 1, S128);
        make_map(e, &maps.m[MP_GATE], d_in[7], 1792, 512, 1, 1, 3584, 3584, 3584, 64, 128, 1, 1, S128);
        make_map(e, &maps.m[MP_UP], d_in[8], 1792, 512, 1, 1, 3584, 3584, 3584, 64, 128, 1, 1, S128);
        make_map(e, &maps.m[MP_DOWN], d_in[9], 64, 1792, 8, 1, 1024, 128, 1024, 64, 32, 2, 1, S128);
        for (int r = 0; r < 3; r++) {
            int ids[58], cnt[128] = {}, tn = tune.t_off - (W0 - 1) * tune.tau;
            uint2* sc = maps.sched[r];
            auto dig = [](char ch) { return ch >= 'a' ? ch - 'a' + 10 : ch >= 'A' ? ch - 'A' + 36 : ch - '0'; };
            for (int i = 0; i < 58; i++) sc[i] = make_uint2(0u, 0u);
            for (int i = 0;; i++) {
                int id = i, buf, dep, w, wl;
                if (i < IT_WUV) {
                    const int u = (i - IT_CKV) >> 2;
                    buf = i < IT_CKV ? 4 + ((i - 1) >> 2) : u % 6;
                    dep = i < IT_CKV || u < 4 ? -1 : u < 6 ? EB_WQ + u - 4 : EB_UNIT0 + u - 6;
                    w = dig(tune.win[i]); wl = dig(tune.late[i]);
                    if (i) tn += tune.tau;
                } else {
                    const char ch = tune.tail[r][0][i - IT_WUV];
                    if (!ch) break;
                    buf = ch == 'V' ? B_WUV : ch == 'O' ? B_WO : ch == 'D' ? B_DN : ch == 'u' ? B_X + 1 : B_X;
                    id = (ch == 'V' ? IT_WUV : ch == 'O' ? IT_WO : ch == 'D' ? IT_DOWN : ch == 'u' ? IT_X + 2 : IT_X) + cnt[(int)ch]++;
                    dep = EB_UNIT0 + (buf < 2 ? buf + 6 : buf);
                    w = dig(tune.tail[r][1][i - IT_WUV]); wl = dig(tune.tail[r][2][i - IT_WUV]);
                    tn += (r == 2 ? 64 : 32) * dig(tune.tail[r][3][i - IT_WUV]);
                }
                if (id < IT_X || id >= IT_DOWN ? (id - 1) & 3 : (id - IT_X) & 1) dep = -1;
                ids[i] = id;
                auto back = [&](int d) { return i < d ? 0 : (ids[i - d] && ids[i - d] <= NCP ? 1 : ids[i - d]) + 1; };
                sc[i].x = id | (buf * 4 + (id < IT_X || id >= IT_DOWN ? (id - 1) & 3 : ((id - IT_X) & 1) * 2)) << 6 | (dep + 1) << 11 | (w > 32 ? NEVER + 1 : back(w)) << 18 | (wl ? back(wl) : 0) << 25;
                const int mp = id < IT_CKV ? MP_WQ + ((id - 1) >> 2) : id < IT_WUV ? MP_CKV : id < IT_WO ? MP_WUV : id < IT_X ? MP_WO
                             : id >= IT_DOWN ? MP_DOWN : r ? MP_MODB : MP_GATE + ((id - IT_X) >> 1);
                const int step = mp == MP_CKV ? id - IT_CKV : mp == MP_WUV ? (id - IT_WUV) * 2 : mp == MP_DOWN ? id - IT_DOWN : id < IT_X ? (id - 1) & 3 : ((id - IT_X) & 1) * 2;
                sc[i].y = (tn & 0xffff) | (mp & 15) << 16 | step << 20;
            }
        }
        cudaGetSymbolAddress((void**)&scratch, g_scratch);
        scratch = (uint32_t*)(((uintptr_t)scratch + (2u << 20) - 1) & ~(uintptr_t)((2u << 20) - 1));
        cudaFuncSetAttribute(fused_kernel, cudaFuncAttributeMaxDynamicSharedMemorySize, SM_TOTAL);
        for (int i = 0; i < 12; i++) cached[i] = d_in[i];
        ready = true;
    }
    const First f = {{(const uint8_t*)d_in[2], (const uint8_t*)d_in[11]}, {(const __nv_bfloat16*)d_in[0], (const __nv_bfloat16*)d_in[10]}};
    fused_kernel<<<NCTA, NTHREADS, SM_TOTAL>>>(f, (__nv_bfloat16*)d_out, scratch, maps);
}
```

```cpp
#include <cuda_runtime.h>
#include <cuda_bf16.h>
#include <cuda.h>
#include <stdint.h>
#include <limits.h>

namespace {

constexpr int NCTA = 128;
constexpr int NTHREADS = 512;
constexpr int NUNITS = 8;
constexpr int NFF = 56, J_RED = 104, J_END = 120;
constexpr uint32_t SPIN_LIMIT = 1u << 22;

#define NEAR_CLK 390
#define E1_EARLY 50
#define STAG 300
#define NUMA 1
#define NPROBE 5
#define NCP 2
#define W0 4
#define RD_ITEM 15
#define JAN_SLEEP 100
#define RD_SLEEP 400
#define HA_DELAY 200
#define H_SLEEP 100
#define QA_DELAY 600
#define QA_SLEEP 200
#define ML_DELAY 300
#define E1_SLEEP 50
#define MB_SLEEP 100
constexpr int B_WUV = 2, B_WO = 3, B_X = 4  , B_DN = 0;

constexpr int SM_U = 0;
constexpr int SM_XA = 6 * 32768;
constexpr int SM_XB = SM_XA + 12288;
constexpr int SM_MX = SM_XB + 16384;
constexpr int SM_FZ = SM_XB + 8192;
constexpr int SM_PB = SM_XB;
constexpr int SM_Y = SM_XB + 12288;
constexpr int SM_RED = SM_XB + 4096;
constexpr int SM_FS = SM_XB + 20480;
constexpr int SM_FV = SM_FS + 1024;
constexpr int SM_QX = SM_XA + 8192;
constexpr int SM_FQ = SM_FV + 512;
constexpr int SM_CLS = SM_FQ + 128;
constexpr int SM_W = SM_FQ + 256;
constexpr int SM_W2 = SM_MX + 2304;
constexpr int SM_SCR = SM_XA + 9216;
constexpr int SM_BAR = SM_W + 256;
constexpr int SM_TOTAL = SM_BAR + 1024;
static_assert(SM_TOTAL <= 232448, "smem");

enum { IT_MODA = 0, IT_WQ = 1, IT_WUK = 5, IT_CKV = 9, IT_WUV = 41, IT_WO = 45, IT_X = 49  , IT_DOWN = 53, NITEMS = 57,
       NEVER = 63,
       SF0 = 64,
       PF0 = 80,
       EB_UNIT0 = 96, MBB = 103,
       EB_WQ = 104, EB_WUK, QT, QB, JD, WR };

enum { MP_WQ = 0, MP_WUK, MP_CKV, MP_WUV, MP_DOWN, MP_WO, MP_GATE, MP_UP, MP_MODB, NMAPS };
struct First { const uint8_t* w[2]; const __nv_bfloat16* v[2]; };
struct Maps { CUtensorMap m[NMAPS]; uint2 sched[3][58]; };

enum { B_HA = 0,
       B_MB = 6,
       B_RD = 7,
       B_E2 = 8,
       B_QA = 16,
       B_ML = 32,
       B_E5 = 64,
       B_E3 = 80,
       B_PR = 96,
       B_TR = 100 };
constexpr int G_E1 = 1 << 19;
__device__ __align__(1024) uint32_t g_scratch[(8 << 20) / 4];

#define TRACE(slot) do {} while (0)
#define TRACE_Q(slot) do {} while (0)
#define TRACE_GT(slot) do {} while (0)

__device__ __forceinline__ uint32_t s2u(const void* p) { return (uint32_t)__cvta_generic_to_shared(p); }
__device__ __forceinline__ void mbar_init(uint32_t b, int c) { asm volatile("mbarrier.init.shared::cta.b64 [%0], %1;" :: "r"(b), "r"(c) : "memory"); }
__device__ __forceinline__ void mbar_expect(uint32_t b, uint32_t bytes) { asm volatile("mbarrier.arrive.expect_tx.shared::cta.b64 _, [%0], %1;" :: "r"(b), "r"(bytes) : "memory"); }
__device__ __forceinline__ void mbar_arrive(uint32_t b) { asm volatile("mbarrier.arrive.shared::cta.b64 _, [%0];" :: "r"(b) : "memory"); }
__device__ __forceinline__ void mbar_wait(uint32_t b, uint32_t ph) {
    asm volatile("{\n.reg .pred p;\nW: mbarrier.try_wait.parity.shared::cta.b64 p, [%0], %1;\n@!p bra W;\n}" :: "r"(b), "r"(ph) : "memory");
}
__device__ __forceinline__ void mbar_waitb(uint32_t b, uint32_t ph) {
    asm volatile("{\n.reg .pred p;\n.reg .u32 n;\nmov.u32 n, 0;\n"
                 "W: mbarrier.try_wait.parity.shared::cta.b64 p, [%0], %1;\n@p bra D;\n"
                 "add.u32 n, n, 1;\nsetp.lt.u32 p, n, 0x100000;\n@p bra W;\ntrap;\nD:\n}" :: "r"(b), "r"(ph) : "memory");
}
__device__ __forceinline__ uint32_t mbar_test(uint32_t b, uint32_t ph) {
    uint32_t ok;
    asm volatile("{\n.reg .pred p;\nmbarrier.test_wait.parity.shared::cta.b64 p, [%1], %2;\nselp.u32 %0, 1, 0, p;\n}" : "=r"(ok) : "r"(b), "r"(ph) : "memory");
    return ok;
}
__device__ __forceinline__ void bar_sync(int id, int n) { asm volatile("bar.sync %0, %1;" :: "r"(id), "r"(n) : "memory"); }
__device__ __forceinline__ void bar_arrive(int id, int n) { asm volatile("bar.arrive %0, %1;" :: "r"(id), "r"(n) : "memory"); }
__device__ __forceinline__ uint32_t peer_addr(uint32_t a, uint32_t rank) { uint32_t r; asm("mapa.shared::cluster.u32 %0, %1, %2;" : "=r"(r) : "r"(a), "r"(rank)); return r; }
__device__ __forceinline__ void st_async2(uint32_t a, float x, float y, uint32_t bar) {
    asm volatile("st.async.weak.shared::cluster.mbarrier::complete_tx::bytes.v2.f32 [%0], {%1, %2}, [%3];" :: "r"(a), "f"(x), "f"(y), "r"(bar) : "memory");
}
__device__ __forceinline__ uint32_t gtime() { uint32_t t; asm volatile("mov.u32 %0, %%globaltimer_lo;" : "=r"(t)); return t; }
__device__ __forceinline__ void fence_gpu() { asm volatile("fence.acq_rel.gpu;" ::: "memory"); }

__device__ __forceinline__ uint32_t enc(uint32_t b) { uint32_t r; asm("max.u32 %0, %1, 1;" : "=r"(r) : "r"(b)); return r; }
__device__ __forceinline__ uint32_t encf(float f) { return enc(__float_as_uint(f)); }
__device__ __forceinline__ void st_x1(uint32_t* p, uint32_t v) { asm volatile("st.relaxed.gpu.global.u32 [%0], %1;" :: "l"(p), "r"(v) : "memory"); }
__device__ __forceinline__ void st_x4(void* p, uint32_t a, uint32_t b, uint32_t c, uint32_t d) {
    asm volatile("st.relaxed.gpu.global.v4.u32 [%0], {%1, %2, %3, %4};" :: "l"(p), "r"(a), "r"(b), "r"(c), "r"(d) : "memory");
}
__device__ __forceinline__ void st2_x1(uint32_t* p, uint32_t v) { st_x1(p, v); st_x1(p + 1024, v); }
__device__ __forceinline__ void st2_x4(uint32_t* p, uint32_t a, uint32_t b, uint32_t c, uint32_t d) { st_x4(p, a, b, c, d); st_x4(p + 1024, a, b, c, d); }
__device__ __forceinline__ int near_off(int b, uint32_t cls) { return b * 4096 + (((__popc(b & 0x2C) ^ cls) & 1) << 10); }
__device__ __forceinline__ void ld_x(uint32_t& v, const void* p) { asm volatile("ld.relaxed.gpu.global.u32 %0, [%1];" : "=r"(v) : "l"(p) : "memory"); }
__device__ __forceinline__ void ld_x(uint4& v, const void* p) {
    asm volatile("ld.relaxed.gpu.global.v4.u32 {%0, %1, %2, %3}, [%4];" : "=r"(v.x), "=r"(v.y), "=r"(v.z), "=r"(v.w) : "l"(p) : "memory");
}
__device__ __forceinline__ void ld_x(uint2& v, const void* p) { asm volatile("ld.relaxed.gpu.global.v2.u32 {%0, %1}, [%2];" : "=r"(v.x), "=r"(v.y) : "l"(p) : "memory"); }
__device__ __forceinline__ uint32_t minw(uint32_t v) { return v; }
__device__ __forceinline__ uint32_t minw(const uint2& v) { return min(v.x, v.y); }
__device__ __forceinline__ uint32_t minw(const uint4& v) { return min(__vimin3_u32(v.x, v.y, v.z), v.w); }
template <int N> __device__ __forceinline__ uint32_t mint(const uint32_t* m) {
    if constexpr (N == 1) return m[0];
    else if constexpr (N == 2) return min(m[0], m[1]);
    else return __vimin3_u32(mint<(N + 2) / 3>(m), mint<(N + 1) / 3>(m + (N + 2) / 3), mint<N / 3>(m + (N + 2) / 3 + (N + 1) / 3));
}

template <int STRIDE, int S4 = 4 * STRIDE, typename T, int N>
__device__ __forceinline__ void poll_start(T (&v)[N], const void* base) {
#pragma unroll
    for (int i = 0; i < N; i++) ld_x(v[i], (const uint8_t*)base + (i & 3) * STRIDE + (i >> 2) * S4);
}
struct Nop { __device__ void operator()() const {} };
template <int STRIDE, int SLEEP, bool STARTED = false, int S4 = 4 * STRIDE, typename T, int N, typename F = Nop, typename G = Nop>
__device__ __forceinline__ void poll(T (&v)[N], const void* base, F idle = F(), G ahead = G()) {
    if (!STARTED) { poll_start<STRIDE, S4>(v, base); idle(); }
#pragma unroll 1
    for (uint32_t it = 0;; it++) {
        uint32_t m[N];
        ahead();
#pragma unroll
        for (int i = 0; i < N; i++) m[i] = minw(v[i]);
        if (__all_sync(0xffffffffu, mint<N>(m) != 0)) break;
        if (SLEEP && it > 0) __nanosleep(SLEEP);
#pragma unroll
        for (int i = 0; i < N; i++) if (!m[i]) ld_x(v[i], (const uint8_t*)base + (i & 3) * STRIDE + (i >> 2) * S4);
        idle();
        if (it > SPIN_LIMIT) __trap();
    }
}

__device__ __forceinline__ float bflo(uint32_t w) { return __uint_as_float(w << 16); }
__device__ __forceinline__ float bfhi(uint32_t w) { return __uint_as_float(w & 0xffff0000u); }
__device__ __forceinline__ uint32_t pack2(float lo, float hi) {
    uint32_t r; asm("cvt.rn.bf16x2.f32 %0, %1, %2;" : "=r"(r) : "f"(hi), "f"(lo)); return r;
}
__device__ __forceinline__ float rbf(float x) { return __uint_as_float(pack2(0.f, x)); }
__device__ __forceinline__ float ex2(float x) { float r; asm("ex2.approx.ftz.f32 %0, %1;" : "=f"(r) : "f"(x)); return r; }
__device__ __forceinline__ float shx(float v, int m) { return __shfl_xor_sync(0xffffffffu, v, m); }
__device__ __forceinline__ uint4 lds128(uint32_t a) { uint4 v; asm volatile("ld.shared.v4.u32 {%0, %1, %2, %3}, [%4];" : "=r"(v.x), "=r"(v.y), "=r"(v.z), "=r"(v.w) : "r"(a) : "memory"); return v; }
__device__ __forceinline__ uint32_t lds32(uint32_t a) { uint32_t v; asm volatile("ld.shared.u32 %0, [%1];" : "=r"(v) : "r"(a) : "memory"); return v; }
__device__ __forceinline__ void sts32(uint32_t a, uint32_t v) { asm volatile("st.shared.u32 [%0], %1;" :: "r"(a), "r"(v) : "memory"); }
__device__ __forceinline__ void sts16(uint32_t a, uint32_t v) { asm volatile("st.shared.u16 [%0], %1;" :: "r"(a), "h"((uint16_t)v) : "memory"); }
__device__ __forceinline__ int frag_off(int k) { return (k >> 5) * 64 + ((k >> 1) & 3) * 16 + ((k >> 4) & 1) * 8 + ((k >> 3) & 1) * 4 + (k & 1) * 2; }

template <bool TRANS>
__device__ __forceinline__ uint4 ldsm(uint32_t a) {
    uint4 r;
    if (TRANS) asm volatile("ldmatrix.sync.aligned.m8n8.x4.trans.shared.b16 {%0, %1, %2, %3}, [%4];" : "=r"(r.x), "=r"(r.y), "=r"(r.z), "=r"(r.w) : "r"(a) : "memory");
    else asm volatile("ldmatrix.sync.aligned.m8n8.x4.shared.b16 {%0, %1, %2, %3}, [%4];" : "=r"(r.x), "=r"(r.y), "=r"(r.z), "=r"(r.w) : "r"(a) : "memory");
    return r;
}
__device__ __forceinline__ void mma(float (&c)[4], uint32_t a0, uint32_t a1, uint32_t a2, uint32_t a3, uint32_t b0, uint32_t b1) {
    asm volatile("mma.sync.aligned.m16n8k16.row.col.f32.bf16.bf16.f32 {%0,%1,%2,%3}, {%4,%5,%6,%7}, {%8,%9}, {%0,%1,%2,%3};"
                 : "+f"(c[0]), "+f"(c[1]), "+f"(c[2]), "+f"(c[3]) : "r"(a0), "r"(a1), "r"(a2), "r"(a3), "r"(b0), "r"(b1));
}
template <bool TRANS, typename F>
__device__ __forceinline__ void load8(uint4 (&a)[8], F addr) {
    __syncwarp();
#pragma unroll
    for (int s = 0; s < 8; s++) a[s] = ldsm<TRANS>(addr(s));
}
__device__ __forceinline__ void mma8(float (&c)[4], const uint4 (&a)[8], const uint4 (&b)[4]) {
    float e[4][4];
#pragma unroll
    for (int s = 0; s < 8; s++) {
        if (s < 4) e[s][0] = e[s][1] = e[s][2] = e[s][3] = 0.f;
        mma(e[s & 3], a[s].x, a[s].y, a[s].z, a[s].w, (s & 1) ? b[s >> 1].z : b[s >> 1].x, (s & 1) ? b[s >> 1].w : b[s >> 1].y);
    }
#pragma unroll
    for (int i = 0; i < 4; i++) c[i] = (e[0][i] + e[1][i]) + (e[2][i] + e[3][i]);
}
__device__ __forceinline__ void ldfrag(uint4 (&b)[4], uint32_t a) {
    asm volatile("ld.shared.v4.u32 {%0,%1,%2,%3}, [%16];\nld.shared.v4.u32 {%4,%5,%6,%7}, [%16+64];\n"
                 "ld.shared.v4.u32 {%8,%9,%10,%11}, [%16+128];\nld.shared.v4.u32 {%12,%13,%14,%15}, [%16+192];\n"
                 : "=r"(b[0].x), "=r"(b[0].y), "=r"(b[0].z), "=r"(b[0].w), "=r"(b[1].x), "=r"(b[1].y), "=r"(b[1].z), "=r"(b[1].w),
                   "=r"(b[2].x), "=r"(b[2].y), "=r"(b[2].z), "=r"(b[2].w), "=r"(b[3].x), "=r"(b[3].y), "=r"(b[3].z), "=r"(b[3].w) : "r"(a) : "memory");
}
__device__ __forceinline__ void quad_pair(float x, float y, int t, float& lo, float& hi) {
    const float k = ((t & 1) ? y : x) + shx((t & 1) ? x : y, 1);
    lo = k + shx(k, 2); hi = shx(k, 4) + shx(k, 6);
}
__device__ __forceinline__ void pin(uint32_t& x) { asm volatile("" : "+r"(x)); }
template <typename T> __device__ __forceinline__ void pin(T*& x) { asm volatile("" : "+l"(x)); }
__device__ __forceinline__ float4 ldsf4(uint32_t a) { const uint4 v = lds128(a); return make_float4(__uint_as_float(v.x), __uint_as_float(v.y), __uint_as_float(v.z), __uint_as_float(v.w)); }
__device__ __forceinline__ float sum4(const float4& f) { return (f.x + f.y) + (f.z + f.w); }
__device__ __forceinline__ void stsf(uint32_t a, float v) { sts32(a, __float_as_uint(v)); }

__device__ __forceinline__ void wg_fence() { asm volatile("wgmma.fence.sync.aligned;" ::: "memory"); }
__device__ __forceinline__ void wg_commit() { asm volatile("wgmma.commit_group.sync.aligned;" ::: "memory"); }
__device__ __forceinline__ void wg_wait1() { asm volatile("wgmma.wait_group.sync.aligned 1;" ::: "memory"); }
__device__ __forceinline__ void wg_wait0() { asm volatile("wgmma.wait_group.sync.aligned 0;" ::: "memory"); }
#define R8(o) "+f"(d[o]), "+f"(d[o + 1]), "+f"(d[o + 2]), "+f"(d[o + 3]), "+f"(d[o + 4]), "+f"(d[o + 5]), "+f"(d[o + 6]), "+f"(d[o + 7])
__device__ __forceinline__ void wgmma_rs_n32(float (&d)[16], const uint4& a, uint64_t db, int acc) {
    asm volatile("{\n.reg .pred p;\nsetp.ne.b32 p, %21, 0;\n"
        "wgmma.mma_async.sync.aligned.m64n32k16.f32.bf16.bf16 "
        "{%0,%1,%2,%3,%4,%5,%6,%7,%8,%9,%10,%11,%12,%13,%14,%15}, {%16,%17,%18,%19}, %20, p, 1, 1, 0;\n}"
        : R8(0), R8(8) : "r"(a.x), "r"(a.y), "r"(a.z), "r"(a.w), "l"(db), "r"(acc));
}
#define PV_LO "{%0,%1,%2,%3,%4,%5,%6,%7,%8,%9,%10,%11,%12,%13,%14,%15,%16,%17,%18,%19,%20,%21,%22,%23,%24,%25,%26,%27,%28,%29,%30,%31,%32,%33,%34,%35,%36,%37,%38,%39,%40,%41,%42,%43,%44,%45,%46,%47,%48,%49,%50,%51,%52,%53,%54,%55,%56,%57,%58,%59,%60,%61,%62,%63}, "
#define PV_HI "{%64,%65,%66,%67,%68,%69,%70,%71,%72,%73,%74,%75,%76,%77,%78,%79,%80,%81,%82,%83,%84,%85,%86,%87,%88,%89,%90,%91,%92,%93,%94,%95,%96,%97,%98,%99,%100,%101,%102,%103,%104,%105,%106,%107,%108,%109,%110,%111,%112,%113,%114,%115,%116,%117,%118,%119,%120,%121,%122,%123,%124,%125,%126,%127}, "
__device__ __forceinline__ void wgmma_pv(float (&d)[128], const uint4& a, uint32_t blo, int acc) {
    asm volatile("{\n.reg .pred p;\n.reg .b32 u0, u1, u2, u3, t;\n.reg .b64 d0, d1, d2, d3;\nsetp.ne.b32 p, %133, 0;\n"
        "mov.b64 d0, {%132, 0x40000100};\nadd.u32 t, %132, 512;\nmov.b64 d1, {t, 0x40000100};\n"
        "add.u32 t, %132, 128;\nmov.b64 d2, {t, 0x40000100};\nadd.u32 t, %132, 640;\nmov.b64 d3, {t, 0x40000100};\n"
        "wgmma.fence.sync.aligned;\n"
        "wgmma.mma_async.sync.aligned.m64n128k16.f32.bf16.bf16 " PV_LO "{%128, u0, %129, u1}, d0, p, 1, 1, 1;\n"
        "wgmma.mma_async.sync.aligned.m64n128k16.f32.bf16.bf16 " PV_LO "{%130, u2, %131, u3}, d1, 1, 1, 1, 1;\n"
        "wgmma.commit_group.sync.aligned;\n"
        "wgmma.mma_async.sync.aligned.m64n128k16.f32.bf16.bf16 " PV_HI "{%128, u0, %129, u1}, d2, p, 1, 1, 1;\n"
        "wgmma.mma_async.sync.aligned.m64n128k16.f32.bf16.bf16 " PV_HI "{%130, u2, %131, u3}, d3, 1, 1, 1, 1;\n"
        "wgmma.commit_group.sync.aligned;\n}"
        : R8(0), R8(8), R8(16), R8(24), R8(32), R8(40), R8(48), R8(56), R8(64), R8(72), R8(80), R8(88), R8(96), R8(104), R8(112), R8(120)
        : "r"(a.x), "r"(a.y), "r"(a.z), "r"(a.w), "r"(blo), "r"(acc) : "memory");
}

template <int NW>
__device__ __forceinline__ void ln_stats(float s, float q, float sh, float* scr, int w, int lane, int bar, float& mean_b, float& sd_b) {
#pragma unroll
    for (int o = 16; o; o >>= 1) { s += shx(s, o); q += shx(q, o); }
    constexpr float n = 512.f / NW;
    if (lane == 0) { scr[w] = sh + s * (1.f / n); scr[NW + w] = q - s * s * (1.f / n); }
    bar_sync(bar, NW * 32);
    float mu = 0.f, m2 = 0.f;
#pragma unroll
    for (int i = 0; i < NW; i++) { mu += scr[i]; m2 += scr[NW + i]; }
    mu *= 1.f / NW;
#pragma unroll
    for (int i = 0; i < NW; i++) { const float d = scr[i] - mu; m2 = fmaf(n * d, d, m2); }
    mean_b = rbf(mu);
    sd_b = rbf(sqrtf(rbf(rbf(fmaxf(m2, 0.f) * (1.f / 512.f)) + 1e-5f)));
}
__device__ __forceinline__ float ln_mod(float x, float mean_b, float sd_b, float c, float s) {
    return rbf(rbf(__fdividef(rbf(x - mean_b), sd_b)) * rbf(1.f + c)) + s;
}

__global__ void __cluster_dims__(2, 1, 1) __launch_bounds__(NTHREADS, 1)
fused_kernel(const __grid_constant__ First F, __nv_bfloat16* __restrict__ out, uint32_t* __restrict__ gs, const __grid_constant__ Maps M) {
    extern __shared__ __align__(1024) uint8_t sm[];
    const uint32_t sb = s2u(sm);
    const int tid = threadIdx.x, lane = tid & 31;
    const int j = blockIdx.x, rk = j & 1;
    const int g = lane >> 2, t = lane & 3;
    const int r8 = lane & 7, lb3 = (lane >> 3) & 1, lb4 = lane >> 4;
    uint64_t pol;
    asm("createpolicy.fractional.L2::evict_first.b64 %0, 1.0;" : "=l"(pol));
    {
        auto cpa = [&](uint32_t d, const uint8_t* s) {
            asm volatile("cp.async.cg.shared.global.L2::cache_hint.L2::128B [%0], [%1], 16, %2;" :: "r"(d), "l"(s), "l"(pol) : "memory");
        };
        const uint32_t ut = threadIdx.x, uj = blockIdx.x;
        const uint8_t* w = F.w[ut >= 128];
        if (ut < 128) {
            const uint32_t dq = (sb + ut * 16) ^ ((ut * 2) & 0x70);
            const uint8_t* sq = w + (uint32_t)(((uj & 1) * 256 + (ut >> 3)) * 8192 + (uj >> 1) * 128 + (ut & 7) * 16);
#pragma unroll
            for (int i = 0; i < 4 * NCP; i++) cpa(dq + 4 * 32768 + i * 2048, sq + i * 131072);
        } else if (ut < 384) {
            const uint32_t dm = (sb + ut * 16) ^ ((ut * 2) & 0x10);
            const uint8_t* sa = w + (uint32_t)(((uj >> 5) * 128 + (ut >> 1) - 64) * 6144 + (uj & 31) * 32 + (ut & 1) * 16);
            cpa(dm + SM_XA - 2048, sa); cpa(dm + SM_XA + 2048, sa + 1024);
        }
        else if (ut == 480 && uj < 64) asm volatile("prefetch.global.L2 [%0];" :: "l"(F.v[(uj >> 3) & 1] + (uj & 7) * 64));
    }
    const int warp = __shfl_sync(0xffffffffu, tid >> 5, 0);
    const __nv_bfloat16* const xin = F.v[0];
    uint32_t* const pl = gs + (warp < 2 ? (B_PR + (j >> 5)) * 4096 + (j & 31) * 32 : G_E1 + j * 8192) + (warp & 1) * 1024 + lane;
    if (warp < 4) st_x1(pl, 1u);
    auto BAR = [&](int i) -> uint32_t { return sb + SM_BAR + i * 8; };
    const uint32_t a16 = (r8 + 8 * lb4) * 32 + ((lb3 ^ (r8 >> 2)) * 16);
    const uint32_t a128 = (r8 + 8 * lb4) * 128 + ((((warp & 3) * 2 + lb3) ^ r8) * 16);
    auto ldcls = [&]() -> uint32_t { return *(const volatile uint32_t*)(sm + SM_CLS); };
    auto clear_head = [&]() {
        st2_x1(gs + (B_HA + ((j >> 4) & 1) * 2 + lb4) * 4096 + (j >> 5) * 256 + (j & 15) * 16 + (lane & 15), 0u);
        st2_x4(gs + (B_QA + rk * 8 + ((j >> 1) & 1) * 4 + (j >> 5)) * 4096 + g * 128 + ((j >> 2) & 7) * 16 + t * 4, 0u, 0u, 0u, 0u);
        if (lane < 8) st2_x1(gs + B_RD * 4096 + j * 8 + lane, 0u);
    };
    auto tma = [&](uint32_t dst, const CUtensorMap* mp, uint32_t bar, int c0, int c1, int c2, int c3) {
        asm volatile("{\n.reg .pred p;\nelect.sync _|p, 0xffffffff;\n"
                     "@p cp.async.bulk.tensor.4d.shared::cluster.global.mbarrier::complete_tx::bytes.L2::cache_hint [%0], [%1, {%3, %4, %5, %6}], [%2], %7;\n}"
                     :: "r"(dst), "l"(mp), "r"(bar), "r"(c0), "r"(c1), "r"(c2), "r"(c3), "l"(pol) : "memory");
    };
    if (warp <= 12 || warp == 15) {
        const int grp = warp == 12 ? 0 : warp == 15 ? 13 : warp + 1;
        const uint32_t cnt = grp < 10 ? 1 : grp < 13 ? 4 : 8;
        if (lane == 0) {
#pragma unroll
            for (int i = 0; i < 8; i++) mbar_init(BAR(grp * 8 + i), (i < 2 && grp == 0) ? (i ? 128 : 256) : cnt);
        }
        __syncwarp();
        if (grp < 10 && lane < 8 && (grp || lane > NCP)) mbar_expect(BAR(grp * 8 + lane), grp >= 8 ? 4096 : (uint32_t)(grp * 8 + lane - IT_X) < 4 ? 16384 : 8192);
        asm volatile("fence.mbarrier_init.release.cluster;" ::: "memory");
        __syncwarp();
        if (warp == 12) {
#pragma unroll
            for (int i = NCP + 1; i < W0; i++) tma(sb + (15 + i) * 8192, &M.m[MP_WQ], BAR(i), 0, rk * 256 + (i - 1) * 64, j >> 1, 0);
        }
    } else if (warp == 13) {
        if (lane < NMAPS) asm volatile("prefetch.tensormap [%0];" :: "l"(&M.m[lane]) : "memory");
    } else if (warp == 14) {
        clear_head();
    }
    __syncthreads();
    uint32_t in1 = 0, in2 = 0;
    if (warp < 4) { in1 = *(const uint32_t*)(xin + 2 * tid); in2 = *(const uint32_t*)(xin + 256 + 2 * tid); }
    else if (warp < 12) in1 = *(const uint32_t*)(F.v[1] + 2 * (tid - 128));
    if (warp < 12) asm volatile("cp.async.mbarrier.arrive.noinc.shared::cta.b64 [%0];" :: "r"(BAR(warp < 4)) : "memory");
    asm volatile("barrier.cluster.arrive.relaxed.aligned;" ::: "memory");

    if (warp >= 12) {
    asm volatile("setmaxnreg.dec.sync.aligned.u32 64;");
    if (warp == 12) {
        static_assert(W0 > NCP && W0 <= 5 && NCP >= 1 && NCP <= 4, "W0");
        const uint2* sched = M.sched[j < NFF ? 0 : j < J_RED ? 1 : 2];
        uint2 en = sched[W0];
        const uint32_t t0 = gtime();
        const uint32_t sp = __reduce_or_sync(0xffffffffu, sb);
        const int cx = (j >> 1) * 64 + (j < NFF ? 0 : 1024 - NFF * 32);
#pragma unroll 1
        for (int i = W0; en.x; i++) {
            uint32_t e = en.x, st = (en.y >> 20) * 64;
            const uint32_t tn = t0 + (int16_t)en.y, mp = (en.y >> 16) & 15;
            if (mp == MP_GATE || mp == MP_UP) st ^= (j & 16) * 8;
            if (mp == MP_DOWN) { st ^= (j & 3) * 64; e ^= (j & 3) << 6; }
            en = sched[i + 1];
            if (mp == MP_MODB && j >= J_END) break;
            uint32_t c0 = mp == MP_WO ? (j & 7) * 64 : mp > MP_WO ? cx : 0;
            uint32_t c1 = mp == MP_CKV ? 0 : mp == MP_DOWN ? j * 32 : st + (mp == MP_WUV ? (j & 3) * 32 : mp == MP_WO ? (j >> 3) * 256 : rk * 256);
            uint32_t c2 = mp < MP_CKV ? j >> 1 : mp == MP_CKV ? rk * 4 : mp == MP_WUV ? (j >> 2) * 2 : mp == MP_DOWN ? st >> 5 : 0;
            uint32_t c3 = mp == MP_CKV ? st * 2 + (j & ~1) : 0;
            uint32_t dst = sp + ((e << 7) & 0x3e000), bar = sp + SM_BAR + (e & 63) * 8;
            const uint32_t w0 = (e >> 8) & 0x3f8, w1 = (e >> 15) & 0x3f8, w2 = (e >> 22) & 0x3f8, bb = sp + SM_BAR - 8;
            const CUtensorMap* pm = &M.m[mp];
            pin(dst); pin(bar); pin(c0); pin(c1); pin(c2); pin(c3); pin(pm);
            if (w0) mbar_wait(bb + w0, 0);
            if (w2) {
                mbar_wait(bb + w2, 0);
                while (!__any_sync(0xffffffffu, mbar_test(bb + w1, 0) | ((int)(gtime() - tn) > 0))) {}
            } else if (w1) mbar_wait(bb + w1, 0);
            tma(dst, pm, bar, c0, c1, c2, c3);
        }
    } else if (warp == 13) {
#pragma unroll
        for (int i = 0; i < 2; i++) st_x4(gs + (B_ML + rk * 16 + i * 8 + g) * 4096 + (t >> 1) * 1024 + (j >> 1) * 8 + (t & 1) * 4, 0u, 0u, 0u, 0u);
        if (lane < 16) st2_x4(gs + (B_E2 + (j >> 4)) * 4096 + (j & 15) * 64 + lane * 4, 0u, 0u, 0u, 0u);
        st2_x1(gs + (B_E3 + (j >> 5)) * 4096 + (j & 31) * 32 + lane, 0u);
        if (lane < 8) st2_x1(gs + B_MB * 4096 + j * 8 + lane, 0u);
        if (j < NFF) {
#pragma unroll
            for (int i = 0; i < 2; i++) st2_x4(gs + (B_E5 + i * 8 + g) * 4096 + j * 16 + t * 4, 0u, 0u, 0u, 0u);
        }
        bar_sync(9, 64);
        const uint32_t cs = ldcls();
#pragma unroll 1
        for (int i = 0; i < 32; i++) {
            st_x4(gs + G_E1 + j * 8192 + (i >> 3) * 2048 + ((((cs >> 1) ^ (i >> 3)) & 1) << 10) + (i & 7) * 128 + lane * 4, 0u, 0u, 0u, 0u);
            __nanosleep(JAN_SLEEP);
        }
        fence_gpu();
        if (lane < 8) st2_x1(gs + B_RD * 4096 + j * 8 + lane, 1u + (cs >> 1));
        if (lane == 0) TRACE(41);
        uint32_t rd[4];
        mbar_wait(BAR(IT_CKV + RD_ITEM), 0);
        poll<1024, RD_SLEEP>(rd, gs + near_off(B_RD, cs) + lane * 8);
#pragma unroll
        for (int i = 0; i < 4; i++) {
            const uint32_t m = __ballot_sync(0xffffffffu, rd[i] == 2u);
            if (lane == 0) sts32(sb + SM_CLS + 16 + i * 4, m);
        }
        __syncwarp();
        if (lane < 8) mbar_arrive(BAR(JD));
        if (lane == 0) TRACE(42);
    } else if (warp == 14) {
        uint2 ml[2];
        mbar_waitb(BAR(JD), 0);
        const uint32_t cls = ldcls();
        mbar_waitb(BAR(PF0 + 2 * NUNITS - 1), 0);
        __nanosleep(ML_DELAY);
        const uint32_t* pl2 = gs + near_off(B_ML + (j >> 2), cls) + lane * 8;
        const uint32_t wa = sb + SM_W + lb4 * 64 + t * 16 + (g & 3) * 4;
        poll_start<1024>(ml, pl2);
        uint32_t w0 = 0, w1 = 0, redo = 0;
        bool first = true;
#pragma unroll 1
        for (uint32_t it = 0;; it++) {
            const bool p0 = minw(ml[0]) != 0, p1 = minw(ml[1]) != 0;
            const int n = __popc(__ballot_sync(0xffffffffu, p0)) + __popc(__ballot_sync(0xffffffffu, p1));
            const uint32_t x0 = ml[0].x, x1 = ml[1].x;
            if (n < 64) {
                if (!p0) ld_x(ml[0], pl2);
                if (!p1) ld_x(ml[1], pl2 + 256);
            }
            if (n == 64 || (first && n >= E1_EARLY)) {
                auto ord = [](int x) { return x ^ ((x >> 31) & 0x7fffffff); };
                const int o0 = ord(x0), o1 = ord(x1);
                const float mm = __int_as_float(ord(__reduce_max_sync(0xffffffffu, max(p0 ? o0 : INT_MIN, p1 ? o1 : INT_MIN))));
                const float lo = __int_as_float(ord(__reduce_min_sync(0xffffffffu, min(p0 ? o0 : INT_MAX, p1 ? o1 : INT_MAX))));
                const uint32_t v0 = pack2(ex2((p0 ? __uint_as_float(x0) : lo) - mm), 0.f), v1 = pack2(ex2((p1 ? __uint_as_float(x1) : lo) - mm), 0.f);
                redo = !first && __any_sync(0xffffffffu, v0 != w0 || v1 != w1);
                w0 = v0; w1 = v1;
                sts32(wa - redo * (SM_W - SM_W2), w0 * 0x10001u); sts32(wa - redo * (SM_W - SM_W2) + 128, w1 * 0x10001u);
                if (first) bar_arrive(3, 416);
                first = false;
                if (n == 64) break;
            }
            if (it > SPIN_LIMIT) __trap();
        }
        if (lane == 0) TRACE_Q(37);
        float L = bflo(w0) * __uint_as_float(ml[0].y) + bflo(w1) * __uint_as_float(ml[1].y);
#pragma unroll
        for (int o = 16; o; o >>= 1) L += shx(L, o);
        if (lane == 0) *(float2*)(sm + SM_FQ) = make_float2(__frcp_rn(L), __uint_as_float(redo));
        __syncwarp();
        if (lane < 8) mbar_arrive(BAR(WR));
        if (lane == 0) TRACE(10);
        bar_sync(4, 416);
        clear_head();
        if (j < NFF) {
            uint32_t ya = sb + SM_Y + lane * 16, sa = peer_addr(sb + SM_RED + 2048 + rk * 8, lane & 1), tb = peer_addr(BAR(MBB), lane & 1);
            pin(ya); pin(sa); pin(tb);
            bar_sync(7, 288);
            const float4 y0 = ldsf4(ya), y1 = ldsf4(ya + 512);
            float s = sum4(y0) + sum4(y1);
            float q = (fmaf(y0.x, y0.x, y0.y * y0.y) + fmaf(y0.z, y0.z, y0.w * y0.w)) + (fmaf(y1.x, y1.x, y1.y * y1.y) + fmaf(y1.z, y1.z, y1.w * y1.w));
#pragma unroll
            for (int o = 16; o; o >>= 1) { s += shx(s, o); q += shx(q, o); }
            if (lane < 2) st_async2(sa, s, q, tb);
        }
    } else if (warp == 15) {
        mbar_waitb(BAR(IT_X - 1), 0);
        if (j < J_END) mbar_waitb(BAR(j < NFF ? NITEMS - 1 : MBB), 0);
    }
    } else if (warp < 4) {
        float* scr = (float*)(sm + SM_SCR);
        uint32_t cls;
        {
            uint2 ha[8];
            uint32_t best = 0xffffffffu;
            sts32(sb + SM_SCR + 64 + warp * 4, best);
            const float sh = __shfl_sync(0xffffffffu, bflo(in1), 0);
            const float v0 = bflo(in1) - sh, v1 = bfhi(in1) - sh, v2 = bflo(in2) - sh, v3 = bfhi(in2) - sh;
            float mb, sd;
            ln_stats<4>((v0 + v1) + (v2 + v3), (v0 * v0 + v1 * v1) + (v2 * v2 + v3 * v3), sh, scr, warp, lane, 2, mb, sd);
            if (!rk) in2 = in1;
#pragma unroll 1
            for (int i = 0; i < NPROBE; i++) {
                uint32_t t0, t1, o;
                asm volatile("mov.u32 %0, %%clock;" : "=r"(t0));
                asm volatile("atom.relaxed.gpu.global.exch.b32 %0, [%1], %2;" : "=r"(o) : "l"(pl), "r"(2u + i) : "memory");
                asm volatile("{\n.reg .pred p;\nsetp.ne.u32 p, %1, 0x1234567;\nmov.u32 %0, 0;\n@p mov.u32 %0, %%clock;\n}" : "=r"(t1) : "r"(o));
                best = min(best, t1 - t0);
                sts32(sb + SM_SCR + 64 + warp * 4, best);
                if (__all_sync(0xffffffffu, min(best, lds32(sb + SM_SCR + 64 + (warp ^ 1) * 4)) < NEAR_CLK)) break;
            }
            bar_sync(2, 128);
            const uint4 lt = *(const uint4*)(scr + 16);
            cls = NUMA ? ((lt.y < lt.x) ^ (__popc((B_PR + (j >> 5)) & 0x2C) & 1)) | (lt.w < lt.z) << 1 : 0;
            if (warp == 0) { if (lane == 0) sts32(sb + SM_CLS, cls); bar_arrive(9, 64); }
            if (tid == 0) TRACE(38);
            asm volatile("barrier.cluster.wait.aligned;" ::: "memory");
            mbar_wait(BAR(IT_MODA), 0);
            if (HA_DELAY) __nanosleep(HA_DELAY);
            poll<1024, H_SLEEP, false, 16384>(ha, gs + near_off(B_HA + rk * 2, cls) + 2 * tid);
            auto rsum = [](uint32_t a, uint32_t b, uint32_t c, uint32_t d) { return rbf((__uint_as_float(a) + __uint_as_float(b)) + (__uint_as_float(c) + __uint_as_float(d))); };
            sts32(sb + SM_FV + frag_off(2 * tid),
                  pack2(ln_mod(bflo(in2), mb, sd, rsum(ha[4].x, ha[5].x, ha[6].x, ha[7].x), rsum(ha[0].x, ha[1].x, ha[2].x, ha[3].x)),
                        ln_mod(bfhi(in2), mb, sd, rsum(ha[4].y, ha[5].y, ha[6].y, ha[7].y), rsum(ha[0].y, ha[1].y, ha[2].y, ha[3].y))));
            bar_arrive(5, 384);
            mbar_wait(BAR(QB), 0);
            if (tid < 64) {
                const float* qx = (const float*)(sm + SM_QX) + tid;
                sts16(sb + SM_FQ + frag_off(tid), pack2((qx[0] + qx[64]) + (qx[128] + qx[192]), 0.f));
            }
            bar_arrive(6, 384);
        }
        asm volatile("setmaxnreg.inc.sync.aligned.u32 192;");
        float acc[128];
        float M = 0.f;
        uint32_t pa = sb + SM_XA + warp * 512 + lane * 16, ma = sb + SM_MX + (warp * 8 + g) * 4, pf = BAR(PF0);
        uint32_t blo = __reduce_or_sync(0xffffffffu, (((sb + SM_U) & 0x3FFFFu) >> 4) | 0x400000u);
        uint32_t* e1[4];
#pragma unroll
        for (int i = 0; i < 4; i++) e1[i] = gs + G_E1 + (warp * 8 + g) * 4 * 8192 + (rk * 2 + (j >> 6)) * 2048 + ((j >> 1) & 31) * 32 + t * 4;
#pragma unroll 1
        for (int h = 0; h < 2 * NUNITS; h++) {
            mbar_wait(pf, 0);
            const float m = __uint_as_float(lds32(ma));
            const uint4 pn = lds128(pa);
            wg_wait0();
#pragma unroll
            for (int i = 0; i < 128; i++) asm volatile("" : "+f"(acc[i]) :: "memory");
            if (h == 0) M = m;
            uint32_t b2 = 0x3f803f80u;
            if (__builtin_expect(__any_sync(0xffffffffu, m != M), 0)) {
                const float Mn = fmaxf(M, m), alpha = ex2(M - Mn), beta = ex2(m - Mn);
                M = Mn;
                b2 = pack2(beta, beta);
#pragma unroll
                for (int jj = 0; jj < 32; jj++) { acc[4 * jj] *= alpha; acc[4 * jj + 1] *= alpha; }
            }
            auto mul2 = [](uint32_t x, uint32_t y) { uint32_t r; asm("mul.rn.bf16x2 %0, %1, %2;" : "=r"(r) : "r"(x), "r"(y)); return r; };
            const uint4 p = make_uint4(mul2(pn.x, b2), mul2(pn.y, b2), mul2(pn.z, b2), mul2(pn.w, b2));
            if (tid == 0 && (h & 1)) TRACE_Q(48 + (h >> 1));
            wgmma_pv(acc, p, blo, h);
            if (lane == 0 && h > 0 && !(h & 1)) mbar_arrive(BAR(EB_UNIT0 + (h >> 1) - 1));
            blo += h == 11 ? -11 * 1024 : 1024;
            pa += (h == 5 || h == 11) ? -5 * 2048 : 2048;
            ma += 128; pf += 8;
            if (h == 2 * NUNITS - 3) {
                mbar_wait(BAR(JD), 0);
                const uint32_t hm = (*(const uint32_t*)(sm + SM_CLS + 16 + warp * 4) >> (g * 4)) ^ ((j >> 6) ? 15u : 0u);
#pragma unroll
                for (int i = 0; i < 4; i++) e1[i] += ((hm >> i) & 1) << 10;
            }
        }
#pragma unroll
        for (int vv = 0; vv < 2; vv++) {
            if (vv && M == 1.f) __trap();
            if (vv) wg_wait0(); else wg_wait1();
#pragma unroll
            for (int i = 0; i < 64; i++) asm volatile("" : "+f"(acc[vv * 64 + i]) :: "memory");
            if (tid == 0 && !vv) TRACE_Q(63);
#pragma unroll
            for (int i = 0; i < 4; i++) {
                const float* a = &acc[vv * 64 + i * 16];
                st_x4(e1[i] + i * 8192 + vv * 16, enc(pack2(a[0], a[1])), enc(pack2(a[4], a[5])), enc(pack2(a[8], a[9])), enc(pack2(a[12], a[13])));
            }
        }
        bar_arrive(3, 416);
        if (tid == 0) TRACE_Q(17);
#pragma unroll 1
        for (int pass = 0;; pass++) {
            if (j >= NFF && j < J_END && pass == (j >= J_RED)) {
                uint4 a[8], b[4];
                float c[4], e[4];
                const bool own = (warp >> 1) == rk;
                const uint32_t xa = sb + SM_FV + (warp & 1) * 64 + g * 8;
                if (lane == 0) mbar_expect(BAR(MBB), own ? 64 : 0);
#pragma unroll
                for (int i = 0; i < 2; i++) {
                    ldfrag(b, sb + SM_FS + rk * 512 + i * 256 + t * 16);
                    mbar_wait(BAR(IT_X + i), 0);
                    const uint32_t ab = sb + SM_U + B_X * 32768 + i * 16384 + a128;
                    load8<true>(a, [&](int s) { return ab + s * 2048; });
                    mma8(i ? e : c, a, b);
                }
                c[0] += e[0]; c[2] += e[2];
                if (!own) {
                    if (t == 0) st_async2(peer_addr(xa, rk ^ 1), c[0], c[2], peer_addr(BAR(MBB), rk ^ 1));
                } else {
                    mbar_wait(BAR(MBB), 0);
                    const float2 pp = *(const float2*)(sm + (xa - sb));
                    const float mine = t ? c[2] + pp.y : c[0] + pp.x, other = shx(mine, 4);
                    const uint32_t w = (warp & 1) * 8 + t * 4 + (g >> 1), val = enc(pack2(mine, other));
                    if (t < 2 && !(g & 1)) {
                        if (j < J_RED) st2_x1(gs + B_MB * 4096 + (j - NFF) * 16 + w, val);
                        else sts32(sb + SM_FV + 256 + w * 4, val);
                    }
                    __syncwarp();
                    if (j >= J_RED && lane < 4) mbar_arrive(BAR(QB));
                    if (lane == 0) TRACE(11);
                }
            }
            if (pass) break;
            uint4 a[8], a2[8];
            const uint32_t ab = sb + SM_U + B_WO * 32768 + a128;
            uint32_t* p3 = gs + (B_E3 + ((j >> 1) & 3)) * 4096 + (t >> 1) * 1024 + (rk * 2 + (warp >> 1)) * 256 + (j >> 3) * 16 + (warp & 1) * 8 + (t & 1) * 4 + (g >> 1);
            const uint32_t* pb = gs + near_off(B_E2 + (j >> 4), cls) + (((j >> 3) & 1) * 2 + lb4) * 256 + (lane & 15) * 2;
            pin(p3); pin(pb);
            uint2 bb[8];
            uint2 bq[2] = {make_uint2(0u, 0u), make_uint2(0u, 0u)};
            uint32_t xa = sb + SM_XA + lane * 16;
            pin(xa);
            bool h0 = false, h1 = false;
            auto idle = [&]() {
                if (!h0) {
                    h0 = __all_sync(0xffffffffu, mbar_test(BAR(IT_WO + (t & 1)), 0));
                    if (h0) load8<true>(a, [&](int s) { return ab + s * 2048; });
                }
                if (!h1) {
                    h1 = __all_sync(0xffffffffu, mbar_test(BAR(IT_WO + 2 + (t & 1)), 0));
                    if (h1) load8<true>(a2, [&](int s) { return ab + 16384 + s * 2048; });
                }
            };
            bar_sync(4, 416);
            idle();
            poll<128, 0, true>(bq, pb + warp * 64, idle);
            asm volatile("st.shared.v4.u32 [%0], {%1, %2, %3, %4};" :: "r"(xa + warp * 512), "r"(bq[0].x), "r"(bq[0].y), "r"(bq[1].x), "r"(bq[1].y) : "memory");
            bar_sync(2, 128);
#pragma unroll
            for (int i = 0; i < 4; i++) { const uint4 q = lds128(xa + i * 512); bb[2 * i] = make_uint2(q.x, q.y); bb[2 * i + 1] = make_uint2(q.z, q.w); }
            if (tid == 0) TRACE(21);
            float e[4][4];
#pragma unroll
            for (int s = 0; s < 16; s++) {
                if (s == 0 && !h0) { mbar_wait(BAR(IT_WO), 0); mbar_wait(BAR(IT_WO + 1), 0); load8<true>(a, [&](int q) { return ab + q * 2048; }); }
                if (s == 0 && !h1) { mbar_wait(BAR(IT_WO + 2), 0); mbar_wait(BAR(IT_WO + 3), 0); load8<true>(a2, [&](int q) { return ab + 16384 + q * 2048; }); }
                const int z = (s & 1) | (s & 2) << 2 | (s >> 2) << 1;
                const uint4& x = z < 8 ? a[z] : a2[z & 7];
                float (&d)[4] = e[(z >> 3) * 2 + (z & 1)];
                if (!(z & 6)) d[0] = d[1] = d[2] = d[3] = 0.f;
                mma(d, x.x, x.y, x.z, x.w, bb[z & 7].x, bb[z & 7].y);
            }
            float lo, hi;
            quad_pair((t & 2) ? (e[2][0] + e[3][0]) + (e[2][1] + e[3][1]) : (e[0][0] + e[1][0]) + (e[0][1] + e[1][1]),
                      (t & 2) ? (e[2][2] + e[3][2]) + (e[2][3] + e[3][3]) : (e[0][2] + e[1][2]) + (e[0][3] + e[1][3]), t, lo, hi);
            if (!(g & 1)) st_x1(p3, enc(pack2(lo, hi)));
            if (j < NFF) bar_arrive(8, 384); else if (j >= J_RED && j < J_END) bar_arrive(8, 192);
            if (tid == 0) TRACE(22);
        }
        if (j < NFF) {
            uint4 a[16];
            const uint32_t ad = sb + SM_U + B_DN * 32768 + warp * 8192 + (r8 + 8 * lb4) * 128 + (lb3 ^ r8) * 16;
            uint32_t rl = sb + SM_RED + lane * 16;
            uint32_t* p5 = gs + (B_E5 + warp * 4 + (t >> 1)) * 4096 + j * 16 + (t & 1) * 8 + g;
            pin(rl); pin(p5);
            if (lane == 0) mbar_expect(BAR(MBB), 4);
            auto ldd = [&]() {
#pragma unroll
                for (int s = 0; s < 16; s++) a[s] = ldsm<true>((ad ^ ((s & 3) * 32)) + (s >> 2) * 2048);
            };
            const uint32_t db = BAR(IT_DOWN + (warp ^ (j & 3)));
            mbar_wait(BAR(MBB), 0);
            const float4 st = ldsf4(sb + SM_RED + 2048);
            const bool hd = __all_sync(0xffffffffu, mbar_test(db, 0));
            if (hd) ldd();
            const float mu = (st.x + st.z) * (1.f / 512.f);
            float rstd;
            asm volatile("rsqrt.approx.ftz.f32 %0, %1;" : "=f"(rstd) : "f"(fmaxf(fmaf(-mu, mu, (st.y + st.w) * (1.f / 512.f)), 0.f) + 1e-5f));
            mbar_wait(BAR(QB), 1);
            if (tid == 0) TRACE(25);
            const float4 f0 = ldsf4(rl), f2 = ldsf4(rl + 1024), f1 = ldsf4(rl + 512), f3 = ldsf4(rl + 1536);
            const float gg = fmaf(rstd, fmaf(-mu, f0.z + f2.z, (f0.x + f0.y) + (f2.x + f2.y)), f0.w + f2.w);
            const float uu = fmaf(rstd, fmaf(-mu, f1.z + f3.z, (f1.x + f1.y) + (f3.x + f3.y)), f1.w + f3.w);
            const float hh = __fdividef(gg * uu, 1.f + ex2(-gg * fmaf(gg * gg, 0.10294324f, 2.3022082f)));
            uint32_t hb[4];
#pragma unroll
            for (int i = 0; i < 4; i++) hb[i] = pack2(__shfl_sync(0xffffffffu, hh, 2 * t + 8 * i), __shfl_sync(0xffffffffu, hh, 2 * t + 8 * i + 1));
            auto down = [&]() {
#pragma unroll
                for (int i = 0; i < 2; i++) {
                    uint32_t res = 0;
#pragma unroll
                    for (int k = 0; k < 4; k++) {
                        float c[4] = {0.f, 0.f, 0.f, 0.f};
                        const uint4 &x = a[i * 8 + k], &y = a[i * 8 + k + 4];
                        mma(c, x.x, x.y, x.z, x.w, hb[0], hb[1]);
                        mma(c, y.x, y.y, y.z, y.w, hb[2], hb[3]);
                        if (t == k) res = pack2(c[0], c[2]);
                    }
                    st2_x1(p5 + i * 8192, enc(res));
                }
            };
            if (hd) down();
            else { mbar_wait(db, 0); ldd(); down(); asm volatile("// late" ::: "memory"); }
            if (tid == 0) { TRACE(27); TRACE_GT(47); }
        }
    } else {
        const int u8 = tid - 128, w8 = warp - 4;
        const int v = w8 >> 2, wq4 = w8 & 3;
        {
            const float c0 = bflo(in1), c1 = bfhi(in1);
            sts32(sb + SM_FS + frag_off(2 * u8), pack2(__fdividef(c0, 1.f + __expf(-c0)), __fdividef(c1, 1.f + __expf(-c1))));
        }
        bar_sync(1, 256);
        asm volatile("barrier.cluster.wait.aligned;" ::: "memory");
        uint4 a[8], b[4]; float c[4];
        if (w8 < 2) {
            ldfrag(b, sb + SM_FS + (j >> 5) * 256 + t * 16);
            mbar_wait(BAR(IT_MODA), 0);
            if (u8 == 0) TRACE(12);
            const uint32_t ab = sb + SM_XA + w8 * 4096 + a16;
            load8<true>(a, [&](int s) { return ab + s * 512; });
            mma8(c, a, b);
            if (t < 2) st2_x1(gs + (B_HA + ((j >> 4) & 1) * 2 + w8) * 4096 + (j >> 5) * 256 + (j & 15) * 16 + t * 8 + g, encf(t ? c[2] : c[0]));
        }
        {
            mbar_wait(BAR(IT_WQ + 2 * v <= NCP ? 1 : IT_WQ + 2 * v), 0); mbar_wait(BAR(IT_WQ + 2 * v + 1 <= NCP ? 1 : IT_WQ + 2 * v + 1), 0);
            const uint32_t ab = sb + SM_U + 4 * 32768 + v * 16384 + a128;
            load8<true>(a, [&](int s) { return ab + s * 2048; });
            if (lane == 0) mbar_arrive(BAR(EB_WQ));
            bar_sync(5, 384);
            if (u8 == 0) TRACE(13);
            ldfrag(b, sb + SM_FV + v * 256 + t * 16);
            mma8(c, a, b);
            if (t < 2) {
                const float qv = t ? c[2] : c[0];
                const uint32_t qa_ = sb + SM_QX + ((rk * 2 + v) * 64 + wq4 * 16 + t * 8 + g) * 4;
                asm volatile("st.async.weak.shared::cluster.mbarrier::complete_tx::bytes.f32 [%0], %1, [%2];"
                             :: "r"(peer_addr(qa_, rk ^ 1)), "f"(qv), "r"(peer_addr(BAR(QB), rk ^ 1)) : "memory");
                sts32(qa_, __float_as_uint(qv));
            }
            __syncwarp();
            if (lane == 0) mbar_expect(BAR(QB), 64);
        }
        {
            mbar_wait(BAR(IT_WUK + v), 0); mbar_wait(BAR(IT_WUK + v + 2), 0);
            const uint32_t ab = sb + SM_U + 5 * 32768 + (w8 * 16 + r8 + 8 * lb3) * 128;
            const uint32_t x16 = (lb4 ^ r8) * 16;
            load8<false>(a, [&](int s) { return ab + (s & 1) * 16384 + (x16 ^ ((s >> 1) * 32)); });
            bar_sync(6, 384);
            if (u8 == 0) TRACE(14);
            b[0] = lds128(sb + SM_FQ + t * 16); b[1] = lds128(sb + SM_FQ + 64 + t * 16);
            float e[4] = {0.f, 0.f, 0.f, 0.f};
            c[0] = c[1] = c[2] = c[3] = 0.f;
#pragma unroll
            for (int k = 0; k < 4; k++) {
                const uint32_t b0 = (k & 1) ? b[k >> 1].z : b[k >> 1].x, b1 = (k & 1) ? b[k >> 1].w : b[k >> 1].y;
                mma(c, a[2 * k].x, a[2 * k].y, a[2 * k].z, a[2 * k].w, b0, b1);
                mma(e, a[2 * k + 1].x, a[2 * k + 1].y, a[2 * k + 1].z, a[2 * k + 1].w, b0, b1);
            }
            const float mine = ((t & 1) ? ((t & 2) ? e[2] : e[0]) : ((t & 2) ? c[2] : c[0])) * 0.12751743f;
            const float other = shx(mine, 4);
            if (!(g & 1)) st2_x1(gs + (B_QA + rk * 8 + ((j >> 1) & 1) * 4 + (j >> 5)) * 4096 + w8 * 128 + ((j >> 2) & 7) * 16 + (g >> 1) * 4 + t, enc(pack2(mine, other)));
            if (u8 == 0) TRACE(15);
        }
        const uint32_t cls = ldcls();
        __nanosleep(QA_DELAY);
        {
            uint4 qb[8];
            const uint32_t* pq = gs + near_off(B_QA + rk * 8 + wq4, cls) + lane * 4;
            const uint32_t* pq2 = gs + near_off(B_QA + rk * 8 + 4 + wq4, cls) + lane * 4;
            if (lane == 0) {
                mbar_expect(BAR(QT), 4096);
                asm volatile("cp.async.bulk.shared::cluster.global.mbarrier::complete_tx::bytes [%0], [%1], 4096, [%2];"
                             :: "r"(sb + SM_U + 5 * 32768 + w8 * 4096), "l"(gs + near_off(B_QA + rk * 8 + w8, cls)), "r"(BAR(QT)) : "memory");
            }
            const uint32_t qs = sb + SM_U + 5 * 32768 + wq4 * 4096 + lane * 16;
            mbar_wait(BAR(QT), 0);
#pragma unroll
            for (int i = 0; i < 8; i++) { a[i] = lds128(qs + i * 512); qb[i] = lds128(qs + 16384 + i * 512); }
            poll<512, QA_SLEEP, true>(a, pq);
            poll<512, QA_SLEEP, true>(qb, pq2);
            if (lane == 0) mbar_arrive(BAR(EB_WUK));
            auto add2 = [](uint32_t x, uint32_t y) { uint32_t r; asm("add.rn.bf16x2 %0, %1, %2;" : "=r"(r) : "r"(x), "r"(y)); return r; };
#pragma unroll
            for (int i = 0; i < 8; i++) a[i] = make_uint4(add2(a[i].x, qb[i].x), add2(a[i].y, qb[i].y), add2(a[i].z, qb[i].z), add2(a[i].w, qb[i].w));
        }
        if (u8 == 0) TRACE(8);
        {
            float m = -INFINITY, l = 0.f;
            uint32_t xl = sb + SM_XB + w8 * 2048 + lane * 16, xr = peer_addr(xl, rk ^ 1), bsr = peer_addr(BAR(SF0 + v), rk ^ 1);
            uint32_t pa = sb + SM_XA + v * 2048 + wq4 * 512 + lane * 16, ma = sb + SM_MX + v * 128 + (wq4 * 8 + g) * 4;
            uint32_t fb = BAR(IT_CKV + v * 2), sf = BAR(SF0 + v);
            uint32_t dlo = __reduce_or_sync(0xffffffffu, (((sb + SM_U + v * 16384) & 0x3FFFFu) >> 4) | 0x10000u);
            if (STAG && v) __nanosleep(STAG);
#pragma unroll 1
            for (int n = 0; n < NUNITS; n++) {
                float d[2][16], sc[8];
#pragma unroll
                for (int i = 0; i < 2; i++) {
                    mbar_wait(fb + i * 8, 0);
                    wg_fence();
#pragma unroll
                    for (int s = 0; s < 8; s++) wgmma_rs_n32(d[i], a[s], (0x40000080ull << 32) | (dlo + i * 512 + (s >> 2) * 64 + (s & 3) * 2), s);
                    wg_commit();
                }
#pragma unroll
                for (int i = 0; i < 2; i++) {
                    if (i) wg_wait0(); else wg_wait1();
#pragma unroll
                    for (int k = 0; k < 16; k++) asm volatile("" : "+f"(d[i][k]) :: "memory");
                    sc[4 * i] = d[i][0] + d[i][6]; sc[4 * i + 1] = d[i][1] + d[i][7]; sc[4 * i + 2] = d[i][8] + d[i][14]; sc[4 * i + 3] = d[i][9] + d[i][15];
                    asm volatile("st.async.weak.shared::cluster.mbarrier::complete_tx::bytes.v4.f32 [%0], {%1, %2, %3, %4}, [%5];"
                                 :: "r"(xr + i * 1024), "f"(sc[4 * i]), "f"(sc[4 * i + 1]), "f"(sc[4 * i + 2]), "f"(sc[4 * i + 3]), "r"(bsr) : "memory");
                }
                if (u8 == 128) TRACE_Q(56 + (n < 6 ? n : -40));
                if (n >= 3) mbar_wait(BAR(EB_UNIT0 + n - 3), 0);
                dlo += n == 5 ? -5 * 2048 : 2048;
                fb += 32; xr ^= 512; bsr += 16;
                pin(fb); pin(xr); pin(bsr);
                mbar_wait(sf, 0);
                const float4 x = ldsf4(xl), y = ldsf4(xl + 1024);
                sc[0] += x.x; sc[1] += x.y; sc[2] += x.z; sc[3] += x.w; sc[4] += y.x; sc[5] += y.y; sc[6] += y.z; sc[7] += y.w;
                float pr[8];
#pragma unroll
                for (int i = 0; i < 8; i++) pr[i] = ex2(sc[i] - m);
                float mx = fmaxf(fmaxf(fmaxf(sc[0], sc[1]), fmaxf(sc[2], sc[3])), fmaxf(fmaxf(sc[4], sc[5]), fmaxf(sc[6], sc[7])));
                if (__builtin_expect(__any_sync(0xffffffffu, mx > m), 0)) {
                    mx = fmaxf(mx, shx(mx, 1));
                    mx = fmaxf(mx, shx(mx, 2));
                    const float mn = fmaxf(m, ceilf(mx * 0.0625f) * 16.f);
                    l *= ex2(m - mn);
                    m = mn;
#pragma unroll
                    for (int i = 0; i < 8; i++) pr[i] = ex2(sc[i] - m);
                }
                stsf(ma, m);
                asm volatile("st.shared.v4.u32 [%0], {%1, %2, %3, %4};" :: "r"(pa), "r"(pack2(pr[0], pr[1])), "r"(pack2(pr[2], pr[3])),
                             "r"(pack2(pr[4], pr[5])), "r"(pack2(pr[6], pr[7])) : "memory");
                __syncwarp();
                if (lane == 0) mbar_arrive(sf + (PF0 - SF0) * 8);
                l += ((pr[0] + pr[1]) + (pr[2] + pr[3])) + ((pr[4] + pr[5]) + (pr[6] + pr[7]));
                xl ^= 512; sf += 16; ma += 256; pa += (n == 2 || n == 5) ? -8192 : 4096;
            }
            l += shx(l, 1);
            l += shx(l, 2);
            float2* mlx = (float2*)(sm + SM_MX + 2048) + wq4 * 8 + g;
            if (v == 0) { *mlx = make_float2(m, l); bar_arrive(11, 256); }
            else {
                mbar_wait(BAR(JD), 0);
                bar_sync(11, 256);
                const float2 o = *mlx;
                const float mn = fmaxf(m, o.x);
                l = l * ex2(m - mn) + o.y * ex2(o.x - mn);
                if ((wq4 >> 1) == rk) st_x4(gs + (B_ML + wq4 * 8 + g) * 4096 + (t >> 1) * 1024 + (j >> 1) * 8 + (t & 1) * 4, encf(mn), encf(l), 1u, 1u);
            }
        }
        const int pi = j < NFF ? rk * 128 + w8 * 16 + (lane >> 1) : ((j - J_RED) & 15) * 16 + (w8 & 1) * 8 + g;
        const uint32_t xw = *(const uint32_t*)(xin + 2 * pi);
        const uint32_t one = (g & 1) ? 0x3f800000u : 0x00003f80u;
        const uint32_t* pm = gs + near_off(B_MB, cls) + pi;
        {
            const uint32_t ab = sb + SM_U + B_WUV * 32768 + v * 4096 + a128;
            uint32_t pa = sb + SM_PB + wq4 * 320 + frag_off(64 * v + 32 * (g >> 2) + 16 * (t & 1) + 8 * (t >> 1) + 2 * (g & 3));
            uint32_t fa = sb + SM_PB + g * 320 + t * 16;
            const uint32_t* pe = gs + G_E1 + j * 8192 + (w8 >> 1) * 2048 + ((((cls >> 1) ^ (w8 >> 1)) & 1) << 10) + (((w8 & 1) * 16 + t) * 8 + g) * 4;
            uint32_t* p2 = gs + (B_E2 + (j >> 4)) * 4096 + (t >> 1) * 1024 + (j & 12) * 64 + w8 * 32 + (j & 3) * 8 + (g & 6) + (t & 1);
            pin(pa); pin(fa); pin(pe); pin(p2);
            const uint32_t mk = (g & 1) ? 0xffff0000u : 0x0000ffffu, m0 = (g & 2) ? 0u : mk, m1 = (g & 2) ? mk : 0u;
            uint4 pv[4];
            bool hv = false;
            bar_sync(3, 416);
            uint4 wa = lds128(sb + SM_W + (wq4 * 4 + t) * 16);
            uint32_t wb[8] = {wa.x & m0, wa.x & m1, wa.y & m0, wa.y & m1, wa.z & m0, wa.z & m1, wa.w & m0, wa.w & m1};
            pv[0] = pv[1] = pv[2] = pv[3] = make_uint4(0u, 0u, 0u, 0u);
            float e[4][4];
            auto wsum = [&]() {
#pragma unroll
                for (int i = 0; i < 4; i++) {
                    e[i][0] = e[i][1] = e[i][2] = e[i][3] = 0.f;
                    mma(e[i], pv[i].x, pv[i].y, pv[i].z, pv[i].w, wb[2 * i], wb[2 * i + 1]);
                }
            };
            poll<512, E1_SLEEP, true>(pv, pe, [&]() {
                if (!hv) {
                    hv = __all_sync(0xffffffffu, mbar_test(BAR(IT_WUV + t), 0));
                    if (hv) load8<true>(a, [&](int s) { return ab + (s >> 1) * 8192 + (s & 1) * 2048; });
                }
            }, wsum);
            if (lane == 0) TRACE_Q(48 + w8);
            if (u8 == 0) TRACE_Q(18);
            float lo, hi2;
            float2 inv;
#pragma unroll 1
            for (int pass = 0;; pass++) {
                const float r0 = (t & 2) ? (e[0][2] + e[1][2]) + (e[2][2] + e[3][2]) : (e[0][0] + e[1][0]) + (e[2][0] + e[3][0]);
                const float r1 = (t & 2) ? (e[0][3] + e[1][3]) + (e[2][3] + e[3][3]) : (e[0][1] + e[1][1]) + (e[2][1] + e[3][1]);
                const uint32_t hi = pack2(r0, r1);
                sts32(pa, hi); sts32(pa + 1280, pack2(r0 - bflo(hi), r1 - bfhi(hi)));
                if (!hv) {
#pragma unroll 1
                    for (int i = 0; i < 4; i++) mbar_wait(BAR(IT_WUV + i), 0);
                    load8<true>(a, [&](int s) { return ab + (s >> 1) * 8192 + (s & 1) * 2048; });
                    hv = true;
                }
                bar_sync(1, 256);
                if (u8 == 0) TRACE(19);
                ldfrag(b, fa);
                mma8(c, a, b);
                mbar_wait(BAR(WR), 0);
                asm volatile("ld.shared.v2.f32 {%0, %1}, [%2];" : "=f"(inv.x), "=f"(inv.y) : "r"(sb + SM_FQ) : "memory");
                quad_pair(c[0] + c[1], c[2] + c[3], t, lo, hi2);
                if (__builtin_expect(__all_sync(0xffffffffu, pass || __float_as_uint(inv.y) == 0), 1)) break;
                wa = lds128(sb + SM_W2 + (wq4 * 4 + t) * 16);
                wb[0] = wa.x & m0; wb[1] = wa.x & m1; wb[2] = wa.y & m0; wb[3] = wa.y & m1; wb[4] = wa.z & m0; wb[5] = wa.z & m1; wb[6] = wa.w & m0; wb[7] = wa.w & m1;
                wsum();
                bar_sync(1, 256);
            }
            if (!(g & 1)) st_x1(p2, enc(pack2(lo * inv.x, hi2 * inv.x)));
            bar_arrive(4, 416);
            if (u8 == 0) TRACE(20);
        }
        if (j < NFF) {
            const uint32_t* p3 = gs + near_off(B_E3 + rk * 2 + v, cls) + wq4 * 256 + t * 16 + g * 2;
            const int od = lane & 1;
            uint32_t za = sb + SM_FZ + od * 576 + frag_off(w8 * 32 + (lane & 30));
            uint32_t fa = sb + SM_FZ + (g & 3) * 576 + ((lane ^ j) & 16) * 16 + t * 16, ya = sb + SM_Y + u8 * 4;
            uint32_t mb[3];
            uint4 a2[8];
            poll<1024, MB_SLEEP>(mb, pm);
            const uint32_t kk = pack2(1.f + bflo(mb[2]), 1.f + bfhi(mb[2]));
            sts32(za + 2 * 576, od ? mb[1] : kk);
            uint2 e3[4] = {make_uint2(0u, 0u), make_uint2(0u, 0u), make_uint2(0u, 0u), make_uint2(0u, 0u)};
            uint32_t ra = peer_addr(sb + SM_RED + (rk * 2 + v) * 512 + ((wq4 & 1) * 16 + (t >> 1) * 8 + g) * 16 + (t & 1) * 8, wq4 >> 1), tbo = peer_addr(BAR(QB), wq4 >> 1);
            pin(za); pin(fa); pin(ya); pin(ra); pin(tbo);
            if (lane == 0) mbar_expect(BAR(QB), 256);
            const uint32_t gb = BAR(IT_X + v * 2), ab = sb + SM_U + (B_X + v) * 32768 + a128;
            bool early = false, early2 = false;
            auto ldw = [&]() {
                if (!early) {
                    early = __all_sync(0xffffffffu, mbar_test(gb, 0));
                    if (early) load8<true>(a, [&](int s) { return ab + s * 2048; });
                }
                if (!early2) {
                    early2 = __all_sync(0xffffffffu, mbar_test(gb + 8, 0));
                    if (early2) load8<true>(a2, [&](int s) { return ab + 16384 + s * 2048; });
                }
            };
            bar_sync(8, 384);
            float s0[4], s1[4];
            auto sum = [&]() {
                s0[0] = s0[1] = s0[2] = s0[3] = s1[0] = s1[1] = s1[2] = s1[3] = 0.f;
                mma(s0, e3[0].x, e3[0].y, e3[1].x, e3[1].y, one, one); mma(s1, e3[2].x, e3[2].y, e3[3].x, e3[3].y, one, one);
            };
            poll<256, 0, true>(e3, p3, ldw, sum);
            if (u8 == 0) TRACE(23);
            const float y0 = fmaf(bflo(mb[0]), (t & 2) ? s0[2] + s1[2] : s0[0] + s1[0], bflo(xw)), y1 = fmaf(bfhi(mb[0]), (t & 2) ? s0[3] + s1[3] : s0[1] + s1[1], bfhi(xw));
            stsf(ya, od ? y1 : y0);
            const float z0 = y0 * bflo(kk), z1 = y1 * bfhi(kk);
            const uint32_t zh = pack2(z0, z1);
            sts32(za, od ? pack2(z0 - bflo(zh), z1 - bfhi(zh)) : zh);
            bar_sync(7, 288);
            if (u8 == 0) TRACE(24);
            ldfrag(b, fa);
            if (!early) { mbar_wait(gb, 0); load8<true>(a, [&](int s) { return ab + s * 2048; }); }
            {
                float e[4][4];
#pragma unroll
                for (int s = 0; s < 16; s++) {
                    if (s == 8 && !early2) { mbar_wait(gb + 8, 0); load8<true>(a2, [&](int q) { return ab + 16384 + q * 2048; }); }
                    const uint4& x = s < 8 ? a[s] : a2[s & 7];
                    const uint4& y = b[(s >> 1) & 3];
                    float (&d)[4] = e[(s >> 3) * 2 + (s & 1)];
                    if (!(s & 6)) d[0] = d[1] = d[2] = d[3] = 0.f;
                    mma(d, x.x, x.y, x.z, x.w, (s & 1) ? y.z : y.x, (s & 1) ? y.w : y.y);
                }
                const bool hi = t >> 1;
                const float k0 = hi ? e[2][2] + e[3][2] : e[0][0] + e[1][0], k1 = hi ? e[2][3] + e[3][3] : e[0][1] + e[1][1];
                const float o0 = hi ? e[2][0] + e[3][0] : e[0][2] + e[1][2], o1 = hi ? e[2][1] + e[3][1] : e[0][3] + e[1][3];
                st_async2(ra, k0 + shx(o0, 2), k1 + shx(o1, 2), tbo);
            }
        } else if (j >= J_RED && j < J_END && w8 < 2) {
            uint32_t ga[1], e3[4];
            poll<0, MB_SLEEP>(ga, pm);
            bar_sync(8, 192);
            poll<64, 100>(e3, gs + near_off(B_E3 + (pi >> 6), cls) + (pi & 48) * 16 + t * 64 + (pi & 15));
            float y0 = (bflo(e3[0]) + bflo(e3[1])) + (bflo(e3[2]) + bflo(e3[3])), y1 = (bfhi(e3[0]) + bfhi(e3[1])) + (bfhi(e3[2]) + bfhi(e3[3]));
#pragma unroll
            for (int o = 1; o < 4; o <<= 1) { y0 += shx(y0, o); y1 += shx(y1, o); }
            const int col = g + (t & 1) * 8;
            y0 = __shfl_sync(0xffffffffu, (t & 1) ? fmaf(bfhi(ga[0]), y1, bfhi(xw)) : fmaf(bflo(ga[0]), y0, bflo(xw)), (col >> 1) * 4 + (col & 1));
            uint16_t* po = (uint16_t*)out + (j - J_RED) * 32 + w8 * 16 + col;
            const uint32_t* pe = gs + near_off(B_E5 + j - J_RED, cls) + t * 16 + w8 * 8 + g;
            pin(po);
            const uint32_t sel = (g & 2) ? 0x3f800000u : 0x00003f80u;
            uint32_t yv[NFF / 4 + 1];
            float e[4][4], gb = 0.f;
#pragma unroll
            for (int i = 0; i <= NFF / 4; i++) yv[i] = 0u;
#pragma unroll 1
            for (uint32_t it = 0;; it++) {
#pragma unroll
                for (int i = 0; i < NFF / 4; i++) if (!yv[i]) ld_x(yv[i], pe + i * 64);
                if (__all_sync(0xffffffffu, !yv[NFF / 4] && mbar_test(BAR(QB), 1))) {
                    yv[NFF / 4] = lds32(sb + SM_FV + 256 + w8 * 32 + (col >> 1) * 4);
                    gb = (col & 1) ? bfhi(yv[NFF / 4]) : bflo(yv[NFF / 4]);
                }
                if (it > SPIN_LIMIT) __trap();
#pragma unroll
                for (int i = 0; i < 4; i++) {
                    e[i][0] = e[i][1] = e[i][2] = e[i][3] = 0.f;
                    mma(e[i], yv[4 * i], yv[4 * i + 1], i < 3 ? yv[(4 * i + 2) % (NFF / 4)] : 0u, i < 3 ? yv[(4 * i + 3) % (NFF / 4)] : 0u, sel, sel);
                }
                if (__all_sync(0xffffffffu, mint<NFF / 4 + 1>(yv) != 0)) break;
            }
            if (u8 == 0) TRACE(26);
            const float s = ((e[0][0] + e[0][2]) + (e[1][0] + e[1][2])) + ((e[2][0] + e[2][2]) + (e[3][0] + e[3][2]));
            asm volatile("{\n.reg .pred p;\nsetp.lt.u32 p, %2, 2;\n@p st.global.u16 [%0], %1;\n}" :: "l"(po), "h"((uint16_t)pack2(fmaf(gb, s, y0), 0.f)), "r"(t) : "memory");
            asm volatile("{\n.reg .pred p;\nsetp.eq.f32 p, %0, 0f7F7FFFFF;\n@p nanosleep.u32 0;\n}" :: "f"(((e[0][1] + e[0][3]) + (e[1][1] + e[1][3])) + ((e[2][1] + e[2][3]) + (e[3][1] + e[3][3]))));
            if (u8 == 0) TRACE(27);
        }
    }
}

typedef CUresult (*EncFn)(CUtensorMap*, CUtensorMapDataType, cuuint32_t, void*, const cuuint64_t*, const cuuint64_t*,
                          const cuuint32_t*, const cuuint32_t*, CUtensorMapInterleave, CUtensorMapSwizzle,
                          CUtensorMapL2promotion, CUtensorMapFloatOOBfill);

void make_map(EncFn enc_fn, CUtensorMap* m, const void* p, cuuint64_t d0, cuuint64_t d1, cuuint64_t d2, cuuint64_t d3,
              cuuint64_t s1, cuuint64_t s2, cuuint64_t s3, cuuint32_t b0, cuuint32_t b1, cuuint32_t b2, cuuint32_t b3, CUtensorMapSwizzle sw) {
    const cuuint64_t dims[4] = {d0, d1, d2, d3}, strides[3] = {s1, s2, s3};
    const cuuint32_t box[4] = {b0, b1, b2, b3}, es[4] = {1, 1, 1, 1};
    enc_fn(m, CU_TENSOR_MAP_DATA_TYPE_BFLOAT16, 4, (void*)p, dims, strides, box, es,
           CU_TENSOR_MAP_INTERLEAVE_NONE, sw, CU_TENSOR_MAP_L2_PROMOTION_L2_128B, CU_TENSOR_MAP_FLOAT_OOB_FILL_NONE);
}

uint32_t* scratch = nullptr;

struct Tune { const char* win; const char* late; int tau, t_off; const char* tail[3][4]; };
Tune tune = {"77777777755555555555555555555555555555544",
             "00000000000000888888888888888888888888888", 322, -410,
             {{"VVVVOOOOguguDDDD", "zzzzzzzzzzzzzzzz", "7777aaaaaaaa6789", "9bbp94o3h3b7f73b"},
              {"VMVMVVOOOO", "zzzzzzzzzz", "9999999999", "467o45e7n7"},
              {"VVVVOOOOMM", "zzzzzzzzzz", "aaaaaaaa88", "d11352cao7"}}};
bool ready = false;

}

extern "C" void kernel_launch(void* const* d_in, const int* in_sizes, int n_in, void* d_out, int out_size) {
    (void)in_sizes; (void)n_in; (void)out_size;
    static Maps maps;
    static const void* cached[12] = {};
    bool same = ready;
    for (int i = 0; i < 12 && same; i++) same = cached[i] == d_in[i];
    if (!same) {
        void* fn = nullptr;
        cudaDriverEntryPointQueryResult qr;
        cudaGetDriverEntryPoint("cuTensorMapEncodeTiled", &fn, cudaEnableDefault, &qr);
        EncFn e = (EncFn)fn;
        const CUtensorMapSwizzle S128 = CU_TENSOR_MAP_SWIZZLE_128B;
        make_map(e, &maps.m[MP_WQ], d_in[2], 64, 512, 64, 1, 8192, 128, 8192, 64, 64, 1, 1, S128);
        make_map(e, &maps.m[MP_WUK], d_in[3], 64, 512, 64, 1, 8192, 128, 8192, 64, 64, 1, 1, S128);
        make_map(e, &maps.m[MP_CKV], d_in[1], 64, 8, 8, 4096, 1024, 128, 8192, 64, 8, 4, 2, S128);
        make_map(e, &maps.m[MP_MODB], d_in[11], 3072, 512, 1, 1, 6144, 6144, 6144, 64, 128, 1, 1, S128);
        make_map(e, &maps.m[MP_WUV], d_in[4], 64, 512, 64, 1, 8192, 128, 8192, 64, 32, 2, 1, S128);
        make_map(e, &maps.m[MP_WO], d_in[5], 512, 4096, 1, 1, 1024, 1024, 1024, 64, 64, 1, 1, S128);
        make_map(e, &maps.m[MP_GATE], d_in[7], 1792, 512, 1, 1, 3584, 3584, 3584, 64, 128, 1, 1, S128);
        make_map(e, &maps.m[MP_UP], d_in[8], 1792, 512, 1, 1, 3584, 3584, 3584, 64, 128, 1, 1, S128);
        make_map(e, &maps.m[MP_DOWN], d_in[9], 64, 1792, 8, 1, 1024, 128, 1024, 64, 32, 2, 1, S128);
        for (int r = 0; r < 3; r++) {
            int ids[58], cnt[128] = {}, tn = tune.t_off - (W0 - 1) * tune.tau;
            uint2* sc = maps.sched[r];
            auto dig = [](char ch) { return ch >= 'a' ? ch - 'a' + 10 : ch >= 'A' ? ch - 'A' + 36 : ch - '0'; };
            for (int i = 0; i < 58; i++) sc[i] = make_uint2(0u, 0u);
            for (int i = 0;; i++) {
                int id = i, buf, dep, w, wl;
                if (i < IT_WUV) {
                    const int u = (i - IT_CKV) >> 2;
                    buf = i < IT_CKV ? 4 + ((i - 1) >> 2) : u % 6;
                    dep = i < IT_CKV || u < 4 ? -1 : u < 6 ? EB_WQ + u - 4 : EB_UNIT0 + u - 6;
                    w = dig(tune.win[i]); wl = dig(tune.late[i]);
                    if (i) tn += tune.tau;
                } else {
                    const char ch = tune.tail[r][0][i - IT_WUV];
                    if (!ch) break;
                    buf = ch == 'V' ? B_WUV : ch == 'O' ? B_WO : ch == 'D' ? B_DN : ch == 'u' ? B_X + 1 : B_X;
                    id = (ch == 'V' ? IT_WUV : ch == 'O' ? IT_WO : ch == 'D' ? IT_DOWN : ch == 'u' ? IT_X + 2 : IT_X) + cnt[(int)ch]++;
                    dep = EB_UNIT0 + (buf < 2 ? buf + 6 : buf);
                    w = dig(tune.tail[r][1][i - IT_WUV]); wl = dig(tune.tail[r][2][i - IT_WUV]);
                    tn += (r == 2 ? 64 : 32) * dig(tune.tail[r][3][i - IT_WUV]);
                }
                if (id < IT_X || id >= IT_DOWN ? (id - 1) & 3 : (id - IT_X) & 1) dep = -1;
                ids[i] = id;
                auto back = [&](int d) { return i < d ? 0 : (ids[i - d] && ids[i - d] <= NCP ? 1 : ids[i - d]) + 1; };
                sc[i].x = id | (buf * 4 + (id < IT_X || id >= IT_DOWN ? (id - 1) & 3 : ((id - IT_X) & 1) * 2)) << 6 | (dep + 1) << 11 | (w > 32 ? NEVER + 1 : back(w)) << 18 | (wl ? back(wl) : 0) << 25;
                const int mp = id < IT_CKV ? MP_WQ + ((id - 1) >> 2) : id < IT_WUV ? MP_CKV : id < IT_WO ? MP_WUV : id < IT_X ? MP_WO
                             : id >= IT_DOWN ? MP_DOWN : r ? MP_MODB : MP_GATE + ((id - IT_X) >> 1);
                const int step = mp == MP_CKV ? id - IT_CKV : mp == MP_WUV ? (id - IT_WUV) * 2 : mp == MP_DOWN ? id - IT_DOWN : id < IT_X ? (id - 1) & 3 : ((id - IT_X) & 1) * 2;
                sc[i].y = (tn & 0xffff) | (mp & 15) << 16 | step << 20;
            }
        }
        cudaGetSymbolAddress((void**)&scratch, g_scratch);
        scratch = (uint32_t*)(((uintptr_t)scratch + (2u << 20) - 1) & ~(uintptr_t)((2u << 20) - 1));
        cudaFuncSetAttribute(fused_kernel, cudaFuncAttributeMaxDynamicSharedMemorySize, SM_TOTAL);
        for (int i = 0; i < 12; i++) cached[i] = d_in[i];
        ready = true;
    }
    const First f = {{(const uint8_t*)d_in[2], (const uint8_t*)d_in[11]}, {(const __nv_bfloat16*)d_in[0], (const __nv_bfloat16*)d_in[10]}};
    fused_kernel<<<NCTA, NTHREADS, SM_TOTAL>>>(f, (__nv_bfloat16*)d_out, scratch, maps);
}
```
